```python
import torch

def _softmax(x, axis=-1):
    return torch.softmax(x, dim=axis)
def _gelu(x):
    return torch.nn.functional.gelu(x, approximate="tanh")
def _silu(x):
    return torch.nn.functional.silu(x)
def _sigmoid(x):
    return torch.sigmoid(x)
def _layernorm(x, axis=-1, eps=1e-5):
    m = x.mean(dim=axis, keepdim=True)
    v = x.var(dim=axis, keepdim=True, unbiased=False)
    return (x - m) / torch.sqrt(v + eps)
def _scatter_add(tgt, idx, src, axis=0):
    return tgt.clone().index_add_(axis, idx, src)
def _segment_sum(src, seg, n):
    out = torch.zeros((n,) + src.shape[1:], dtype=src.dtype)
    return out.index_add_(0, seg, src)
def _pad(x, pw):
    flat = tuple(v for pair in reversed(pw) for v in pair)
    return torch.nn.functional.pad(x, flat)

kernel_name = 'standalone__seq2seq_rnn_t_joint__speech'

def setup_inputs():

    _w = (lambda a: (lambda t: t.to(torch.bfloat16) if t.is_floating_point() else t)(torch.as_tensor(a)))
    B, T, D, K = 2, 16000, 256, 31
    U = 8
    sc = (1.0 / (K * D)) ** 0.5
    sd = (1.0 / D) ** 0.5
    return {
        "x": _w((lambda *s: torch.randn(*s, dtype=torch.bfloat16) * 0.2)(B, T, D) * 0.5),
        "w1": _w((lambda *s: torch.randn(*s, dtype=torch.bfloat16) * 3.2)(K, D, D) * sc),
        "w2": _w((lambda *s: torch.randn(*s, dtype=torch.bfloat16) * 3.2)(K, D, D) * sc),
        "g": _w((lambda *s: torch.randn(*s, dtype=torch.bfloat16) * 3.2)(B, U, D) * 0.5),
        "w_f": _w((lambda *s: torch.randn(*s, dtype=torch.bfloat16) * 3.2)(D, D) * sd),
        "w_g": _w((lambda *s: torch.randn(*s, dtype=torch.bfloat16) * 3.2)(D, D) * sd),
        "w_o": _w((lambda *s: torch.randn(*s, dtype=torch.bfloat16) * 3.2)(D, D) * sd),
    }

def reference(x, w1, w2, g, w_f, w_g, w_o):
    B, T, D = x.shape
    K = w1.shape[0]
    pad = K // 2
    xp = _pad(x, ((0,0),(pad,pad),(0,0)))
    h = torch.zeros_like(x)
    for i in range(K):
        h = h + torch.einsum("btc,cd->btd", xp[:, i:i+T, :], w1[i])
    h = _gelu(h)[:, ::2, :]
    T1 = h.shape[1]
    hp = _pad(h, ((0,0),(pad,pad),(0,0)))
    f = torch.zeros_like(h)
    for i in range(K):
        f = f + torch.einsum("btc,cd->btd", hp[:, i:i+T1, :], w2[i])
    f = _gelu(f)[:, ::2, :]
    fe = torch.einsum("btd,de->bte", f, w_f)
    ge = torch.einsum("bud,de->bue", g, w_g)
    j = torch.tanh(fe[:, :, None, :] + ge[:, None, :, :])
    return torch.einsum("btud,dv->btuv", j, w_o)
```

```cpp
#include <cuda_runtime.h>
#include <cuda_bf16.h>
#include <cuda.h>
#include <stdint.h>
#include <type_traits>

#define W_SHIFT 1
namespace {

constexpr int NB1 = 168;
constexpr int NB2 = 84;

__device__ __align__(1024) __nv_bfloat16 g_W[(9 + W_SHIFT) * 64 * 4 * 64 * 64];
__device__ __align__(1024) __nv_bfloat16 g_Y2[2 * NB2 * 4 * 64 * 64];
__device__ __align__(1024) float g_ge[16 * 256];

__device__ __forceinline__ uint32_t s2u(const void* p) { return (uint32_t)__cvta_generic_to_shared(p); }
__device__ __forceinline__ void mbar_init(uint32_t b, int c) {
  asm volatile("mbarrier.init.shared::cta.b64 [%0], %1;" ::"r"(b), "r"(c) : "memory");
}
__device__ __forceinline__ void mbar_expect(uint32_t b, int bytes) {
  asm volatile("mbarrier.arrive.expect_tx.shared::cta.b64 _, [%0], %1;" ::"r"(b), "r"(bytes) : "memory");
}
__device__ __forceinline__ void mbar_arrive(uint32_t b) {
  asm volatile("mbarrier.arrive.shared::cta.b64 _, [%0];" ::"r"(b) : "memory");
}
__device__ __forceinline__ void mbar_arrive_cta(uint32_t b, uint32_t cta) {
  asm volatile("{\n.reg .b32 r;\nmapa.shared::cluster.u32 r, %0, %1;\nmbarrier.arrive.shared::cluster.b64 _, [r];\n}" ::"r"(b), "r"(cta) : "memory");
}
__device__ __forceinline__ void mbar_wait(uint32_t b, int ph) {
  asm volatile(
      "{\n.reg .pred p;\n.reg .u32 n;\n"
      "mov.u32 n, 0;\n"
      "MBW_LOOP:\n"
      "mbarrier.try_wait.parity.shared::cta.b64 p, [%0], %1;\n"
      "@p bra MBW_DONE;\n"
      "add.u32 n, n, 1;\n"
      "setp.lt.u32 p, n, 1048576;\n"
      "@p bra MBW_LOOP;\n"
      "MBW_DONE:\n}" ::"r"(b), "r"(ph) : "memory");
}
__device__ __forceinline__ void fence_bar_init() { asm volatile("fence.mbarrier_init.release.cluster;" ::: "memory"); }
__device__ __forceinline__ void fence_async() { asm volatile("fence.proxy.async.shared::cta;" ::: "memory"); }
__device__ __forceinline__ void bar_sync(int id, int n) { asm volatile("bar.sync %0, %1;" ::"r"(id), "r"(n) : "memory"); }
__device__ __forceinline__ void bar_arrive(int id, int n) { asm volatile("bar.arrive %0, %1;" ::"r"(id), "r"(n) : "memory"); }
__device__ __forceinline__ void pdl_wait() { asm volatile("griddepcontrol.wait;" ::: "memory"); }
__device__ __forceinline__ void pdl_launch() { asm volatile("griddepcontrol.launch_dependents;" ::: "memory"); }
__device__ __forceinline__ void prefetch_map(const CUtensorMap* m) {
  asm volatile("prefetch.tensormap [%0];" ::"l"(m) : "memory");
}
template <int P> __device__ __forceinline__ uint64_t policy() {
  uint64_t p;
  if (P == 2) asm("createpolicy.fractional.L2::evict_unchanged.b64 %0, 1.0;" : "=l"(p));
  else asm("createpolicy.fractional.L2::evict_first.b64 %0, 1.0;" : "=l"(p));
  return p;
}
template <int P> __device__ __forceinline__ void tma_ld3(uint32_t dst, const CUtensorMap* m, uint32_t bar, int c0, int c1, int c2) {
  if constexpr (P == 0)
    asm volatile("cp.async.bulk.tensor.3d.shared::cluster.global.mbarrier::complete_tx::bytes [%0], [%1, {%3, %4, %5}], [%2];"
                 ::"r"(dst), "l"(m), "r"(bar), "r"(c0), "r"(c1), "r"(c2) : "memory");
  else
    asm volatile("cp.async.bulk.tensor.3d.shared::cluster.global.mbarrier::complete_tx::bytes.L2::cache_hint [%0], [%1, {%3, %4, %5}], [%2], %6;"
                 ::"r"(dst), "l"(m), "r"(bar), "r"(c0), "r"(c1), "r"(c2), "l"(policy<P>()) : "memory");
}
template <int P> __device__ __forceinline__ void tma_ld3mc(uint32_t dst, const CUtensorMap* m, uint32_t bar, int c0, int c1, int c2) {
  if constexpr (P == 0)
    asm volatile("cp.async.bulk.tensor.3d.shared::cluster.global.mbarrier::complete_tx::bytes.multicast::cluster [%0], [%1, {%3, %4, %5}], [%2], %6;"
                 ::"r"(dst), "l"(m), "r"(bar), "r"(c0), "r"(c1), "r"(c2), "h"((uint16_t)3) : "memory");
  else
    asm volatile("cp.async.bulk.tensor.3d.shared::cluster.global.mbarrier::complete_tx::bytes.multicast::cluster.L2::cache_hint [%0], [%1, {%3, %4, %5}], [%2], %6, %7;"
                 ::"r"(dst), "l"(m), "r"(bar), "r"(c0), "r"(c1), "r"(c2), "h"((uint16_t)3), "l"(policy<P>()) : "memory");
}
template <int P> __device__ __forceinline__ void tma_ld4(uint32_t dst, const CUtensorMap* m, uint32_t bar, int c0, int c1, int c2, int c3) {
  if constexpr (P == 0)
    asm volatile("cp.async.bulk.tensor.4d.shared::cluster.global.mbarrier::complete_tx::bytes [%0], [%1, {%3, %4, %5, %6}], [%2];"
                 ::"r"(dst), "l"(m), "r"(bar), "r"(c0), "r"(c1), "r"(c2), "r"(c3) : "memory");
  else
    asm volatile("cp.async.bulk.tensor.4d.shared::cluster.global.mbarrier::complete_tx::bytes.L2::cache_hint [%0], [%1, {%3, %4, %5, %6}], [%2], %7;"
                 ::"r"(dst), "l"(m), "r"(bar), "r"(c0), "r"(c1), "r"(c2), "r"(c3), "l"(policy<P>()) : "memory");
}
template <int P> __device__ __forceinline__ void tma_ld4mc(uint32_t dst, const CUtensorMap* m, uint32_t bar, int c0, int c1, int c2, int c3) {
  if constexpr (P == 0)
    asm volatile("cp.async.bulk.tensor.4d.shared::cluster.global.mbarrier::complete_tx::bytes.multicast::cluster [%0], [%1, {%3, %4, %5, %6}], [%2], %7;"
                 ::"r"(dst), "l"(m), "r"(bar), "r"(c0), "r"(c1), "r"(c2), "r"(c3), "h"((uint16_t)3) : "memory");
  else
    asm volatile("cp.async.bulk.tensor.4d.shared::cluster.global.mbarrier::complete_tx::bytes.multicast::cluster.L2::cache_hint [%0], [%1, {%3, %4, %5, %6}], [%2], %7, %8;"
                 ::"r"(dst), "l"(m), "r"(bar), "r"(c0), "r"(c1), "r"(c2), "r"(c3), "h"((uint16_t)3), "l"(policy<P>()) : "memory");
}
template <int P> __device__ __forceinline__ void tma_ld5(uint32_t dst, const CUtensorMap* m, uint32_t bar, int c0, int c1, int c2, int c3, int c4) {
  if constexpr (P == 0)
    asm volatile("cp.async.bulk.tensor.5d.shared::cluster.global.mbarrier::complete_tx::bytes [%0], [%1, {%3, %4, %5, %6, %7}], [%2];"
                 ::"r"(dst), "l"(m), "r"(bar), "r"(c0), "r"(c1), "r"(c2), "r"(c3), "r"(c4) : "memory");
  else
    asm volatile("cp.async.bulk.tensor.5d.shared::cluster.global.mbarrier::complete_tx::bytes.L2::cache_hint [%0], [%1, {%3, %4, %5, %6, %7}], [%2], %8;"
                 ::"r"(dst), "l"(m), "r"(bar), "r"(c0), "r"(c1), "r"(c2), "r"(c3), "r"(c4), "l"(policy<P>()) : "memory");
}
template <int P> __device__ __forceinline__ void tma_st3(const CUtensorMap* m, uint32_t src, int c0, int c1, int c2) {
  if constexpr (P == 0)
    asm volatile("cp.async.bulk.tensor.3d.global.shared::cta.bulk_group [%0, {%2, %3, %4}], [%1];" ::"l"(m), "r"(src), "r"(c0), "r"(c1), "r"(c2) : "memory");
  else
    asm volatile("cp.async.bulk.tensor.3d.global.shared::cta.bulk_group.L2::cache_hint [%0, {%2, %3, %4}], [%1], %5;" ::"l"(m), "r"(src), "r"(c0), "r"(c1), "r"(c2), "l"(policy<P>()) : "memory");
}
template <int P> __device__ __forceinline__ void tma_st4(const CUtensorMap* m, uint32_t src, int c0, int c1, int c2, int c3) {
  if constexpr (P == 0)
    asm volatile("cp.async.bulk.tensor.4d.global.shared::cta.bulk_group [%0, {%2, %3, %4, %5}], [%1];" ::"l"(m), "r"(src), "r"(c0), "r"(c1), "r"(c2), "r"(c3) : "memory");
  else
    asm volatile("cp.async.bulk.tensor.4d.global.shared::cta.bulk_group.L2::cache_hint [%0, {%2, %3, %4, %5}], [%1], %6;" ::"l"(m), "r"(src), "r"(c0), "r"(c1), "r"(c2), "r"(c3), "l"(policy<P>()) : "memory");
}
template <int P> __device__ __forceinline__ void tma_st5(const CUtensorMap* m, uint32_t src, int c0, int c1, int c2, int c3, int c4) {
  if constexpr (P == 0)
    asm volatile("cp.async.bulk.tensor.5d.global.shared::cta.bulk_group [%0, {%2, %3, %4, %5, %6}], [%1];" ::"l"(m), "r"(src), "r"(c0), "r"(c1), "r"(c2), "r"(c3), "r"(c4) : "memory");
  else
    asm volatile("cp.async.bulk.tensor.5d.global.shared::cta.bulk_group.L2::cache_hint [%0, {%2, %3, %4, %5, %6}], [%1], %7;" ::"l"(m), "r"(src), "r"(c0), "r"(c1), "r"(c2), "r"(c3), "r"(c4), "l"(policy<P>()) : "memory");
}
__device__ __forceinline__ void bulk_commit() { asm volatile("cp.async.bulk.commit_group;" ::: "memory"); }
template <int N> __device__ __forceinline__ void bulk_wait() { asm volatile("cp.async.bulk.wait_group %0;" ::"n"(N) : "memory"); }
template <int N> __device__ __forceinline__ void bulk_wait_read() { asm volatile("cp.async.bulk.wait_group.read %0;" ::"n"(N) : "memory"); }
__device__ __forceinline__ void wg_fence() { asm volatile("wgmma.fence.sync.aligned;" ::: "memory"); }
__device__ __forceinline__ void wg_commit() { asm volatile("wgmma.commit_group.sync.aligned;" ::: "memory"); }
template <int N> __device__ __forceinline__ void wg_wait() { asm volatile("wgmma.wait_group.sync.aligned %0;" ::"n"(N) : "memory"); }
template <int R> __device__ __forceinline__ void reg_fence(float (&d)[R]) {
#pragma unroll
  for (int i = 0; i < R; i++) asm volatile("" : "+f"(d[i])::"memory");
}
template <int R> __device__ __forceinline__ void reg_fence(uint32_t (&d)[R]) {
#pragma unroll
  for (int i = 0; i < R; i++) asm volatile("" : "+r"(d[i])::"memory");
}
__device__ __forceinline__ void stsm4(uint32_t a, uint32_t r0, uint32_t r1, uint32_t r2, uint32_t r3) {
  asm volatile("stmatrix.sync.aligned.m8n8.x4.shared.b16 [%0], {%1, %2, %3, %4};" ::"r"(a), "r"(r0), "r"(r1), "r"(r2), "r"(r3) : "memory");
}
__device__ __forceinline__ void stsm4t(uint32_t a, uint32_t r0, uint32_t r1, uint32_t r2, uint32_t r3) {
  asm volatile("stmatrix.sync.aligned.m8n8.x4.trans.shared.b16 [%0], {%1, %2, %3, %4};" ::"r"(a), "r"(r0), "r"(r1), "r"(r2), "r"(r3) : "memory");
}
__device__ __forceinline__ void ldsm4(uint32_t a, uint32_t& r0, uint32_t& r1, uint32_t& r2, uint32_t& r3) {
  asm volatile("ldmatrix.sync.aligned.m8n8.x4.shared.b16 {%0, %1, %2, %3}, [%4];" : "=r"(r0), "=r"(r1), "=r"(r2), "=r"(r3) : "r"(a) : "memory");
}
__device__ __forceinline__ void ldg128(const uint4* p, uint32_t& a, uint32_t& b, uint32_t& c, uint32_t& d) {
  asm volatile("ld.global.nc.v4.u32 {%0, %1, %2, %3}, [%4];" : "=r"(a), "=r"(b), "=r"(c), "=r"(d) : "l"(p));
}
__device__ __forceinline__ uint32_t pack2(float lo, float hi) {
  uint32_t r;
  asm("cvt.rn.bf16x2.f32 %0, %1, %2;" : "=r"(r) : "f"(hi), "f"(lo));
  return r;
}
__device__ __forceinline__ float tanh_f32(float x) {
  float y;
  asm("tanh.approx.f32 %0, %1;" : "=f"(y) : "f"(x));
  return y;
}
__device__ __forceinline__ float gelu(float hx) {
  const float u = hx * fmaf(hx * hx, 8.0f * 0.044715f * 0.7978845608028654f, 2.0f * 0.7978845608028654f);
  return fmaf(hx, tanh_f32(u), hx);
}
__device__ __forceinline__ uint64_t mk_desc4(uint32_t addr4, uint32_t lbo, uint32_t sbo, uint32_t swz) {
  const uint32_t lo = addr4 + ((lbo >> 4) << 16), hi = (sbo >> 4) | (swz << 30);
  uint64_t d;
  asm("mov.b64 %0, {%1, %2};" : "=l"(d) : "r"(lo), "r"(hi));
  return d;
}
#define mk_desc(base, off, lbo, sbo, swz) mk_desc4((((base) & 0x3FFFF) >> 4) + ((off) >> 4), lbo, sbo, swz)

template <int SA, int SB, int TA, int TB>
__device__ __forceinline__ void wgmma_ss_32(float (&d)[16], uint64_t da, uint64_t db, int sd) {
  asm volatile("{\n.reg .pred p;\nsetp.ne.b32 p, %18, 0;\n"
      "wgmma.mma_async.sync.aligned.m64n32k16.f32.bf16.bf16 {"
      "%0, %1, %2, %3, %4, %5, %6, %7, %8, %9, %10, %11, %12, %13, %14, %15"
      "}, %16, %17, p, %19, %20, %21, %22;\n}\n"
      : "+f"(d[0]), "+f"(d[1]), "+f"(d[2]), "+f"(d[3]), "+f"(d[4]), "+f"(d[5]), "+f"(d[6]), "+f"(d[7]), "+f"(d[8]),
        "+f"(d[9]), "+f"(d[10]), "+f"(d[11]), "+f"(d[12]), "+f"(d[13]), "+f"(d[14]), "+f"(d[15])
      : "l"(da), "l"(db), "r"(sd), "n"(SA), "n"(SB), "n"(TA), "n"(TB));
}
template <int SA, int SB, int TA, int TB>
__device__ __forceinline__ void wgmma_ss_48(float (&d)[24], uint64_t da, uint64_t db, int sd) {
  asm volatile("{\n.reg .pred p;\nsetp.ne.b32 p, %26, 0;\n"
      "wgmma.mma_async.sync.aligned.m64n48k16.f32.bf16.bf16 {"
      "%0, %1, %2, %3, %4, %5, %6, %7, %8, %9, %10, %11, %12, %13, %14, %15, %16, %17, %18, %19, %20, %21, %22, %23"
      "}, %24, %25, p, %27, %28, %29, %30;\n}\n"
      : "+f"(d[0]), "+f"(d[1]), "+f"(d[2]), "+f"(d[3]), "+f"(d[4]), "+f"(d[5]), "+f"(d[6]), "+f"(d[7]), "+f"(d[8]),
        "+f"(d[9]), "+f"(d[10]), "+f"(d[11]), "+f"(d[12]), "+f"(d[13]), "+f"(d[14]), "+f"(d[15]), "+f"(d[16]),
        "+f"(d[17]), "+f"(d[18]), "+f"(d[19]), "+f"(d[20]), "+f"(d[21]), "+f"(d[22]), "+f"(d[23])
      : "l"(da), "l"(db), "r"(sd), "n"(SA), "n"(SB), "n"(TA), "n"(TB));
}
template <int SA, int SB, int TA, int TB>
__device__ __forceinline__ void wgmma_ss_128(float (&d)[64], uint64_t da, uint64_t db, int sd) {
  asm volatile("{\n.reg .pred p;\nsetp.ne.b32 p, %66, 0;\n"
      "wgmma.mma_async.sync.aligned.m64n128k16.f32.bf16.bf16 {"
      "%0, %1, %2, %3, %4, %5, %6, %7, %8, %9, %10, %11, %12, %13, %14, %15, %16, %17, %18, %19, %20, %21, %22, %23, "
      "%24, %25, %26, %27, %28, %29, %30, %31, %32, %33, %34, %35, %36, %37, %38, %39, %40, %41, %42, %43, %44, %45, "
      "%46, %47, %48, %49, %50, %51, %52, %53, %54, %55, %56, %57, %58, %59, %60, %61, %62, %63"
      "}, %64, %65, p, %67, %68, %69, %70;\n}\n"
      : "+f"(d[0]), "+f"(d[1]), "+f"(d[2]), "+f"(d[3]), "+f"(d[4]), "+f"(d[5]), "+f"(d[6]), "+f"(d[7]), "+f"(d[8]),
        "+f"(d[9]), "+f"(d[10]), "+f"(d[11]), "+f"(d[12]), "+f"(d[13]), "+f"(d[14]), "+f"(d[15]), "+f"(d[16]),
        "+f"(d[17]), "+f"(d[18]), "+f"(d[19]), "+f"(d[20]), "+f"(d[21]), "+f"(d[22]), "+f"(d[23]), "+f"(d[24]),
        "+f"(d[25]), "+f"(d[26]), "+f"(d[27]), "+f"(d[28]), "+f"(d[29]), "+f"(d[30]), "+f"(d[31]), "+f"(d[32]),
        "+f"(d[33]), "+f"(d[34]), "+f"(d[35]), "+f"(d[36]), "+f"(d[37]), "+f"(d[38]), "+f"(d[39]), "+f"(d[40]),
        "+f"(d[41]), "+f"(d[42]), "+f"(d[43]), "+f"(d[44]), "+f"(d[45]), "+f"(d[46]), "+f"(d[47]), "+f"(d[48]),
        "+f"(d[49]), "+f"(d[50]), "+f"(d[51]), "+f"(d[52]), "+f"(d[53]), "+f"(d[54]), "+f"(d[55]), "+f"(d[56]),
        "+f"(d[57]), "+f"(d[58]), "+f"(d[59]), "+f"(d[60]), "+f"(d[61]), "+f"(d[62]), "+f"(d[63])
      : "l"(da), "l"(db), "r"(sd), "n"(SA), "n"(SB), "n"(TA), "n"(TB));
}
template <int SA, int SB, int TA, int TB>
__device__ __forceinline__ void wgmma_ss_168(float (&d)[84], uint64_t da, uint64_t db, int sd) {
  asm volatile("{\n.reg .pred p;\nsetp.ne.b32 p, %86, 0;\n"
      "wgmma.mma_async.sync.aligned.m64n168k16.f32.bf16.bf16 {"
      "%0, %1, %2, %3, %4, %5, %6, %7, %8, %9, %10, %11, %12, %13, %14, %15, %16, %17, %18, %19, %20, %21, %22, %23, "
      "%24, %25, %26, %27, %28, %29, %30, %31, %32, %33, %34, %35, %36, %37, %38, %39, %40, %41, %42, %43, %44, %45, "
      "%46, %47, %48, %49, %50, %51, %52, %53, %54, %55, %56, %57, %58, %59, %60, %61, %62, %63, %64, %65, %66, %67, "
      "%68, %69, %70, %71, %72, %73, %74, %75, %76, %77, %78, %79, %80, %81, %82, %83"
      "}, %84, %85, p, %87, %88, %89, %90;\n}\n"
      : "+f"(d[0]), "+f"(d[1]), "+f"(d[2]), "+f"(d[3]), "+f"(d[4]), "+f"(d[5]), "+f"(d[6]), "+f"(d[7]), "+f"(d[8]),
        "+f"(d[9]), "+f"(d[10]), "+f"(d[11]), "+f"(d[12]), "+f"(d[13]), "+f"(d[14]), "+f"(d[15]), "+f"(d[16]),
        "+f"(d[17]), "+f"(d[18]), "+f"(d[19]), "+f"(d[20]), "+f"(d[21]), "+f"(d[22]), "+f"(d[23]), "+f"(d[24]),
        "+f"(d[25]), "+f"(d[26]), "+f"(d[27]), "+f"(d[28]), "+f"(d[29]), "+f"(d[30]), "+f"(d[31]), "+f"(d[32]),
        "+f"(d[33]), "+f"(d[34]), "+f"(d[35]), "+f"(d[36]), "+f"(d[37]), "+f"(d[38]), "+f"(d[39]), "+f"(d[40]),
        "+f"(d[41]), "+f"(d[42]), "+f"(d[43]), "+f"(d[44]), "+f"(d[45]), "+f"(d[46]), "+f"(d[47]), "+f"(d[48]),
        "+f"(d[49]), "+f"(d[50]), "+f"(d[51]), "+f"(d[52]), "+f"(d[53]), "+f"(d[54]), "+f"(d[55]), "+f"(d[56]),
        "+f"(d[57]), "+f"(d[58]), "+f"(d[59]), "+f"(d[60]), "+f"(d[61]), "+f"(d[62]), "+f"(d[63]), "+f"(d[64]),
        "+f"(d[65]), "+f"(d[66]), "+f"(d[67]), "+f"(d[68]), "+f"(d[69]), "+f"(d[70]), "+f"(d[71]), "+f"(d[72]),
        "+f"(d[73]), "+f"(d[74]), "+f"(d[75]), "+f"(d[76]), "+f"(d[77]), "+f"(d[78]), "+f"(d[79]), "+f"(d[80]),
        "+f"(d[81]), "+f"(d[82]), "+f"(d[83])
      : "l"(da), "l"(db), "r"(sd), "n"(SA), "n"(SB), "n"(TA), "n"(TB));
}
template <int SA, int SB, int TB>
__device__ __forceinline__ void wgmma_rs_64(float (&d)[32], uint32_t a0, uint32_t a1, uint32_t a2, uint32_t a3, uint64_t db, int sd) {
  asm volatile("{\n.reg .pred p;\nsetp.ne.b32 p, %37, 0;\n"
      "wgmma.mma_async.sync.aligned.m64n64k16.f32.bf16.bf16 {"
      "%0, %1, %2, %3, %4, %5, %6, %7, %8, %9, %10, %11, %12, %13, %14, %15, %16, %17, %18, %19, %20, %21, %22, %23, "
      "%24, %25, %26, %27, %28, %29, %30, %31"
      "}, {%32, %33, %34, %35}, %36, p, %38, %39, %40;\n}\n"
      : "+f"(d[0]), "+f"(d[1]), "+f"(d[2]), "+f"(d[3]), "+f"(d[4]), "+f"(d[5]), "+f"(d[6]), "+f"(d[7]), "+f"(d[8]),
        "+f"(d[9]), "+f"(d[10]), "+f"(d[11]), "+f"(d[12]), "+f"(d[13]), "+f"(d[14]), "+f"(d[15]), "+f"(d[16]),
        "+f"(d[17]), "+f"(d[18]), "+f"(d[19]), "+f"(d[20]), "+f"(d[21]), "+f"(d[22]), "+f"(d[23]), "+f"(d[24]),
        "+f"(d[25]), "+f"(d[26]), "+f"(d[27]), "+f"(d[28]), "+f"(d[29]), "+f"(d[30]), "+f"(d[31])
      : "r"(a0), "r"(a1), "r"(a2), "r"(a3), "l"(db), "r"(sd), "n"(SA), "n"(SB), "n"(TB));
}
template <int SA, int SB, int TB>
__device__ __forceinline__ void wgmma_rs_128(float (&d)[64], uint32_t a0, uint32_t a1, uint32_t a2, uint32_t a3, uint64_t db, int sd) {
  asm volatile("{\n.reg .pred p;\nsetp.ne.b32 p, %69, 0;\n"
      "wgmma.mma_async.sync.aligned.m64n128k16.f32.bf16.bf16 {"
      "%0, %1, %2, %3, %4, %5, %6, %7, %8, %9, %10, %11, %12, %13, %14, %15, %16, %17, %18, %19, %20, %21, %22, %23, "
      "%24, %25, %26, %27, %28, %29, %30, %31, %32, %33, %34, %35, %36, %37, %38, %39, %40, %41, %42, %43, %44, %45, "
      "%46, %47, %48, %49, %50, %51, %52, %53, %54, %55, %56, %57, %58, %59, %60, %61, %62, %63"
      "}, {%64, %65, %66, %67}, %68, p, %70, %71, %72;\n}\n"
      : "+f"(d[0]), "+f"(d[1]), "+f"(d[2]), "+f"(d[3]), "+f"(d[4]), "+f"(d[5]), "+f"(d[6]), "+f"(d[7]), "+f"(d[8]),
        "+f"(d[9]), "+f"(d[10]), "+f"(d[11]), "+f"(d[12]), "+f"(d[13]), "+f"(d[14]), "+f"(d[15]), "+f"(d[16]),
        "+f"(d[17]), "+f"(d[18]), "+f"(d[19]), "+f"(d[20]), "+f"(d[21]), "+f"(d[22]), "+f"(d[23]), "+f"(d[24]),
        "+f"(d[25]), "+f"(d[26]), "+f"(d[27]), "+f"(d[28]), "+f"(d[29]), "+f"(d[30]), "+f"(d[31]), "+f"(d[32]),
        "+f"(d[33]), "+f"(d[34]), "+f"(d[35]), "+f"(d[36]), "+f"(d[37]), "+f"(d[38]), "+f"(d[39]), "+f"(d[40]),
        "+f"(d[41]), "+f"(d[42]), "+f"(d[43]), "+f"(d[44]), "+f"(d[45]), "+f"(d[46]), "+f"(d[47]), "+f"(d[48]),
        "+f"(d[49]), "+f"(d[50]), "+f"(d[51]), "+f"(d[52]), "+f"(d[53]), "+f"(d[54]), "+f"(d[55]), "+f"(d[56]),
        "+f"(d[57]), "+f"(d[58]), "+f"(d[59]), "+f"(d[60]), "+f"(d[61]), "+f"(d[62]), "+f"(d[63])
      : "r"(a0), "r"(a1), "r"(a2), "r"(a3), "l"(db), "r"(sd), "n"(SA), "n"(SB), "n"(TB));
}
template <int SA, int SB, int TB>
__device__ __forceinline__ void wgmma_rs_256(float (&d)[128], uint32_t a0, uint32_t a1, uint32_t a2, uint32_t a3, uint64_t db, int sd) {
  asm volatile("{\n.reg .pred p;\nsetp.ne.b32 p, %133, 0;\n"
      "wgmma.mma_async.sync.aligned.m64n256k16.f32.bf16.bf16 {"
      "%0, %1, %2, %3, %4, %5, %6, %7, %8, %9, %10, %11, %12, %13, %14, %15, %16, %17, %18, %19, %20, %21, %22, %23, "
      "%24, %25, %26, %27, %28, %29, %30, %31, %32, %33, %34, %35, %36, %37, %38, %39, %40, %41, %42, %43, %44, %45, "
      "%46, %47, %48, %49, %50, %51, %52, %53, %54, %55, %56, %57, %58, %59, %60, %61, %62, %63, %64, %65, %66, %67, "
      "%68, %69, %70, %71, %72, %73, %74, %75, %76, %77, %78, %79, %80, %81, %82, %83, %84, %85, %86, %87, %88, %89, "
      "%90, %91, %92, %93, %94, %95, %96, %97, %98, %99, %100, %101, %102, %103, %104, %105, %106, %107, %108, %109, "
      "%110, %111, %112, %113, %114, %115, %116, %117, %118, %119, %120, %121, %122, %123, %124, %125, %126, %127"
      "}, {%128, %129, %130, %131}, %132, p, %134, %135, %136;\n}\n"
      : "+f"(d[0]), "+f"(d[1]), "+f"(d[2]), "+f"(d[3]), "+f"(d[4]), "+f"(d[5]), "+f"(d[6]), "+f"(d[7]), "+f"(d[8]),
        "+f"(d[9]), "+f"(d[10]), "+f"(d[11]), "+f"(d[12]), "+f"(d[13]), "+f"(d[14]), "+f"(d[15]), "+f"(d[16]),
        "+f"(d[17]), "+f"(d[18]), "+f"(d[19]), "+f"(d[20]), "+f"(d[21]), "+f"(d[22]), "+f"(d[23]), "+f"(d[24]),
        "+f"(d[25]), "+f"(d[26]), "+f"(d[27]), "+f"(d[28]), "+f"(d[29]), "+f"(d[30]), "+f"(d[31]), "+f"(d[32]),
        "+f"(d[33]), "+f"(d[34]), "+f"(d[35]), "+f"(d[36]), "+f"(d[37]), "+f"(d[38]), "+f"(d[39]), "+f"(d[40]),
        "+f"(d[41]), "+f"(d[42]), "+f"(d[43]), "+f"(d[44]), "+f"(d[45]), "+f"(d[46]), "+f"(d[47]), "+f"(d[48]),
        "+f"(d[49]), "+f"(d[50]), "+f"(d[51]), "+f"(d[52]), "+f"(d[53]), "+f"(d[54]), "+f"(d[55]), "+f"(d[56]),
        "+f"(d[57]), "+f"(d[58]), "+f"(d[59]), "+f"(d[60]), "+f"(d[61]), "+f"(d[62]), "+f"(d[63]), "+f"(d[64]),
        "+f"(d[65]), "+f"(d[66]), "+f"(d[67]), "+f"(d[68]), "+f"(d[69]), "+f"(d[70]), "+f"(d[71]), "+f"(d[72]),
        "+f"(d[73]), "+f"(d[74]), "+f"(d[75]), "+f"(d[76]), "+f"(d[77]), "+f"(d[78]), "+f"(d[79]), "+f"(d[80]),
        "+f"(d[81]), "+f"(d[82]), "+f"(d[83]), "+f"(d[84]), "+f"(d[85]), "+f"(d[86]), "+f"(d[87]), "+f"(d[88]),
        "+f"(d[89]), "+f"(d[90]), "+f"(d[91]), "+f"(d[92]), "+f"(d[93]), "+f"(d[94]), "+f"(d[95]), "+f"(d[96]),
        "+f"(d[97]), "+f"(d[98]), "+f"(d[99]), "+f"(d[100]), "+f"(d[101]), "+f"(d[102]), "+f"(d[103]), "+f"(d[104]),
        "+f"(d[105]), "+f"(d[106]), "+f"(d[107]), "+f"(d[108]), "+f"(d[109]), "+f"(d[110]), "+f"(d[111]),
        "+f"(d[112]), "+f"(d[113]), "+f"(d[114]), "+f"(d[115]), "+f"(d[116]), "+f"(d[117]), "+f"(d[118]),
        "+f"(d[119]), "+f"(d[120]), "+f"(d[121]), "+f"(d[122]), "+f"(d[123]), "+f"(d[124]), "+f"(d[125]),
        "+f"(d[126]), "+f"(d[127])
      : "r"(a0), "r"(a1), "r"(a2), "r"(a3), "l"(db), "r"(sd), "n"(SA), "n"(SB), "n"(TB));
}

__device__ const __align__(128) uint32_t c_img[3584] = {
    0x00003c80, 0x00003c80, 0x00003c80, 0x00003c80, 0x00003c80, 0x00003c80, 0x00003c80, 0x00003c80, 0x00003c80, 0x00003c80,
    0x00003c80, 0x00003c80, 0x00003c80, 0x00003c80, 0x00003c80, 0x00003c80, 0x00003c80, 0x00003c80, 0x00003c80, 0x00003c80,
    0x00003c80, 0x00003c80, 0x00003c80, 0x00003c80, 0x00003c80, 0x00003c80, 0x00003c80, 0x00003c80, 0x00003c80, 0x00003c80,
    0x00003c80, 0x00003c80, 0x3c463c22, 0x3c623bf1, 0x3c753b95, 0x3c7f3ac9, 0x3ac93c7f, 0x3b953c75, 0x3bf13c62, 0x3c223c46,
    0x3c22bc46, 0x3bf1bc62, 0x3b95bc75, 0x3ac9bc7f, 0x3c7fbac9, 0x3c75bb95, 0x3c62bbf1, 0x3c46bc22, 0xbc46bc22, 0xbc62bbf1,
    0xbc75bb95, 0xbc7fbac9, 0xbac9bc7f, 0xbb95bc75, 0xbbf1bc62, 0xbc22bc46, 0xbc223c46, 0xbbf13c62, 0xbb953c75, 0xbac93c7f,
    0xbc7f3ac9, 0xbc753b95, 0xbc623bf1, 0xbc463c22, 0xbb48bc7b, 0xbc0ebc55, 0xbc55bc0e, 0xbc7bbb48, 0xbc7b3b48, 0xbc553c0e,
    0xbc0e3c55, 0xbb483c7b, 0x3b483c7b, 0x3c0e3c55, 0x3c553c0e, 0x3c7b3b48, 0x3c7bbb48, 0x3c55bc0e, 0x3c0ebc55, 0x3b48bc7b,
    0xbb48bc7b, 0xbc0ebc55, 0xbc55bc0e, 0xbc7bbb48, 0xbc7b3b48, 0xbc553c0e, 0xbc0e3c55, 0xbb483c7b, 0x3b483c7b, 0x3c0e3c55,
    0x3c553c0e, 0x3c7b3b48, 0x3c7bbb48, 0x3c55bc0e, 0x3c0ebc55, 0x3b48bc7b, 0x3c623bf1, 0x3c7fbac9, 0x3c46bc22, 0x3b95bc75,
    0xbc753b95, 0xbc223c46, 0xbac93c7f, 0x3bf13c62, 0x3bf1bc62, 0xbac9bc7f, 0xbc22bc46, 0xbc75bb95, 0x3b953c75, 0x3c463c22,
    0x3c7f3ac9, 0x3c62bbf1, 0xbc62bbf1, 0xbc7f3ac9, 0xbc463c22, 0xbb953c75, 0x3c75bb95, 0x3c22bc46, 0x3ac9bc7f, 0xbbf1bc62,
    0xbbf13c62, 0x3ac93c7f, 0x3c223c46, 0x3c753b95, 0xbb95bc75, 0xbc46bc22, 0xbc7fbac9, 0xbc623bf1, 0x3bc43c6d, 0x3c6d3bc4,
    0x3c6dbbc4, 0x3bc4bc6d, 0xbbc4bc6d, 0xbc6dbbc4, 0xbc6d3bc4, 0xbbc43c6d, 0x3bc43c6d, 0x3c6d3bc4, 0x3c6dbbc4, 0x3bc4bc6d,
    0xbbc4bc6d, 0xbc6dbbc4, 0xbc6d3bc4, 0xbbc43c6d, 0x3bc43c6d, 0x3c6d3bc4, 0x3c6dbbc4, 0x3bc4bc6d, 0xbbc4bc6d, 0xbc6dbbc4,
    0xbc6d3bc4, 0xbbc43c6d, 0x3bc43c6d, 0x3c6d3bc4, 0x3c6dbbc4, 0x3bc4bc6d, 0xbbc4bc6d, 0xbc6dbbc4, 0xbc6d3bc4, 0xbbc43c6d,
    0x3c753b95, 0x3c46bc22, 0xbac9bc7f, 0xbc62bbf1, 0xbbf1bc62, 0xbc7fbac9, 0xbc223c46, 0x3b953c75, 0x3b95bc75, 0xbc22bc46,
    0xbc7f3ac9, 0xbbf13c62, 0xbc623bf1, 0xbac93c7f, 0x3c463c22, 0x3c75bb95, 0xbc75bb95, 0xbc463c22, 0x3ac93c7f, 0x3c623bf1,
    0x3bf13c62, 0x3c7f3ac9, 0x3c22bc46, 0xbb95bc75, 0xbb953c75, 0x3c223c46, 0x3c7fbac9, 0x3bf1bc62, 0x3c62bbf1, 0x3ac9bc7f,
    0xbc46bc22, 0xbc753b95, 0xbc0ebc55, 0xbc7b3b48, 0xbb483c7b, 0x3c553c0e, 0x3c55bc0e, 0xbb48bc7b, 0xbc7bbb48, 0xbc0e3c55,
    0x3c0e3c55, 0x3c7bbb48, 0x3b48bc7b, 0xbc55bc0e, 0xbc553c0e, 0x3b483c7b, 0x3c7b3b48, 0x3c0ebc55, 0xbc0ebc55, 0xbc7b3b48,
    0xbb483c7b, 0x3c553c0e, 0x3c55bc0e, 0xbb48bc7b, 0xbc7bbb48, 0xbc0e3c55, 0x3c0e3c55, 0x3c7bbb48, 0x3b48bc7b, 0xbc55bc0e,
    0xbc553c0e, 0x3b483c7b, 0x3c7b3b48, 0x3c0ebc55, 0x3c7f3ac9, 0x3b95bc75, 0xbc62bbf1, 0xbc223c46, 0x3c46bc22, 0xbbf1bc62,
    0xbc753b95, 0x3ac93c7f, 0x3ac9bc7f, 0xbc75bb95, 0xbbf13c62, 0x3c463c22, 0xbc22bc46, 0xbc623bf1, 0x3b953c75, 0x3c7fbac9,
    0xbc7fbac9, 0xbb953c75, 0x3c623bf1, 0x3c22bc46, 0xbc463c22, 0x3bf13c62, 0x3c75bb95, 0xbac9bc7f, 0xbac93c7f, 0x3c753b95,
    0x3bf1bc62, 0xbc46bc22, 0x3c223c46, 0x3c62bbf1, 0xbb95bc75, 0xbc7f3ac9, 0x3a493c80, 0x3b163c7d, 0x3b793c78, 0x3bac3c71,
    0x3bdb3c67, 0x3c043c5c, 0x3c183c4e, 0x3c2c3c3e, 0x3c3e3c2c, 0x3c4e3c18, 0x3c5c3c04, 0x3c673bdb, 0x3c713bac, 0x3c783b79,
    0x3c7d3b16, 0x3c803a49, 0x3c80ba49, 0x3c7dbb16, 0x3c78bb79, 0x3c71bbac, 0x3c67bbdb, 0x3c5cbc04, 0x3c4ebc18, 0x3c3ebc2c,
    0x3c2cbc3e, 0x3c18bc4e, 0x3c04bc5c, 0x3bdbbc67, 0x3bacbc71, 0x3b79bc78, 0x3b16bc7d, 0x3a49bc80, 0x3c783b79, 0x3c80ba49,
    0x3c71bbac, 0x3c4ebc18, 0x3b163c7d, 0x3bdb3c67, 0x3c2c3c3e, 0x3c5c3c04, 0xbc04bc5c, 0xbc3ebc2c, 0xbc67bbdb, 0xbc7dbb16,
    0x3c18bc4e, 0x3bacbc71, 0x3a49bc80, 0xbb79bc78, 0xbb793c78, 0x3a493c80, 0x3bac3c71, 0x3c183c4e, 0xbc7d3b16, 0xbc673bdb,
    0xbc3e3c2c, 0xbc043c5c, 0x3c5cbc04, 0x3c2cbc3e, 0x3bdbbc67, 0x3b16bc7d, 0x3c4e3c18, 0x3c713bac, 0x3c803a49, 0x3c78bb79,
    0xbc5cbc04, 0xbc80ba49, 0xbc673bdb, 0xbc183c4e, 0xbb163c7d, 0x3bac3c71, 0x3c3e3c2c, 0x3c783b79, 0x3b793c78, 0x3c2c3c3e,
    0x3c713bac, 0x3c7dbb16, 0x3c4ebc18, 0x3bdbbc67, 0xba49bc80, 0xbc04bc5c, 0xbc043c5c, 0xba493c80, 0x3bdb3c67, 0x3c4e3c18,
    0x3c7d3b16, 0x3c71bbac, 0x3c2cbc3e, 0x3b79bc78, 0x3c78bb79, 0x3c3ebc2c, 0x3bacbc71, 0xbb16bc7d, 0xbc18bc4e, 0xbc67bbdb,
    0xbc803a49, 0xbc5c3c04, 0x3c3ebc2c, 0x3b16bc7d, 0xbc04bc5c, 0xbc71bbac, 0xbbdb3c67, 0x3b793c78, 0x3c4e3c18, 0x3c80ba49,
    0x3a49bc80, 0xbc18bc4e, 0xbc78bb79, 0xbc673bdb, 0x3bac3c71, 0x3c5c3c04, 0x3c7dbb16, 0x3c2cbc3e, 0x3c2c3c3e, 0x3c7d3b16,
    0x3c5cbc04, 0x3bacbc71, 0xbc67bbdb, 0xbc783b79, 0xbc183c4e, 0x3a493c80, 0x3c803a49, 0x3c4ebc18, 0x3b79bc78, 0xbbdbbc67,
    0xbc713bac, 0xbc043c5c, 0x3b163c7d, 0x3c3e3c2c, 0x3c67bbdb, 0x3b79bc78, 0xbc18bc4e, 0xbc80ba49, 0xbc2c3c3e, 0x3b163c7d,
    0x3c5c3c04, 0x3c71bbac, 0x3bacbc71, 0xbc04bc5c, 0xbc7dbb16, 0xbc3e3c2c, 0x3a493c80, 0x3c4e3c18, 0x3c78bb79, 0x3bdbbc67,
    0x3bdb3c67, 0x3c783b79, 0x3c4ebc18, 0x3a49bc80, 0xbc3ebc2c, 0xbc7d3b16, 0xbc043c5c, 0x3bac3c71, 0x3c713bac, 0x3c5cbc04,
    0x3b16bc7d, 0xbc2cbc3e, 0xbc803a49, 0xbc183c4e, 0x3b793c78, 0x3c673bdb, 0xbb16bc7d, 0xbc71bbac, 0xbc3e3c2c, 0x3b793c78,
    0xbc5c3c04, 0x3a493c80, 0x3c673bdb, 0x3c4ebc18, 0xbc183c4e, 0x3bdb3c67, 0x3c803a49, 0x3c04bc5c, 0x3c783b79, 0x3c2cbc3e,
    0xbbacbc71, 0xbc7dbb16, 0xbc7d3b16, 0xbbac3c71, 0x3c2c3c3e, 0x3c78bb79, 0x3c043c5c, 0x3c80ba49, 0x3bdbbc67, 0xbc18bc4e,
    0x3c4e3c18, 0x3c67bbdb, 0x3a49bc80, 0xbc5cbc04, 0x3b79bc78, 0xbc3ebc2c, 0xbc713bac, 0xbb163c7d, 0xbb163c7d, 0x3c673bdb,
    0x3c2cbc3e, 0xbc04bc5c, 0xbc783b79, 0xba493c80, 0x3c713bac, 0x3c18bc4e, 0x3c4ebc18, 0xbbacbc71, 0xbc803a49, 0xbb793c78,
    0x3c5c3c04, 0x3c3ebc2c, 0xbbdbbc67, 0xbc7d3b16, 0xbc7dbb16, 0xbbdb3c67, 0x3c3e3c2c, 0x3c5cbc04, 0xbb79bc78, 0xbc80ba49,
    0xbbac3c71, 0x3c4e3c18, 0x3c183c4e, 0x3c71bbac, 0xba49bc80, 0xbc78bb79, 0xbc043c5c, 0x3c2c3c3e, 0x3c67bbdb, 0xbb16bc7d,
    0xbc67bbdb, 0xbc043c5c, 0x3c4e3c18, 0x3c2cbc3e, 0xbc80ba49, 0xbb163c7d, 0x3c783b79, 0x3bacbc71, 0xbc713bac, 0x3b793c78,
    0x3c7dbb16, 0xba49bc80, 0xbc3e3c2c, 0x3c183c4e, 0x3c5cbc04, 0xbbdbbc67, 0xbbdb3c67, 0x3c5c3c04, 0x3c18bc4e, 0xbc3ebc2c,
    0xba493c80, 0x3c7d3b16, 0x3b79bc78, 0xbc71bbac, 0x3bac3c71, 0x3c78bb79, 0xbb16bc7d, 0xbc803a49, 0x3c2c3c3e, 0x3c4ebc18,
    0xbc04bc5c, 0xbc673bdb, 0x3c353c35, 0x3c35bc35, 0xbc35bc35, 0xbc353c35, 0x3c353c35, 0x3c35bc35, 0xbc35bc35, 0xbc353c35,
    0x3c353c35, 0x3c35bc35, 0xbc35bc35, 0xbc353c35, 0x3c353c35, 0x3c35bc35, 0xbc35bc35, 0xbc353c35, 0x3c353c35, 0x3c35bc35,
    0xbc35bc35, 0xbc353c35, 0x3c353c35, 0x3c35bc35, 0xbc35bc35, 0xbc353c35, 0x3c353c35, 0x3c35bc35, 0xbc35bc35, 0xbc353c35,
    0x3c353c35, 0x3c35bc35, 0xbc35bc35, 0xbc353c35, 0x3c7fbac9, 0xbb95bc75, 0xbc623bf1, 0x3c223c46, 0x3c463c22, 0x3bf1bc62,
    0xbc75bb95, 0xbac93c7f, 0xbac9bc7f, 0xbc753b95, 0x3bf13c62, 0x3c46bc22, 0x3c22bc46, 0xbc62bbf1, 0xbb953c75, 0x3c7f3ac9,
    0xbc7f3ac9, 0x3b953c75, 0x3c62bbf1, 0xbc22bc46, 0xbc46bc22, 0xbbf13c62, 0x3c753b95, 0x3ac9bc7f, 0x3ac93c7f, 0x3c75bb95,
    0xbbf1bc62, 0xbc463c22, 0xbc223c46, 0x3c623bf1, 0x3b95bc75, 0xbc7fbac9, 0xbc55bc0e, 0xbb483c7b, 0x3c7bbb48, 0xbc0ebc55,
    0xbc0e3c55, 0x3c7b3b48, 0xbb48bc7b, 0xbc553c0e, 0x3c553c0e, 0x3b48bc7b, 0xbc7b3b48, 0x3c0e3c55, 0x3c0ebc55, 0xbc7bbb48,
    0x3b483c7b, 0x3c55bc0e, 0xbc55bc0e, 0xbb483c7b, 0x3c7bbb48, 0xbc0ebc55, 0xbc0e3c55, 0x3c7b3b48, 0xbb48bc7b, 0xbc553c0e,
    0x3c553c0e, 0x3b48bc7b, 0xbc7b3b48, 0x3c0e3c55, 0x3c0ebc55, 0xbc7bbb48, 0x3b483c7b, 0x3c55bc0e, 0x3c75bb95, 0xbc46bc22,
    0xbac93c7f, 0x3c62bbf1, 0xbbf13c62, 0x3c7fbac9, 0xbc22bc46, 0xbb953c75, 0xbb95bc75, 0xbc223c46, 0x3c7f3ac9, 0xbbf1bc62,
    0x3c623bf1, 0xbac9bc7f, 0xbc463c22, 0x3c753b95, 0xbc753b95, 0x3c463c22, 0x3ac9bc7f, 0xbc623bf1, 0x3bf1bc62, 0xbc7f3ac9,
    0x3c223c46, 0x3b95bc75, 0x3b953c75, 0x3c22bc46, 0xbc7fbac9, 0x3bf13c62, 0xbc62bbf1, 0x3ac93c7f, 0x3c46bc22, 0xbc75bb95,
    0x3c6d3bc4, 0xbbc4bc6d, 0xbbc43c6d, 0x3c6dbbc4, 0xbc6dbbc4, 0x3bc43c6d, 0x3bc4bc6d, 0xbc6d3bc4, 0x3c6d3bc4, 0xbbc4bc6d,
    0xbbc43c6d, 0x3c6dbbc4, 0xbc6dbbc4, 0x3bc43c6d, 0x3bc4bc6d, 0xbc6d3bc4, 0x3c6d3bc4, 0xbbc4bc6d, 0xbbc43c6d, 0x3c6dbbc4,
    0xbc6dbbc4, 0x3bc43c6d, 0x3bc4bc6d, 0xbc6d3bc4, 0x3c6d3bc4, 0xbbc4bc6d, 0xbbc43c6d, 0x3c6dbbc4, 0xbc6dbbc4, 0x3bc43c6d,
    0x3bc4bc6d, 0xbc6d3bc4, 0x3c62bbf1, 0xbc7fbac9, 0x3c463c22, 0xbb95bc75, 0xbc75bb95, 0x3c223c46, 0xbac9bc7f, 0xbbf13c62,
    0xbbf1bc62, 0xbac93c7f, 0x3c22bc46, 0xbc753b95, 0xbb953c75, 0x3c46bc22, 0xbc7f3ac9, 0x3c623bf1, 0xbc623bf1, 0x3c7f3ac9,
    0xbc46bc22, 0x3b953c75, 0x3c753b95, 0xbc22bc46, 0x3ac93c7f, 0x3bf1bc62, 0x3bf13c62, 0x3ac9bc7f, 0xbc223c46, 0x3c75bb95,
    0x3b95bc75, 0xbc463c22, 0x3c7fbac9, 0xbc62bbf1, 0xbc7bbb48, 0x3c553c0e, 0xbc0ebc55, 0x3b483c7b, 0x3b48bc7b, 0xbc0e3c55,
    0x3c55bc0e, 0xbc7b3b48, 0x3c7b3b48, 0xbc55bc0e, 0x3c0e3c55, 0xbb48bc7b, 0xbb483c7b, 0x3c0ebc55, 0xbc553c0e, 0x3c7bbb48,
    0xbc7bbb48, 0x3c553c0e, 0xbc0ebc55, 0x3b483c7b, 0x3b48bc7b, 0xbc0e3c55, 0x3c55bc0e, 0xbc7b3b48, 0x3c7b3b48, 0xbc55bc0e,
    0x3c0e3c55, 0xbb48bc7b, 0xbb483c7b, 0x3c0ebc55, 0xbc553c0e, 0x3c7bbb48, 0x3c46bc22, 0xbc623bf1, 0x3c75bb95, 0xbc7f3ac9,
    0x3ac9bc7f, 0xbb953c75, 0x3bf1bc62, 0xbc223c46, 0xbc22bc46, 0x3bf13c62, 0xbb95bc75, 0x3ac93c7f, 0xbc7fbac9, 0x3c753b95,
    0xbc62bbf1, 0x3c463c22, 0xbc463c22, 0x3c62bbf1, 0xbc753b95, 0x3c7fbac9, 0xbac93c7f, 0x3b95bc75, 0xbbf13c62, 0x3c22bc46,
    0x3c223c46, 0xbbf1bc62, 0x3b953c75, 0xbac9bc7f, 0x3c7f3ac9, 0xbc75bb95, 0x3c623bf1, 0xbc46bc22, 0x3c3e3c2c, 0x3c18bc4e,
    0xbc5cbc04, 0xbbdb3c67, 0x3c713bac, 0x3b79bc78, 0xbc7dbb16, 0xba493c80, 0x3c80ba49, 0xbb16bc7d, 0xbc783b79, 0x3bac3c71,
    0x3c67bbdb, 0xbc04bc5c, 0xbc4e3c18, 0x3c2c3c3e, 0x3c2cbc3e, 0xbc4ebc18, 0xbc043c5c, 0x3c673bdb, 0x3bacbc71, 0xbc78bb79,
    0xbb163c7d, 0x3c803a49, 0xba49bc80, 0xbc7d3b16, 0x3b793c78, 0x3c71bbac, 0xbbdbbc67, 0xbc5c3c04, 0x3c183c4e, 0x3c3ebc2c,
    0x3c5cbc04, 0xbc3ebc2c, 0xbbdb3c67, 0x3c7d3b16, 0x3c4e3c18, 0x3bacbc71, 0xbc80ba49, 0x3b793c78, 0xbc78bb79, 0x3a493c80,
    0x3c71bbac, 0xbc18bc4e, 0xbb16bc7d, 0xbc673bdb, 0x3c2c3c3e, 0x3c04bc5c, 0x3c043c5c, 0x3c2cbc3e, 0xbc67bbdb, 0xbb163c7d,
    0xbc183c4e, 0x3c713bac, 0x3a49bc80, 0xbc783b79, 0x3b79bc78, 0xbc803a49, 0x3bac3c71, 0x3c4ebc18, 0x3c7dbb16, 0xbbdbbc67,
    0xbc3e3c2c, 0x3c5c3c04, 0xbc783b79, 0x3c2c3c3e, 0x3bacbc71, 0xbc7d3b16, 0x3c183c4e, 0x3bdbbc67, 0xbc803a49, 0x3c043c5c,
    0x3c5c3c04, 0x3a49bc80, 0xbc673bdb, 0x3c4e3c18, 0x3b16bc7d, 0xbc713bac, 0x3c3e3c2c, 0x3b79bc78, 0x3b793c78, 0x3c3ebc2c,
    0xbc71bbac, 0x3b163c7d, 0x3c4ebc18, 0xbc67bbdb, 0x3a493c80, 0x3c5cbc04, 0x3c04bc5c, 0xbc80ba49, 0x3bdb3c67, 0x3c18bc4e,
    0xbc7dbb16, 0x3bac3c71, 0x3c2cbc3e, 0xbc78bb79, 0x3a49bc80, 0xbc4e3c18, 0x3c783b79, 0xbbdbbc67, 0x3bac3c71, 0x3c04bc5c,
    0xbc7d3b16, 0x3c3e3c2c, 0xbc2cbc3e, 0xbb163c7d, 0x3c5cbc04, 0xbc71bbac, 0x3c673bdb, 0xbb79bc78, 0xbc183c4e, 0x3c80ba49,
    0x3c803a49, 0xbc18bc4e, 0xbb793c78, 0x3c67bbdb, 0xbc713bac, 0x3c5c3c04, 0xbb16bc7d, 0xbc2c3c3e, 0x3c3ebc2c, 0xbc7dbb16,
    0x3c043c5c, 0x3bacbc71, 0xbbdb3c67, 0x3c78bb79, 0xbc4ebc18, 0x3a493c80, 0x3bacbc71, 0xbc5c3c04, 0x3c7d3b16, 0xbc2cbc3e,
    0x3a493c80, 0x3c18bc4e, 0xbc783b79, 0x3c673bdb, 0xbbdbbc67, 0xbb793c78, 0x3c4ebc18, 0xbc80ba49, 0x3c3e3c2c, 0xbb16bc7d,
    0xbc043c5c, 0x3c71bbac, 0x3c713bac, 0xbc04bc5c, 0xbb163c7d, 0x3c3ebc2c, 0xbc803a49, 0x3c4e3c18, 0xbb79bc78, 0xbbdb3c67,
    0x3c67bbdb, 0xbc78bb79, 0x3c183c4e, 0x3a49bc80, 0xbc2c3c3e, 0x3c7dbb16, 0xbc5cbc04, 0x3bac3c71, 0xbc4ebc18, 0x3bdb3c67,
    0x3a49bc80, 0xbc043c5c, 0xbb793c78, 0x3c2cbc3e, 0xbc713bac, 0x3c7d3b16, 0x3b163c7d, 0x3bacbc71, 0xbc3e3c2c, 0x3c78bb79,
    0x3c5cbc04, 0xbc803a49, 0x3c673bdb, 0xbc18bc4e, 0xbc183c4e, 0x3c67bbdb, 0xbc80ba49, 0x3c5c3c04, 0x3c783b79, 0xbc3ebc2c,
    0x3bac3c71, 0x3b16bc7d, 0x3c7dbb16, 0xbc71bbac, 0x3c2c3c3e, 0xbb79bc78, 0xbc04bc5c, 0x3a493c80, 0x3bdbbc67, 0xbc4e3c18,
    0x3c183c4e, 0xbbacbc71, 0x3a493c80, 0x3b79bc78, 0xbc043c5c, 0x3c3ebc2c, 0xbc673bdb, 0x3c7dbb16, 0x3b16bc7d, 0xbbdb3c67,
    0x3c2cbc3e, 0xbc5c3c04, 0x3c78bb79, 0xbc80ba49, 0x3c713bac, 0xbc4ebc18, 0xbc4e3c18, 0x3c71bbac, 0xbc803a49, 0x3c783b79,
    0xbc5cbc04, 0x3c2c3c3e, 0xbbdbbc67, 0x3b163c7d, 0x3c7d3b16, 0xbc67bbdb, 0x3c3e3c2c, 0xbc04bc5c, 0x3b793c78, 0x3a49bc80,
    0xbbac3c71, 0x3c18bc4e, 0xbc713bac, 0x3c78bb79, 0xbc7d3b16, 0x3c80ba49, 0xbc3e3c2c, 0x3c4ebc18, 0xbc5c3c04, 0x3c67bbdb,
    0xbbdb3c67, 0x3c04bc5c, 0xbc183c4e, 0x3c2cbc3e, 0xba493c80, 0x3b16bc7d, 0xbb793c78, 0x3bacbc71, 0x3bac3c71, 0xbb79bc78,
    0x3b163c7d, 0xba49bc80, 0x3c2c3c3e, 0xbc18bc4e, 0x3c043c5c, 0xbbdbbc67, 0x3c673bdb, 0xbc5cbc04, 0x3c4e3c18, 0xbc3ebc2c,
    0x3c803a49, 0xbc7dbb16, 0x3c783b79, 0xbc71bbac, 0x3c800000, 0xbc800000, 0x3c800000, 0xbc800000, 0x3c800000, 0xbc800000,
    0x3c800000, 0xbc800000, 0x3c800000, 0xbc800000, 0x3c800000, 0xbc800000, 0x3c800000, 0xbc800000, 0x3c800000, 0xbc800000,
    0x3c800000, 0xbc800000, 0x3c800000, 0xbc800000, 0x3c800000, 0xbc800000, 0x3c800000, 0xbc800000, 0x3c800000, 0xbc800000,
    0x3c800000, 0xbc800000, 0x3c800000, 0xbc800000, 0x3c800000, 0xbc800000, 0x3c22bc46, 0xbbf13c62, 0x3b95bc75, 0xbac93c7f,
    0x3c7fbac9, 0xbc753b95, 0x3c62bbf1, 0xbc463c22, 0xbc46bc22, 0x3c623bf1, 0xbc75bb95, 0x3c7f3ac9, 0xbac9bc7f, 0x3b953c75,
    0xbbf1bc62, 0x3c223c46, 0xbc223c46, 0x3bf1bc62, 0xbb953c75, 0x3ac9bc7f, 0xbc7f3ac9, 0x3c75bb95, 0xbc623bf1, 0x3c46bc22,
    0x3c463c22, 0xbc62bbf1, 0x3c753b95, 0xbc7fbac9, 0x3ac93c7f, 0xbb95bc75, 0x3bf13c62, 0xbc22bc46, 0xbc7b3b48, 0x3c55bc0e,
    0xbc0e3c55, 0x3b48bc7b, 0x3b483c7b, 0xbc0ebc55, 0x3c553c0e, 0xbc7bbb48, 0x3c7bbb48, 0xbc553c0e, 0x3c0ebc55, 0xbb483c7b,
    0xbb48bc7b, 0x3c0e3c55, 0xbc55bc0e, 0x3c7b3b48, 0xbc7b3b48, 0x3c55bc0e, 0xbc0e3c55, 0x3b48bc7b, 0x3b483c7b, 0xbc0ebc55,
    0x3c553c0e, 0xbc7bbb48, 0x3c7bbb48, 0xbc553c0e, 0x3c0ebc55, 0xbb483c7b, 0xbb48bc7b, 0x3c0e3c55, 0xbc55bc0e, 0x3c7b3b48,
    0x3bf1bc62, 0x3ac93c7f, 0xbc22bc46, 0x3c753b95, 0x3b953c75, 0xbc46bc22, 0x3c7f3ac9, 0xbc623bf1, 0xbc62bbf1, 0x3c7fbac9,
    0xbc463c22, 0x3b95bc75, 0x3c75bb95, 0xbc223c46, 0x3ac9bc7f, 0x3bf13c62, 0xbbf13c62, 0xbac9bc7f, 0x3c223c46, 0xbc75bb95,
    0xbb95bc75, 0x3c463c22, 0xbc7fbac9, 0x3c62bbf1, 0x3c623bf1, 0xbc7f3ac9, 0x3c46bc22, 0xbb953c75, 0xbc753b95, 0x3c22bc46,
    0xbac93c7f, 0xbbf1bc62, 0x3c6dbbc4, 0xbbc43c6d, 0xbbc4bc6d, 0x3c6d3bc4, 0xbc6d3bc4, 0x3bc4bc6d, 0x3bc43c6d, 0xbc6dbbc4,
    0x3c6dbbc4, 0xbbc43c6d, 0xbbc4bc6d, 0x3c6d3bc4, 0xbc6d3bc4, 0x3bc4bc6d, 0x3bc43c6d, 0xbc6dbbc4, 0x3c6dbbc4, 0xbbc43c6d,
    0xbbc4bc6d, 0x3c6d3bc4, 0xbc6d3bc4, 0x3bc4bc6d, 0x3bc43c6d, 0xbc6dbbc4, 0x3c6dbbc4, 0xbbc43c6d, 0xbbc4bc6d, 0x3c6d3bc4,
    0xbc6d3bc4, 0x3bc4bc6d, 0x3bc43c6d, 0xbc6dbbc4, 0x3b95bc75, 0x3c223c46, 0xbc7f3ac9, 0x3bf1bc62, 0xbc623bf1, 0x3ac9bc7f,
    0x3c463c22, 0xbc753b95, 0xbc75bb95, 0x3c46bc22, 0x3ac93c7f, 0xbc62bbf1, 0x3bf13c62, 0xbc7fbac9, 0x3c22bc46, 0x3b953c75,
    0xbb953c75, 0xbc22bc46, 0x3c7fbac9, 0xbbf13c62, 0x3c62bbf1, 0xbac93c7f, 0xbc46bc22, 0x3c75bb95, 0x3c753b95, 0xbc463c22,
    0xbac9bc7f, 0x3c623bf1, 0xbbf1bc62, 0x3c7f3ac9, 0xbc223c46, 0xbb95bc75, 0xbc553c0e, 0xbb48bc7b, 0x3c7b3b48, 0xbc0e3c55,
    0xbc0ebc55, 0x3c7bbb48, 0xbb483c7b, 0xbc55bc0e, 0x3c55bc0e, 0x3b483c7b, 0xbc7bbb48, 0x3c0ebc55, 0x3c0e3c55, 0xbc7b3b48,
    0x3b48bc7b, 0x3c553c0e, 0xbc553c0e, 0xbb48bc7b, 0x3c7b3b48, 0xbc0e3c55, 0xbc0ebc55, 0x3c7bbb48, 0xbb483c7b, 0xbc55bc0e,
    0x3c55bc0e, 0x3b483c7b, 0xbc7bbb48, 0x3c0ebc55, 0x3c0e3c55, 0xbc7b3b48, 0x3b48bc7b, 0x3c553c0e, 0x3ac9bc7f, 0x3c753b95,
    0xbbf13c62, 0xbc46bc22, 0xbc22bc46, 0x3c62bbf1, 0x3b953c75, 0xbc7f3ac9, 0xbc7fbac9, 0x3b95bc75, 0x3c623bf1, 0xbc223c46,
    0xbc463c22, 0xbbf1bc62, 0x3c75bb95, 0x3ac93c7f, 0xbac93c7f, 0xbc75bb95, 0x3bf1bc62, 0x3c463c22, 0x3c223c46, 0xbc623bf1,
    0xbb95bc75, 0x3c7fbac9, 0x3c7f3ac9, 0xbb953c75, 0xbc62bbf1, 0x3c22bc46, 0x3c46bc22, 0x3bf13c62, 0xbc753b95, 0xbac9bc7f,
    0x3c80ba49, 0xbc7d3b16, 0x3c78bb79, 0xbc713bac, 0x3c67bbdb, 0xbc5c3c04, 0x3c4ebc18, 0xbc3e3c2c, 0x3c2cbc3e, 0xbc183c4e,
    0x3c04bc5c, 0xbbdb3c67, 0x3bacbc71, 0xbb793c78, 0x3b16bc7d, 0xba493c80, 0xba49bc80, 0x3b163c7d, 0xbb79bc78, 0x3bac3c71,
    0xbbdbbc67, 0x3c043c5c, 0xbc18bc4e, 0x3c2c3c3e, 0xbc3ebc2c, 0x3c4e3c18, 0xbc5cbc04, 0x3c673bdb, 0xbc71bbac, 0x3c783b79,
    0xbc7dbb16, 0x3c803a49, 0x3b79bc78, 0x3a493c80, 0xbbacbc71, 0x3c183c4e, 0x3c7dbb16, 0xbc673bdb, 0x3c3ebc2c, 0xbc043c5c,
    0xbc5c3c04, 0x3c2cbc3e, 0xbbdb3c67, 0x3b16bc7d, 0xbc4ebc18, 0x3c713bac, 0xbc80ba49, 0x3c78bb79, 0x3c783b79, 0xbc803a49,
    0x3c71bbac, 0xbc4e3c18, 0x3b163c7d, 0xbbdbbc67, 0x3c2c3c3e, 0xbc5cbc04, 0xbc04bc5c, 0x3c3e3c2c, 0xbc67bbdb, 0x3c7d3b16,
    0x3c18bc4e, 0xbbac3c71, 0x3a49bc80, 0x3b793c78, 0xbc043c5c, 0x3a49bc80, 0x3bdb3c67, 0xbc4ebc18, 0x3c7d3b16, 0xbc713bac,
    0x3c2cbc3e, 0xbb793c78, 0x3c78bb79, 0xbc3e3c2c, 0x3bacbc71, 0x3b163c7d, 0xbc18bc4e, 0x3c673bdb, 0xbc803a49, 0x3c5cbc04,
    0x3c5c3c04, 0xbc80ba49, 0x3c67bbdb, 0xbc183c4e, 0x3b16bc7d, 0x3bac3c71, 0xbc3ebc2c, 0x3c783b79, 0xbb79bc78, 0x3c2c3c3e,
    0xbc71bbac, 0x3c7dbb16, 0xbc4e3c18, 0x3bdbbc67, 0x3a493c80, 0xbc04bc5c, 0xbc2cbc3e, 0x3c7d3b16, 0xbc5c3c04, 0x3bacbc71,
    0x3c673bdb, 0xbc783b79, 0x3c18bc4e, 0x3a493c80, 0xbc80ba49, 0x3c4ebc18, 0xbb793c78, 0xbbdbbc67, 0x3c71bbac, 0xbc043c5c,
    0xbb16bc7d, 0x3c3e3c2c, 0x3c3ebc2c, 0xbb163c7d, 0xbc04bc5c, 0x3c713bac, 0xbbdb3c67, 0xbb79bc78, 0x3c4e3c18, 0xbc803a49,
    0x3a49bc80, 0x3c183c4e, 0xbc78bb79, 0x3c67bbdb, 0x3bac3c71, 0xbc5cbc04, 0x3c7dbb16, 0xbc2c3c3e, 0xbbdbbc67, 0x3c783b79,
    0xbc4e3c18, 0x3a49bc80, 0x3c3e3c2c, 0xbc7d3b16, 0x3c04bc5c, 0x3bac3c71, 0xbc71bbac, 0x3c5cbc04, 0xbb163c7d, 0xbc2cbc3e,
    0x3c80ba49, 0xbc183c4e, 0xbb79bc78, 0x3c673bdb, 0x3c67bbdb, 0xbb793c78, 0xbc18bc4e, 0x3c803a49, 0xbc2c3c3e, 0xbb16bc7d,
    0x3c5c3c04, 0xbc713bac, 0x3bacbc71, 0x3c043c5c, 0xbc7dbb16, 0x3c3ebc2c, 0x3a493c80, 0xbc4ebc18, 0x3c78bb79, 0xbbdb3c67,
    0xbc7d3b16, 0x3bacbc71, 0x3c2c3c3e, 0xbc783b79, 0x3c043c5c, 0xbc803a49, 0x3bdbbc67, 0x3c183c4e, 0x3c4e3c18, 0xbc673bdb,
    0x3a49bc80, 0x3c5c3c04, 0x3b79bc78, 0x3c3e3c2c, 0xbc713bac, 0x3b16bc7d, 0x3b163c7d, 0xbc71bbac, 0x3c3ebc2c, 0x3b793c78,
    0x3c5cbc04, 0x3a493c80, 0xbc67bbdb, 0x3c4ebc18, 0x3c18bc4e, 0x3bdb3c67, 0xbc80ba49, 0x3c04bc5c, 0xbc78bb79, 0x3c2cbc3e,
    0x3bac3c71, 0xbc7dbb16, 0x3c7d3b16, 0xbbdb3c67, 0xbc3ebc2c, 0x3c5cbc04, 0x3b793c78, 0xbc80ba49, 0x3bacbc71, 0x3c4e3c18,
    0xbc18bc4e, 0x3c71bbac, 0x3a493c80, 0xbc78bb79, 0x3c04bc5c, 0x3c2c3c3e, 0xbc673bdb, 0xbb16bc7d, 0xbb163c7d, 0xbc67bbdb,
    0x3c2cbc3e, 0x3c043c5c, 0xbc783b79, 0x3a49bc80, 0x3c713bac, 0xbc183c4e, 0x3c4ebc18, 0x3bac3c71, 0xbc803a49, 0x3b79bc78,
    0x3c5c3c04, 0xbc3e3c2c, 0xbbdbbc67, 0x3c7dbb16, 0xbbdb3c67, 0xbc5cbc04, 0x3c18bc4e, 0x3c3e3c2c, 0xba493c80, 0xbc7dbb16,
    0x3b79bc78, 0x3c713bac, 0x3bac3c71, 0xbc783b79, 0xbb16bc7d, 0x3c80ba49, 0x3c2c3c3e, 0xbc4e3c18, 0xbc04bc5c, 0x3c67bbdb,
    0x3c673bdb, 0xbc043c5c, 0xbc4ebc18, 0x3c2cbc3e, 0x3c803a49, 0xbb163c7d, 0xbc78bb79, 0x3bacbc71, 0x3c71bbac, 0x3b793c78,
    0xbc7d3b16, 0xba49bc80, 0x3c3ebc2c, 0x3c183c4e, 0xbc5c3c04, 0xbbdbbc67, 0x3f803f80, 0x3f7d3f7f, 0x3f783f7b, 0x3f713f75,
    0x3f673f6d, 0x3f5c3f62, 0x3f4e3f55, 0x3f3e3f46, 0x3f2c3f35, 0x3f183f22, 0x3f043f0e, 0x3edb3ef1, 0x3eac3ec4, 0x3e793e95,
    0x3e163e48, 0x3d493dc9, 0xbd490000, 0xbe16bdc9, 0xbe79be48, 0xbeacbe95, 0xbedbbec4, 0xbf04bef1, 0xbf18bf0e, 0xbf2cbf22,
    0xbf3ebf35, 0xbf4ebf46, 0xbf5cbf55, 0xbf67bf62, 0xbf71bf6d, 0xbf78bf75, 0xbf7dbf7b, 0xbf80bf7f, 0x3edb3ec4, 0x3f043ef1,
    0x3f183f0e, 0x3f2c3f22, 0x3d490000, 0x3e163dc9, 0x3e793e48, 0x3eac3e95, 0x3f713f6d, 0x3f783f75, 0x3f7d3f7b, 0x3f803f7f,
    0x3f3e3f35, 0x3f4e3f46, 0x3f5c3f55, 0x3f673f62, 0x3f673f6d, 0x3f5c3f62, 0x3f4e3f55, 0x3f3e3f46, 0x3f803f80, 0x3f7d3f7f,
    0x3f783f7b, 0x3f713f75, 0x3eac3ec4, 0x3e793e95, 0x3e163e48, 0x3d493dc9, 0x3f2c3f35, 0x3f183f22, 0x3f043f0e, 0x3edb3ef1,
    0xbf4ebf35, 0xbf71bf62, 0xbf80bf7b, 0xbf78bf7f, 0xbf5cbf6d, 0xbf2cbf46, 0xbedbbf0e, 0xbe16be95, 0x3f7d3f80, 0x3f673f75,
    0x3f3e3f55, 0x3f043f22, 0x3e793ec4, 0xbd493dc9, 0xbeacbe48, 0xbf18bef1, 0x3f183f35, 0x3eac3ef1, 0x3d493e48, 0xbe79bdc9,
    0xbf04bec4, 0xbf3ebf22, 0xbf67bf55, 0xbf7dbf75, 0x3e160000, 0x3edb3e95, 0x3f2c3f0e, 0x3f5c3f46, 0x3f783f6d, 0x3f803f7f,
    0x3f713f7b, 0x3f4e3f62, 0xbf04bec4, 0xbf3ebf22, 0xbf67bf55, 0xbf7dbf75, 0x3f183f35, 0x3eac3ef1, 0x3d493e48, 0xbe79bdc9,
    0x3f783f6d, 0x3f803f7f, 0x3f713f7b, 0x3f4e3f62, 0x3e160000, 0x3edb3e95, 0x3f2c3f0e, 0x3f5c3f46, 0x3f5c3f6d, 0x3f2c3f46,
    0x3edb3f0e, 0x3e163e95, 0x3f4e3f35, 0x3f713f62, 0x3f803f7b, 0x3f783f7f, 0xbe79bec4, 0x3d49bdc9, 0x3eac3e48, 0x3f183ef1,
    0xbf7dbf80, 0xbf67bf75, 0xbf3ebf55, 0xbf04bf22, 0xbe790000, 0xbf2cbef1, 0xbf71bf55, 0xbf7dbf7f, 0xbf4ebf6d, 0xbedbbf22,
    0x3d49be48, 0x3f043e95, 0x3f5c3f35, 0x3f803f75, 0x3f673f7b, 0x3f183f46, 0x3e163ec4, 0xbeacbdc9, 0xbf3ebf0e, 0xbf78bf62,
    0x3f783f80, 0x3f3e3f62, 0x3eac3f0e, 0xbe163dc9, 0xbf18bec4, 0xbf67bf46, 0xbf80bf7b, 0xbf5cbf75, 0xbf04bf35, 0xbd49be95,
    0x3edb3e48, 0x3f4e3f22, 0x3f7d3f6d, 0x3f713f7f, 0x3f2c3f55, 0x3e793ef1, 0xbf18bec4, 0xbf67bf46, 0xbf80bf7b, 0xbf5cbf75,
    0x3f783f80, 0x3f3e3f62, 0x3eac3f0e, 0xbe163dc9, 0x3f7d3f6d, 0x3f713f7f, 0x3f2c3f55, 0x3e793ef1, 0xbf04bf35, 0xbd49be95,
    0x3edb3e48, 0x3f4e3f22, 0x3f4e3f6d, 0x3edb3f22, 0xbd493e48, 0xbf04be95, 0x3e790000, 0x3f2c3ef1, 0x3f713f55, 0x3f7d3f7f,
    0xbe16bec4, 0x3eac3dc9, 0x3f3e3f0e, 0x3f783f62, 0xbf5cbf35, 0xbf80bf75, 0xbf67bf7b, 0xbf18bf46, 0xbedbbf35, 0x3e79bdc9,
    0x3f4e3f0e, 0x3f803f75, 0x3f3e3f6d, 0x3e163ef1, 0xbf04be48, 0xbf71bf46, 0x3eac0000, 0x3f5c3f22, 0x3f7d3f7b, 0x3f2c3f62,
    0x3d493ec4, 0xbf18be95, 0xbf78bf55, 0xbf67bf7f, 0x3f673f35, 0x3f783f7f, 0x3f183f55, 0xbd493e95, 0xbf2cbec4, 0xbf7dbf62,
    0xbf5cbf7b, 0xbeacbf22, 0x3f713f80, 0x3f043f46, 0xbe163e48, 0xbf3ebef1, 0xbf80bf6d, 0xbf4ebf75, 0xbe79bf0e, 0x3edb3dc9,
    0x3f2c3ec4, 0x3f7d3f62, 0x3f5c3f7b, 0x3eac3f22, 0xbf67bf35, 0xbf78bf7f, 0xbf18bf55, 0x3d49be95, 0x3f803f6d, 0x3f4e3f75,
    0x3e793f0e, 0xbedbbdc9, 0xbf71bf80, 0xbf04bf46, 0x3e16be48, 0x3f3e3ef1, 0x3f3e3f6d, 0x3e163ef1, 0xbf04be48, 0xbf71bf46,
    0xbedbbf35, 0x3e79bdc9, 0x3f4e3f0e, 0x3f803f75, 0x3d493ec4, 0xbf18be95, 0xbf78bf55, 0xbf67bf7f, 0x3eac0000, 0x3f5c3f22,
    0x3f7d3f7b, 0x3f2c3f62, 0x3f673f80, 0x3e793f22, 0xbf18be48, 0xbf80bf62, 0xbf2cbf6d, 0x3e16be95, 0x3f5c3f0e, 0x3f713f7f,
    0x3eac3f35, 0xbf04bdc9, 0xbf7dbf55, 0xbf3ebf75, 0x3d49bec4, 0x3f4e3ef1, 0x3f783f7b, 0x3edb3f46, 0xbedb0000, 0xbf78bf46,
    0xbf4ebf7b, 0xbd49bef1, 0x3f3e3ec4, 0x3f7d3f75, 0x3f043f55, 0xbeac3dc9, 0xbf71bf35, 0xbf5cbf7f, 0xbe16bf0e, 0x3f2c3e95,
    0x3f803f6d, 0x3f183f62, 0xbe793e48, 0xbf67bf22, 0xbf3ebec4, 0xbf7dbf75, 0xbf04bf55, 0x3eacbdc9, 0x3edb0000, 0x3f783f46,
    0x3f4e3f7b, 0x3d493ef1, 0xbf80bf6d, 0xbf18bf62, 0x3e79be48, 0x3f673f22, 0x3f713f35, 0x3f5c3f7f, 0x3e163f0e, 0xbf2cbe95,
    0xbf2cbf6d, 0x3e16be95, 0x3f5c3f0e, 0x3f713f7f, 0x3f673f80, 0x3e793f22, 0xbf18be48, 0xbf80bf62, 0x3d49bec4, 0x3f4e3ef1,
    0x3f783f7b, 0x3edb3f46, 0x3eac3f35, 0xbf04bdc9, 0xbf7dbf55, 0xbf3ebf75, 0xbf78bf35, 0xbf2cbf75, 0x3eacbe48, 0x3f7d3f46,
    0x3f183f6d, 0xbedb3dc9, 0xbf80bf55, 0xbf04bf62, 0x3f5c3f80, 0xbd493ef1, 0xbf67bf0e, 0xbf4ebf7f, 0x3e16bec4, 0x3f713f22,
    0x3f3e3f7b, 0xbe793e95, 0x3e793f35, 0xbf3ebe95, 0xbf71bf7b, 0xbe16bf22, 0x3f4e3ec4, 0x3f673f7f, 0x3d493f0e, 0xbf5cbef1,
    0x3f040000, 0x3f803f62, 0x3edb3f55, 0xbf18bdc9, 0xbf7dbf6d, 0xbeacbf46, 0x3f2c3e48, 0x3f783f75, 0x3f4e3ec4, 0x3f673f7f,
    0x3d493f0e, 0xbf5cbef1, 0x3e793f35, 0xbf3ebe95, 0xbf71bf7b, 0xbe16bf22, 0xbf7dbf6d, 0xbeacbf46, 0x3f2c3e48, 0x3f783f75,
    0x3f040000, 0x3f803f62, 0x3edb3f55, 0xbf18bdc9, 0xbf18bf6d, 0x3edbbdc9, 0x3f803f55, 0x3f043f62, 0x3f783f35, 0x3f2c3f75,
    0xbeac3e48, 0xbf7dbf46, 0xbe163ec4, 0xbf71bf22, 0xbf3ebf7b, 0x3e79be95, 0xbf5cbf80, 0x3d49bef1, 0x3f673f0e, 0x3f4e3f7f,
    0xbf180000, 0xbf71bf75, 0x3d49bf0e, 0x3f783f22, 0x3f043f6d, 0xbf2cbdc9, 0xbf67bf7b, 0x3e16bef1, 0x3f7d3f35, 0x3edb3f62,
    0xbf3ebe48, 0xbf5cbf7f, 0x3e79bec4, 0x3f803f46, 0x3eac3f55, 0xbf4ebe95, 0x3f4e3f80, 0xbeac3e95, 0xbf80bf55, 0xbe79bf46,
    0x3f5c3ec4, 0x3f3e3f7f, 0xbedb3e48, 0xbf7dbf62, 0xbe16bf35, 0x3f673ef1, 0x3f2c3f7b, 0xbf043dc9, 0xbf78bf6d, 0xbd49bf22,
    0x3f713f0e, 0x3f183f75, 0x3f5c3ec4, 0x3f3e3f7f, 0xbedb3e48, 0xbf7dbf62, 0x3f4e3f80, 0xbeac3e95, 0xbf80bf55, 0xbe79bf46,
    0xbf78bf6d, 0xbd49bf22, 0x3f713f0e, 0x3f183f75, 0xbe16bf35, 0x3f673ef1, 0x3f2c3f7b, 0xbf043dc9, 0xbf04bf6d, 0x3f2c3dc9,
    0x3f673f7b, 0xbe163ef1, 0x3f180000, 0x3f713f75, 0xbd493f0e, 0xbf78bf22, 0xbe793ec4, 0xbf80bf46, 0xbeacbf55, 0x3f4e3e95,
    0xbf7dbf35, 0xbedbbf62, 0x3f3e3e48, 0x3f5c3f7f, 0xbd49bf35, 0x3f7d3f22, 0x3e793f55, 0xbf71bef1, 0xbedbbf6d, 0x3f5c3e95,
    0x3f183f7b, 0xbf3ebdc9, 0x3f2c0000, 0x3f4e3f7f, 0xbf043e48, 0xbf67bf75, 0x3eacbec4, 0x3f783f62, 0xbe163f0e, 0xbf80bf46,
    0x3f803f35, 0x3e163f46, 0xbf78bf0e, 0xbeacbf62, 0x3f673ec4, 0x3f043f75, 0xbf4ebe48, 0xbf2cbf7f, 0x3f3e3f80, 0xbf183dc9,
    0xbf5cbf7b, 0x3edbbe95, 0x3f713f6d, 0xbe793ef1, 0xbf7dbf55, 0x3d49bf22, 0xbf67bec4, 0xbf04bf75, 0x3f4e3e48, 0x3f2c3f7f,
    0xbf80bf35, 0xbe16bf46, 0x3f783f0e, 0x3eac3f62, 0xbf71bf6d, 0x3e79bef1, 0x3f7d3f55, 0xbd493f22, 0xbf3ebf80, 0x3f18bdc9,
    0x3f5c3f7b, 0xbedb3e95, 0xbedbbf6d, 0x3f5c3e95, 0x3f183f7b, 0xbf3ebdc9, 0xbd49bf35, 0x3f7d3f22, 0x3e793f55, 0xbf71bef1,
    0x3eacbec4, 0x3f783f62, 0xbe163f0e, 0xbf80bf46, 0x3f2c0000, 0x3f4e3f7f, 0xbf043e48, 0xbf67bf75, 0x3f2c3f80, 0xbf4ebdc9,
    0xbf04bf7b, 0x3f673e95, 0x3eac3f6d, 0xbf78bef1, 0xbe16bf55, 0x3f803f22, 0xbd493f35, 0xbf7dbf46, 0x3e79bf0e, 0x3f713f62,
    0xbedb3ec4, 0xbf5cbf75, 0x3f18be48, 0x3f3e3f7f, 0xbf3e0000, 0xbf18bf7f, 0x3f5c3e48, 0x3edb3f75, 0xbf71bec4, 0xbe79bf62,
    0x3f7d3f0e, 0x3d493f46, 0xbf80bf35, 0x3e16bf22, 0x3f783f55, 0xbeac3ef1, 0xbf67bf6d, 0x3f04be95, 0x3f4e3f7b, 0xbf2c3dc9,
    0x3f713ec4, 0x3e793f62, 0xbf7dbf0e, 0xbd49bf46, 0x3f3e0000, 0x3f183f7f, 0xbf5cbe48, 0xbedbbf75, 0x3f673f6d, 0xbf043e95,
    0xbf4ebf7b, 0x3f2cbdc9, 0x3f803f35, 0xbe163f22, 0xbf78bf55, 0x3eacbef1, 0x3eac3f6d, 0xbf78bef1, 0xbe16bf55, 0x3f803f22,
    0x3f2c3f80, 0xbf4ebdc9, 0xbf04bf7b, 0x3f673e95, 0xbedb3ec4, 0xbf5cbf75, 0x3f18be48, 0x3f3e3f7f, 0xbd493f35, 0xbf7dbf46,
    0x3e79bf0e, 0x3f713f62, 0xbf7dbf35, 0x3edbbef1, 0x3f3e3f7b, 0xbf5cbdc9, 0xbe79bf6d, 0x3f803f22, 0xbeac3f0e, 0xbf4ebf75,
    0x3f183f80, 0xbf71be95, 0xbd49bf55, 0x3f783f46, 0xbf043ec4, 0xbf2cbf7f, 0x3f673e48, 0x3e163f62, 0xbe163f35, 0xbf67bf62,
    0x3f2cbe48, 0x3f043f7f, 0xbf78bec4, 0x3d49bf46, 0x3f713f55, 0xbf183e95, 0x3f4e0000, 0x3eac3f75, 0xbf80bf0e, 0x3e79bf22,
    0x3f5c3f6d, 0xbf3e3dc9, 0xbedbbf7b, 0x3f7d3ef1, 0xbf78bec4, 0x3d49bf46, 0x3f713f55, 0xbf183e95, 0xbe163f35, 0xbf67bf62,
    0x3f2cbe48, 0x3f043f7f, 0x3f5c3f6d, 0xbf3e3dc9, 0xbedbbf7b, 0x3f7d3ef1, 0x3f4e0000, 0x3eac3f75, 0xbf80bf0e, 0x3e79bf22,
    0x3e793f6d, 0xbf80bf22, 0x3eacbf0e, 0x3f4e3f75, 0x3f7d3f35, 0xbedb3ef1, 0xbf3ebf7b, 0x3f5c3dc9, 0x3f04bec4, 0x3f2c3f7f,
    0xbf67be48, 0xbe16bf62, 0xbf18bf80, 0x3f713e95, 0x3d493f55, 0xbf78bf46, 0xbf5c0000, 0xbd49bf62, 0x3f673f55, 0xbf4e3dc9,
    0xbe16bf6d, 0x3f713f46, 0xbf3e3e48, 0xbe79bf75, 0x3f783f35, 0xbf2c3e95, 0xbeacbf7b, 0x3f7d3f22, 0xbf183ec4, 0xbedbbf7f,
    0x3f803f0e, 0xbf043ef1, 0x3f043f80, 0xbf80bef1, 0x3edbbf0e, 0x3f183f7f, 0xbf7dbec4, 0x3eacbf22, 0x3f2c3f7b, 0xbf78be95,
    0x3e79bf35, 0x3f3e3f75, 0xbf71be48, 0x3e16bf46, 0x3f4e3f6d, 0xbf67bdc9, 0x3d49bf55, 0x3f5c3f62, 0xbf7dbec4, 0x3eacbf22,
    0x3f2c3f7b, 0xbf78be95, 0x3f043f80, 0xbf80bef1, 0x3edbbf0e, 0x3f183f7f, 0x3f4e3f6d, 0xbf67bdc9, 0x3d49bf55, 0x3f5c3f62,
    0x3e79bf35, 0x3f3e3f75, 0xbf71be48, 0x3e16bf46, 0x3e163f6d, 0xbf71bf46, 0x3f3ebe48, 0x3e793f75, 0x3f5c0000, 0x3d493f62,
    0xbf67bf55, 0x3f4ebdc9, 0x3f18bec4, 0x3edb3f7f, 0xbf80bf0e, 0x3f04bef1, 0xbf78bf35, 0x3f2cbe95, 0x3eac3f7b, 0xbf7dbf22,
    0x3eacbf35, 0x3f043f7f, 0xbf7dbf0e, 0x3f3ebe95, 0x3d493f6d, 0xbf4ebf62, 0x3f783e48, 0xbedb3f22, 0x3f670000, 0xbe793f46,
    0xbf18bf7b, 0x3f803ef1, 0xbf2c3ec4, 0xbe16bf75, 0x3f5c3f55, 0xbf71bdc9, 0x3f713f35, 0xbf5c3dc9, 0x3e16bf55, 0x3f2c3f75,
    0xbf80bec4, 0x3f18bef1, 0x3e793f7b, 0xbf67bf46, 0x3edb3f80, 0xbf78bf22, 0x3f4ebe48, 0xbd493f62, 0xbf3ebf6d, 0x3f7d3e95,
    0xbf043f0e, 0xbeacbf7f, 0x3f803ec4, 0xbf183ef1, 0xbe79bf7b, 0x3f673f46, 0xbf71bf35, 0x3f5cbdc9, 0xbe163f55, 0xbf2cbf75,
    0x3f3e3f6d, 0xbf7dbe95, 0x3f04bf0e, 0x3eac3f7f, 0xbedbbf80, 0x3f783f22, 0xbf4e3e48, 0x3d49bf62, 0x3d493f6d, 0xbf4ebf62,
    0x3f783e48, 0xbedb3f22, 0x3eacbf35, 0x3f043f7f, 0xbf7dbf0e, 0x3f3ebe95, 0xbf2c3ec4, 0xbe16bf75, 0x3f5c3f55, 0xbf71bdc9,
    0x3f670000, 0xbe793f46, 0xbf18bf7b, 0x3f803ef1, 0x3eac3f80, 0xbf5cbf46, 0x3f7d3e48, 0xbf2c3ef1, 0x3d49bf6d, 0x3f183f75,
    0xbf78bf0e, 0x3f67bdc9, 0xbedb3f35, 0xbe79bf7f, 0x3f4e3f55, 0xbf80be95, 0x3f3ebec4, 0xbe163f62, 0xbf04bf7b, 0x3f713f22,
    0xbf710000, 0x3f04bf22, 0x3e163f7b, 0xbf3ebf62, 0x3f803ec4, 0xbf4e3e95, 0x3e79bf55, 0x3edb3f7f, 0xbf67bf35, 0x3f783dc9,
    0xbf183f0e, 0xbd49bf75, 0x3f2c3f6d, 0xbf7dbef1, 0x3f5cbe48, 0xbeac3f46, 0xbf80bec4, 0x3f4ebe95, 0xbe793f55, 0xbedbbf7f,
    0x3f710000, 0xbf043f22, 0xbe16bf7b, 0x3f3e3f62, 0xbf2cbf6d, 0x3f7d3ef1, 0xbf5c3e48, 0x3eacbf46, 0x3f673f35, 0xbf78bdc9,
    0x3f18bf0e, 0x3d493f75, 0x3d49bf6d, 0x3f183f75, 0xbf78bf0e, 0x3f67bdc9, 0x3eac3f80, 0xbf5cbf46, 0x3f7d3e48, 0xbf2c3ef1,
    0x3f3ebec4, 0xbe163f62, 0xbf04bf7b, 0x3f713f22, 0xbedb3f35, 0xbe79bf7f, 0x3f4e3f55, 0xbf80be95, 0xbf5cbf35, 0x3f803e95,
    0xbf673e48, 0x3f18bf22, 0xbe163f6d, 0xbeacbf7f, 0x3f3e3f55, 0xbf78bef1, 0x3e793f80, 0xbf2cbf62, 0x3f713f0e, 0xbf7dbdc9,
    0x3f4ebec4, 0xbedb3f46, 0xbd49bf7b, 0x3f043f75, 0xbf043f35, 0x3d49bf75, 0x3edb3f7b, 0xbf4ebf46, 0x3f7d3ec4, 0xbf713dc9,
    0x3f2cbf0e, 0xbe793f62, 0x3f780000, 0xbf3e3ef1, 0x3eacbf55, 0x3e163f7f, 0xbf18bf6d, 0x3f673f22, 0xbf80be48, 0x3f5cbe95,
    0x3f7d3ec4, 0xbf713dc9, 0x3f2cbf0e, 0xbe793f62, 0xbf043f35, 0x3d49bf75, 0x3edb3f7b, 0xbf4ebf46, 0xbf18bf6d, 0x3f673f22,
    0xbf80be48, 0x3f5cbe95, 0x3f780000, 0xbf3e3ef1, 0x3eacbf55, 0x3e163f7f, 0x3e16bf6d, 0x3eac3f7f, 0xbf3ebf55, 0x3f783ef1,
    0x3f5c3f35, 0xbf80be95, 0x3f67be48, 0xbf183f22, 0xbf4e3ec4, 0x3edbbf46, 0x3d493f7b, 0xbf04bf75, 0xbe79bf80, 0x3f2c3f62,
    0xbf71bf0e, 0x3f7d3dc9, 0xbf7d0000, 0x3f67be95, 0xbf3e3f0e, 0x3f04bf46, 0xbe793f6d, 0xbd49bf7f, 0x3eac3f7b, 0xbf18bf62,
    0x3f4e3f35, 0xbf71bef1, 0x3f803e48, 0xbf783dc9, 0x3f5cbec4, 0xbf2c3f22, 0x3edbbf55, 0xbe163f75, 0x3e163f80, 0xbedbbf75,
    0x3f2c3f55, 0xbf5cbf22, 0x3f783ec4, 0xbf80bdc9, 0x3f71be48, 0xbf4e3ef1, 0x3f18bf35, 0xbeac3f62, 0x3d49bf7b, 0x3e793f7f,
    0xbf04bf6d, 0x3f3e3f46, 0xbf67bf0e, 0x3f7d3e95, 0x3f783ec4, 0xbf80bdc9, 0x3f71be48, 0xbf4e3ef1, 0x3e163f80, 0xbedbbf75,
    0x3f2c3f55, 0xbf5cbf22, 0xbf04bf6d, 0x3f3e3f46, 0xbf67bf0e, 0x3f7d3e95, 0x3f18bf35, 0xbeac3f62, 0x3d49bf7b, 0x3e793f7f,
    0x3e79bf6d, 0x3d493f7f, 0xbeacbf7b, 0x3f183f62, 0x3f7d0000, 0xbf673e95, 0x3f3ebf0e, 0xbf043f46, 0xbf5c3ec4, 0x3f2cbf22,
    0xbedb3f55, 0x3e16bf75, 0xbf4ebf35, 0x3f713ef1, 0xbf80be48, 0x3f78bdc9, 0x3f2cbf35, 0xbf183f46, 0x3f04bf55, 0xbedb3f62,
    0x3eacbf6d, 0xbe793f75, 0x3e16bf7b, 0xbd493f7f, 0x3f800000, 0xbf7d3dc9, 0x3f78be48, 0xbf713e95, 0x3f67bec4, 0xbf5c3ef1,
    0x3f4ebf0e, 0xbf3e3f22, 0x3f3e3f35, 0xbf4ebf22, 0x3f5c3f0e, 0xbf67bef1, 0x3f713ec4, 0xbf78be95, 0x3f7d3e48, 0xbf80bdc9,
    0x3d493f80, 0xbe16bf7f, 0x3e793f7b, 0xbeacbf75, 0x3edb3f6d, 0xbf04bf62, 0x3f183f55, 0xbf2cbf46, 0xbf71bec4, 0x3f783e95,
    0xbf7dbe48, 0x3f803dc9, 0xbf3ebf35, 0x3f4e3f22, 0xbf5cbf0e, 0x3f673ef1, 0xbedbbf6d, 0x3f043f62, 0xbf18bf55, 0x3f2c3f46,
    0xbd49bf80, 0x3e163f7f, 0xbe79bf7b, 0x3eac3f75, 0x3eacbf6d, 0xbe793f75, 0x3e16bf7b, 0xbd493f7f, 0x3f2cbf35, 0xbf183f46,
    0x3f04bf55, 0xbedb3f62, 0x3f67bec4, 0xbf5c3ef1, 0x3f4ebf0e, 0xbf3e3f22, 0x3f800000, 0xbf7d3dc9, 0x3f78be48, 0xbf713e95,
    0xbd493f80, 0x3e16bf7f, 0xbe793f7b, 0x3eacbf75, 0xbedb3f6d, 0x3f04bf62, 0xbf183f55, 0x3f2cbf46, 0xbf3e3f35, 0x3f4ebf22,
    0xbf5c3f0e, 0x3f67bef1, 0xbf713ec4, 0x3f78be95, 0xbf7d3e48, 0x3f80bdc9, 0xbf800000, 0x3f7d3dc9, 0xbf78be48, 0x3f713e95,
    0xbf67bec4, 0x3f5c3ef1, 0xbf4ebf0e, 0x3f3e3f22, 0xbf2cbf35, 0x3f183f46, 0xbf04bf55, 0x3edb3f62, 0xbeacbf6d, 0x3e793f75,
    0xbe16bf7b, 0x3d493f7f, 0x3f673ec4, 0xbf5cbef1, 0x3f4e3f0e, 0xbf3ebf22, 0x3f800000, 0xbf7dbdc9, 0x3f783e48, 0xbf71be95,
    0x3eac3f6d, 0xbe79bf75, 0x3e163f7b, 0xbd49bf7f, 0x3f2c3f35, 0xbf18bf46, 0x3f043f55, 0xbedbbf62, 0xbedb3f6d, 0x3f04bf62,
    0xbf183f55, 0x3f2cbf46, 0xbd493f80, 0x3e16bf7f, 0xbe793f7b, 0x3eacbf75, 0xbf713ec4, 0x3f78be95, 0xbf7d3e48, 0x3f80bdc9,
    0xbf3e3f35, 0x3f4ebf22, 0xbf5c3f0e, 0x3f67bef1, 0xbf18bf35, 0x3eac3f62, 0xbd49bf7b, 0xbe793f7f, 0x3f04bf6d, 0xbf3e3f46,
    0x3f67bf0e, 0xbf7d3e95, 0xbe163f80, 0x3edbbf75, 0xbf2c3f55, 0x3f5cbf22, 0xbf783ec4, 0x3f80bdc9, 0xbf71be48, 0x3f4e3ef1,
    0xbf4e3f35, 0x3f71bef1, 0xbf803e48, 0x3f783dc9, 0xbf5cbec4, 0x3f2c3f22, 0xbedbbf55, 0x3e163f75, 0x3f7d0000, 0xbf67be95,
    0x3f3e3f0e, 0xbf04bf46, 0x3e793f6d, 0x3d49bf7f, 0xbeac3f7b, 0x3f18bf62, 0xbf5cbec4, 0x3f2c3f22, 0xbedbbf55, 0x3e163f75,
    0xbf4e3f35, 0x3f71bef1, 0xbf803e48, 0x3f783dc9, 0x3e793f6d, 0x3d49bf7f, 0xbeac3f7b, 0x3f18bf62, 0x3f7d0000, 0xbf67be95,
    0x3f3e3f0e, 0xbf04bf46, 0xbf043f6d, 0x3f3ebf46, 0xbf673f0e, 0x3f7dbe95, 0x3f183f35, 0xbeacbf62, 0x3d493f7b, 0x3e79bf7f,
    0x3f78bec4, 0xbf803dc9, 0x3f713e48, 0xbf4ebef1, 0x3e16bf80, 0xbedb3f75, 0x3f2cbf55, 0xbf5c3f22, 0xbf780000, 0x3f3e3ef1,
    0xbeacbf55, 0xbe163f7f, 0x3f18bf6d, 0xbf673f22, 0x3f80be48, 0xbf5cbe95, 0x3f043f35, 0xbd49bf75, 0xbedb3f7b, 0x3f4ebf46,
    0xbf7d3ec4, 0x3f713dc9, 0xbf2cbf0e, 0x3e793f62, 0xbe793f80, 0x3f2cbf62, 0xbf713f0e, 0x3f7dbdc9, 0xbf4ebec4, 0x3edb3f46,
    0x3d49bf7b, 0xbf043f75, 0x3f5cbf35, 0xbf803e95, 0x3f673e48, 0xbf18bf22, 0x3e163f6d, 0x3eacbf7f, 0xbf3e3f55, 0x3f78bef1,
    0xbf4ebec4, 0x3edb3f46, 0x3d49bf7b, 0xbf043f75, 0xbe793f80, 0x3f2cbf62, 0xbf713f0e, 0x3f7dbdc9, 0x3e163f6d, 0x3eacbf7f,
    0xbf3e3f55, 0x3f78bef1, 0x3f5cbf35, 0xbf803e95, 0x3f673e48, 0xbf18bf22, 0xbf183f6d, 0x3f67bf22, 0xbf803e48, 0x3f5c3e95,
    0x3f780000, 0xbf3ebef1, 0x3eac3f55, 0x3e16bf7f, 0x3f7dbec4, 0xbf71bdc9, 0x3f2c3f0e, 0xbe79bf62, 0xbf04bf35, 0x3d493f75,
    0x3edbbf7b, 0xbf4e3f46, 0x3f67bf35, 0xbf783dc9, 0x3f183f0e, 0x3d49bf75, 0xbf2c3f6d, 0x3f7dbef1, 0xbf5cbe48, 0x3eac3f46,
    0x3f710000, 0xbf04bf22, 0xbe163f7b, 0x3f3ebf62, 0xbf803ec4, 0x3f4e3e95, 0xbe79bf55, 0xbedb3f7f, 0x3edb3f35, 0x3e79bf7f,
    0xbf4e3f55, 0x3f80be95, 0xbf3ebec4, 0x3e163f62, 0x3f04bf7b, 0xbf713f22, 0xbeac3f80, 0x3f5cbf46, 0xbf7d3e48, 0x3f2c3ef1,
    0xbd49bf6d, 0xbf183f75, 0x3f78bf0e, 0xbf67bdc9, 0x3f3e3ec4, 0xbe16bf62, 0xbf043f7b, 0x3f71bf22, 0xbedbbf35, 0xbe793f7f,
    0x3f4ebf55, 0xbf803e95, 0x3d493f6d, 0x3f18bf75, 0xbf783f0e, 0x3f673dc9, 0x3eacbf80, 0xbf5c3f46, 0x3f7dbe48, 0xbf2cbef1,
    0xbf2c3f6d, 0x3f7dbef1, 0xbf5cbe48, 0x3eac3f46, 0x3f67bf35, 0xbf783dc9, 0x3f183f0e, 0x3d49bf75, 0xbf803ec4, 0x3f4e3e95,
    0xbe79bf55, 0xbedb3f7f, 0x3f710000, 0xbf04bf22, 0xbe163f7b, 0x3f3ebf62, 0xbedb3f80, 0x3f78bf22, 0xbf4ebe48, 0x3d493f62,
    0x3f3ebf6d, 0xbf7d3e95, 0x3f043f0e, 0x3eacbf7f, 0xbf713f35, 0x3f5c3dc9, 0xbe16bf55, 0xbf2c3f75, 0x3f80bec4, 0xbf18bef1,
    0xbe793f7b, 0x3f67bf46, 0xbf670000, 0x3e793f46, 0x3f18bf7b, 0xbf803ef1, 0x3f2c3ec4, 0x3e16bf75, 0xbf5c3f55, 0x3f71bdc9,
    0xbeacbf35, 0xbf043f7f, 0x3f7dbf0e, 0xbf3ebe95, 0xbd493f6d, 0x3f4ebf62, 0xbf783e48, 0x3edb3f22, 0xbf2cbec4, 0xbe163f75,
    0x3f5cbf55, 0xbf713dc9, 0x3f670000, 0xbe79bf46, 0xbf183f7b, 0x3f80bef1, 0x3d49bf6d, 0xbf4e3f62, 0x3f78be48, 0xbedbbf22,
    0x3eac3f35, 0x3f04bf7f, 0xbf7d3f0e, 0x3f3e3e95, 0x3f3ebf6d, 0xbf7d3e95, 0x3f043f0e, 0x3eacbf7f, 0xbedb3f80, 0x3f78bf22,
    0xbf4ebe48, 0x3d493f62, 0x3f80bec4, 0xbf18bef1, 0xbe793f7b, 0x3f67bf46, 0xbf713f35, 0x3f5c3dc9, 0xbe16bf55, 0xbf2c3f75,
    0xbe79bf35, 0xbf3e3f75, 0x3f71be48, 0xbe16bf46, 0xbf4e3f6d, 0x3f67bdc9, 0xbd49bf55, 0xbf5c3f62, 0xbf043f80, 0x3f80bef1,
    0xbedbbf0e, 0xbf183f7f, 0x3f7dbec4, 0xbeacbf22, 0xbf2c3f7b, 0x3f78be95, 0xbf783f35, 0x3f2c3e95, 0x3eacbf7b, 0xbf7d3f22,
    0x3f183ec4, 0x3edbbf7f, 0xbf803f0e, 0x3f043ef1, 0x3f5c0000, 0x3d49bf62, 0xbf673f55, 0x3f4e3dc9, 0x3e16bf6d, 0xbf713f46,
    0x3f3e3e48, 0x3e79bf75, 0x3f183ec4, 0x3edbbf7f, 0xbf803f0e, 0x3f043ef1, 0xbf783f35, 0x3f2c3e95, 0x3eacbf7b, 0xbf7d3f22,
    0x3e16bf6d, 0xbf713f46, 0x3f3e3e48, 0x3e79bf75, 0x3f5c0000, 0x3d49bf62, 0xbf673f55, 0x3f4e3dc9, 0x3f4ebf6d, 0xbf673dc9,
    0x3d493f55, 0x3f5cbf62, 0x3e793f35, 0x3f3ebf75, 0xbf713e48, 0x3e163f46, 0xbf7d3ec4, 0x3eac3f22, 0x3f2cbf7b, 0xbf783e95,
    0x3f04bf80, 0xbf803ef1, 0x3edb3f0e, 0x3f18bf7f, 0xbf4e0000, 0xbeac3f75, 0x3f80bf0e, 0xbe79bf22, 0xbf5c3f6d, 0x3f3e3dc9,
    0x3edbbf7b, 0xbf7d3ef1, 0x3e163f35, 0x3f67bf62, 0xbf2cbe48, 0xbf043f7f, 0x3f78bec4, 0xbd49bf46, 0xbf713f55, 0x3f183e95,
    0xbf183f80, 0x3f71be95, 0x3d49bf55, 0xbf783f46, 0x3f043ec4, 0x3f2cbf7f, 0xbf673e48, 0xbe163f62, 0x3f7dbf35, 0xbedbbef1,
    0xbf3e3f7b, 0x3f5cbdc9, 0x3e79bf6d, 0xbf803f22, 0x3eac3f0e, 0x3f4ebf75, 0x3f043ec4, 0x3f2cbf7f, 0xbf673e48, 0xbe163f62,
    0xbf183f80, 0x3f71be95, 0x3d49bf55, 0xbf783f46, 0x3e79bf6d, 0xbf803f22, 0x3eac3f0e, 0x3f4ebf75, 0x3f7dbf35, 0xbedbbef1,
    0xbf3e3f7b, 0x3f5cbdc9, 0x3f5cbf6d, 0xbf3ebdc9, 0xbedb3f7b, 0x3f7dbef1, 0x3f4e0000, 0x3eacbf75, 0xbf803f0e, 0x3e793f22,
    0xbf783ec4, 0x3d493f46, 0x3f71bf55, 0xbf18be95, 0xbe16bf35, 0xbf673f62, 0x3f2c3e48, 0x3f04bf7f, 0x3f80bf35, 0xbe16bf22,
    0xbf783f55, 0x3eac3ef1, 0x3f67bf6d, 0xbf04be95, 0xbf4e3f7b, 0x3f2c3dc9, 0x3f3e0000, 0x3f18bf7f, 0xbf5c3e48, 0xbedb3f75,
    0x3f71bec4, 0x3e79bf62, 0xbf7d3f0e, 0xbd493f46, 0x3d493f35, 0x3f7dbf46, 0xbe79bf0e, 0xbf713f62, 0x3edb3ec4, 0x3f5cbf75,
    0xbf18be48, 0xbf3e3f7f, 0xbf2c3f80, 0x3f4ebdc9, 0x3f04bf7b, 0xbf673e95, 0xbeac3f6d, 0x3f78bef1, 0x3e16bf55, 0xbf803f22,
    0xbedbbec4, 0xbf5c3f75, 0x3f183e48, 0x3f3ebf7f, 0xbd49bf35, 0xbf7d3f46, 0x3e793f0e, 0x3f71bf62, 0x3eacbf6d, 0xbf783ef1,
    0xbe163f55, 0x3f80bf22, 0x3f2cbf80, 0xbf4e3dc9, 0xbf043f7b, 0x3f67be95, 0x3f67bf6d, 0xbf04be95, 0xbf4e3f7b, 0x3f2c3dc9,
    0x3f80bf35, 0xbe16bf22, 0xbf783f55, 0x3eac3ef1, 0x3f71bec4, 0x3e79bf62, 0xbf7d3f0e, 0xbd493f46, 0x3f3e0000, 0x3f18bf7f,
    0xbf5c3e48, 0xbedb3f75, 0xbf3e3f80, 0x3f183dc9, 0x3f5cbf7b, 0xbedbbe95, 0xbf713f6d, 0x3e793ef1, 0x3f7dbf55, 0xbd49bf22,
    0xbf803f35, 0xbe163f46, 0x3f78bf0e, 0x3eacbf62, 0xbf673ec4, 0xbf043f75, 0x3f4ebe48, 0x3f2cbf7f, 0xbf2c0000, 0xbf4e3f7f,
    0x3f043e48, 0x3f67bf75, 0xbeacbec4, 0xbf783f62, 0x3e163f0e, 0x3f80bf46, 0x3d49bf35, 0xbf7d3f22, 0xbe793f55, 0x3f71bef1,
    0x3edbbf6d, 0xbf5c3e95, 0xbf183f7b, 0x3f3ebdc9, 0x3eac3ec4, 0x3f78bf62, 0xbe16bf0e, 0xbf803f46, 0x3f2c0000, 0x3f4ebf7f,
    0xbf04be48, 0xbf673f75, 0xbedb3f6d, 0x3f5cbe95, 0x3f18bf7b, 0xbf3e3dc9, 0xbd493f35, 0x3f7dbf22, 0x3e79bf55, 0xbf713ef1,
    0xbf713f6d, 0x3e793ef1, 0x3f7dbf55, 0xbd49bf22, 0xbf3e3f80, 0x3f183dc9, 0x3f5cbf7b, 0xbedbbe95, 0xbf673ec4, 0xbf043f75,
    0x3f4ebe48, 0x3f2cbf7f, 0xbf803f35, 0xbe163f46, 0x3f78bf0e, 0x3eacbf62, 0x3e16bf35, 0xbf673ef1, 0xbf2c3f7b, 0x3f043dc9,
    0x3f78bf6d, 0x3d49bf22, 0xbf713f0e, 0xbf183f75, 0xbf4e3f80, 0x3eac3e95, 0x3f80bf55, 0x3e79bf46, 0xbf5c3ec4, 0xbf3e3f7f,
    0x3edb3e48, 0x3f7dbf62, 0xbf7d3f35, 0xbedb3f62, 0x3f3ebe48, 0x3f5cbf7f, 0xbe79bec4, 0xbf803f46, 0xbeac3f55, 0x3f4ebe95,
    0x3f180000, 0x3f71bf75, 0xbd49bf0e, 0xbf783f22, 0xbf043f6d, 0x3f2cbdc9, 0x3f67bf7b, 0xbe16bef1, 0xbe79bec4, 0xbf803f46,
    0xbeac3f55, 0x3f4ebe95, 0xbf7d3f35, 0xbedb3f62, 0x3f3ebe48, 0x3f5cbf7f, 0xbf043f6d, 0x3f2cbdc9, 0x3f67bf7b, 0xbe16bef1,
    0x3f180000, 0x3f71bf75, 0xbd49bf0e, 0xbf783f22, 0xbf783f6d, 0xbd493f22, 0x3f71bf0e, 0x3f18bf75, 0xbe163f35, 0x3f67bef1,
    0x3f2cbf7b, 0xbf04bdc9, 0x3f5cbec4, 0x3f3ebf7f, 0xbedbbe48, 0xbf7d3f62, 0x3f4ebf80, 0xbeacbe95, 0xbf803f55, 0xbe793f46,
    0xbf040000, 0xbf803f62, 0xbedb3f55, 0x3f18bdc9, 0x3f7dbf6d, 0x3eacbf46, 0xbf2c3e48, 0xbf783f75, 0xbe793f35, 0x3f3ebe95,
    0x3f71bf7b, 0x3e16bf22, 0xbf4e3ec4, 0xbf673f7f, 0xbd493f0e, 0x3f5cbef1, 0xbf5c3f80, 0x3d493ef1, 0x3f67bf0e, 0x3f4ebf7f,
    0xbe16bec4, 0xbf713f22, 0xbf3e3f7b, 0x3e793e95, 0x3f78bf35, 0x3f2cbf75, 0xbeacbe48, 0xbf7d3f46, 0xbf183f6d, 0x3edb3dc9,
    0x3f80bf55, 0x3f04bf62, 0xbe16bec4, 0xbf713f22, 0xbf3e3f7b, 0x3e793e95, 0xbf5c3f80, 0x3d493ef1, 0x3f67bf0e, 0x3f4ebf7f,
    0xbf183f6d, 0x3edb3dc9, 0x3f80bf55, 0x3f04bf62, 0x3f78bf35, 0x3f2cbf75, 0xbeacbe48, 0xbf7d3f46, 0xbf7d3f6d, 0xbeac3f46,
    0x3f2cbe48, 0x3f78bf75, 0x3f040000, 0x3f80bf62, 0x3edbbf55, 0xbf183dc9, 0x3f4ebec4, 0x3f67bf7f, 0x3d49bf0e, 0xbf5c3ef1,
    0x3e79bf35, 0xbf3e3e95, 0xbf713f7b, 0xbe163f22, 0x3f71bf35, 0x3f5cbf7f, 0x3e16bf0e, 0xbf2c3e95, 0xbf803f6d, 0xbf183f62,
    0x3e793e48, 0x3f67bf22, 0x3edb0000, 0x3f78bf46, 0x3f4ebf7b, 0x3d49bef1, 0xbf3e3ec4, 0xbf7d3f75, 0xbf043f55, 0x3eac3dc9,
    0xbeac3f35, 0x3f04bdc9, 0x3f7dbf55, 0x3f3ebf75, 0xbd49bec4, 0xbf4e3ef1, 0xbf783f7b, 0xbedb3f46, 0xbf673f80, 0xbe793f22,
    0x3f18be48, 0x3f80bf62, 0x3f2cbf6d, 0xbe16be95, 0xbf5c3f0e, 0xbf713f7f, 0x3d493ec4, 0x3f4ebef1, 0x3f78bf7b, 0x3edbbf46,
    0x3eacbf35, 0xbf043dc9, 0xbf7d3f55, 0xbf3e3f75, 0xbf2c3f6d, 0x3e163e95, 0x3f5cbf0e, 0x3f71bf7f, 0x3f67bf80, 0x3e79bf22,
    0xbf183e48, 0xbf803f62, 0xbf803f6d, 0xbf183f62, 0x3e793e48, 0x3f67bf22, 0x3f71bf35, 0x3f5cbf7f, 0x3e16bf0e, 0xbf2c3e95,
    0xbf3e3ec4, 0xbf7d3f75, 0xbf043f55, 0x3eac3dc9, 0x3edb0000, 0x3f78bf46, 0x3f4ebf7b, 0x3d49bef1, 0xbf713f80, 0xbf043f46,
    0x3e163e48, 0x3f3ebef1, 0x3f80bf6d, 0x3f4ebf75, 0x3e79bf0e, 0xbedb3dc9, 0xbf673f35, 0xbf783f7f, 0xbf183f55, 0x3d493e95,
    0x3f2cbec4, 0x3f7dbf62, 0x3f5cbf7b, 0x3eacbf22, 0xbeac0000, 0xbf5c3f22, 0xbf7d3f7b, 0xbf2c3f62, 0xbd493ec4, 0x3f18be95,
    0x3f78bf55, 0x3f67bf7f, 0x3edbbf35, 0xbe79bdc9, 0xbf4e3f0e, 0xbf803f75, 0xbf3e3f6d, 0xbe163ef1, 0x3f04be48, 0x3f71bf46,
    0x3d49bec4, 0xbf183e95, 0xbf783f55, 0xbf673f7f, 0x3eac0000, 0x3f5cbf22, 0x3f7dbf7b, 0x3f2cbf62, 0x3f3ebf6d, 0x3e16bef1,
    0xbf043e48, 0xbf713f46, 0xbedb3f35, 0x3e793dc9, 0x3f4ebf0e, 0x3f80bf75, 0x3f80bf6d, 0x3f4ebf75, 0x3e79bf0e, 0xbedb3dc9,
    0xbf713f80, 0xbf043f46, 0x3e163e48, 0x3f3ebef1, 0x3f2cbec4, 0x3f7dbf62, 0x3f5cbf7b, 0x3eacbf22, 0xbf673f35, 0xbf783f7f,
    0xbf183f55, 0x3d493e95, 0x3f04bf35, 0x3d49be95, 0xbedb3e48, 0xbf4e3f22, 0xbf7d3f6d, 0xbf713f7f, 0xbf2c3f55, 0xbe793ef1,
    0xbf783f80, 0xbf3e3f62, 0xbeac3f0e, 0x3e163dc9, 0x3f18bec4, 0x3f67bf46, 0x3f80bf7b, 0x3f5cbf75, 0xbf5c3f35, 0xbf803f75,
    0xbf673f7b, 0xbf183f46, 0xbe163ec4, 0x3eacbdc9, 0x3f3ebf0e, 0x3f78bf62, 0x3e790000, 0x3f2cbef1, 0x3f71bf55, 0x3f7dbf7f,
    0x3f4ebf6d, 0x3edbbf22, 0xbd49be48, 0xbf043e95, 0xbe163ec4, 0x3eacbdc9, 0x3f3ebf0e, 0x3f78bf62, 0xbf5c3f35, 0xbf803f75,
    0xbf673f7b, 0xbf183f46, 0x3f4ebf6d, 0x3edbbf22, 0xbd49be48, 0xbf043e95, 0x3e790000, 0x3f2cbef1, 0x3f71bf55, 0x3f7dbf7f,
    0x3f7dbf6d, 0x3f71bf7f, 0x3f2cbf55, 0x3e79bef1, 0xbf043f35, 0xbd493e95, 0x3edbbe48, 0x3f4ebf22, 0xbf183ec4, 0xbf673f46,
    0xbf803f7b, 0xbf5c3f75, 0x3f78bf80, 0x3f3ebf62, 0x3eacbf0e, 0xbe16bdc9, 0xbe160000, 0xbedb3e95, 0xbf2c3f0e, 0xbf5c3f46,
    0xbf783f6d, 0xbf803f7f, 0xbf713f7b, 0xbf4e3f62, 0xbf183f35, 0xbeac3ef1, 0xbd493e48, 0x3e79bdc9, 0x3f04bec4, 0x3f3ebf22,
    0x3f67bf55, 0x3f7dbf75, 0xbf7d3f80, 0xbf673f75, 0xbf3e3f55, 0xbf043f22, 0xbe793ec4, 0x3d493dc9, 0x3eacbe48, 0x3f18bef1,
    0x3f4ebf35, 0x3f71bf62, 0x3f80bf7b, 0x3f78bf7f, 0x3f5cbf6d, 0x3f2cbf46, 0x3edbbf0e, 0x3e16be95, 0xbe793ec4, 0x3d493dc9,
    0x3eacbe48, 0x3f18bef1, 0xbf7d3f80, 0xbf673f75, 0xbf3e3f55, 0xbf043f22, 0x3f5cbf6d, 0x3f2cbf46, 0x3edbbf0e, 0x3e16be95,
    0x3f4ebf35, 0x3f71bf62, 0x3f80bf7b, 0x3f78bf7f, 0x3f78bf6d, 0x3f80bf7f, 0x3f71bf7b, 0x3f4ebf62, 0x3e160000, 0x3edbbe95,
    0x3f2cbf0e, 0x3f5cbf46, 0xbf043ec4, 0xbf3e3f22, 0xbf673f55, 0xbf7d3f75, 0x3f18bf35, 0x3eacbef1, 0x3d49be48, 0xbe793dc9,
    0x3f3ebf35, 0x3f4ebf46, 0x3f5cbf55, 0x3f67bf62, 0x3f71bf6d, 0x3f78bf75, 0x3f7dbf7b, 0x3f80bf7f, 0x3d490000, 0x3e16bdc9,
    0x3e79be48, 0x3eacbe95, 0x3edbbec4, 0x3f04bef1, 0x3f18bf0e, 0x3f2cbf22, 0xbf2c3f35, 0xbf183f22, 0xbf043f0e, 0xbedb3ef1,
    0xbeac3ec4, 0xbe793e95, 0xbe163e48, 0xbd493dc9, 0xbf803f80, 0xbf7d3f7f, 0xbf783f7b, 0xbf713f75, 0xbf673f6d, 0xbf5c3f62,
    0xbf4e3f55, 0xbf3e3f46, 0x3eacbec4, 0x3e79be95, 0x3e16be48, 0x3d49bdc9, 0x3f2cbf35, 0x3f18bf22, 0x3f04bf0e, 0x3edbbef1,
    0x3f67bf6d, 0x3f5cbf62, 0x3f4ebf55, 0x3f3ebf46, 0x3f80bf80, 0x3f7dbf7f, 0x3f78bf7b, 0x3f71bf75, 0x3f71bf6d, 0x3f78bf75,
    0x3f7dbf7b, 0x3f80bf7f, 0x3f3ebf35, 0x3f4ebf46, 0x3f5cbf55, 0x3f67bf62, 0x3edbbec4, 0x3f04bef1, 0x3f18bf0e, 0x3f2cbf22,
    0x3d490000, 0x3e16bdc9, 0x3e79be48, 0x3eacbe95,
};
__device__ const __align__(128) uint32_t c_fa[512] = {
    0x3f803f80, 0x3f673f80, 0x3f673f6d, 0xbf2cbf6d, 0x3f7d3f7f, 0x3e793f22, 0x3f5c3f62, 0x3e16be95, 0x3f783f7b, 0xbf18be48,
    0x3f4e3f55, 0x3f5c3f0e, 0x3f713f75, 0xbf80bf62, 0x3f3e3f46, 0x3f713f7f, 0x3d490000, 0x3edb0000, 0x3edb3ec4, 0xbf3ebec4,
    0x3e163dc9, 0x3f783f46, 0x3f043ef1, 0xbf7dbf75, 0x3e793e48, 0x3f4e3f7b, 0x3f183f0e, 0xbf04bf55, 0x3eac3e95, 0x3d493ef1,
    0x3f2c3f22, 0x3eacbdc9, 0x3f7d3f80, 0x3f5c3f80, 0x3e793ec4, 0x3e16bec4, 0x3f673f75, 0xbd493ef1, 0xbd493dc9, 0x3f713f22,
    0x3f3e3f55, 0xbf67bf0e, 0xbeacbe48, 0x3f3e3f7b, 0x3f043f22, 0xbf4ebf7f, 0xbf18bef1, 0xbe793e95, 0x3e160000, 0x3f040000,
    0x3f783f6d, 0xbf7dbf6d, 0x3edb3e95, 0x3f803f62, 0x3f803f7f, 0xbeacbf46, 0x3f2c3f0e, 0x3edb3f55, 0x3f713f7b, 0x3f2c3e48,
    0x3f5c3f46, 0xbf18bdc9, 0x3f4e3f62, 0x3f783f75, 0x3f783f80, 0x3f4e3f80, 0xbf18bec4, 0x3f5c3ec4, 0x3f3e3f62, 0xbeac3e95,
    0xbf67bf46, 0x3f3e3f7f, 0x3eac3f0e, 0xbf80bf55, 0xbf80bf7b, 0xbedb3e48, 0xbe163dc9, 0xbe79bf46, 0xbf5cbf75, 0xbf7dbf62,
    0x3e790000, 0x3f180000, 0x3f4e3f6d, 0xbf04bf6d, 0x3f2c3ef1, 0x3f713f75, 0x3edb3f22, 0x3f2c3dc9, 0x3f713f55, 0xbd493f0e,
    0xbd493e48, 0x3f673f7b, 0x3f7d3f7f, 0xbf78bf22, 0xbf04be95, 0xbe163ef1, 0x3f713f80, 0x3f3e3f80, 0xbf80bf6d, 0x3f713f6d,
    0x3f043f46, 0xbf183dc9, 0xbf4ebf75, 0xbe793ef1, 0xbe163e48, 0xbf5cbf7b, 0xbe79bf0e, 0xbf7dbf55, 0xbf3ebef1, 0x3edbbe95,
    0x3edb3dc9, 0x3d49bf22, 0x3eac0000, 0x3f2c0000, 0x3d493ec4, 0x3eacbec4, 0x3f5c3f22, 0x3f4e3f7f, 0xbf18be95, 0x3f783f62,
    0x3f7d3f7b, 0xbf043e48, 0xbf78bf55, 0xbe163f0e, 0x3f2c3f62, 0xbf67bf75, 0xbf67bf7f, 0xbf80bf46, 0x3f2c3f80, 0x3eac3f80,
    0x3eac3f6d, 0x3d49bf6d, 0xbf4ebdc9, 0xbf5cbf46, 0xbf78bef1, 0x3f183f75, 0xbf04bf7b, 0x3f7d3e48, 0xbe16bf55, 0xbf78bf0e,
    0x3f673e95, 0xbf2c3ef1, 0x3f803f22, 0x3f67bdc9, 0x3f3e0000, 0x3f710000, 0x3f713ec4, 0xbf80bec4, 0x3f183f7f, 0xbf043f22,
    0x3e793f62, 0x3f4ebe95, 0xbf5cbe48, 0xbe16bf7b, 0xbf7dbf0e, 0xbe793f55, 0xbedbbf75, 0x3f3e3f62, 0xbd49bf46, 0xbedbbf7f,
    0x3f183f80, 0x3e793f80, 0xbf043ec4, 0x3f4ebec4, 0xbf71be95, 0xbf2cbf62, 0xbf2cbf7f, 0xbedb3f46, 0xbd49bf55, 0x3f713f0e,
    0x3f673e48, 0xbd49bf7b, 0x3f783f46, 0xbf7dbdc9, 0x3e163f62, 0x3f043f75, 0x3f4e0000, 0x3f780000, 0x3f5c3f6d, 0xbf18bf6d,
    0x3eac3f75, 0xbf3e3ef1, 0xbf3e3dc9, 0x3f673f22, 0xbf80bf0e, 0x3eacbf55, 0xbedbbf7b, 0xbf80be48, 0x3e79bf22, 0x3e163f7f,
    0x3f7d3ef1, 0x3f5cbe95, 0x3f043f80, 0x3e163f80, 0xbf7dbec4, 0x3f783ec4, 0xbf80bef1, 0xbedbbf75, 0x3eacbf22, 0xbf80bdc9,
    0x3edbbf0e, 0x3f2c3f55, 0x3f2c3f7b, 0x3f71be48, 0x3f183f7f, 0xbf5cbf22, 0xbf78be95, 0xbf4e3ef1, 0x3f5c0000, 0x3f7d0000,
    0x3e163f6d, 0x3e79bf6d, 0x3d493f62, 0xbf673e95, 0xbf71bf46, 0x3d493f7f, 0xbf67bf55, 0x3f3ebf0e, 0x3f3ebe48, 0xbeacbf7b,
    0x3f4ebdc9, 0xbf043f46, 0x3e793f75, 0x3f183f62, 0x3edb3f80, 0x3d493f80, 0xbf3ebf6d, 0x3edb3f6d, 0xbf78bf22, 0xbe16bf7f,
    0x3f7d3e95, 0xbf04bf62, 0x3f4ebe48, 0x3e793f7b, 0xbf043f0e, 0x3f183f55, 0xbd493f62, 0xbeacbf75, 0xbeacbf7f, 0xbf2cbf46,
    0x3f670000, 0x3f800000, 0xbf2c3ec4, 0x3f67bec4, 0xbe793f46, 0xbf7d3dc9, 0xbe16bf75, 0xbf5c3ef1, 0xbf18bf7b, 0x3f78be48,
    0x3f5c3f55, 0x3f4ebf0e, 0x3f803ef1, 0xbf713e95, 0xbf71bdc9, 0xbf3e3f22, 0xbd493f80, 0xbedb3f80, 0xbedb3f6d, 0x3f3ebf6d,
    0x3e16bf7f, 0x3f78bf22, 0x3f04bf62, 0xbf7d3e95, 0xbe793f7b, 0xbf4ebe48, 0xbf183f55, 0x3f043f0e, 0x3eacbf75, 0x3d493f62,
    0x3f2cbf46, 0x3eacbf7f, 0x3f800000, 0x3f670000, 0x3f673ec4, 0xbf2cbec4, 0xbf7dbdc9, 0xbe79bf46, 0xbf5cbef1, 0xbe163f75,
    0x3f783e48, 0xbf183f7b, 0x3f4e3f0e, 0x3f5cbf55, 0xbf71be95, 0x3f80bef1, 0xbf3ebf22, 0xbf713dc9, 0xbe163f80, 0xbf043f80,
    0xbf783ec4, 0x3f7dbec4, 0x3edbbf75, 0x3f80bef1, 0x3f80bdc9, 0xbeacbf22, 0xbf2c3f55, 0xbedbbf0e, 0xbf71be48, 0xbf2c3f7b,
    0x3f5cbf22, 0xbf183f7f, 0x3f4e3ef1, 0x3f78be95, 0x3f7d0000, 0x3f5c0000, 0x3e793f6d, 0x3e16bf6d, 0xbf67be95, 0x3d49bf62,
    0x3d49bf7f, 0xbf713f46, 0x3f3e3f0e, 0xbf673f55, 0xbeac3f7b, 0x3f3e3e48, 0xbf04bf46, 0x3f4e3dc9, 0x3f18bf62, 0x3e79bf75,
    0xbe793f80, 0xbf183f80, 0xbf4ebec4, 0x3f043ec4, 0x3f2cbf62, 0x3f71be95, 0x3edb3f46, 0x3f2cbf7f, 0xbf713f0e, 0x3d49bf55,
    0x3d49bf7b, 0xbf673e48, 0x3f7dbdc9, 0xbf783f46, 0xbf043f75, 0xbe163f62, 0x3f780000, 0x3f4e0000, 0xbf183f6d, 0x3f5cbf6d,
    0xbf3ebef1, 0x3eacbf75, 0x3f67bf22, 0xbf3ebdc9, 0x3eac3f55, 0xbf803f0e, 0xbf803e48, 0xbedb3f7b, 0x3e16bf7f, 0x3e793f22,
    0x3f5c3e95, 0x3f7dbef1, 0xbeac3f80, 0xbf2c3f80, 0xbd49bf6d, 0xbeac3f6d, 0x3f5cbf46, 0x3f4ebdc9, 0xbf183f75, 0x3f78bef1,
    0xbf7d3e48, 0x3f04bf7b, 0x3f78bf0e, 0x3e16bf55, 0x3f2c3ef1, 0xbf673e95, 0xbf67bdc9, 0xbf803f22, 0x3f710000, 0x3f3e0000,
    0xbf803ec4, 0x3f71bec4, 0xbf04bf22, 0x3f18bf7f, 0x3f4e3e95, 0x3e79bf62, 0xbe163f7b, 0xbf5c3e48, 0xbe79bf55, 0xbf7d3f0e,
    0x3f3ebf62, 0xbedb3f75, 0xbedb3f7f, 0xbd493f46, 0xbf3e3f80, 0xbf713f80, 0xbf713f6d, 0x3f80bf6d, 0x3f183dc9, 0xbf043f46,
    0x3e793ef1, 0x3f4ebf75, 0x3f5cbf7b, 0x3e163e48, 0x3f7dbf55, 0x3e79bf0e, 0xbedbbe95, 0x3f3ebef1, 0xbd49bf22, 0xbedb3dc9,
    0x3f2c0000, 0x3eac0000, 0x3eac3ec4, 0x3d49bec4, 0x3f4ebf7f, 0x3f5cbf22, 0x3f78bf62, 0xbf183e95, 0xbf04be48, 0x3f7dbf7b,
    0xbe16bf0e, 0xbf783f55, 0xbf673f75, 0x3f2cbf62, 0xbf803f46, 0xbf673f7f, 0xbf4e3f80, 0xbf783f80, 0xbf5c3ec4, 0x3f18bec4,
    0x3eac3e95, 0xbf3e3f62, 0xbf3e3f7f, 0x3f67bf46, 0x3f80bf55, 0xbeac3f0e, 0x3edb3e48, 0x3f80bf7b, 0x3e79bf46, 0x3e163dc9,
    0x3f7dbf62, 0x3f5cbf75, 0x3f180000, 0x3e790000, 0xbf043f6d, 0x3f4ebf6d, 0x3f71bf75, 0x3f2cbef1, 0x3f2cbdc9, 0x3edbbf22,
    0xbd49bf0e, 0x3f71bf55, 0x3f67bf7b, 0xbd49be48, 0xbf783f22, 0x3f7dbf7f, 0xbe16bef1, 0xbf043e95, 0xbf5c3f80, 0xbf7d3f80,
    0xbe16bec4, 0xbe793ec4, 0x3d493ef1, 0xbf673f75, 0xbf713f22, 0x3d493dc9, 0x3f67bf0e, 0xbf3e3f55, 0xbf3e3f7b, 0x3eacbe48,
    0x3f4ebf7f, 0xbf043f22, 0x3e793e95, 0x3f18bef1, 0x3f040000, 0x3e160000, 0xbf7d3f6d, 0x3f78bf6d, 0x3f80bf62, 0x3edbbe95,
    0xbeac3f46, 0x3f80bf7f, 0x3edbbf55, 0x3f2cbf0e, 0x3f2cbe48, 0x3f71bf7b, 0xbf183dc9, 0x3f5cbf46, 0x3f78bf75, 0x3f4ebf62,
    0xbf673f80, 0xbf803f80, 0x3f2cbf6d, 0xbf673f6d, 0xbe793f22, 0xbf7d3f7f, 0xbe16be95, 0xbf5c3f62, 0x3f18be48, 0xbf783f7b,
    0xbf5c3f0e, 0xbf4e3f55, 0x3f80bf62, 0xbf713f75, 0xbf713f7f, 0xbf3e3f46, 0x3edb0000, 0x3d490000, 0xbf3e3ec4, 0x3edbbec4,
    0x3f78bf46, 0x3e16bdc9, 0xbf7d3f75, 0x3f04bef1, 0x3f4ebf7b, 0x3e79be48, 0xbf043f55, 0x3f18bf0e, 0x3d49bef1, 0x3eacbe95,
    0x3eac3dc9, 0x3f2cbf22,
};
__device__ const __align__(128) uint32_t c_ga[1536] = {
    0x00003c80, 0x3bc43c6d, 0x00003c80, 0xbbc4bc6d, 0x00003c80, 0x3c6d3bc4, 0x00003c80, 0xbc6dbbc4, 0x00003c80, 0x3c6dbbc4,
    0x00003c80, 0xbc6d3bc4, 0x00003c80, 0x3bc4bc6d, 0x00003c80, 0xbbc43c6d, 0x3a493c80, 0x3bdb3c67, 0x3bdb3c67, 0xbc3ebc2c,
    0x3b163c7d, 0x3c783b79, 0x3c043c5c, 0xbc7d3b16, 0x3b793c78, 0x3c4ebc18, 0x3c183c4e, 0xbc043c5c, 0x3bac3c71, 0x3a49bc80,
    0x3c2c3c3e, 0x3bac3c71, 0x3ac93c7f, 0x3bf13c62, 0x3c463c22, 0xbc75bb95, 0x3b953c75, 0x3c7f3ac9, 0x3c623bf1, 0xbc463c22,
    0x3bf13c62, 0x3c22bc46, 0x3c753b95, 0x3ac93c7f, 0x3c223c46, 0xbb95bc75, 0x3c7f3ac9, 0x3c623bf1, 0x3b163c7d, 0x3c043c5c,
    0x3c783b79, 0xbc7d3b16, 0x3bdb3c67, 0x3c80ba49, 0x3c80ba49, 0xbbac3c71, 0x3c2c3c3e, 0x3bdbbc67, 0x3c71bbac, 0x3c2c3c3e,
    0x3c5c3c04, 0xbc18bc4e, 0x3c4ebc18, 0x3c78bb79, 0x3b483c7b, 0x3c0e3c55, 0x3c7bbb48, 0xbc553c0e, 0x3c0e3c55, 0x3c7bbb48,
    0x3c55bc0e, 0x3b483c7b, 0x3c553c0e, 0x3b48bc7b, 0x3c0ebc55, 0x3c7b3b48, 0x3c7b3b48, 0xbc55bc0e, 0x3b48bc7b, 0x3c0ebc55,
    0x3b793c78, 0x3c183c4e, 0x3c4ebc18, 0xbc043c5c, 0x3c2c3c3e, 0x3c71bbac, 0x3bdbbc67, 0x3c2c3c3e, 0x3c713bac, 0xba49bc80,
    0xba49bc80, 0x3c67bbdb, 0x3c7dbb16, 0xbc78bb79, 0xbc04bc5c, 0xbb16bc7d, 0x3b953c75, 0x3c223c46, 0x3bf1bc62, 0xbac93c7f,
    0x3c463c22, 0x3c62bbf1, 0xbac9bc7f, 0x3c753b95, 0x3c7f3ac9, 0xbb95bc75, 0xbc22bc46, 0x3bf1bc62, 0x3c62bbf1, 0xbc7f3ac9,
    0xbc75bb95, 0xbc46bc22, 0x3bac3c71, 0x3c2c3c3e, 0x3a49bc80, 0x3bac3c71, 0x3c5c3c04, 0x3c4ebc18, 0xbc18bc4e, 0x3c78bb79,
    0x3c7dbb16, 0xbc04bc5c, 0xbc78bb79, 0xbb16bc7d, 0x3c2cbc3e, 0xbc673bdb, 0xbc673bdb, 0xbc803a49, 0x00003c80, 0x3bc43c6d,
    0x00003c80, 0xbbc4bc6d, 0x00003c80, 0x3c6d3bc4, 0x00003c80, 0xbc6dbbc4, 0x00003c80, 0x3c6dbbc4, 0x00003c80, 0xbc6d3bc4,
    0x00003c80, 0x3bc4bc6d, 0x00003c80, 0xbbc43c6d, 0x3c3e3c2c, 0x3c713bac, 0x3c713bac, 0xbc803a49, 0x3c4e3c18, 0x3c5cbc04,
    0x3c783b79, 0xbc183c4e, 0x3c5c3c04, 0x3b16bc7d, 0x3c7d3b16, 0x3b793c78, 0x3c673bdb, 0xbc2cbc3e, 0x3c803a49, 0x3c673bdb,
    0x3c7fbac9, 0x3c62bbf1, 0x3c22bc46, 0xbb953c75, 0x3c75bb95, 0x3ac9bc7f, 0x3bf1bc62, 0x3c223c46, 0x3c62bbf1, 0xbc46bc22,
    0x3b95bc75, 0x3c7fbac9, 0x3c46bc22, 0xbc753b95, 0x3ac9bc7f, 0x3bf1bc62, 0x3c18bc4e, 0x3b79bc78, 0xbc04bc5c, 0x3c4e3c18,
    0x3bacbc71, 0xbc3ebc2c, 0xbc3ebc2c, 0x3c67bbdb, 0x3a49bc80, 0xbc713bac, 0xbc67bbdb, 0x3a49bc80, 0xbb79bc78, 0xbb163c7d,
    0xbc7dbb16, 0xbc5cbc04, 0xbb48bc7b, 0xbc0ebc55, 0xbc7b3b48, 0x3c55bc0e, 0xbc0ebc55, 0xbc7b3b48, 0xbc553c0e, 0xbb48bc7b,
    0xbc55bc0e, 0xbb483c7b, 0xbc0e3c55, 0xbc7bbb48, 0xbc7bbb48, 0x3c553c0e, 0xbb483c7b, 0xbc0e3c55, 0xbc5cbc04, 0xbc7dbb16,
    0xbb163c7d, 0xbb79bc78, 0xbc80ba49, 0xbbdb3c67, 0x3bac3c71, 0xbc80ba49, 0xbc673bdb, 0x3c3e3c2c, 0x3c3e3c2c, 0xbbac3c71,
    0xbc183c4e, 0x3c5cbc04, 0x3c783b79, 0x3c4e3c18, 0xbc753b95, 0xbc463c22, 0x3c623bf1, 0xbc7fbac9, 0xbc223c46, 0x3bf13c62,
    0x3c7fbac9, 0xbb953c75, 0xbac93c7f, 0x3c75bb95, 0x3c46bc22, 0x3c623bf1, 0x3bf13c62, 0xbac9bc7f, 0x3b95bc75, 0x3c22bc46,
    0xbbdb3c67, 0xba493c80, 0x3c3ebc2c, 0xbbdb3c67, 0x3b793c78, 0x3c7d3b16, 0x3b16bc7d, 0x3c5c3c04, 0x3c4e3c18, 0x3b79bc78,
    0xbc04bc5c, 0x3c18bc4e, 0x3c80ba49, 0xbc71bbac, 0xbc71bbac, 0xbc3ebc2c, 0x00003c80, 0x3bc43c6d, 0x00003c80, 0xbbc4bc6d,
    0x00003c80, 0x3c6d3bc4, 0x00003c80, 0xbc6dbbc4, 0x00003c80, 0x3c6dbbc4, 0x00003c80, 0xbc6d3bc4, 0x00003c80, 0x3bc4bc6d,
    0x00003c80, 0xbbc43c6d, 0x3c80ba49, 0x3c67bbdb, 0x3c67bbdb, 0xbc2c3c3e, 0x3c7dbb16, 0x3b79bc78, 0x3c5cbc04, 0x3b163c7d,
    0x3c78bb79, 0xbc18bc4e, 0x3c4ebc18, 0x3c5c3c04, 0x3c71bbac, 0xbc80ba49, 0x3c3ebc2c, 0x3c71bbac, 0xbac9bc7f, 0xbbf1bc62,
    0xbc46bc22, 0x3c753b95, 0xbb95bc75, 0xbc7fbac9, 0xbc62bbf1, 0x3c46bc22, 0xbbf1bc62, 0xbc223c46, 0xbc75bb95, 0xbac9bc7f,
    0xbc22bc46, 0x3b953c75, 0xbc7fbac9, 0xbc62bbf1, 0xbc7d3b16, 0xbc5c3c04, 0xbb793c78, 0xbb16bc7d, 0xbc673bdb, 0x3a493c80,
    0x3a493c80, 0xbc71bbac, 0xbc3e3c2c, 0x3c673bdb, 0x3bac3c71, 0xbc3e3c2c, 0xbc043c5c, 0x3c4ebc18, 0x3c183c4e, 0x3b793c78,
    0x3b483c7b, 0x3c0e3c55, 0x3c7bbb48, 0xbc553c0e, 0x3c0e3c55, 0x3c7bbb48, 0x3c55bc0e, 0x3b483c7b, 0x3c553c0e, 0x3b48bc7b,
    0x3c0ebc55, 0x3c7b3b48, 0x3c7b3b48, 0xbc55bc0e, 0x3b48bc7b, 0x3c0ebc55, 0x3c78bb79, 0x3c4ebc18, 0xbc18bc4e, 0x3c5c3c04,
    0x3c3ebc2c, 0xbbacbc71, 0xbc67bbdb, 0x3c3ebc2c, 0x3bacbc71, 0xbc803a49, 0xbc803a49, 0xbbdbbc67, 0xbb16bc7d, 0xbb793c78,
    0xbc5c3c04, 0xbc7d3b16, 0xbb95bc75, 0xbc22bc46, 0xbbf13c62, 0x3ac9bc7f, 0xbc46bc22, 0xbc623bf1, 0x3ac93c7f, 0xbc75bb95,
    0xbc7fbac9, 0x3b953c75, 0x3c223c46, 0xbbf13c62, 0xbc623bf1, 0x3c7fbac9, 0x3c753b95, 0x3c463c22, 0xbc713bac, 0xbc3e3c2c,
    0x3c803a49, 0xbc713bac, 0xbc043c5c, 0x3c183c4e, 0x3c4ebc18, 0x3b793c78, 0x3b163c7d, 0x3c5cbc04, 0x3b79bc78, 0x3c7dbb16,
    0x3c3e3c2c, 0xbbdbbc67, 0xbbdbbc67, 0xba49bc80, 0x00003c80, 0x3bc43c6d, 0x00003c80, 0xbbc4bc6d, 0x00003c80, 0x3c6d3bc4,
    0x00003c80, 0xbc6dbbc4, 0x00003c80, 0x3c6dbbc4, 0x00003c80, 0xbc6d3bc4, 0x00003c80, 0x3bc4bc6d, 0x00003c80, 0xbbc43c6d,
    0x3c2cbc3e, 0x3bacbc71, 0x3bacbc71, 0x3a493c80, 0x3c18bc4e, 0xbc04bc5c, 0x3b79bc78, 0x3c4e3c18, 0x3c04bc5c, 0xbc7dbb16,
    0x3b16bc7d, 0x3c78bb79, 0x3bdbbc67, 0xbc3e3c2c, 0x3a49bc80, 0x3bdbbc67, 0xbc7f3ac9, 0xbc623bf1, 0xbc223c46, 0x3b95bc75,
    0xbc753b95, 0xbac93c7f, 0xbbf13c62, 0xbc22bc46, 0xbc623bf1, 0x3c463c22, 0xbb953c75, 0xbc7f3ac9, 0xbc463c22, 0x3c75bb95,
    0xbac93c7f, 0xbbf13c62, 0x3c4e3c18, 0x3c783b79, 0x3c5cbc04, 0xbc183c4e, 0x3c713bac, 0x3c2cbc3e, 0x3c2cbc3e, 0x3bdb3c67,
    0x3c803a49, 0xbbacbc71, 0x3bdbbc67, 0x3c803a49, 0x3c78bb79, 0xbc7dbb16, 0x3b16bc7d, 0x3c04bc5c, 0xbb48bc7b, 0xbc0ebc55,
    0xbc7b3b48, 0x3c55bc0e, 0xbc0ebc55, 0xbc7b3b48, 0xbc553c0e, 0xbb48bc7b, 0xbc55bc0e, 0xbb483c7b, 0xbc0e3c55, 0xbc7bbb48,
    0xbc7bbb48, 0x3c553c0e, 0xbb483c7b, 0xbc0e3c55, 0xbc043c5c, 0xbb163c7d, 0x3c7d3b16, 0xbc783b79, 0xba493c80, 0x3c673bdb,
    0x3c71bbac, 0xba493c80, 0x3bdb3c67, 0x3c2cbc3e, 0x3c2cbc3e, 0x3c713bac, 0x3c4e3c18, 0xbc04bc5c, 0x3b79bc78, 0x3c18bc4e,
    0x3c75bb95, 0x3c46bc22, 0xbc62bbf1, 0x3c7f3ac9, 0x3c22bc46, 0xbbf1bc62, 0xbc7f3ac9, 0x3b95bc75, 0x3ac9bc7f, 0xbc753b95,
    0xbc463c22, 0xbc62bbf1, 0xbbf1bc62, 0x3ac93c7f, 0xbb953c75, 0xbc223c46, 0xbc67bbdb, 0xbc80ba49, 0x3c2c3c3e, 0xbc67bbdb,
    0xbc783b79, 0xbb163c7d, 0x3c7d3b16, 0xbc043c5c, 0xbc183c4e, 0x3c783b79, 0x3c5cbc04, 0x3c4e3c18, 0x3a493c80, 0x3bacbc71,
    0x3bacbc71, 0x3c2cbc3e, 0x3c353c35, 0x3c6d3bc4, 0x3c353c35, 0xbc6dbbc4, 0x3c35bc35, 0xbbc4bc6d, 0x3c35bc35, 0x3bc43c6d,
    0xbc35bc35, 0xbbc43c6d, 0xbc35bc35, 0x3bc4bc6d, 0xbc353c35, 0x3c6dbbc4, 0xbc353c35, 0xbc6d3bc4, 0x3c3e3c2c, 0x3c713bac,
    0x3c713bac, 0xbc803a49, 0x3c18bc4e, 0xbc04bc5c, 0x3b79bc78, 0x3c4e3c18, 0xbc5cbc04, 0xbb163c7d, 0xbc7dbb16, 0xbb79bc78,
    0xbbdb3c67, 0x3c3ebc2c, 0xba493c80, 0xbbdb3c67, 0x3c463c22, 0x3c753b95, 0x3c7fbac9, 0xbc623bf1, 0x3bf1bc62, 0xbc22bc46,
    0xbb95bc75, 0x3c7f3ac9, 0xbc75bb95, 0x3ac93c7f, 0xbc623bf1, 0xbc46bc22, 0xbac93c7f, 0x3bf1bc62, 0x3c223c46, 0x3b953c75,
    0x3c4e3c18, 0x3c783b79, 0x3c5cbc04, 0xbc183c4e, 0x3bacbc71, 0xbc3ebc2c, 0xbc3ebc2c, 0x3c67bbdb, 0xbc80ba49, 0x3bac3c71,
    0xbbdb3c67, 0xbc80ba49, 0x3b793c78, 0x3b16bc7d, 0x3c7d3b16, 0x3c5c3c04, 0x3c553c0e, 0x3c7b3b48, 0x3c0ebc55, 0xbb483c7b,
    0x3b48bc7b, 0xbc55bc0e, 0xbc7bbb48, 0x3c0ebc55, 0xbc7b3b48, 0x3c0e3c55, 0x3b483c7b, 0xbc553c0e, 0x3c0e3c55, 0xbb48bc7b,
    0x3c55bc0e, 0x3c7bbb48, 0x3c5c3c04, 0x3c7d3b16, 0x3b16bc7d, 0x3b793c78, 0x3a49bc80, 0xbc67bbdb, 0xbc713bac, 0x3a49bc80,
    0xbc673bdb, 0x3c3e3c2c, 0x3c3e3c2c, 0xbbac3c71, 0x3c4e3c18, 0xbc04bc5c, 0x3b79bc78, 0x3c18bc4e, 0x3c623bf1, 0x3c7f3ac9,
    0xbb95bc75, 0x3c223c46, 0xbac9bc7f, 0xbc75bb95, 0xbc223c46, 0xbbf1bc62, 0xbc463c22, 0x3c623bf1, 0x3c7f3ac9, 0x3b953c75,
    0x3c753b95, 0xbc46bc22, 0xbbf1bc62, 0xbac9bc7f, 0x3c673bdb, 0x3c803a49, 0xbc2cbc3e, 0x3c673bdb, 0xbb79bc78, 0xbc7dbb16,
    0xbb163c7d, 0xbc5cbc04, 0xbc183c4e, 0x3c783b79, 0x3c5cbc04, 0x3c4e3c18, 0x3c80ba49, 0xbc71bbac, 0xbc71bbac, 0xbc3ebc2c,
    0x3c353c35, 0x3c6d3bc4, 0x3c353c35, 0xbc6dbbc4, 0x3c35bc35, 0xbbc4bc6d, 0x3c35bc35, 0x3bc43c6d, 0xbc35bc35, 0xbbc43c6d,
    0xbc35bc35, 0x3bc4bc6d, 0xbc353c35, 0x3c6dbbc4, 0xbc353c35, 0xbc6d3bc4, 0x3c80ba49, 0x3c67bbdb, 0x3c67bbdb, 0xbc2c3c3e,
    0xbb16bc7d, 0xbc78bb79, 0xbc04bc5c, 0x3c7dbb16, 0xbc783b79, 0x3c183c4e, 0xbc4e3c18, 0xbc5cbc04, 0x3bac3c71, 0x3a49bc80,
    0x3c2c3c3e, 0x3bac3c71, 0x3c22bc46, 0x3b95bc75, 0xbac9bc7f, 0x3bf13c62, 0xbc62bbf1, 0xbc463c22, 0xbc753b95, 0x3ac9bc7f,
    0xbb953c75, 0x3c7fbac9, 0x3bf13c62, 0xbc223c46, 0x3c7f3ac9, 0xbc62bbf1, 0x3c46bc22, 0x3c75bb95, 0xbb16bc7d, 0xbc04bc5c,
    0xbc78bb79, 0x3c7dbb16, 0xbc673bdb, 0x3a493c80, 0x3a493c80, 0xbc71bbac, 0x3c2c3c3e, 0x3bdbbc67, 0x3c71bbac, 0x3c2c3c3e,
    0x3c04bc5c, 0xbc4e3c18, 0xbc18bc4e, 0xbb79bc78, 0xbc55bc0e, 0xbc7bbb48, 0xbc0e3c55, 0x3b48bc7b, 0xbb483c7b, 0x3c553c0e,
    0x3c7b3b48, 0xbc0e3c55, 0x3c7bbb48, 0xbc0ebc55, 0xbb48bc7b, 0x3c55bc0e, 0xbc0ebc55, 0x3b483c7b, 0xbc553c0e, 0xbc7b3b48,
    0xbc783b79, 0xbc4e3c18, 0x3c183c4e, 0xbc5cbc04, 0x3c2c3c3e, 0x3c71bbac, 0x3bdbbc67, 0x3c2c3c3e, 0x3bacbc71, 0xbc803a49,
    0xbc803a49, 0xbbdbbc67, 0xbc7d3b16, 0x3c783b79, 0x3c043c5c, 0x3b163c7d, 0xbbf13c62, 0xbac93c7f, 0x3c75bb95, 0xbc463c22,
    0x3c7fbac9, 0x3b95bc75, 0xbc46bc22, 0x3c62bbf1, 0xbc22bc46, 0xbbf13c62, 0xbac93c7f, 0xbc753b95, 0xbb953c75, 0x3c22bc46,
    0x3c62bbf1, 0x3c7fbac9, 0x3bac3c71, 0x3c2c3c3e, 0x3a49bc80, 0x3bac3c71, 0x3c04bc5c, 0xbc18bc4e, 0xbc4e3c18, 0xbb79bc78,
    0xbc7d3b16, 0x3c043c5c, 0x3c783b79, 0x3b163c7d, 0x3c3e3c2c, 0xbbdbbc67, 0xbbdbbc67, 0xba49bc80, 0x3c353c35, 0x3c6d3bc4,
    0x3c353c35, 0xbc6dbbc4, 0x3c35bc35, 0xbbc4bc6d, 0x3c35bc35, 0x3bc43c6d, 0xbc35bc35, 0xbbc43c6d, 0xbc35bc35, 0x3bc4bc6d,
    0xbc353c35, 0x3c6dbbc4, 0xbc353c35, 0xbc6d3bc4, 0x3c2cbc3e, 0x3bacbc71, 0x3bacbc71, 0x3a493c80, 0xbc4ebc18, 0xbc5c3c04,
    0xbc78bb79, 0x3c18bc4e, 0xbc043c5c, 0x3c7d3b16, 0xbb163c7d, 0xbc783b79, 0x3c673bdb, 0xbc2cbc3e, 0x3c803a49, 0x3c673bdb,
    0xbc46bc22, 0xbc75bb95, 0xbc7f3ac9, 0x3c62bbf1, 0xbbf13c62, 0x3c223c46, 0x3b953c75, 0xbc7fbac9, 0x3c753b95, 0xbac9bc7f,
    0x3c62bbf1, 0x3c463c22, 0x3ac9bc7f, 0xbbf13c62, 0xbc22bc46, 0xbb95bc75, 0xbc183c4e, 0xbb793c78, 0x3c043c5c, 0xbc4ebc18,
    0x3c713bac, 0x3c2cbc3e, 0x3c2cbc3e, 0x3bdb3c67, 0x3a49bc80, 0xbc713bac, 0xbc67bbdb, 0x3a49bc80, 0xbc783b79, 0x3c7d3b16,
    0xbb163c7d, 0xbc043c5c, 0x3c553c0e, 0x3c7b3b48, 0x3c0ebc55, 0xbb483c7b, 0x3b48bc7b, 0xbc55bc0e, 0xbc7bbb48, 0x3c0ebc55,
    0xbc7b3b48, 0x3c0e3c55, 0x3b483c7b, 0xbc553c0e, 0x3c0e3c55, 0xbb48bc7b, 0x3c55bc0e, 0x3c7bbb48, 0x3c04bc5c, 0x3b16bc7d,
    0xbc7dbb16, 0x3c78bb79, 0xbc80ba49, 0xbbdb3c67, 0x3bac3c71, 0xbc80ba49, 0x3bdb3c67, 0x3c2cbc3e, 0x3c2cbc3e, 0x3c713bac,
    0x3c18bc4e, 0xbc5c3c04, 0xbc78bb79, 0xbc4ebc18, 0xbc62bbf1, 0xbc7fbac9, 0x3b953c75, 0xbc22bc46, 0x3ac93c7f, 0x3c753b95,
    0x3c22bc46, 0x3bf13c62, 0x3c46bc22, 0xbc62bbf1, 0xbc7fbac9, 0xbb95bc75, 0xbc75bb95, 0x3c463c22, 0x3bf13c62, 0x3ac93c7f,
    0xbbdb3c67, 0xba493c80, 0x3c3ebc2c, 0xbbdb3c67, 0x3c78bb79, 0x3b16bc7d, 0xbc7dbb16, 0x3c04bc5c, 0xbc4ebc18, 0xbb793c78,
    0x3c043c5c, 0xbc183c4e, 0x3a493c80, 0x3bacbc71, 0x3bacbc71, 0x3c2cbc3e, 0x3c353c35, 0x3c6d3bc4, 0x3c353c35, 0xbc6dbbc4,
    0x3c35bc35, 0xbbc4bc6d, 0x3c35bc35, 0x3bc43c6d, 0xbc35bc35, 0xbbc43c6d, 0xbc35bc35, 0x3bc4bc6d, 0xbc353c35, 0x3c6dbbc4,
    0xbc353c35, 0xbc6d3bc4, 0xba49bc80, 0xbbdbbc67, 0xbbdbbc67, 0x3c3e3c2c, 0xbc7d3b16, 0xbb793c78, 0xbc5c3c04, 0xbb16bc7d,
    0x3b793c78, 0x3c4ebc18, 0x3c183c4e, 0xbc043c5c, 0x3c71bbac, 0xbc80ba49, 0x3c3ebc2c, 0x3c71bbac, 0xbc223c46, 0xbb953c75,
    0x3ac93c7f, 0xbbf1bc62, 0x3c623bf1, 0x3c46bc22, 0x3c75bb95, 0xbac93c7f, 0x3b95bc75, 0xbc7f3ac9, 0xbbf1bc62, 0x3c22bc46,
    0xbc7fbac9, 0x3c623bf1, 0xbc463c22, 0xbc753b95, 0x3c7dbb16, 0x3c5cbc04, 0x3b79bc78, 0x3b163c7d, 0xbbdbbc67, 0xbc803a49,
    0xbc803a49, 0x3bacbc71, 0xbc3e3c2c, 0x3c673bdb, 0x3bac3c71, 0xbc3e3c2c, 0x3c5c3c04, 0xbc18bc4e, 0x3c4ebc18, 0x3c78bb79,
    0xbc55bc0e, 0xbc7bbb48, 0xbc0e3c55, 0x3b48bc7b, 0xbb483c7b, 0x3c553c0e, 0x3c7b3b48, 0xbc0e3c55, 0x3c7bbb48, 0xbc0ebc55,
    0xbb48bc7b, 0x3c55bc0e, 0xbc0ebc55, 0x3b483c7b, 0xbc553c0e, 0xbc7b3b48, 0x3b793c78, 0x3c183c4e, 0x3c4ebc18, 0xbc043c5c,
    0x3c3ebc2c, 0xbbacbc71, 0xbc67bbdb, 0x3c3ebc2c, 0xbc71bbac, 0x3a493c80, 0x3a493c80, 0xbc673bdb, 0x3b163c7d, 0x3b79bc78,
    0x3c5cbc04, 0x3c7dbb16, 0x3bf1bc62, 0x3ac9bc7f, 0xbc753b95, 0x3c46bc22, 0xbc7f3ac9, 0xbb953c75, 0x3c463c22, 0xbc623bf1,
    0x3c223c46, 0x3bf1bc62, 0x3ac9bc7f, 0x3c75bb95, 0x3b95bc75, 0xbc223c46, 0xbc623bf1, 0xbc7f3ac9, 0xbc713bac, 0xbc3e3c2c,
    0x3c803a49, 0xbc713bac, 0x3c5c3c04, 0x3c4ebc18, 0xbc18bc4e, 0x3c78bb79, 0xbb16bc7d, 0xbc5c3c04, 0xbb793c78, 0xbc7d3b16,
    0xbc2c3c3e, 0x3c67bbdb, 0x3c67bbdb, 0x3c80ba49, 0x3c800000, 0x3c6dbbc4, 0x3c800000, 0xbc6d3bc4, 0xbc800000, 0xbbc43c6d,
    0xbc800000, 0x3bc4bc6d, 0x3c800000, 0xbbc4bc6d, 0x3c800000, 0x3bc43c6d, 0xbc800000, 0x3c6d3bc4, 0xbc800000, 0xbc6dbbc4,
    0x3c80ba49, 0x3c67bbdb, 0x3c67bbdb, 0xbc2c3c3e, 0xbc7d3b16, 0xbb793c78, 0xbc5c3c04, 0xbb16bc7d, 0x3c78bb79, 0xbc18bc4e,
    0x3c4ebc18, 0x3c5c3c04, 0xbc713bac, 0x3c803a49, 0xbc3e3c2c, 0xbc713bac, 0x3c7fbac9, 0x3c62bbf1, 0x3c22bc46, 0xbb953c75,
    0xbc753b95, 0xbac93c7f, 0xbbf13c62, 0xbc22bc46, 0x3c62bbf1, 0xbc46bc22, 0x3b95bc75, 0x3c7fbac9, 0xbc463c22, 0x3c75bb95,
    0xbac93c7f, 0xbbf13c62, 0x3c7dbb16, 0x3c5cbc04, 0x3b79bc78, 0x3b163c7d, 0xbc673bdb, 0x3a493c80, 0x3a493c80, 0xbc71bbac,
    0x3c3ebc2c, 0xbc67bbdb, 0xbbacbc71, 0x3c3ebc2c, 0xbc043c5c, 0x3c4ebc18, 0x3c183c4e, 0x3b793c78, 0x3c7bbb48, 0x3c55bc0e,
    0xbb48bc7b, 0x3c0e3c55, 0xbc553c0e, 0x3b483c7b, 0x3c0e3c55, 0xbc7b3b48, 0x3c0ebc55, 0xbc7bbb48, 0xbc55bc0e, 0x3b48bc7b,
    0xbb483c7b, 0x3c0ebc55, 0x3c7b3b48, 0x3c553c0e, 0x3c78bb79, 0x3c4ebc18, 0xbc18bc4e, 0x3c5c3c04, 0xbc3e3c2c, 0x3bac3c71,
    0x3c673bdb, 0xbc3e3c2c, 0x3bacbc71, 0xbc803a49, 0xbc803a49, 0xbbdbbc67, 0x3b163c7d, 0x3b79bc78, 0x3c5cbc04, 0x3c7dbb16,
    0x3c75bb95, 0x3c46bc22, 0xbc62bbf1, 0x3c7f3ac9, 0xbc223c46, 0x3bf13c62, 0x3c7fbac9, 0xbb953c75, 0x3ac9bc7f, 0xbc753b95,
    0xbc463c22, 0xbc62bbf1, 0x3bf13c62, 0xbac9bc7f, 0x3b95bc75, 0x3c22bc46, 0x3c71bbac, 0x3c3ebc2c, 0xbc80ba49, 0x3c71bbac,
    0xbc043c5c, 0x3c183c4e, 0x3c4ebc18, 0x3b793c78, 0xbb16bc7d, 0xbc5c3c04, 0xbb793c78, 0xbc7d3b16, 0x3c3e3c2c, 0xbbdbbc67,
    0xbbdbbc67, 0xba49bc80, 0x3c800000, 0x3c6dbbc4, 0x3c800000, 0xbc6d3bc4, 0xbc800000, 0xbbc43c6d, 0xbc800000, 0x3bc4bc6d,
    0x3c800000, 0xbbc4bc6d, 0x3c800000, 0x3bc43c6d, 0xbc800000, 0x3c6d3bc4, 0xbc800000, 0xbc6dbbc4, 0x3c2cbc3e, 0x3bacbc71,
    0x3bacbc71, 0x3a493c80, 0xbc183c4e, 0x3c043c5c, 0xbb793c78, 0xbc4ebc18, 0x3c04bc5c, 0xbc7dbb16, 0x3b16bc7d, 0x3c78bb79,
    0xbbdb3c67, 0x3c3ebc2c, 0xba493c80, 0xbbdb3c67, 0xbac9bc7f, 0xbbf1bc62, 0xbc46bc22, 0x3c753b95, 0x3b953c75, 0x3c7f3ac9,
    0x3c623bf1, 0xbc463c22, 0xbbf1bc62, 0xbc223c46, 0xbc75bb95, 0xbac9bc7f, 0x3c223c46, 0xbb95bc75, 0x3c7f3ac9, 0x3c623bf1,
    0xbc4ebc18, 0xbc78bb79, 0xbc5c3c04, 0x3c18bc4e, 0x3c713bac, 0x3c2cbc3e, 0x3c2cbc3e, 0x3bdb3c67, 0xbc80ba49, 0x3bac3c71,
    0xbbdb3c67, 0xbc80ba49, 0x3c78bb79, 0xbc7dbb16, 0x3b16bc7d, 0x3c04bc5c, 0xbc7b3b48, 0xbc553c0e, 0x3b483c7b, 0xbc0ebc55,
    0x3c55bc0e, 0xbb48bc7b, 0xbc0ebc55, 0x3c7bbb48, 0xbc0e3c55, 0x3c7b3b48, 0x3c553c0e, 0xbb483c7b, 0x3b48bc7b, 0xbc0e3c55,
    0xbc7bbb48, 0xbc55bc0e, 0xbc043c5c, 0xbb163c7d, 0x3c7d3b16, 0xbc783b79, 0x3a49bc80, 0xbc67bbdb, 0xbc713bac, 0x3a49bc80,
    0x3bdb3c67, 0x3c2cbc3e, 0x3c2cbc3e, 0x3c713bac, 0xbc4ebc18, 0x3c043c5c, 0xbb793c78, 0xbc183c4e, 0x3b953c75, 0x3c223c46,
    0x3bf1bc62, 0xbac93c7f, 0xbc46bc22, 0xbc623bf1, 0x3ac93c7f, 0xbc75bb95, 0x3c7f3ac9, 0xbb95bc75, 0xbc22bc46, 0x3bf1bc62,
    0xbc623bf1, 0x3c7fbac9, 0x3c753b95, 0x3c463c22, 0x3c673bdb, 0x3c803a49, 0xbc2cbc3e, 0x3c673bdb, 0xbc783b79, 0xbb163c7d,
    0x3c7d3b16, 0xbc043c5c, 0x3c18bc4e, 0xbc78bb79, 0xbc5c3c04, 0xbc4ebc18, 0x3a493c80, 0x3bacbc71, 0x3bacbc71, 0x3c2cbc3e,
    0x3c800000, 0x3c6dbbc4, 0x3c800000, 0xbc6d3bc4, 0xbc800000, 0xbbc43c6d, 0xbc800000, 0x3bc4bc6d, 0x3c800000, 0xbbc4bc6d,
    0x3c800000, 0x3bc43c6d, 0xbc800000, 0x3c6d3bc4, 0xbc800000, 0xbc6dbbc4, 0xba49bc80, 0xbbdbbc67, 0xbbdbbc67, 0x3c3e3c2c,
    0x3b163c7d, 0x3c783b79, 0x3c043c5c, 0xbc7d3b16, 0xbb79bc78, 0xbc4e3c18, 0xbc18bc4e, 0x3c04bc5c, 0x3bac3c71, 0x3a49bc80,
    0x3c2c3c3e, 0x3bac3c71, 0xbc7f3ac9, 0xbc623bf1, 0xbc223c46, 0x3b95bc75, 0x3c75bb95, 0x3ac9bc7f, 0x3bf1bc62, 0x3c223c46,
    0xbc623bf1, 0x3c463c22, 0xbb953c75, 0xbc7f3ac9, 0x3c46bc22, 0xbc753b95, 0x3ac9bc7f, 0x3bf1bc62, 0x3b163c7d, 0x3c043c5c,
    0x3c783b79, 0xbc7d3b16, 0xbbdbbc67, 0xbc803a49, 0xbc803a49, 0x3bacbc71, 0x3c2c3c3e, 0x3bdbbc67, 0x3c71bbac, 0x3c2c3c3e,
    0xbc5cbc04, 0x3c183c4e, 0xbc4e3c18, 0xbc783b79, 0x3c7bbb48, 0x3c55bc0e, 0xbb48bc7b, 0x3c0e3c55, 0xbc553c0e, 0x3b483c7b,
    0x3c0e3c55, 0xbc7b3b48, 0x3c0ebc55, 0xbc7bbb48, 0xbc55bc0e, 0x3b48bc7b, 0xbb483c7b, 0x3c0ebc55, 0x3c7b3b48, 0x3c553c0e,
    0xbb79bc78, 0xbc18bc4e, 0xbc4e3c18, 0x3c04bc5c, 0x3c2c3c3e, 0x3c71bbac, 0x3bdbbc67, 0x3c2c3c3e, 0xbc71bbac, 0x3a493c80,
    0x3a493c80, 0xbc673bdb, 0x3c7dbb16, 0xbc78bb79, 0xbc04bc5c, 0xbb16bc7d, 0xbc753b95, 0xbc463c22, 0x3c623bf1, 0xbc7fbac9,
    0x3c22bc46, 0xbbf1bc62, 0xbc7f3ac9, 0x3b95bc75, 0xbac93c7f, 0x3c75bb95, 0x3c46bc22, 0x3c623bf1, 0xbbf1bc62, 0x3ac93c7f,
    0xbb953c75, 0xbc223c46, 0x3bac3c71, 0x3c2c3c3e, 0x3a49bc80, 0x3bac3c71, 0xbc5cbc04, 0xbc4e3c18, 0x3c183c4e, 0xbc783b79,
    0x3c7dbb16, 0xbc04bc5c, 0xbc78bb79, 0xbb16bc7d, 0xbc2c3c3e, 0x3c67bbdb, 0x3c67bbdb, 0x3c80ba49, 0x3c800000, 0x3c6dbbc4,
    0x3c800000, 0xbc6d3bc4, 0xbc800000, 0xbbc43c6d, 0xbc800000, 0x3bc4bc6d, 0x3c800000, 0xbbc4bc6d, 0x3c800000, 0x3bc43c6d,
    0xbc800000, 0x3c6d3bc4, 0xbc800000, 0xbc6dbbc4, 0xbc3ebc2c, 0xbc71bbac, 0xbc71bbac, 0x3c80ba49, 0x3c4e3c18, 0x3c5cbc04,
    0x3c783b79, 0xbc183c4e, 0xbc5cbc04, 0xbb163c7d, 0xbc7dbb16, 0xbb79bc78, 0x3c673bdb, 0xbc2cbc3e, 0x3c803a49, 0x3c673bdb,
    0x3ac93c7f, 0x3bf13c62, 0x3c463c22, 0xbc75bb95, 0xbb95bc75, 0xbc7fbac9, 0xbc62bbf1, 0x3c46bc22, 0x3bf13c62, 0x3c22bc46,
    0x3c753b95, 0x3ac93c7f, 0xbc22bc46, 0x3b953c75, 0xbc7fbac9, 0xbc62bbf1, 0x3c18bc4e, 0x3b79bc78, 0xbc04bc5c, 0x3c4e3c18,
    0xbbac3c71, 0x3c3e3c2c, 0x3c3e3c2c, 0xbc673bdb, 0x3a49bc80, 0xbc713bac, 0xbc67bbdb, 0x3a49bc80, 0x3b793c78, 0x3b16bc7d,
    0x3c7d3b16, 0x3c5c3c04, 0xbc7b3b48, 0xbc553c0e, 0x3b483c7b, 0xbc0ebc55, 0x3c55bc0e, 0xbb48bc7b, 0xbc0ebc55, 0x3c7bbb48,
    0xbc0e3c55, 0x3c7b3b48, 0x3c553c0e, 0xbb483c7b, 0x3b48bc7b, 0xbc0e3c55, 0xbc7bbb48, 0xbc55bc0e, 0x3c5c3c04, 0x3c7d3b16,
    0x3b16bc7d, 0x3b793c78, 0xbc80ba49, 0xbbdb3c67, 0x3bac3c71, 0xbc80ba49, 0x3c67bbdb, 0xbc3ebc2c, 0xbc3ebc2c, 0x3bacbc71,
    0xbc183c4e, 0x3c5cbc04, 0x3c783b79, 0x3c4e3c18, 0xbb95bc75, 0xbc22bc46, 0xbbf13c62, 0x3ac9bc7f, 0x3c463c22, 0x3c62bbf1,
    0xbac9bc7f, 0x3c753b95, 0xbc7fbac9, 0x3b953c75, 0x3c223c46, 0xbbf13c62, 0x3c62bbf1, 0xbc7f3ac9, 0xbc75bb95, 0xbc46bc22,
    0xbbdb3c67, 0xba493c80, 0x3c3ebc2c, 0xbbdb3c67, 0xbb79bc78, 0xbc7dbb16, 0xbb163c7d, 0xbc5cbc04, 0x3c4e3c18, 0x3b79bc78,
    0xbc04bc5c, 0x3c18bc4e, 0xbc803a49, 0x3c713bac, 0x3c713bac, 0x3c3e3c2c,
};

template <int G = 1024> __device__ __forceinline__ void store_tile_64(const float (&d)[32], uint32_t base, int warp, int lane) {
  const uint32_t rb = base + (warp * 2 + ((lane >> 3) & 1)) * G + (lane & 7) * 128;
#pragma unroll
  for (int j = 0; j < 8; j += 2) {
    const int jj = j + (lane >> 4);
    stsm4(rb + ((jj ^ (lane & 7)) << 4), pack2(d[4 * j], d[4 * j + 1]), pack2(d[4 * j + 2], d[4 * j + 3]),
          pack2(d[4 * j + 4], d[4 * j + 5]), pack2(d[4 * j + 6], d[4 * j + 7]));
  }
}

#define A_XM0 0xF55C
#define A_XM1 0xEABC
#define A_REL 0x22110
#define A_W0 3
#define A_W1 3
#define A_PF0 0
#define A_PF 0
#define A_WR 0x146
#define A_W2PF 4
#define G_XPOL 1
#define G_WPOL 1
#define G_XPOLK 0
#define G_WPOLK 8
#define A_WS A_W0
#define A_WFAR 0
#define W2_AFF 1
#define A_W2R 9
#define A_FREE 0x3F000
#define A_RELS 0x8888
#define A_ACQ 0x1111
#define A_DEP 3
#define A_PACE0 1000
#define A_PACE1 A_PACE0
#define A_PACE2 0
#define A_PIPE 18
#define A_PACE_N 8
#define A_LOOK 3
#define G_TMASK 0x0FB0
constexpr int A_IN = 112 * 128, A_OUT = 16384, A_NIN = 5, A_NOUT = 6;
constexpr int A_NREL = __builtin_popcount(A_REL);
constexpr int G_XP = NB1 * 64;
constexpr int G_STAGE = 16384 + 2 * G_XP, G_NST = 5;
constexpr int G_TIN = G_NST * G_STAGE, G_TOUT = G_TIN + 8192, G_SMEM = G_TOUT + 32768 + 1024;
#define G_SLOTS 0x2310423104231043ull
__host__ __device__ constexpr int g_slot(int k) { return (G_SLOTS >> (4 * k)) & 7; }
constexpr uint32_t g_parities() {
  uint32_t m = 0;
  for (int k = 0; k < 16; k++)
    for (int j = 0; j < k; j++)
      if (g_slot(j) == g_slot(k)) m ^= 1u << k;
  return m;
}
constexpr uint32_t G_PAR = g_parities();
constexpr int G_KS = 12;
__device__ __align__(128) int g_done[16 * 32];

__device__ __forceinline__ int x_decode(int r, int cta) {
  const int v = r * 64 + ((cta >> 2) << 1) + (cta & 1);
  return cta < 128 ? ((7 - v / 80) << 7) | (v % 80) : ((7 - (r >> 1)) << 7) | (80 + 2 * (cta & 1) + (r & 1));
}
__device__ __forceinline__ uint32_t a_out(int n) {
  const int p = n % A_NOUT;
  return (p < 4 ? (1 + (p >> 1)) * G_STAGE : G_TOUT) + (p & 1) * A_OUT;
}
template <int P> __device__ __forceinline__ void w_load(int s, int i, uint32_t dst, uint32_t bar, const CUtensorMap* mwe, const CUtensorMap* mwo) {
  mbar_expect(bar, 4096);
  tma_ld4<P>(dst, s < 4 ? mwo : mwe, bar, 0, s < 4 ? -1 : 0, (i & 1) * 2, (s & 3) * 64 + (i >> 1));
}
__device__ __forceinline__ uint32_t x1_addr(int L, int b, uint32_t flips) {
  const int p = L >> 4, sel = (b ^ __popc(L & 15) ^ (flips >> p)) & 1;
  return (p << 21) | (sel << 12) | ((L & 1) << 13) | ((L & 6) << 15) | ((L & 8) << 16);
}
__device__ __forceinline__ uint32_t spread16(int i) { return ((i & 3) << 14) | ((i & 4) << 16) | ((i & 8) << 17); }
constexpr int NPG = 19 + W_SHIFT, NVOTE = 6;
__device__ __forceinline__ uint32_t w_addr(int P, int f, int c, int dhalf, uint32_t flips) {
  return x1_addr(16 * P + (c >> 5) + 2 * (f >> 3), dhalf, flips >> 12) + spread16(2 * f) + (c & 31) * 128;
}
__device__ __forceinline__ void w_store(const CUtensorMap* m, uint32_t src, uint32_t a) {
#pragma unroll
  for (int j = 0; j < 8; j++)
    tma_st5<0>(m, src + j * 2048, ((a & 16383) >> 1) ^ ((__popc(j) & 1) << 11), (j & 3) << 1, (j >> 2) << 1, a >> 20, 0);
}
__device__ __forceinline__ uint32_t read_votes(int lane, int& side) {
  int v;
  for (int it = 0; it < (1 << 20); it++) {
    asm volatile("ld.relaxed.gpu.global.s32 %0, [%1];" : "=r"(v) : "l"(&g_done[15 * 32 + lane]) : "memory");
    if ((__ballot_sync(0xffffffffu, v < NVOTE * 256) & ((2 << NPG) - 2)) == 0) break;
  }
  uint32_t smid;
  asm("mov.u32 %0, %%smid;" : "=r"(smid));
  side = (__shfl_sync(0xffffffffu, v, 24 + ((smid >> 5) & 7)) >> (smid & 31)) & 1;
  return __ballot_sync(0xffffffffu, (v & 255) > NVOTE / 2);
}
__device__ __forceinline__ void send_role(uint32_t dst, uint32_t bar, int v) {
  for (int c = 0; c < 2; c++)
    asm volatile("{\n.reg .b32 a, b;\nmapa.shared::cluster.u32 a, %0, %2;\nmapa.shared::cluster.u32 b, %1, %2;\n"
                 "st.async.shared::cluster.mbarrier::complete_tx::bytes.u32 [a], %3, [b];\n}" ::"r"(dst), "r"(bar), "r"(c), "r"(v) : "memory");
}
struct GMaps {
  CUtensorMap w1e, x, w1o, ws, xs, w, y, w2e, w2o;
};
__device__ __forceinline__ void poll_ge(const int* p, int target) {
  for (int it = 0; it < (1 << 20); it++) {
    int v;
    asm volatile("ld.relaxed.gpu.global.s32 %0, [%1];" : "=r"(v) : "l"(p) : "memory");
    if (v >= target) break;
  }
  asm volatile("fence.acquire.gpu;" ::: "memory");
}

__global__ void __cluster_dims__(2, 1, 1) __launch_bounds__(384, 1)
kG(const __grid_constant__ GMaps m, char* __restrict__ x1, char* __restrict__ wt, const __nv_bfloat16* __restrict__ g, const __nv_bfloat16* __restrict__ wgt) {
  extern __shared__ uint8_t smem_raw[];
  __shared__ __align__(8) uint64_t bars[20 + A_NIN + 2 * A_NOUT + 2 * G_NST + 8 + 2 * A_NREL];
  __shared__ uint16_t tab[128];
  __shared__ uint32_t lat[8], s_role, s_flips;
  const uint32_t sb = (s2u(smem_raw) + 1023) & ~1023u;
  const int tid = threadIdx.x, wg = __shfl_sync(0xffffffffu, tid >> 7, 0), t = tid & 127;
  const int warp = __shfl_sync(0xffffffffu, t >> 5, 0), lane = t & 31;
  const int blk = blockIdx.x, hf = blk & 1, page = blk < NPG * NVOTE ? 1 + blk % NPG : 1;
  const bool spare = blk >= 128;
  const int nu = spare ? 16 : 18;
  const uint32_t xm = spare ? 0xFFFF : hf ? A_XM1 : A_XM0;
  const uint32_t wf0 = s2u(&bars[0]), xf0 = wf0 + 32, xe0 = xf0 + 128, aof0 = xe0 + 8 * A_NIN, aoe0 = aof0 + 8 * A_NOUT;
  const uint32_t full0 = aoe0 + 8 * A_NOUT, empty0 = full0 + 8 * G_NST;
  const uint32_t inf0 = empty0 + 8 * G_NST, sf0 = inf0 + 16, se0 = sf0 + 16, roleb = se0 + 16, flipb = roleb + 8;
  const uint32_t rel0 = flipb + 8, acq0 = rel0 + 8 * A_NREL;
  auto role = [&]() {
    if (spare) return blk;
    mbar_wait(roleb, 0);
    return 2 * (int)*(volatile uint32_t*)&s_role + hf;
  };
  auto flips = [&]() {
    mbar_wait(flipb, 0);
    return *(volatile uint32_t*)&s_flips;
  };
  auto w_unit = [&](int j, int cta) { return j >= A_WS ? blk : (cta & ~3) | (hf << 1) | (((cta >> 1) ^ (A_WFAR >> j)) & 1); };
  auto w1_load = [&](int j, int cta) {
    const int i = w_unit(j, cta);
    mbar_expect(wf0 + 8 * j, 8192);
    tma_ld5<1>(sb + j * 8192, j < 2 ? &m.w1o : &m.w1e, wf0 + 8 * j, 0, -(j < 2), 2 * (i & 1), i >> 1, 2 * (j & 1));
  };
  auto w2_unit = [&](int cta) { return W2_AFF ? (cta & ~3) | (hf << 1) | ((cta >> 1) & 1) : blk; };
  auto x_prefetch = [&](int r) {
    const int c = x_decode(r, blk);
    asm volatile("cp.async.bulk.prefetch.tensor.4d.L2.global [%0, {0, %1, %2, %3}];" ::"l"(&m.x), "r"(96 * (c & 127) - 24), "r"(c >> 7), "r"((blk >> 1) & 1) : "memory");
  };
  if (wg == 2) {
    asm volatile("setmaxnreg.dec.sync.aligned.u32 40;");
    if (lane == 0) {
      if (warp == 0) {
        for (int i = 0; i < 4; i++) mbar_init(wf0 + 8 * i, 1);
        fence_async();
        if (!spare) {
          for (int j = 3; j >= A_W1; j--) w1_load(j, 0);
          for (int r = 0; r < A_PF0; r++) x_prefetch(r);
        }
        for (int i = 0; i < 16; i++) mbar_init(xf0 + 8 * i, 1);
      } else if (warp == 1) {
        prefetch_map(&m.x);
        prefetch_map(&m.w1o);
        prefetch_map(&m.w2e);
        prefetch_map(&m.ws);
        prefetch_map(&m.xs);
        for (int i = 0; i < 2 + 2 * A_NREL; i++) mbar_init(roleb + 8 * i, 1);
        mbar_expect(roleb, 4);
      } else if (warp == 2) {
        for (int i = 0; i < A_NIN + A_NOUT; i++) mbar_init(xe0 + 8 * i, 4);
        for (int i = 0; i < A_NOUT; i++) mbar_init(aoe0 + 8 * i, 1);
      } else {
        for (int i = 0; i < G_NST; i++) {
          mbar_init(full0 + 8 * i, 1);
          mbar_init(empty0 + 8 * i, 16);
        }
        for (int i = 0; i < 2; i++) {
          mbar_init(inf0 + 8 * i, 1);
          mbar_init(sf0 + 8 * i, 8);
          mbar_init(se0 + 8 * i, 1);
        }
      }
      fence_bar_init();
    }
    __syncwarp();
    asm volatile("barrier.cluster.arrive.relaxed.aligned;" ::: "memory");
    if (warp != 2) bar_sync(9, 352);
    int ticket = 0;
    if (lane == 0) {
      const int side = min(lat[0], lat[2]) > min(lat[1], lat[3]);
      if (warp == 1 && hf == 0 && !spare) ticket = 2 * atomicAdd(&g_done[14 * 32 + side], 1) + side;
      if (warp == 3) {
        uint32_t smid;
        asm("mov.u32 %0, %%smid;" : "=r"(smid));
        if (blk < NPG * NVOTE)
          asm volatile("red.relaxed.gpu.global.add.s32 [%0], %1;" ::"l"(&g_done[15 * 32 + page]), "r"(256 + (side ^ (min(lat[4], lat[6]) > min(lat[5], lat[7])))) : "memory");
        if (side) asm volatile("red.relaxed.gpu.global.or.b32 [%0], %1;" ::"l"(&g_done[15 * 32 + 24 + ((smid >> 5) & 7)]), "r"(1 << (smid & 31)) : "memory");
      }
      if (warp == 0 && !spare) {
        for (int r = A_PF0; r < A_PF; r++) x_prefetch(r);
        for (int j = A_W1 - 1; j >= A_W0; j--) w1_load(j, 0);
      }
    }
    __syncwarp();
    asm volatile("barrier.cluster.wait.aligned;" ::: "memory");
    if (t == 32 && hf == 0 && !spare) {
      send_role(s2u(&s_role), roleb, ticket < 64 ? ticket : 127 - ticket);
    }
    if (warp == 0) {
      const int np = lane + A_NIN - A_DEP;
      const uint32_t dst = sb + 3 * G_STAGE + (lane % A_NIN) * A_IN, be = xe0 + 8 * (np % A_NIN) + ((np / A_NIN - 1) & 1);
      const int cta = role(), b = (cta >> 1) & 1, code = x_decode(lane, cta);
#pragma unroll 1
      for (int r = 0; r < (spare ? 16 : 10); r++) {
        const int c = __shfl_sync(0xffffffffu, code, r);
        const uint32_t d = __shfl_sync(0xffffffffu, dst, r), f = xf0 + 8 * r, e = __shfl_sync(0xffffffffu, be, r);
        mbar_wait(e & ~1u, e & 1);
        if (lane == 0) {
          mbar_expect(f, A_IN);
          tma_ld4<1>(d, &m.x, f, 0, 96 * (c & 127) - 24, c >> 7, b);
          if (!spare)
            for (int j = A_W0 - 1; j >= 0; j--)
              if (r == ((A_WR >> (4 * j)) & 15)) w1_load(j, cta);
          if (r == A_W2R && !spare) {
            const int i = w2_unit(cta);
            for (int j = 0; j < 2; j++) w_load<1>(7 - j, i, sb + G_TIN + j * 4096, inf0 + 8 * j, &m.w2e, &m.w2o);
            for (int s = 5; s >= A_W2PF; s--)
              asm volatile("cp.async.bulk.prefetch.tensor.4d.L2.global [%0, {0, %1, %2, %3}];" ::"l"(s < 4 ? &m.w2o : &m.w2e), "r"(-(s < 4)), "r"((i & 1) * 2), "r"((s & 3) * 64 + (i >> 1)) : "memory");
          }
        }
        __syncwarp();
      }
      if (!spare) {
        const int bin = cta >> 2, f = 2 * bin + hf;
        if (lane == 0) {
          prefetch_map(&m.w);
          prefetch_map(&m.y);
          prefetch_map(&m.w2o);
        }
        const uint32_t xa = x1_addr((21 - lane + 2 * (lane % 3)) * 8 + (f >> 4), b, flips()) + spread16(f);
        const uint32_t wa = w_addr(7 - (lane >> 1), 2 * bin, (lane & 1) * 32, hf, s_flips);
#pragma unroll 1
        for (int k = 0; k < 16; k++) {
          const int st = g_slot(k);
          uint32_t a[3];
#pragma unroll
          for (int th = 0; th < 3; th++) a[th] = __shfl_sync(0xffffffffu, xa, 3 * (k >> 1) + th) ^ ((k & 1) * 0x21000);
          const uint32_t w = __shfl_sync(0xffffffffu, wa, k);
          if ((A_ACQ >> k) & 1) {
            mbar_wait(acq0 + 8 * __popc(A_ACQ & ((1 << k) - 1)), 0);
            asm volatile("fence.proxy.async.global;" ::: "memory");
          }
          mbar_wait(empty0 + 8 * st, (G_PAR >> k) & 1);
          if (lane == 0) {
            const uint32_t base = sb + st * G_STAGE, bar = full0 + 8 * st;
            mbar_expect(bar, G_STAGE);
#pragma unroll
            for (int th = 0; th < 3; th++)
              if (G_XPOL && k >= G_XPOLK)
                asm volatile("cp.async.bulk.shared::cluster.global.mbarrier::complete_tx::bytes.multicast::cluster.L2::cache_hint [%0], [%1], %2, [%3], %4, %5;"
                             ::"r"(base + 16384 + hf * G_XP + th * 3584), "l"(x1 + a[th]), "n"(3584), "r"(bar), "h"((uint16_t)3), "l"(policy<G_XPOL>()) : "memory");
              else
                asm volatile("cp.async.bulk.shared::cluster.global.mbarrier::complete_tx::bytes.multicast::cluster [%0], [%1], %2, [%3], %4;"
                             ::"r"(base + 16384 + hf * G_XP + th * 3584), "l"(x1 + a[th]), "n"(3584), "r"(bar), "h"((uint16_t)3) : "memory");
            if (k >= G_WPOLK) tma_ld3<G_WPOL>(base, &m.w, bar, 0, (w >> 7) & 127, w >> 14);
            else tma_ld3<0>(base, &m.w, bar, 0, (w >> 7) & 127, w >> 14);
          }
          __syncwarp();
        }
        if (blk == 0 && lane == 0) asm volatile("cp.async.bulk.prefetch.L2.global [%0], 14336;" ::"l"(c_img) : "memory");
      }
    } else if (warp == 1) {
      if (lane == 0) {
#pragma unroll 1
        for (int r = 0; r < A_NREL; r++) {
          mbar_wait(rel0 + 8 * r, 0);
          asm volatile("fence.acq_rel.gpu;\nred.relaxed.gpu.global.add.s32 [%0], 1;" ::"l"(&g_done[(8 + r) * 32]) : "memory");
        }
      }
    } else if (warp == 2) {
      const uint32_t relm = spare ? A_RELS : A_REL;
      const int xr = __popc(xm & ((1 << lane) - 1));
      const uint32_t srcs = sb + a_out(lane), bars = aof0 + 8 * (lane % A_NOUT);
      const uint32_t done = lane < 16 ? bars + 8 * A_NOUT : se0 + 8 * (lane & 1), relb = rel0 + 8 * __popc(relm & ((1 << lane) - 1));
      const int cta = role(), xc = x_decode(xr, cta), q = xc & 127, th = q / 28, ws = 7 - lane + xr, wi = w_unit(ws >> 1, cta);
      const uint32_t fl = flips();
      const int code = (xm >> lane) & 1 ? 0x80000000u + x1_addr(((xc >> 7) * 3 + th) * 8, (cta >> 1) & 1, fl) + (q - 28 * th) * 128
                                        : w_addr(ws, 0, wi >> 1, wi & 1, fl);
      uint32_t tnext = clock(), src = __shfl_sync(0xffffffffu, srcs, 0), bar = aof0;
      int c = __shfl_sync(0xffffffffu, code, 0);
#pragma unroll 1
      for (int n = 0; n < nu; n++) {
        mbar_wait(bar, (n >= A_NOUT) ^ (n >= 2 * A_NOUT));
        while ((int)(clock() - tnext) < 0);
        tnext = clock() + (n < A_PACE_N ? A_PACE0 : n < A_PIPE ? A_PACE1 : A_PACE2);
        if (lane == n) {
          if (c >= 0) {
            w_store(&m.ws, src, c);
          } else {
#pragma unroll
            for (int j = 0; j < 8; j++)
              tma_st4<0>(&m.xs, src + j * 2048, ((c & 16383) >> 1) ^ ((__popc(j) & 1) << 11) ^ ((j & 1) << 12), (j >> 1) << 2, (c >> 18) & 3, (c >> 20) & 31);
          }
          bulk_commit();
        }
        __syncwarp();
        c = __shfl_sync(0xffffffffu, code, n + 1);
        src = __shfl_sync(0xffffffffu, srcs, n + 1);
        bar = __shfl_sync(0xffffffffu, bars, n + 1);
        if (n >= A_PIPE && !(n & 1)) continue;
        bulk_wait<0>();
        if (lane == n || (n > A_PIPE && lane == n - 1)) {
          mbar_arrive(done);
          if ((relm >> lane) & 1) mbar_arrive(relb);
        }
        __syncwarp();
        if (!spare && (n == 13 || n == 15) && lane < 16) mbar_arrive_cta(empty0 + 8 * ((n - 11) >> 1), lane & 1);
      }
      if (!spare) {
        const int i = w2_unit(cta);
        const uint32_t wa = w_addr(7 + W_SHIFT - lane, 0, i >> 1, i & 1, fl);
        uint32_t seen = 256 + (1 << W_SHIFT) - 1;
        auto look = [&]() {
          int v;
          asm volatile("ld.relaxed.gpu.global.s32 %0, [%1];\nfence.acquire.gpu;" : "=r"(v) : "l"(&g_done[lane & 7]) : "memory");
          seen |= __ballot_sync(0xffffffffu, v >= 128) << W_SHIFT;
        };
#pragma unroll 1
        for (int it = 0; it < 8; it++) {
          const uint32_t a = __shfl_sync(0xffffffffu, wa, it);
          mbar_wait(sf0 + 8 * (it & 1), (it >> 1) & 1);
          if (lane == 0 && it < 6) w_load<1>(5 - it, i, sb + G_TIN + (it & 1) * 4096, inf0 + 8 * (it & 1), &m.w2e, &m.w2o);
          for (int p = 0; p < (1 << 20) && !((seen >> it) & 1); p++) look();
          if (lane == 0) {
            w_store(&m.ws, sb + G_TOUT + (it & 1) * A_OUT, a);
            bulk_commit();
          }
          __syncwarp();
          if (!((seen >> (it + 1)) & 1)) look();
          bulk_wait_read<0>();
          if (lane == 0) mbar_arrive(se0 + 8 * (it & 1));
        }
      }
    } else {
      int unused;
      const uint32_t fl = read_votes(lane, unused);
      if (lane == 0) {
        s_flips = fl;
        mbar_arrive(flipb);
        if (!spare) {
          int r = 0;
#pragma unroll 1
          for (int k = 0; k < 16 - 2 * W_SHIFT; k++) {
            for (; r < __popc(A_ACQ & ((2 << (k + A_LOOK)) - 1)); r++) {
              mbar_wait(rel0 + 8 * r, 0);
              poll_ge(&g_done[(8 + r) * 32], 132);
              mbar_arrive(acq0 + 8 * r);
            }
            mbar_wait(full0 + 8 * g_slot(k), (G_PAR >> k) & 1);
            if (k & 1) asm volatile("red.relaxed.gpu.global.add.s32 [%0], 1;" ::"l"(&g_done[k >> 1]) : "memory");
          }
        }
      }
    }
  } else {
    asm volatile("barrier.cluster.arrive.relaxed.aligned;" ::: "memory");
    if (lane == 0) {
      const uint32_t gr = 2 * blk, par = (gr >> 1) ^ (gr >> 4) ^ (gr >> 5) ^ (gr >> 7);
      char* p = (wg && page >= 12 ? wt - (12 << 21) : x1) + ((wg * page) << 21) + ((gr + ((warp ^ par) & 1)) << 12) + 3584 + (warp >> 1) * 128;
      uint32_t c0, c1;
      asm volatile("{\n.reg .u32 v;\n"
                   "st.global.v4.u32 [%1], {0, 0, 0, 0};\nst.global.v4.u32 [%1 + 16], {0, 0, 0, 0};\n"
                   "mov.u32 %0, %%clock;\natom.relaxed.gpu.global.add.u32 v, [%1], 1;\nsub.u32 %0, %0, v;\n}\n" : "=r"(c0) : "l"(p) : "memory");
      asm volatile("mov.u32 %0, %%clock;" : "=r"(c1) : "r"(c0) : "memory");
      lat[wg * 4 + warp] = c1 - c0;
    }
    __syncwarp();
    bar_arrive(9, 352);
    if (wg == 1) tab[t] = __bfloat16_as_ushort(__float2bfloat16_rn(cospif((float)t * (1.0f / 64.0f))));
    pdl_launch();
    bar_sync(1, 256);
    asm volatile("setmaxnreg.inc.sync.aligned.u32 232;");
    uint32_t fa[16];
#pragma unroll
    for (int i = 0; i < 16; i++) {
      const int f = warp * 16 + (lane >> 2) + 8 * (i & 1), r = 8 * (i >> 1) + (lane & 3) * 2;
      const int k0 = (f | 1) * r - ((f & 1) << 5);
      fa[i] = tab[k0 & 127] | ((uint32_t)tab[(k0 + (f | 1)) & 127] << 16);
    }
    reg_fence(fa);
    asm volatile("barrier.cluster.wait.aligned;" ::: "memory");
    int cta = blk, qs = 2 * hf + wg;
#pragma unroll 1
    for (int n = wg; n < nu; n += 2) {
      float e[64];
      if ((n >> 1) == 1 && !spare) {
        cta = role();
        qs = ((cta >> 1) & 2) + hf;
      }
      const bool isx = (xm >> n) & 1;
      const int r = __popc(xm & ((1 << n) - 1)), s = 7 - n + r;
      const uint32_t in = isx ? sb + 3 * G_STAGE + (r % A_NIN) * A_IN : sb + s * 4096;
      mbar_wait(isx ? xf0 + 8 * r : wf0 + 8 * (s >> 1), 0);
      if (!isx) {
        wg_fence();
        wgmma_rs_128<1, 1, 1>(e, fa[0], fa[1], fa[2], fa[3], mk_desc(in, 0, 2048, 1024, 1), 0);
        wg_commit();
      } else {
        wg_fence();
#pragma unroll
        for (int k = 0; k < 4; k++)
          wgmma_rs_128<1, 1, 1>(e, fa[4 * k], fa[4 * k + 1], fa[4 * k + 2], fa[4 * k + 3], mk_desc(in, k * 2048, 6144, 1024, 1), k);
        wg_commit();
      }
      wg_wait<0>();
      reg_fence(e);
      if (isx && lane == 0) mbar_arrive(xe0 + 8 * (r % A_NIN));
      if (((A_FREE >> n) & 1) && !spare && lane < 2) mbar_arrive_cta(empty0 + 8 * g_slot(__popc(A_FREE & ((1 << n) - 1)) >> 1), lane);
      if (n >= A_NOUT) mbar_wait(aoe0 + 8 * (n % A_NOUT), (n / A_NOUT - 1) & 1);
      const int row = warp * 16 + (lane & 7) + ((lane >> 3) & 1) * 8, hi = lane >> 4;
      const uint32_t rb = sb + a_out(n) + (isx ? row : row + (row & ~7)) * 128, ts = isx ? 8192 : 1024, xr = (lane & 7) ^ (isx ? qs : 0);
#pragma unroll
      for (int j = 0; j < 16; j += 2) {
        const uint32_t tile = isx ? (j >> 2) & 1 : j >> 3, pos = (isx ? (j >> 3) * 4 + (j & 3) : (j & 7)) + hi;
        stsm4(rb + tile * ts + ((pos ^ xr) << 4), pack2(e[4 * j], e[4 * j + 1]), pack2(e[4 * j + 2], e[4 * j + 3]),
              pack2(e[4 * j + 4], e[4 * j + 5]), pack2(e[4 * j + 6], e[4 * j + 7]));
      }
      fence_async();
      __syncwarp();
      if (lane == 0) mbar_arrive(aof0 + 8 * (n % A_NOUT));
    }
    if (spare) {
      float* sg = reinterpret_cast<float*>(smem_raw + (sb + 3 * G_STAGE - s2u(smem_raw)));
      __nv_bfloat16* sw = reinterpret_cast<__nv_bfloat16*>(sg + 16 * 256);
      const int c0 = (cta - 128) * 64;
      uint4 vw[8], vg[2];
#pragma unroll
      for (int i = 0; i < 8; i++) vw[i] = __ldg(reinterpret_cast<const uint4*>(wgt + ((i * 256 + tid) >> 3) * 256 + c0 + (tid & 7) * 8));
#pragma unroll
      for (int i = 0; i < 2; i++) vg[i] = __ldg(reinterpret_cast<const uint4*>(g) + i * 256 + tid);
      bar_sync(3, 256);
#pragma unroll
      for (int i = 0; i < 8; i++) reinterpret_cast<uint4*>(sw)[i * 256 + tid] = vw[i];
#pragma unroll
      for (int i = 0; i < 2; i++) {
        const uint32_t w4[4] = {vg[i].x, vg[i].y, vg[i].z, vg[i].w};
#pragma unroll
        for (int e = 0; e < 4; e++) {
          sg[(i * 256 + tid) * 8 + 2 * e] = __uint_as_float(w4[e] << 16);
          sg[(i * 256 + tid) * 8 + 2 * e + 1] = __uint_as_float(w4[e] & 0xffff0000u);
        }
      }
      bar_sync(3, 256);
      const int col = tid & 63, r0 = (tid >> 6) * 4;
      float a0 = 0.f, a1 = 0.f, a2 = 0.f, a3 = 0.f;
#pragma unroll 8
      for (int k = 0; k < 256; k++) {
        const float w = __bfloat162float(sw[k * 64 + col]);
        a0 = fmaf(sg[(r0 + 0) * 256 + k], w, a0);
        a1 = fmaf(sg[(r0 + 1) * 256 + k], w, a1);
        a2 = fmaf(sg[(r0 + 2) * 256 + k], w, a2);
        a3 = fmaf(sg[(r0 + 3) * 256 + k], w, a3);
      }
      const int cc = c0 + col;
      const int pos = (cc & ~15) + ((cc >> 1) & 3) * 4 + ((cc >> 3) & 1) * 2 + (cc & 1);
      g_ge[(r0 + 0) * 256 + pos] = __bfloat162float(__float2bfloat16_rn(a0));
      g_ge[(r0 + 1) * 256 + pos] = __bfloat162float(__float2bfloat16_rn(a1));
      g_ge[(r0 + 2) * 256 + pos] = __bfloat162float(__float2bfloat16_rn(a2));
      g_ge[(r0 + 3) * 256 + pos] = __bfloat162float(__float2bfloat16_rn(a3));
      return;
    }
    const int b = (cta >> 1) & 1, bin = cta >> 2;
    float d[32];
    auto t_begin = [&](int it, int hh) {
      mbar_wait(inf0 + 8 * (it & 1), (it >> 1) & 1);
      wg_fence();
      wgmma_rs_64<1, 1, 1>(d, fa[0], fa[1], fa[2], fa[3], mk_desc(sb + G_TIN + (it & 1) * 4096 + hh * 2048, 0, 0, 1024, 1), 0);
      wg_commit();
    };
    auto t_end = [&](int it, int hh) {
      reg_fence(d);
      const int j = it & 1;
      mbar_wait(se0 + 8 * j, (it >> 1) & 1);
      store_tile_64<2048>(d, sb + G_TOUT + j * A_OUT + hh * 1024, warp, lane);
      fence_async();
      __syncwarp();
      if (lane == 0) mbar_arrive(sf0 + 8 * j);
    };
    float re[NB1 / 2], im[NB1 / 2];
#pragma unroll 1
    for (int k = 0; k < G_KS; k++) {
      const int st = g_slot(k);
      const int it = __popc(G_TMASK & ((1 << k) - 1));
      const bool T = (G_TMASK >> k) & 1;
      if (T) t_begin(it, wg);
      mbar_wait(full0 + 8 * st, (G_PAR >> k) & 1);
      const uint32_t base = sb + st * G_STAGE;
      const uint32_t wb = base + wg * 4096;
      wg_fence();
#pragma unroll
      for (int s = 0; s < 2; s++) {
        const int acc = (k | s) != 0;
        const uint64_t dP = mk_desc(wb, s * 2048, 0, 1024, 1), dQ = mk_desc(wb, 8192 + s * 2048, 0, 1024, 1);
        const uint64_t dA = mk_desc(base, 16384 + s * 32, 0, 512, 2), dB = mk_desc(base, 16384 + G_XP + s * 32, 0, 512, 2);
        wgmma_ss_168<1, 1, 1, 0>(re, dP, dA, acc);
        wgmma_ss_168<1, 1, 1, 0>(im, dP, dB, acc);
        wgmma_ss_168<1, 1, 1, 0>(re, dQ, dB, 1);
        wgmma_ss_168<-1, 1, 1, 0>(im, dQ, dA, 1);
      }
      wg_commit();
      wg_wait<1>();
      if (k > 0 && lane < 2) mbar_arrive_cta(empty0 + 8 * g_slot(k - 1), lane);
      if (T) t_end(it, wg);
    }
    auto tail = [&](auto part, bool wait) {
      constexpr int PART = decltype(part)::value;
#pragma unroll
      for (int k = G_KS; k < 16; k++) {
        if (wait) mbar_wait(full0 + 8 * g_slot(k), (G_PAR >> k) & 1);
        const uint32_t base = sb + g_slot(k) * G_STAGE, wb = base + wg * 4096;
        wg_fence();
#pragma unroll
        for (int s = 0; s < 2; s++) {
          const uint64_t dP = mk_desc(wb, s * 2048, 0, 1024, 1), dQ = mk_desc(wb, 8192 + s * 2048, 0, 1024, 1);
          const uint64_t dA = mk_desc(base, 16384 + s * 32, 0, 512, 2), dB = mk_desc(base, 16384 + G_XP + s * 32, 0, 512, 2);
          if (PART == 0) {
            wgmma_ss_168<1, 1, 1, 0>(re, dP, dA, 1);
            wgmma_ss_168<1, 1, 1, 0>(re, dQ, dB, 1);
          } else {
            wgmma_ss_168<1, 1, 1, 0>(im, dP, dB, 1);
            wgmma_ss_168<-1, 1, 1, 0>(im, dQ, dA, 1);
          }
        }
      }
      wg_commit();
    };
    auto put = [&](const float (&v)[NB1 / 2], uint32_t stg, int f) {
      const int mi = lane >> 3, i = lane & 7;
      const uint32_t a0 = stg + (mi >> 1) * 1024 + i * 128 + (((2 * warp + (mi & 1)) ^ i) << 4);
      const uint32_t ya = x1_addr(96 + 8 * lane + 4 * hf + 2 * wg + (f >> 5), b, s_flips) + (f & 31) * 128;
#pragma unroll
      for (int c = 0; c < 3; c++) {
#pragma unroll
        for (int j = 8 * c; j < 8 * c + 8 && j < 20; j += 2)
          stsm4t(a0 + j * 1024, pack2(v[4 * j], v[4 * j + 1]), pack2(v[4 * j + 2], v[4 * j + 3]),
                 pack2(v[4 * j + 4], v[4 * j + 5]), pack2(v[4 * j + 6], v[4 * j + 7]));
        if (c == 2)
          asm volatile("stmatrix.sync.aligned.m8n8.x2.trans.shared.b16 [%0], {%1, %2};" ::"r"(a0 + 20 * 1024),
                       "r"(pack2(v[80], v[81])), "r"(pack2(v[82], v[83])) : "memory");
        const uint32_t a = __shfl_sync(0xffffffffu, ya, 4 * c + warp);
        fence_async();
        bar_sync(2 + wg, 128);
        if (lane == 0 && (c < 2 || warp < 3)) {
          tma_st4<0>(c == 2 && warp == 2 ? &m.y : &m.xs, stg + (4 * c + warp) * 2048, (a & 16383) >> 1, (a >> 14) & 15, (a >> 18) & 3, a >> 20);
          bulk_commit();
        }
      }
    };
    if (wg == 0) {
      tail(std::integral_constant<int, 0>(), true);
      bar_arrive(4, 256);
      bar_sync(5, 256);
      wg_wait<0>();
      reg_fence(re);
      put(re, sb + 4 * G_STAGE, 2 * bin);
      bar_sync(7, 256);
      tail(std::integral_constant<int, 1>(), false);
      bar_arrive(8, 256);
      wg_wait<0>();
      reg_fence(im);
      bar_arrive(6, 256);
      put(im, sb + 4 * G_STAGE + NB1 * 128, 2 * bin + 1);
    } else {
#pragma unroll 1
      for (int h2 = 2 * __popc(G_TMASK); h2 < 16; h2++) {
        t_begin(h2 >> 1, h2 & 1);
        wg_wait<0>();
        t_end(h2 >> 1, h2 & 1);
      }
      wg_wait<0>();
      bar_arrive(5, 256);
      bar_sync(4, 256);
      tail(std::integral_constant<int, 0>(), true);
      bar_arrive(7, 256);
      mbar_wait(se0, 0);
      mbar_wait(se0 + 8, 0);
      wg_wait<0>();
      reg_fence(re);
      put(re, sb + G_TOUT, 2 * bin);
      bar_sync(8, 256);
      tail(std::integral_constant<int, 1>(), false);
      wg_wait<0>();
      reg_fence(im);
      bar_sync(6, 256);
      put(im, sb, 2 * bin + 1);
    }
    bulk_wait_read<0>();
  }
}

#define G_WPRE 2
#define H_EPI 3
#define H_KS 11
constexpr int H_XP = 168 * 64, H_STAGE = 8192 + 2 * H_XP, H_NST = 7, H_SMEM = H_NST * H_STAGE + 21504 + 1024;

template <int WG>
__device__ __forceinline__ void h_loop(float (&acc)[84], uint32_t sb, uint32_t full0, uint32_t empty0, int lane) {
#pragma unroll 1
  for (int k = 0; k < 16; k++) {
    const int st = k % H_NST;
    if (WG == 1 && k == H_KS) bar_sync(4, 256);
    mbar_wait(full0 + 8 * st, (k / H_NST) & 1);
    const uint32_t base = sb + st * H_STAGE;
    wg_fence();
#pragma unroll
    for (int s = 0; s < 2; s++) {
      const uint64_t dP = mk_desc(base, s * 2048, 0, 1024, 1), dQ = mk_desc(base, 4096 + s * 2048, 0, 1024, 1);
      const uint64_t dA = mk_desc(base, 8192 + s * 32, 0, 512, 2), dB = mk_desc(base, 8192 + H_XP + s * 32, 0, 512, 2);
      wgmma_ss_168<1, 1, 1, 0>(acc, dP, WG == 0 ? dA : dB, k | s);
      wgmma_ss_168<WG == 0 ? 1 : -1, 1, 1, 0>(acc, dQ, WG == 0 ? dB : dA, 1);
    }
    wg_commit();
    if (WG == 0 && k == 15) bar_arrive(4, 256);
    if (k <= 10) {
      wg_wait<1>();
      if (k > 0 && k - 1 + H_NST < 16 && lane < 2) mbar_arrive_cta(empty0 + 8 * ((k - 1) % H_NST), lane);
    }
  }
  wg_wait<0>();
  reg_fence(acc);
}

__global__ void __cluster_dims__(2, 1, 1) __launch_bounds__(288, 1)
kH(const __grid_constant__ CUtensorMap mx, const __grid_constant__ CUtensorMap mw, const __grid_constant__ CUtensorMap my,
   const __nv_bfloat16* __restrict__ wf, const __nv_bfloat16* __restrict__ wo) {
  extern __shared__ uint8_t smem_raw[];
  __shared__ __align__(8) uint64_t bars[2 * H_NST];
  const uint32_t sb = (s2u(smem_raw) + 1023) & ~1023u;
  const int tid = threadIdx.x, wg = __shfl_sync(0xffffffffu, tid >> 7, 0), t = tid & 127;
  const int warp = __shfl_sync(0xffffffffu, t >> 5, 0), lane = t & 31;
  __shared__ __align__(8) uint64_t role_bar;
  __shared__ uint32_t s_role;
  const int rank = blockIdx.x & 1;
  const uint32_t full0 = s2u(&bars[0]), empty0 = full0 + 8 * H_NST, roleb = s2u(&role_bar);
  pdl_launch();
  if (tid == 32) {
    for (int i = 0; i < H_NST; i++) {
      mbar_init(full0 + 8 * i, 1);
      mbar_init(empty0 + 8 * i, 16);
    }
    mbar_init(roleb, 1);
    mbar_expect(roleb, 4);
    fence_bar_init();
    fence_async();
  } else if (tid == 64) {
    prefetch_map(&mw);
    prefetch_map(&mx);
    prefetch_map(&my);
  }
  __syncwarp();
  asm volatile("barrier.cluster.arrive.relaxed.aligned;" ::: "memory");
  uint32_t fl = 0;
  int ticket = 0;
  if (warp == 0 && wg != 1) {
    int side;
    fl = read_votes(lane, side);
    if (tid == 256 && rank == 0) ticket = W2_AFF ? 2 * atomicAdd(&g_done[14 * 32 + 4 + side], 1) + side : blockIdx.x >> 1;
    __syncwarp();
  }
  asm volatile("barrier.cluster.wait.aligned;" ::: "memory");
  if (tid == 256 && rank == 0) send_role(s2u(&s_role), roleb, ticket < 64 ? ticket : 127 - ticket);
  __syncwarp();
  mbar_wait(roleb, 0);
  __syncwarp();
  const int cta = 2 * *(volatile uint32_t*)&s_role + rank, dc = cta & 3, bin = cta >> 2;
  const uint32_t wa = w_addr((lane >> 1) + W_SHIFT, 2 * bin, (lane & 1) * 32, dc >> 1, fl) + (rank << 14);
  if (wg == 0 && warp == 0) {
#pragma unroll
    for (int k = 0; k < G_WPRE; k++) {
      const uint32_t w = __shfl_sync(0xffffffffu, wa, k);
      if (lane == 0) tma_ld3<1>(sb + k * H_STAGE, &mw, full0 + 8 * k, 0, (w >> 7) & 255, w >> 15);
    }
    __syncwarp();
  }
  if (wg == 2) {
    if (lane < H_NST) mbar_expect(full0 + 8 * lane, H_STAGE);
    pdl_wait();
    int st = 0;
#pragma unroll 1
    for (int k = 0; k < 16; k++) {
      const uint32_t w = __shfl_sync(0xffffffffu, wa, k);
      if (k >= H_NST) mbar_wait(empty0 + 8 * st, k >= 2 * H_NST);
      if (lane == 0) {
        const uint32_t base = sb + st * H_STAGE, bar = full0 + 8 * st;
        if (k >= H_NST) mbar_expect(bar, H_STAGE);
        tma_ld3mc<0>(base + 8192 + rank * H_XP, &mx, bar, (k & 1) * 32, 0, (k >> 1) * 64 + 2 * bin + rank);
        if (k >= G_WPRE) tma_ld3<1>(base, &mw, bar, 0, (w >> 7) & 255, w >> 15);
        if (k == H_NST - 1) {
          if (cta == 0) asm volatile("cp.async.bulk.prefetch.L2.global [%0], 6144;" ::"l"(c_ga) : "memory");
          asm volatile("cp.async.bulk.prefetch.L2.global [%0], 1024;" ::"l"(wf + cta * 512) : "memory");
          asm volatile("cp.async.bulk.prefetch.L2.global [%0], 1024;" ::"l"(wo + cta * 512) : "memory");
        }
      }
      __syncwarp();
      if (++st == H_NST) st = 0;
    }
  } else {
    float acc[84];
    if (wg == 0) {
      h_loop<0>(acc, sb, full0, empty0, lane);
    } else {
      h_loop<1>(acc, sb, full0, empty0, lane);
      bar_sync(3, 128);
    }
    const uint32_t stg = sb + (wg == 0 ? H_NST : 9 % H_NST) * H_STAGE;
    const int mi = lane >> 3, i = lane & 7;
    const uint32_t a0 = stg + (mi >> 1) * 1024 + i * 128 + (((2 * warp + (mi & 1)) ^ i) << 4);
    constexpr int J = 21 / H_EPI;
#pragma unroll
    for (int c = 0; c < H_EPI; c++) {
#pragma unroll
      for (int j = c * J; j + 1 < (c + 1) * J; j += 2)
        stsm4t(a0 + j * 1024, pack2(acc[4 * j], acc[4 * j + 1]), pack2(acc[4 * j + 2], acc[4 * j + 3]),
               pack2(acc[4 * j + 4], acc[4 * j + 5]), pack2(acc[4 * j + 6], acc[4 * j + 7]));
      const int j = (c + 1) * J - 1;
      asm volatile("stmatrix.sync.aligned.m8n8.x2.trans.shared.b16 [%0], {%1, %2};" ::"r"(a0 + j * 1024),
                   "r"(pack2(acc[4 * j], acc[4 * j + 1])), "r"(pack2(acc[4 * j + 2], acc[4 * j + 3])) : "memory");
      fence_async();
      bar_sync(2 + wg, 128);
      if (t == 0) {
        tma_st4<0>(&my, stg + c * J * 1024, 0, c * J * 8, 2 * bin + wg, dc);
        bulk_commit();
      }
    }
    if (t == 0) {
      bulk_wait_read<0>();
    }
  }
}

#define C_AFF 1
#define C_TOK 1
constexpr int C_OUT = 13 * 8192, C_GI = C_OUT + 6 * 16384, C_F = C_GI + 6144;
constexpr int C_SMEM = C_F + 8192 + 1024;

template <int NC> __device__ __forceinline__ void gelu_pack(uint32_t (&hp)[32], const float (&h)[4 * NC], int rc0, bool zero_first, bool zero_all) {
#pragma unroll
  for (int c = 0; c < NC; c++) {
    const uint32_t lo = pack2(gelu(h[4 * c]), gelu(h[4 * c + 1])), hi = pack2(gelu(h[4 * c + 2]), gelu(h[4 * c + 3]));
    const bool z = zero_all || (zero_first && c < 2);
    hp[(c & 1) * 16 + (rc0 + (c >> 1)) * 2] = z ? 0u : lo;
    hp[(c & 1) * 16 + (rc0 + (c >> 1)) * 2 + 1] = z ? 0u : hi;
  }
}

__global__ void __launch_bounds__(512, 1)
kC(const __grid_constant__ CUtensorMap my0, const __grid_constant__ CUtensorMap my1, const __grid_constant__ CUtensorMap mxs) {
  extern __shared__ uint8_t smem_raw[];
  __shared__ __align__(8) uint64_t bars[14];
  __shared__ int s_role;
  const uint32_t sb = (s2u(smem_raw) + 1023) & ~1023u;
  const int tid = threadIdx.x, wg = __shfl_sync(0xffffffffu, tid >> 7, 0), t = tid & 127, warp = t >> 5, lane = t & 31;
  const bool loader = __shfl_sync(0xffffffffu, tid >> 5, 0) == 15;
  const uint32_t sGi = sb + C_GI, sF = sb + C_F, barc = s2u(&bars[0]);
  uint32_t fl = 0;
  if (loader) {
    int side;
    fl = read_votes(lane, side);
    if (lane == 0) {
      const int ticket = C_AFF ? 2 * atomicAdd(&g_done[14 * 32 + 2 + side], 1) + side : blockIdx.x;
      s_role = ticket < 128 ? ticket : 255 - ticket;
    }
  } else if (tid == 384) {
    prefetch_map(&my0);
    prefetch_map(&my1);
    for (int i = 0; i < 14; i++) mbar_init(barc + 8 * i, 1);
    fence_bar_init();
    fence_async();
    mbar_expect(barc + 8 * 13, 14336);
    asm volatile("cp.async.bulk.shared::cluster.global.mbarrier::complete_tx::bytes [%0], [%1], 14336, [%2];"
                 ::"r"(sGi), "l"(c_img), "r"(barc + 8 * 13) : "memory");
  }
  __syncthreads();
  const int b = s_role & 1, cs = (s_role >> 1) & 3, j = s_role >> 3;
  const int n0 = 5 * j + min(j, 4), cnt = j < 4 ? 6 : 5;
  if (loader) {
    const int blk = min(2 * n0 + lane, NB1 - 1);
    const uint32_t ya = x1_addr(96 + 8 * (blk >> 4) + 2 * cs, b, fl) + spread16(blk);
    if (lane <= 2 * cnt) mbar_expect(barc + 8 * lane, 8192);
    pdl_wait();
#pragma unroll 1
    for (int i = 0; i <= 2 * cnt; i++) {
      const uint32_t a = __shfl_sync(0xffffffffu, ya, i);
      if (lane == 0) tma_ld3<1>(sb + i * 8192, (a & 4096) ? &my1 : &my0, barc + 8 * i, 0, a >> 7, 0);
      __syncwarp();
    }
    pdl_launch();
    if (lane == 0) prefetch_map(&mxs);
  }
  mbar_wait(barc + 8 * 13, 0);
#pragma unroll 1
  for (int i = wg; i < cnt; i += 4) {
    const int n2 = n0 + i;
    const uint32_t in = sb + i * 16384, bar = barc + i * 16, outb = sb + C_OUT + i * 16384;
    float h0[24], h1[24], h2[16];
    uint32_t hp[32];
    mbar_wait(bar, 0);
    wg_fence();
#pragma unroll
    for (int k = 0; k < 4; k++) wgmma_ss_48<1, 1, 1, 0>(h0, mk_desc(in, k * 2048, 0, 1024, 1), mk_desc(sGi, k * 32, 0, 1024, 1), k);
    wg_commit();
    mbar_wait(bar + 8, 0);
    wg_fence();
#pragma unroll
    for (int k = 0; k < 4; k++) wgmma_ss_48<1, 1, 1, 0>(h1, mk_desc(in, 8192 + k * 2048, 0, 1024, 1), mk_desc(sGi, k * 32, 0, 1024, 1), k);
    wg_commit();
    if (C_TOK && i > 0) bar_sync(5 + wg, 256);
    wg_wait<1>();
    reg_fence(h0);
    gelu_pack<6>(hp, h0, 0, n2 == 0, false);
    mbar_wait(bar + 16, 0);
    wg_fence();
#pragma unroll
    for (int k = 0; k < 4; k++) wgmma_ss_32<1, 1, 1, 0>(h2, mk_desc(in, 16384 + k * 2048, 0, 1024, 1), mk_desc(sGi, k * 32, 0, 1024, 1), k);
    wg_commit();
    if (C_TOK == 1 && i + 1 < cnt) bar_arrive(5 + ((wg + 1) & 3), 256);
    wg_wait<1>();
    reg_fence(h1);
    gelu_pack<6>(hp, h1, 3, false, n2 == NB2 - 1);
    if (C_TOK == 2 && i + 1 < cnt) bar_arrive(5 + ((wg + 1) & 3), 256);
    wg_wait<0>();
    reg_fence(h2);
    gelu_pack<4>(hp, h2, 6, false, n2 == NB2 - 1);
    float e0[32], e1[32];
    reg_fence(hp);
    if (C_TOK == 3 && i + 1 < cnt) bar_arrive(5 + ((wg + 1) & 3), 256);
    wg_fence();
#pragma unroll
    for (int k = 0; k < 4; k++) {
      const uint64_t db = mk_desc(sF, k * 32, 0, 1024, 1);
      wgmma_rs_64<1, 1, 0>(e0, hp[4 * k], hp[4 * k + 1], hp[4 * k + 2], hp[4 * k + 3], db, k);
      wgmma_rs_64<1, 1, 0>(e1, hp[16 + 4 * k], hp[16 + 4 * k + 1], hp[16 + 4 * k + 2], hp[16 + 4 * k + 3], db, k);
    }
    wg_commit();
    wg_wait<0>();
    reg_fence(e0);
    reg_fence(e1);
    {
      const int mi = lane >> 3, r = lane & 7;
      const uint32_t a0 = outb + (mi >> 1) * 8192 + r * 128 + (((2 * warp + (mi & 1)) ^ r) << 4);
#pragma unroll
      for (int q = 0; q < 8; q++)
        stsm4t(a0 + q * 1024, pack2(e0[4 * q], e0[4 * q + 1]), pack2(e0[4 * q + 2], e0[4 * q + 3]),
               pack2(e1[4 * q], e1[4 * q + 1]), pack2(e1[4 * q + 2], e1[4 * q + 3]));
    }
    fence_async();
    bar_sync(1 + wg, 128);
    if (t == 0) {
      tma_st3<0>(&mxs, outb, 0, cs * 64, b * NB2 + n2);
      tma_st3<0>(&mxs, outb + 8192, 0, (4 + cs) * 64, b * NB2 + n2);
      bulk_commit();
    }
  }
  if (t == 0) bulk_wait_read<0>();
}

#define E_WPRE 2
#define E_EARLY0 2
#define E_CHUNK 1
#define E_EARLY 2
constexpr int E_SMEM = 65536 + 131072 + 32768 + 1024;

__device__ __forceinline__ uint32_t joint2(uint32_t fe, uint32_t g0, uint32_t g1) {
  uint32_t s0, s1;
  asm("{\n.reg .b16 l, h;\n.reg .b32 ll;\nmov.b32 {l, h}, %2;\nmov.b32 ll, {l, l};\n"
      "fma.rn.bf16x2 %0, ll, %5, %3;\nfma.rn.bf16x2 %1, %2, %5, %4;\n}"
      : "=r"(s0), "=r"(s1) : "r"(fe), "r"(g0), "r"(g1), "r"(0x3F800000u));
  return pack2(tanh_f32(__uint_as_float(s0)), tanh_f32(__uint_as_float(s1)));
}
__device__ __forceinline__ uint4 lds128(uint32_t a) {
  uint4 v;
  asm volatile("ld.shared.v4.u32 {%0, %1, %2, %3}, [%4];" : "=r"(v.x), "=r"(v.y), "=r"(v.z), "=r"(v.w) : "r"(a));
  return v;
}
__device__ __forceinline__ void joint_group(uint32_t (&ja)[8], const uint32_t* fe, uint4& g0, uint4& g1, uint32_t gnext) {
  const uint4 c0 = g0, c1 = g1;
  g0 = lds128(gnext);
  g1 = lds128(gnext + 64);
  ja[0] = joint2(fe[0], c0.x, c0.y);
  ja[1] = joint2(fe[1], c0.x, c0.y);
  ja[2] = joint2(fe[2], c0.z, c0.w);
  ja[3] = joint2(fe[3], c0.z, c0.w);
  ja[4] = joint2(fe[4], c1.x, c1.y);
  ja[5] = joint2(fe[5], c1.x, c1.y);
  ja[6] = joint2(fe[6], c1.z, c1.w);
  ja[7] = joint2(fe[7], c1.z, c1.w);
  reg_fence(ja);
}

__global__ void __launch_bounds__(256, 1)
kE(const __grid_constant__ CUtensorMap my, const __grid_constant__ CUtensorMap mwf, const __grid_constant__ CUtensorMap mwo,
   const __grid_constant__ CUtensorMap mout) {
  extern __shared__ uint8_t smem_raw[];
  __shared__ __align__(8) uint64_t bars[13];
  const uint32_t sb = (s2u(smem_raw) + 1023) & ~1023u;
  const int tid = threadIdx.x, wg = __shfl_sync(0xffffffffu, tid >> 7, 0), t = tid & 127, warp = t >> 5, lane = t & 31;
  const uint32_t R0 = sb, R1 = sb + 65536, R2 = sb + 65536 + 131072;
  const uint32_t barY = s2u(&bars[0]), barF = s2u(&bars[4]), barO = s2u(&bars[8]), barA = s2u(&bars[12]);
  const int b = blockIdx.x / 63, t0 = (blockIdx.x % 63) * 64;
  const int a = t0 / 48, o = t0 % 48;
  const int qw = o + 16 * warp, sel = qw >= 48;
  uint32_t ga[16];
#pragma unroll
  for (int s = 0; s < 4; s++)
    ldg128(reinterpret_cast<const uint4*>(c_ga) + ((qw >> 4) - 3 * sel) * 128 + s * 32 + lane, ga[4 * s], ga[4 * s + 1], ga[4 * s + 2], ga[4 * s + 3]);
  uint4 gev0, gev1;
  asm volatile("ld.global.cg.v4.u32 {%0, %1, %2, %3}, [%4];" : "=r"(gev0.x), "=r"(gev0.y), "=r"(gev0.z), "=r"(gev0.w)
               : "l"(reinterpret_cast<const uint4*>(g_ge) + (b * 8 + wg * 4) * 64 + t));
  asm volatile("ld.global.cg.v4.u32 {%0, %1, %2, %3}, [%4];" : "=r"(gev1.x), "=r"(gev1.y), "=r"(gev1.z), "=r"(gev1.w)
               : "l"(reinterpret_cast<const uint4*>(g_ge) + (b * 8 + wg * 4) * 64 + 128 + t));
  if (tid == 0) {
    prefetch_map(&my);
    for (int i = 0; i < 12; i++) mbar_init(barY + 8 * i, 1);
    mbar_init(barA, 8);
    fence_bar_init();
    fence_async();
    for (int i = 0; i < E_WPRE; i++) {
      const int kc = (i >> 1) | ((i & 1) << 1);
      mbar_expect(barF + 8 * kc, 32768);
      tma_ld3<0>(R1 + kc * 32768, &mwf, barF + 8 * kc, 0, kc * 64, 0);
    }
    pdl_wait();
    for (int i = 0; i < 4; i++) {
      mbar_expect(barY + 8 * i, 16384);
      tma_ld5<0>(R0 + i * 16384, &my, barY + 8 * i, 0, 0, 2 * (i & 1) + (i >> 1), a, b);
    }
    for (int i = E_WPRE; i < 4; i++) {
      const int kc = (i >> 1) | ((i & 1) << 1);
      mbar_expect(barF + 8 * kc, 32768);
      tma_ld3<0>(R1 + kc * 32768, &mwf, barF + 8 * kc, 0, kc * 64, 0);
    }
    prefetch_map(&mwo);
    prefetch_map(&mout);
  }
  uint32_t gs[32];
#pragma unroll
  for (int i = 0; i < 16; i++) {
    gs[i] = sel ? 0u : ga[i];
    gs[16 + i] = sel ? ga[i] : 0u;
  }
  __syncthreads();
  if (blockIdx.x == 125) g_done[tid] = g_done[256 + tid] = 0;
  reg_fence(gs);
  uint32_t gp = R2 + wg * 4096 + (lane & 3) * 16;
  uint4 g0, g1;
  uint32_t fe[64];
  {
    float d0[32], d1[32], e[64];
    mbar_wait(barY + 8 * wg, 0);
    wg_fence();
#pragma unroll
    for (int k = 0; k < 8; k++)
      wgmma_rs_64<1, 1, 1>(d0, gs[4 * k], gs[4 * k + 1], gs[4 * k + 2], gs[4 * k + 3], mk_desc(R0 + wg * 16384, k * 2048, 0, 1024, 1), k);
    wg_commit();
    wg_wait<0>();
    reg_fence(d0);
#pragma unroll
    for (int i = 0; i < 32; i++) d0[i] = gelu(d0[i]);
    store_tile_64(d0, R2 + wg * 16384, warp, lane);
    mbar_wait(barY + 8 * (2 + wg), 0);
    wg_fence();
#pragma unroll
    for (int k = 0; k < 8; k++)
      wgmma_rs_64<1, 1, 1>(d1, gs[4 * k], gs[4 * k + 1], gs[4 * k + 2], gs[4 * k + 3], mk_desc(R0 + wg * 16384, 32768 + k * 2048, 0, 1024, 1), k);
    wg_commit();
    fence_async();
    mbar_wait(barF, 0);
    mbar_wait(barF + 16, 0);
    __syncthreads();
    wg_fence();
#pragma unroll
    for (int i = 0; i < 8; i++) {
      const int kc = (i >> 2) * 2, s = i & 3;
      wgmma_ss_128<1, 1, 0, 1>(e, mk_desc(R2, kc * 8192 + s * 32, 0, 1024, 1),
                               mk_desc(R1 + wg * 16384, kc * 32768 + s * 2048, 8192, 1024, 1), i);
    }
    wg_commit();
    if (tid == 128) {
      mbar_expect(barO, 32768);
      tma_ld3<0>(R0, &mwo, barO, 0, 0, 0);
    }
    wg_wait<1>();
    reg_fence(d1);
#pragma unroll
    for (int i = 0; i < 32; i++) d1[i] = gelu(d1[i]);
    store_tile_64(d1, R2 + wg * 16384 + 8192, warp, lane);
    fence_async();
    mbar_wait(barF + 8, 0);
    mbar_wait(barF + 24, 0);
    __syncthreads();
    if (tid == 128) {
      mbar_expect(barO + 8, 32768);
      tma_ld3<0>(R0 + 32768, &mwo, barO + 8, 0, 64, 0);
    }
    if (wg == 1) bar_sync(4, 256);
    wg_fence();
#pragma unroll
    for (int i = 0; i < 8; i++) {
      const int kc = (i >> 2) * 2 + 1, s = i & 3;
      wgmma_ss_128<1, 1, 0, 1>(e, mk_desc(R2, kc * 8192 + s * 32, 0, 1024, 1),
                               mk_desc(R1 + wg * 16384, kc * 32768 + s * 2048, 8192, 1024, 1), 1);
    }
    wg_commit();
    if (wg == 0) bar_arrive(4, 256);
    wg_wait<1>();
    if (lane == 0) mbar_arrive(barA);
    if (tid == 128) {
      mbar_wait(barA, 0);
      for (int kc = 2; kc < 4; kc++) {
        mbar_expect(barO + 8 * kc, 32768);
        tma_ld3<0>(R1 + (kc - 2) * 65536, &mwo, barO + 8 * kc, 0, kc * 64, 0);
      }
    }
    mbar_wait(barA, 0);
    asm volatile("st.shared.v4.u32 [%0], {%1, %2, %3, %4};" ::"r"(R2 + wg * 4096 + ((t * 16) ^ (wg * 512))), "r"(gev0.x), "r"(gev0.y), "r"(gev0.z), "r"(gev0.w) : "memory");
    asm volatile("st.shared.v4.u32 [%0], {%1, %2, %3, %4};" ::"r"(R2 + wg * 4096 + 2048 + ((t * 16) ^ (wg * 512))), "r"(gev1.x), "r"(gev1.y), "r"(gev1.z), "r"(gev1.w) : "memory");
    bar_sync(1 + wg, 128);
    g0 = lds128(gp);
    g1 = lds128(gp + 64);
    wg_wait<0>();
    reg_fence(e);
#pragma unroll
    for (int i = 0; i < 32; i++) fe[i] = pack2(e[2 * i], e[2 * i + 1]);
  }
  auto publish = [&]() {
    bar_sync(1 + wg, 128);
    const int row = warp * 16 + (lane & 7) + ((lane >> 3) & 1) * 8;
    const uint32_t xb = R1 + (wg == 0 ? 3 * 32768 : 32768 + 16384) + row * 128;
#pragma unroll
    for (int s = 0; s < 8; s++) {
      const int jj = 2 * s + (lane >> 4);
      stsm4(xb + (s >> 2) * 8192 + (((jj & 7) ^ (lane & 7)) << 4), fe[4 * s], fe[4 * s + 1], fe[4 * s + 2], fe[4 * s + 3]);
    }
    bar_arrive(5 + wg, 256);
  };
  if (wg == 1) publish();
  const uint32_t stg = R1 + 32768 + wg * 65536;
  const uint32_t w0 = sb + wg * 65536, w1 = sb + 32768 + wg * 98304, w2 = sb + 65536 - wg * 65536, w3 = sb + 131072 - wg * 98304;
  float acc[128];
  uint32_t j0[8], j1[8], j2[8], j3[8];
  joint_group(j0, fe, g0, g1, gp + 128);
  mbar_wait(barO + 16 * wg, 0);
  joint_group(j1, fe + 8, g0, g1, gp + 256);
#define E_MMA4(J, K, W, FIRSTK, G, NEXTBAR)                                                     \
  wg_fence();                                                                                   \
  wgmma_rs_256<1, 1, 1>(acc, J[0], J[1], J[2], J[3], mk_desc(W, 0, 8192, 1024, 1), FIRSTK);     \
  wgmma_rs_256<1, 1, 1>(acc, J[4], J[5], J[6], J[7], mk_desc(W, 2048, 8192, 1024, 1), 1);       \
  wgmma_rs_256<1, 1, 1>(acc, K[0], K[1], K[2], K[3], mk_desc(W, 4096, 8192, 1024, 1), 1);       \
  wgmma_rs_256<1, 1, 1>(acc, K[4], K[5], K[6], K[7], mk_desc(W, 6144, 8192, 1024, 1), 1);       \
  wg_commit();                                                                                  \
  if ((ui + wg == 0 ? E_EARLY0 : E_EARLY) == (G) && (ui < 3 || wg == 0)) bar_arrive(4 - wg, 256); \
  wg_wait<1>();                                                                                 \
  if (ui == 0) mbar_wait(NEXTBAR, 0);
  const uint32_t bo0 = barO + 16 * wg, bo2 = barO + 16 * (1 - wg);
#pragma unroll 1
  for (int ui = 0; ui < 4; ui++) {
    if (ui > 0 || wg == 1) bar_sync(3 + wg, 256);
    E_MMA4(j0, j1, w0, 0, 0, bo0)
    joint_group(j2, fe + 16, g0, g1, gp + 384);
    if (ui == 0) mbar_wait(bo0 + 8, 0);
    joint_group(j3, fe + 24, g0, g1, gp + 512);
    E_MMA4(j2, j3, w1, 1, 1, bo0 + 8)
    if (ui == 0) {
      if (wg == 0) publish();
      bar_sync(6 - wg, 256);
      const int row = warp * 16 + (lane & 7) + ((lane >> 3) & 1) * 8;
      const uint32_t xb = R1 + (wg == 1 ? 3 * 32768 : 32768 + 16384) + row * 128;
#pragma unroll
      for (int s = 0; s < 8; s++) {
        const int jj = 2 * s + (lane >> 4);
        ldsm4(xb + (s >> 2) * 8192 + (((jj & 7) ^ (lane & 7)) << 4), fe[32 + 4 * s], fe[33 + 4 * s], fe[34 + 4 * s], fe[35 + 4 * s]);
      }
    }
    joint_group(j0, fe + 32, g0, g1, gp + 640);
    if (ui == 0) mbar_wait(bo2, 0);
    joint_group(j1, fe + 40, g0, g1, gp + 768);
    E_MMA4(j0, j1, w2, 1, 2, bo2)
    joint_group(j2, fe + 48, g0, g1, gp + 896);
    if (ui == 0) mbar_wait(bo2 + 8, 0);
    joint_group(j3, fe + 56, g0, g1, gp + 1024);
    E_MMA4(j2, j3, w3, 1, 3, bo2 + 8)
    gp += 1024;
    if (ui < 3) {
      joint_group(j0, fe, g0, g1, gp + 128);
      if (ui == 0) mbar_wait(bo2 + 8, 0);
      joint_group(j1, fe + 8, g0, g1, gp + 256);
    }
    if (t == 0) bulk_wait_read<0>();
    wg_wait<0>();
    reg_fence(acc);
    bar_sync(1 + wg, 128);
    const uint32_t rb = stg + (warp * 16 + (lane & 7) + ((lane >> 3) & 1) * 8) * 128;
#pragma unroll
    for (int h = 0; h < 2; h++) {
#pragma unroll
      for (int j = 16 * h; j < 16 * h + 16; j += 2) {
        const int jj = j + (lane >> 4);
        stsm4(rb + (j >> 3) * 8192 + (((jj & 7) ^ (lane & 7)) << 4), pack2(acc[4 * j], acc[4 * j + 1]), pack2(acc[4 * j + 2], acc[4 * j + 3]),
              pack2(acc[4 * j + 4], acc[4 * j + 5]), pack2(acc[4 * j + 6], acc[4 * j + 7]));
      }
      const bool split = E_CHUNK == 2 || (E_CHUNK == 1 && ui == 3);
      if (h == 1 || split) {
        fence_async();
        bar_sync(1 + wg, 128);
        if (t == 0) {
          if (h == 1 && !split) tma_st5<1>(&mout, stg, 0, t0, 0, wg * 4 + ui, b);
          tma_st5<1>(&mout, stg + h * 16384, 0, t0, 2 * h, wg * 4 + ui, b);
          bulk_commit();
        }
      }
    }
  }
  if (t == 0) bulk_wait_read<0>();
}

typedef CUresult (*EncodeFn)(CUtensorMap*, CUtensorMapDataType, cuuint32_t, void*, const cuuint64_t*, const cuuint64_t*,
                             const cuuint32_t*, const cuuint32_t*, CUtensorMapInterleave, CUtensorMapSwizzle,
                             CUtensorMapL2promotion, CUtensorMapFloatOOBfill);

CUtensorMap make_map(EncodeFn fn, const void* base, int rank, const uint64_t* dims, const uint64_t* strides, const uint32_t* box,
                     CUtensorMapSwizzle swz) {
  CUtensorMap m;
  cuuint64_t gd[5], gs[4];
  cuuint32_t bx[5], es[5];
  for (int i = 0; i < rank; i++) { gd[i] = dims[i]; bx[i] = box[i]; es[i] = 1; }
  for (int i = 0; i + 1 < rank; i++) gs[i] = strides[i];
  fn(&m, CU_TENSOR_MAP_DATA_TYPE_BFLOAT16, rank, const_cast<void*>(base), gd, gs, bx, es, CU_TENSOR_MAP_INTERLEAVE_NONE, swz,
     CU_TENSOR_MAP_L2_PROMOTION_NONE, CU_TENSOR_MAP_FLOAT_OOB_FILL_NONE);
  return m;
}

template <typename... KArgs, typename... Args>
void launch(void (*k)(KArgs...), int grid, int block, int smem, bool pdl, Args... args) {
  cudaLaunchConfig_t c = {};
  c.gridDim = dim3(grid);
  c.blockDim = dim3(block);
  c.dynamicSmemBytes = smem;
  c.stream = cudaStreamPerThread;
  cudaLaunchAttribute at[1];
  at[0].id = cudaLaunchAttributeProgrammaticStreamSerialization;
  at[0].val.programmaticStreamSerializationAllowed = 1;
  c.attrs = at;
  c.numAttrs = pdl ? 1 : 0;
  cudaLaunchKernelEx(&c, k, args...);
}

}

extern "C" void kernel_launch(void* const* d_in, const int* in_sizes, int n_in, void* d_out, int out_size) {
  const __nv_bfloat16* x = (const __nv_bfloat16*)d_in[0];
  const __nv_bfloat16* w1 = (const __nv_bfloat16*)d_in[1];
  const __nv_bfloat16* w2 = (const __nv_bfloat16*)d_in[2];
  const __nv_bfloat16* g = (const __nv_bfloat16*)d_in[3];
  const __nv_bfloat16* wf = (const __nv_bfloat16*)d_in[4];
  const __nv_bfloat16* wgt = (const __nv_bfloat16*)d_in[5];
  const __nv_bfloat16* wo = (const __nv_bfloat16*)d_in[6];

  void* fp = nullptr;
  cudaDriverEntryPointQueryResult qr;
  cudaGetDriverEntryPoint("cuTensorMapEncodeTiled", &fp, cudaEnableDefault, &qr);
  EncodeFn fn = (EncodeFn)fp;
  void *W, *Y2;
  cudaGetSymbolAddress(&W, g_W);
  cudaGetSymbolAddress(&Y2, g_Y2);
  cudaFuncSetAttribute(kG, cudaFuncAttributeMaxDynamicSharedMemorySize, G_SMEM);
  cudaFuncSetAttribute(kC, cudaFuncAttributeMaxDynamicSharedMemorySize, C_SMEM);
  cudaFuncSetAttribute(kH, cudaFuncAttributeMaxDynamicSharedMemorySize, H_SMEM);
  cudaFuncSetAttribute(kE, cudaFuncAttributeMaxDynamicSharedMemorySize, E_SMEM);
  auto page_up = [](void* p) { return (void*)(((uintptr_t)p + (1 << 21) - 1) & ~(uintptr_t)((1 << 21) - 1)); };
  void *X1 = page_up(d_out), *X2 = X1;
  W = page_up(W);
  const CUtensorMapSwizzle S128 = CU_TENSOR_MAP_SWIZZLE_128B, S64 = CU_TENSOR_MAP_SWIZZLE_64B;

  auto map_x = [&]() {
    uint64_t d[] = {64, 8000, 8, 2}, s[] = {1024, 128, 8000ull * 1024};
    uint32_t bx[] = {64, 112, 1, 1};
    return make_map(fn, x, 4, d, s, bx, S128);
  };
  auto map_w_in = [&](const __nv_bfloat16* w, int odd) {
    uint64_t d[] = {64, (uint64_t)(odd ? 15 : 16), 4, 256}, s[] = {2ull * 65536 * 2, 128, 512};
    uint32_t bx[] = {64, 16, 2, 1};
    return make_map(fn, w + (odd ? 65536 : 0), 4, d, s, bx, S128);
  };
  auto map_w_in2 = [&](const __nv_bfloat16* w, int odd) {
    uint64_t d[] = {64, (uint64_t)(odd ? 15 : 16), 4, 64, 4}, s[] = {2ull * 65536 * 2, 128, 512, 32768};
    uint32_t bx[] = {64, 16, 2, 1, 2};
    return make_map(fn, w + (odd ? 65536 : 0), 5, d, s, bx, S128);
  };
  auto map_X_st = [&](void* p, int nb, int boxb) {
    uint64_t d[] = {64, 512, (uint64_t)(2 * nb)}, s[] = {2ull * nb * 128, 128};
    uint32_t bx[] = {64, 64, (uint32_t)boxb};
    return make_map(fn, p, 3, d, s, bx, S128);
  };
  auto map_X1_st = [&](uint32_t rows) {
    uint64_t d[] = {8192, 16, 4, 24}, s[] = {16384, 262144, 1048576};
    uint32_t bx[] = {64, 4, 2, rows / 8};
    return make_map(fn, X1, 4, d, s, bx, S128);
  };
  auto map_Y1_ld = [&](uint64_t step) {
    uint64_t d[] = {64, 12 << 14, 2}, s[] = {128, step};
    uint32_t bx[] = {64, 32, 2};
    return make_map(fn, X1, 3, d, s, bx, S128);
  };
  auto map_W_st = [&]() {
    uint64_t d[] = {8192, 8, 4, 2 * (8 + W_SHIFT), 2}, s[] = {32768, 262144, 1048576, 16384};
    uint32_t bx[] = {64, 2, 2, 2, 2};
    return make_map(fn, W, 5, d, s, bx, S128);
  };
  auto map_X_ld = [&](void* p, int nb, int boxb) {
    uint64_t d[] = {64, (uint64_t)(2 * nb), 512}, s[] = {128, 2ull * nb * 128};
    uint32_t bx[] = {32, (uint32_t)boxb, 1};
    return make_map(fn, p, 3, d, s, bx, S64);
  };
  auto map_W_ld = [&](uint32_t n) {
    uint64_t d[] = {64, 512 / n, (8ull + W_SHIFT) * 32 * n}, s[] = {128, 65536 / n};
    uint32_t bx[] = {64, 32, n};
    return make_map(fn, W, 3, d, s, bx, S128);
  };
  auto map_Y_st = [&](void* p, int nb, int rows) {
    uint64_t d[] = {64, (uint64_t)(2 * nb), 64, 4}, s[] = {32768, 128, 8192};
    uint32_t bx[] = {64, (uint32_t)rows, 1, 1};
    return make_map(fn, p, 4, d, s, bx, S128);
  };
  auto map_Y_ld = [&](void* p, int nb, int boxc, int boxb) {
    uint64_t d[] = {64, 64, 4, (uint64_t)nb, 2}, s[] = {128, 8192, 32768, (uint64_t)nb * 32768};
    uint32_t bx[] = {64, 64, (uint32_t)boxc, (uint32_t)boxb, 1};
    return make_map(fn, p, 5, d, s, bx, S128);
  };
  auto map_wsq = [&](const __nv_bfloat16* w) {
    uint64_t d[] = {64, 256, 4}, s[] = {512, 128};
    uint32_t bx[] = {64, 64, 4};
    return make_map(fn, w, 3, d, s, bx, S128);
  };
  auto map_out = [&]() {
    uint64_t d[] = {64, 4000, 4, 8, 2}, s[] = {4096, 128, 512, 4000ull * 4096};
    uint32_t bx[] = {64, 64, 2, 1, 1};
    return make_map(fn, d_out, 5, d, s, bx, S128);
  };

  GMaps g1;
  g1.w = map_W_ld(4);
  g1.y = map_X1_st(8);
  g1.w2e = map_w_in(w2, 0);
  g1.w2o = map_w_in(w2, 1);
  g1.x = map_x();
  g1.w1e = map_w_in2(w1, 0);
  g1.w1o = map_w_in2(w1, 1);
  g1.xs = map_X1_st(16);
  g1.ws = map_W_st();
  launch(kG, 132, 384, G_SMEM, false, g1, (char*)X1, (char*)W, g, wgt);
  launch(kC, 128, 512, C_SMEM, true, map_Y1_ld(0x3000), map_Y1_ld(0x1000), map_X_st(X2, NB2, 1));
  launch(kH, 128, 288, H_SMEM, true, map_X_ld(X2, NB2, 168), map_W_ld(2), map_Y_st(Y2, NB2, 168 / H_EPI), wf, wo);
  launch(kE, 126, 256, E_SMEM, true, map_Y_ld(Y2, NB2, 1, 2), map_wsq(wf), map_wsq(wo), map_out());
}
```

```cpp
#include <cuda_runtime.h>
#include <cuda_bf16.h>
#include <cuda.h>
#include <stdint.h>
#include <type_traits>

#define W_SHIFT 1
namespace {

constexpr int NB1 = 168;
constexpr int NB2 = 84;

__device__ __align__(1024) __nv_bfloat16 g_W[(9 + W_SHIFT) * 64 * 4 * 64 * 64];
__device__ __align__(1024) __nv_bfloat16 g_Y2[2 * NB2 * 4 * 64 * 64];
__device__ __align__(1024) float g_ge[16 * 256];

__device__ __forceinline__ uint32_t s2u(const void* p) { return (uint32_t)__cvta_generic_to_shared(p); }
__device__ __forceinline__ uint32_t pin(uint32_t v) {
  return __shfl_sync(0xffffffffu, v, 0);
}
__device__ __forceinline__ void mbar_init(uint32_t b, int c) {
  asm volatile("mbarrier.init.shared::cta.b64 [%0], %1;" ::"r"(b), "r"(c) : "memory");
}
__device__ __forceinline__ void mbar_expect(uint32_t b, int bytes) {
  asm volatile("mbarrier.arrive.expect_tx.shared::cta.b64 _, [%0], %1;" ::"r"(b), "r"(bytes) : "memory");
}
__device__ __forceinline__ void mbar_arrive(uint32_t b) {
  asm volatile("mbarrier.arrive.shared::cta.b64 _, [%0];" ::"r"(b) : "memory");
}
__device__ __forceinline__ void mbar_arrive_cta(uint32_t b, uint32_t cta) {
  asm volatile("{\n.reg .b32 r;\nmapa.shared::cluster.u32 r, %0, %1;\nmbarrier.arrive.shared::cluster.b64 _, [r];\n}" ::"r"(b), "r"(cta) : "memory");
}
__device__ __forceinline__ void mbar_wait(uint32_t b, int ph) {
  asm volatile(
      "{\n.reg .pred p;\n.reg .u32 n;\n"
      "mov.u32 n, 0;\n"
      "MBW_LOOP:\n"
      "mbarrier.try_wait.parity.shared::cta.b64 p, [%0], %1;\n"
      "@p bra MBW_DONE;\n"
      "add.u32 n, n, 1;\n"
      "setp.lt.u32 p, n, 1048576;\n"
      "@p bra MBW_LOOP;\n"
      "MBW_DONE:\n}" ::"r"(b), "r"(ph) : "memory");
}
__device__ __forceinline__ bool mbar_test(uint32_t b, int ph) {
  uint32_t ok;
  asm volatile("{\n.reg .pred p;\nmbarrier.test_wait.parity.shared::cta.b64 p, [%1], %2;\nselp.u32 %0, 1, 0, p;\n}" : "=r"(ok) : "r"(b), "r"(ph) : "memory");
  return __all_sync(0xffffffffu, ok);
}
__device__ __forceinline__ void fence_bar_init() { asm volatile("fence.mbarrier_init.release.cluster;" ::: "memory"); }
__device__ __forceinline__ void fence_async() { asm volatile("fence.proxy.async.shared::cta;" ::: "memory"); }
__device__ __forceinline__ void bar_sync(int id, int n) { asm volatile("bar.sync %0, %1;" ::"r"(id), "r"(n) : "memory"); }
__device__ __forceinline__ void bar_arrive(int id, int n) { asm volatile("bar.arrive %0, %1;" ::"r"(id), "r"(n) : "memory"); }
__device__ __forceinline__ void pdl_wait() { asm volatile("griddepcontrol.wait;" ::: "memory"); }
__device__ __forceinline__ void pdl_launch() { asm volatile("griddepcontrol.launch_dependents;" ::: "memory"); }
__device__ __forceinline__ void prefetch_map(const CUtensorMap* m) {
  asm volatile("prefetch.tensormap [%0];" ::"l"(m) : "memory");
}
template <int P> __device__ __forceinline__ uint64_t policy() {
  uint64_t p;
  asm("createpolicy.fractional.L2::evict_first.b64 %0, 1.0;" : "=l"(p));
  return p;
}
template <int P> __device__ __forceinline__ void tma_ld3(uint32_t dst, const CUtensorMap* m, uint32_t bar, int c0, int c1, int c2) {
  if constexpr (P == 0)
    asm volatile("cp.async.bulk.tensor.3d.shared::cluster.global.mbarrier::complete_tx::bytes [%0], [%1, {%3, %4, %5}], [%2];"
                 ::"r"(dst), "l"(m), "r"(bar), "r"(c0), "r"(c1), "r"(c2) : "memory");
  else
    asm volatile("cp.async.bulk.tensor.3d.shared::cluster.global.mbarrier::complete_tx::bytes.L2::cache_hint [%0], [%1, {%3, %4, %5}], [%2], %6;"
                 ::"r"(dst), "l"(m), "r"(bar), "r"(c0), "r"(c1), "r"(c2), "l"(policy<P>()) : "memory");
}
template <int P> __device__ __forceinline__ void tma_ld3mc(uint32_t dst, const CUtensorMap* m, uint32_t bar, int c0, int c1, int c2) {
  if constexpr (P == 0)
    asm volatile("cp.async.bulk.tensor.3d.shared::cluster.global.mbarrier::complete_tx::bytes.multicast::cluster [%0], [%1, {%3, %4, %5}], [%2], %6;"
                 ::"r"(dst), "l"(m), "r"(bar), "r"(c0), "r"(c1), "r"(c2), "h"((uint16_t)3) : "memory");
  else
    asm volatile("cp.async.bulk.tensor.3d.shared::cluster.global.mbarrier::complete_tx::bytes.multicast::cluster.L2::cache_hint [%0], [%1, {%3, %4, %5}], [%2], %6, %7;"
                 ::"r"(dst), "l"(m), "r"(bar), "r"(c0), "r"(c1), "r"(c2), "h"((uint16_t)3), "l"(policy<P>()) : "memory");
}
template <int P> __device__ __forceinline__ void tma_ld4(uint32_t dst, const CUtensorMap* m, uint32_t bar, int c0, int c1, int c2, int c3) {
  if constexpr (P == 0)
    asm volatile("cp.async.bulk.tensor.4d.shared::cluster.global.mbarrier::complete_tx::bytes [%0], [%1, {%3, %4, %5, %6}], [%2];"
                 ::"r"(dst), "l"(m), "r"(bar), "r"(c0), "r"(c1), "r"(c2), "r"(c3) : "memory");
  else
    asm volatile("cp.async.bulk.tensor.4d.shared::cluster.global.mbarrier::complete_tx::bytes.L2::cache_hint [%0], [%1, {%3, %4, %5, %6}], [%2], %7;"
                 ::"r"(dst), "l"(m), "r"(bar), "r"(c0), "r"(c1), "r"(c2), "r"(c3), "l"(policy<P>()) : "memory");
}
template <int P> __device__ __forceinline__ void tma_ld4mc(uint32_t dst, const CUtensorMap* m, uint32_t bar, int c0, int c1, int c2, int c3) {
  if constexpr (P == 0)
    asm volatile("cp.async.bulk.tensor.4d.shared::cluster.global.mbarrier::complete_tx::bytes.multicast::cluster [%0], [%1, {%3, %4, %5, %6}], [%2], %7;"
                 ::"r"(dst), "l"(m), "r"(bar), "r"(c0), "r"(c1), "r"(c2), "r"(c3), "h"((uint16_t)3) : "memory");
  else
    asm volatile("cp.async.bulk.tensor.4d.shared::cluster.global.mbarrier::complete_tx::bytes.multicast::cluster.L2::cache_hint [%0], [%1, {%3, %4, %5, %6}], [%2], %7, %8;"
                 ::"r"(dst), "l"(m), "r"(bar), "r"(c0), "r"(c1), "r"(c2), "r"(c3), "h"((uint16_t)3), "l"(policy<P>()) : "memory");
}
template <int P> __device__ __forceinline__ void tma_ld5(uint32_t dst, const CUtensorMap* m, uint32_t bar, int c0, int c1, int c2, int c3, int c4) {
  if constexpr (P == 0)
    asm volatile("cp.async.bulk.tensor.5d.shared::cluster.global.mbarrier::complete_tx::bytes [%0], [%1, {%3, %4, %5, %6, %7}], [%2];"
                 ::"r"(dst), "l"(m), "r"(bar), "r"(c0), "r"(c1), "r"(c2), "r"(c3), "r"(c4) : "memory");
  else
    asm volatile("cp.async.bulk.tensor.5d.shared::cluster.global.mbarrier::complete_tx::bytes.L2::cache_hint [%0], [%1, {%3, %4, %5, %6, %7}], [%2], %8;"
                 ::"r"(dst), "l"(m), "r"(bar), "r"(c0), "r"(c1), "r"(c2), "r"(c3), "r"(c4), "l"(policy<P>()) : "memory");
}
template <int P> __device__ __forceinline__ void tma_st3(const CUtensorMap* m, uint32_t src, int c0, int c1, int c2) {
  if constexpr (P == 0)
    asm volatile("cp.async.bulk.tensor.3d.global.shared::cta.bulk_group [%0, {%2, %3, %4}], [%1];" ::"l"(m), "r"(src), "r"(c0), "r"(c1), "r"(c2) : "memory");
  else
    asm volatile("cp.async.bulk.tensor.3d.global.shared::cta.bulk_group.L2::cache_hint [%0, {%2, %3, %4}], [%1], %5;" ::"l"(m), "r"(src), "r"(c0), "r"(c1), "r"(c2), "l"(policy<P>()) : "memory");
}
template <int P> __device__ __forceinline__ void tma_st4(const CUtensorMap* m, uint32_t src, int c0, int c1, int c2, int c3) {
  if constexpr (P == 0)
    asm volatile("cp.async.bulk.tensor.4d.global.shared::cta.bulk_group [%0, {%2, %3, %4, %5}], [%1];" ::"l"(m), "r"(src), "r"(c0), "r"(c1), "r"(c2), "r"(c3) : "memory");
  else
    asm volatile("cp.async.bulk.tensor.4d.global.shared::cta.bulk_group.L2::cache_hint [%0, {%2, %3, %4, %5}], [%1], %6;" ::"l"(m), "r"(src), "r"(c0), "r"(c1), "r"(c2), "r"(c3), "l"(policy<P>()) : "memory");
}
template <int P> __device__ __forceinline__ void tma_st5(const CUtensorMap* m, uint32_t src, int c0, int c1, int c2, int c3, int c4) {
  if constexpr (P == 0)
    asm volatile("cp.async.bulk.tensor.5d.global.shared::cta.bulk_group [%0, {%2, %3, %4, %5, %6}], [%1];" ::"l"(m), "r"(src), "r"(c0), "r"(c1), "r"(c2), "r"(c3), "r"(c4) : "memory");
  else
    asm volatile("cp.async.bulk.tensor.5d.global.shared::cta.bulk_group.L2::cache_hint [%0, {%2, %3, %4, %5, %6}], [%1], %7;" ::"l"(m), "r"(src), "r"(c0), "r"(c1), "r"(c2), "r"(c3), "r"(c4), "l"(policy<P>()) : "memory");
}
__device__ __forceinline__ void bulk_commit() { asm volatile("cp.async.bulk.commit_group;" ::: "memory"); }
template <int N> __device__ __forceinline__ void bulk_wait() { asm volatile("cp.async.bulk.wait_group %0;" ::"n"(N) : "memory"); }
template <int N> __device__ __forceinline__ void bulk_wait_read() { asm volatile("cp.async.bulk.wait_group.read %0;" ::"n"(N) : "memory"); }
__device__ __forceinline__ void wg_fence() { asm volatile("wgmma.fence.sync.aligned;" ::: "memory"); }
__device__ __forceinline__ void wg_commit() { asm volatile("wgmma.commit_group.sync.aligned;" ::: "memory"); }
template <int N> __device__ __forceinline__ void wg_wait() { asm volatile("wgmma.wait_group.sync.aligned %0;" ::"n"(N) : "memory"); }
template <int R> __device__ __forceinline__ void reg_fence(float (&d)[R]) {
#pragma unroll
  for (int i = 0; i < R; i++) asm volatile("" : "+f"(d[i])::"memory");
}
template <int R> __device__ __forceinline__ void reg_fence(uint32_t (&d)[R]) {
#pragma unroll
  for (int i = 0; i < R; i++) asm volatile("" : "+r"(d[i])::"memory");
}
__device__ __forceinline__ void stsm4(uint32_t a, uint32_t r0, uint32_t r1, uint32_t r2, uint32_t r3) {
  asm volatile("stmatrix.sync.aligned.m8n8.x4.shared.b16 [%0], {%1, %2, %3, %4};" ::"r"(a), "r"(r0), "r"(r1), "r"(r2), "r"(r3) : "memory");
}
__device__ __forceinline__ void stsm4t(uint32_t a, uint32_t r0, uint32_t r1, uint32_t r2, uint32_t r3) {
  asm volatile("stmatrix.sync.aligned.m8n8.x4.trans.shared.b16 [%0], {%1, %2, %3, %4};" ::"r"(a), "r"(r0), "r"(r1), "r"(r2), "r"(r3) : "memory");
}
__device__ __forceinline__ void ldsm4(uint32_t a, uint32_t& r0, uint32_t& r1, uint32_t& r2, uint32_t& r3) {
  asm volatile("ldmatrix.sync.aligned.m8n8.x4.shared.b16 {%0, %1, %2, %3}, [%4];" : "=r"(r0), "=r"(r1), "=r"(r2), "=r"(r3) : "r"(a) : "memory");
}
__device__ __forceinline__ void ldg128(const uint4* p, uint32_t& a, uint32_t& b, uint32_t& c, uint32_t& d) {
  asm volatile("ld.global.nc.v4.u32 {%0, %1, %2, %3}, [%4];" : "=r"(a), "=r"(b), "=r"(c), "=r"(d) : "l"(p));
}
__device__ __forceinline__ uint32_t pack2(float lo, float hi) {
  uint32_t r;
  asm("cvt.rn.bf16x2.f32 %0, %1, %2;" : "=r"(r) : "f"(hi), "f"(lo));
  return r;
}
__device__ __forceinline__ float tanh_f32(float x) {
  float y;
  asm("tanh.approx.f32 %0, %1;" : "=f"(y) : "f"(x));
  return y;
}
__device__ __forceinline__ float gelu(float hx) {
  const float u = hx * fmaf(hx * hx, 8.0f * 0.044715f * 0.7978845608028654f, 2.0f * 0.7978845608028654f);
  return fmaf(hx, tanh_f32(u), hx);
}
__device__ __forceinline__ uint64_t mk_desc4(uint32_t addr4, uint32_t lbo, uint32_t sbo, uint32_t swz) {
  const uint32_t lo = addr4 + ((lbo >> 4) << 16), hi = (sbo >> 4) | (swz << 30);
  uint64_t d;
  asm("mov.b64 %0, {%1, %2};" : "=l"(d) : "r"(lo), "r"(hi));
  return d;
}
#define mk_desc(base, off, lbo, sbo, swz) mk_desc4((((base) & 0x3FFFF) >> 4) + ((off) >> 4), lbo, sbo, swz)

template <int SA, int SB, int TA, int TB>
__device__ __forceinline__ void wgmma_ss_32(float (&d)[16], uint64_t da, uint64_t db, int sd) {
  asm volatile("{\n.reg .pred p;\nsetp.ne.b32 p, %18, 0;\n"
      "wgmma.mma_async.sync.aligned.m64n32k16.f32.bf16.bf16 {"
      "%0, %1, %2, %3, %4, %5, %6, %7, %8, %9, %10, %11, %12, %13, %14, %15"
      "}, %16, %17, p, %19, %20, %21, %22;\n}\n"
      : "+f"(d[0]), "+f"(d[1]), "+f"(d[2]), "+f"(d[3]), "+f"(d[4]), "+f"(d[5]), "+f"(d[6]), "+f"(d[7]), "+f"(d[8]),
        "+f"(d[9]), "+f"(d[10]), "+f"(d[11]), "+f"(d[12]), "+f"(d[13]), "+f"(d[14]), "+f"(d[15])
      : "l"(da), "l"(db), "r"(sd), "n"(SA), "n"(SB), "n"(TA), "n"(TB));
}
template <int SA, int SB, int TA, int TB>
__device__ __forceinline__ void wgmma_ss_48(float (&d)[24], uint64_t da, uint64_t db, int sd) {
  asm volatile("{\n.reg .pred p;\nsetp.ne.b32 p, %26, 0;\n"
      "wgmma.mma_async.sync.aligned.m64n48k16.f32.bf16.bf16 {"
      "%0, %1, %2, %3, %4, %5, %6, %7, %8, %9, %10, %11, %12, %13, %14, %15, %16, %17, %18, %19, %20, %21, %22, %23"
      "}, %24, %25, p, %27, %28, %29, %30;\n}\n"
      : "+f"(d[0]), "+f"(d[1]), "+f"(d[2]), "+f"(d[3]), "+f"(d[4]), "+f"(d[5]), "+f"(d[6]), "+f"(d[7]), "+f"(d[8]),
        "+f"(d[9]), "+f"(d[10]), "+f"(d[11]), "+f"(d[12]), "+f"(d[13]), "+f"(d[14]), "+f"(d[15]), "+f"(d[16]),
        "+f"(d[17]), "+f"(d[18]), "+f"(d[19]), "+f"(d[20]), "+f"(d[21]), "+f"(d[22]), "+f"(d[23])
      : "l"(da), "l"(db), "r"(sd), "n"(SA), "n"(SB), "n"(TA), "n"(TB));
}
template <int SA, int SB, int TA, int TB>
__device__ __forceinline__ void wgmma_ss_128(float (&d)[64], uint64_t da, uint64_t db, int sd) {
  asm volatile("{\n.reg .pred p;\nsetp.ne.b32 p, %66, 0;\n"
      "wgmma.mma_async.sync.aligned.m64n128k16.f32.bf16.bf16 {"
      "%0, %1, %2, %3, %4, %5, %6, %7, %8, %9, %10, %11, %12, %13, %14, %15, %16, %17, %18, %19, %20, %21, %22, %23, "
      "%24, %25, %26, %27, %28, %29, %30, %31, %32, %33, %34, %35, %36, %37, %38, %39, %40, %41, %42, %43, %44, %45, "
      "%46, %47, %48, %49, %50, %51, %52, %53, %54, %55, %56, %57, %58, %59, %60, %61, %62, %63"
      "}, %64, %65, p, %67, %68, %69, %70;\n}\n"
      : "+f"(d[0]), "+f"(d[1]), "+f"(d[2]), "+f"(d[3]), "+f"(d[4]), "+f"(d[5]), "+f"(d[6]), "+f"(d[7]), "+f"(d[8]),
        "+f"(d[9]), "+f"(d[10]), "+f"(d[11]), "+f"(d[12]), "+f"(d[13]), "+f"(d[14]), "+f"(d[15]), "+f"(d[16]),
        "+f"(d[17]), "+f"(d[18]), "+f"(d[19]), "+f"(d[20]), "+f"(d[21]), "+f"(d[22]), "+f"(d[23]), "+f"(d[24]),
        "+f"(d[25]), "+f"(d[26]), "+f"(d[27]), "+f"(d[28]), "+f"(d[29]), "+f"(d[30]), "+f"(d[31]), "+f"(d[32]),
        "+f"(d[33]), "+f"(d[34]), "+f"(d[35]), "+f"(d[36]), "+f"(d[37]), "+f"(d[38]), "+f"(d[39]), "+f"(d[40]),
        "+f"(d[41]), "+f"(d[42]), "+f"(d[43]), "+f"(d[44]), "+f"(d[45]), "+f"(d[46]), "+f"(d[47]), "+f"(d[48]),
        "+f"(d[49]), "+f"(d[50]), "+f"(d[51]), "+f"(d[52]), "+f"(d[53]), "+f"(d[54]), "+f"(d[55]), "+f"(d[56]),
        "+f"(d[57]), "+f"(d[58]), "+f"(d[59]), "+f"(d[60]), "+f"(d[61]), "+f"(d[62]), "+f"(d[63])
      : "l"(da), "l"(db), "r"(sd), "n"(SA), "n"(SB), "n"(TA), "n"(TB));
}
template <int SA, int SB, int TA, int TB>
__device__ __forceinline__ void wgmma_ss_168(float (&d)[84], uint64_t da, uint64_t db, int sd) {
  asm volatile("{\n.reg .pred p;\nsetp.ne.b32 p, %86, 0;\n"
      "wgmma.mma_async.sync.aligned.m64n168k16.f32.bf16.bf16 {"
      "%0, %1, %2, %3, %4, %5, %6, %7, %8, %9, %10, %11, %12, %13, %14, %15, %16, %17, %18, %19, %20, %21, %22, %23, "
      "%24, %25, %26, %27, %28, %29, %30, %31, %32, %33, %34, %35, %36, %37, %38, %39, %40, %41, %42, %43, %44, %45, "
      "%46, %47, %48, %49, %50, %51, %52, %53, %54, %55, %56, %57, %58, %59, %60, %61, %62, %63, %64, %65, %66, %67, "
      "%68, %69, %70, %71, %72, %73, %74, %75, %76, %77, %78, %79, %80, %81, %82, %83"
      "}, %84, %85, p, %87, %88, %89, %90;\n}\n"
      : "+f"(d[0]), "+f"(d[1]), "+f"(d[2]), "+f"(d[3]), "+f"(d[4]), "+f"(d[5]), "+f"(d[6]), "+f"(d[7]), "+f"(d[8]),
        "+f"(d[9]), "+f"(d[10]), "+f"(d[11]), "+f"(d[12]), "+f"(d[13]), "+f"(d[14]), "+f"(d[15]), "+f"(d[16]),
        "+f"(d[17]), "+f"(d[18]), "+f"(d[19]), "+f"(d[20]), "+f"(d[21]), "+f"(d[22]), "+f"(d[23]), "+f"(d[24]),
        "+f"(d[25]), "+f"(d[26]), "+f"(d[27]), "+f"(d[28]), "+f"(d[29]), "+f"(d[30]), "+f"(d[31]), "+f"(d[32]),
        "+f"(d[33]), "+f"(d[34]), "+f"(d[35]), "+f"(d[36]), "+f"(d[37]), "+f"(d[38]), "+f"(d[39]), "+f"(d[40]),
        "+f"(d[41]), "+f"(d[42]), "+f"(d[43]), "+f"(d[44]), "+f"(d[45]), "+f"(d[46]), "+f"(d[47]), "+f"(d[48]),
        "+f"(d[49]), "+f"(d[50]), "+f"(d[51]), "+f"(d[52]), "+f"(d[53]), "+f"(d[54]), "+f"(d[55]), "+f"(d[56]),
        "+f"(d[57]), "+f"(d[58]), "+f"(d[59]), "+f"(d[60]), "+f"(d[61]), "+f"(d[62]), "+f"(d[63]), "+f"(d[64]),
        "+f"(d[65]), "+f"(d[66]), "+f"(d[67]), "+f"(d[68]), "+f"(d[69]), "+f"(d[70]), "+f"(d[71]), "+f"(d[72]),
        "+f"(d[73]), "+f"(d[74]), "+f"(d[75]), "+f"(d[76]), "+f"(d[77]), "+f"(d[78]), "+f"(d[79]), "+f"(d[80]),
        "+f"(d[81]), "+f"(d[82]), "+f"(d[83])
      : "l"(da), "l"(db), "r"(sd), "n"(SA), "n"(SB), "n"(TA), "n"(TB));
}
template <int SA, int SB, int TB>
__device__ __forceinline__ void wgmma_rs_64(float (&d)[32], uint32_t a0, uint32_t a1, uint32_t a2, uint32_t a3, uint64_t db, int sd) {
  asm volatile("{\n.reg .pred p;\nsetp.ne.b32 p, %37, 0;\n"
      "wgmma.mma_async.sync.aligned.m64n64k16.f32.bf16.bf16 {"
      "%0, %1, %2, %3, %4, %5, %6, %7, %8, %9, %10, %11, %12, %13, %14, %15, %16, %17, %18, %19, %20, %21, %22, %23, "
      "%24, %25, %26, %27, %28, %29, %30, %31"
      "}, {%32, %33, %34, %35}, %36, p, %38, %39, %40;\n}\n"
      : "+f"(d[0]), "+f"(d[1]), "+f"(d[2]), "+f"(d[3]), "+f"(d[4]), "+f"(d[5]), "+f"(d[6]), "+f"(d[7]), "+f"(d[8]),
        "+f"(d[9]), "+f"(d[10]), "+f"(d[11]), "+f"(d[12]), "+f"(d[13]), "+f"(d[14]), "+f"(d[15]), "+f"(d[16]),
        "+f"(d[17]), "+f"(d[18]), "+f"(d[19]), "+f"(d[20]), "+f"(d[21]), "+f"(d[22]), "+f"(d[23]), "+f"(d[24]),
        "+f"(d[25]), "+f"(d[26]), "+f"(d[27]), "+f"(d[28]), "+f"(d[29]), "+f"(d[30]), "+f"(d[31])
      : "r"(a0), "r"(a1), "r"(a2), "r"(a3), "l"(db), "r"(sd), "n"(SA), "n"(SB), "n"(TB));
}
template <int SA, int SB, int TB>
__device__ __forceinline__ void wgmma_rs_128(float (&d)[64], uint32_t a0, uint32_t a1, uint32_t a2, uint32_t a3, uint64_t db, int sd) {
  asm volatile("{\n.reg .pred p;\nsetp.ne.b32 p, %69, 0;\n"
      "wgmma.mma_async.sync.aligned.m64n128k16.f32.bf16.bf16 {"
      "%0, %1, %2, %3, %4, %5, %6, %7, %8, %9, %10, %11, %12, %13, %14, %15, %16, %17, %18, %19, %20, %21, %22, %23, "
      "%24, %25, %26, %27, %28, %29, %30, %31, %32, %33, %34, %35, %36, %37, %38, %39, %40, %41, %42, %43, %44, %45, "
      "%46, %47, %48, %49, %50, %51, %52, %53, %54, %55, %56, %57, %58, %59, %60, %61, %62, %63"
      "}, {%64, %65, %66, %67}, %68, p, %70, %71, %72;\n}\n"
      : "+f"(d[0]), "+f"(d[1]), "+f"(d[2]), "+f"(d[3]), "+f"(d[4]), "+f"(d[5]), "+f"(d[6]), "+f"(d[7]), "+f"(d[8]),
        "+f"(d[9]), "+f"(d[10]), "+f"(d[11]), "+f"(d[12]), "+f"(d[13]), "+f"(d[14]), "+f"(d[15]), "+f"(d[16]),
        "+f"(d[17]), "+f"(d[18]), "+f"(d[19]), "+f"(d[20]), "+f"(d[21]), "+f"(d[22]), "+f"(d[23]), "+f"(d[24]),
        "+f"(d[25]), "+f"(d[26]), "+f"(d[27]), "+f"(d[28]), "+f"(d[29]), "+f"(d[30]), "+f"(d[31]), "+f"(d[32]),
        "+f"(d[33]), "+f"(d[34]), "+f"(d[35]), "+f"(d[36]), "+f"(d[37]), "+f"(d[38]), "+f"(d[39]), "+f"(d[40]),
        "+f"(d[41]), "+f"(d[42]), "+f"(d[43]), "+f"(d[44]), "+f"(d[45]), "+f"(d[46]), "+f"(d[47]), "+f"(d[48]),
        "+f"(d[49]), "+f"(d[50]), "+f"(d[51]), "+f"(d[52]), "+f"(d[53]), "+f"(d[54]), "+f"(d[55]), "+f"(d[56]),
        "+f"(d[57]), "+f"(d[58]), "+f"(d[59]), "+f"(d[60]), "+f"(d[61]), "+f"(d[62]), "+f"(d[63])
      : "r"(a0), "r"(a1), "r"(a2), "r"(a3), "l"(db), "r"(sd), "n"(SA), "n"(SB), "n"(TB));
}
template <int SA, int SB, int TB>
__device__ __forceinline__ void wgmma_rs_256(float (&d)[128], uint32_t a0, uint32_t a1, uint32_t a2, uint32_t a3, uint64_t db, int sd) {
  asm volatile("{\n.reg .pred p;\nsetp.ne.b32 p, %133, 0;\n"
      "wgmma.mma_async.sync.aligned.m64n256k16.f32.bf16.bf16 {"
      "%0, %1, %2, %3, %4, %5, %6, %7, %8, %9, %10, %11, %12, %13, %14, %15, %16, %17, %18, %19, %20, %21, %22, %23, "
      "%24, %25, %26, %27, %28, %29, %30, %31, %32, %33, %34, %35, %36, %37, %38, %39, %40, %41, %42, %43, %44, %45, "
      "%46, %47, %48, %49, %50, %51, %52, %53, %54, %55, %56, %57, %58, %59, %60, %61, %62, %63, %64, %65, %66, %67, "
      "%68, %69, %70, %71, %72, %73, %74, %75, %76, %77, %78, %79, %80, %81, %82, %83, %84, %85, %86, %87, %88, %89, "
      "%90, %91, %92, %93, %94, %95, %96, %97, %98, %99, %100, %101, %102, %103, %104, %105, %106, %107, %108, %109, "
      "%110, %111, %112, %113, %114, %115, %116, %117, %118, %119, %120, %121, %122, %123, %124, %125, %126, %127"
      "}, {%128, %129, %130, %131}, %132, p, %134, %135, %136;\n}\n"
      : "+f"(d[0]), "+f"(d[1]), "+f"(d[2]), "+f"(d[3]), "+f"(d[4]), "+f"(d[5]), "+f"(d[6]), "+f"(d[7]), "+f"(d[8]),
        "+f"(d[9]), "+f"(d[10]), "+f"(d[11]), "+f"(d[12]), "+f"(d[13]), "+f"(d[14]), "+f"(d[15]), "+f"(d[16]),
        "+f"(d[17]), "+f"(d[18]), "+f"(d[19]), "+f"(d[20]), "+f"(d[21]), "+f"(d[22]), "+f"(d[23]), "+f"(d[24]),
        "+f"(d[25]), "+f"(d[26]), "+f"(d[27]), "+f"(d[28]), "+f"(d[29]), "+f"(d[30]), "+f"(d[31]), "+f"(d[32]),
        "+f"(d[33]), "+f"(d[34]), "+f"(d[35]), "+f"(d[36]), "+f"(d[37]), "+f"(d[38]), "+f"(d[39]), "+f"(d[40]),
        "+f"(d[41]), "+f"(d[42]), "+f"(d[43]), "+f"(d[44]), "+f"(d[45]), "+f"(d[46]), "+f"(d[47]), "+f"(d[48]),
        "+f"(d[49]), "+f"(d[50]), "+f"(d[51]), "+f"(d[52]), "+f"(d[53]), "+f"(d[54]), "+f"(d[55]), "+f"(d[56]),
        "+f"(d[57]), "+f"(d[58]), "+f"(d[59]), "+f"(d[60]), "+f"(d[61]), "+f"(d[62]), "+f"(d[63]), "+f"(d[64]),
        "+f"(d[65]), "+f"(d[66]), "+f"(d[67]), "+f"(d[68]), "+f"(d[69]), "+f"(d[70]), "+f"(d[71]), "+f"(d[72]),
        "+f"(d[73]), "+f"(d[74]), "+f"(d[75]), "+f"(d[76]), "+f"(d[77]), "+f"(d[78]), "+f"(d[79]), "+f"(d[80]),
        "+f"(d[81]), "+f"(d[82]), "+f"(d[83]), "+f"(d[84]), "+f"(d[85]), "+f"(d[86]), "+f"(d[87]), "+f"(d[88]),
        "+f"(d[89]), "+f"(d[90]), "+f"(d[91]), "+f"(d[92]), "+f"(d[93]), "+f"(d[94]), "+f"(d[95]), "+f"(d[96]),
        "+f"(d[97]), "+f"(d[98]), "+f"(d[99]), "+f"(d[100]), "+f"(d[101]), "+f"(d[102]), "+f"(d[103]), "+f"(d[104]),
        "+f"(d[105]), "+f"(d[106]), "+f"(d[107]), "+f"(d[108]), "+f"(d[109]), "+f"(d[110]), "+f"(d[111]),
        "+f"(d[112]), "+f"(d[113]), "+f"(d[114]), "+f"(d[115]), "+f"(d[116]), "+f"(d[117]), "+f"(d[118]),
        "+f"(d[119]), "+f"(d[120]), "+f"(d[121]), "+f"(d[122]), "+f"(d[123]), "+f"(d[124]), "+f"(d[125]),
        "+f"(d[126]), "+f"(d[127])
      : "r"(a0), "r"(a1), "r"(a2), "r"(a3), "l"(db), "r"(sd), "n"(SA), "n"(SB), "n"(TB));
}

__device__ const __align__(128) uint32_t c_img[3584] = {
    0x00003c80, 0x00003c80, 0x00003c80, 0x00003c80, 0x00003c80, 0x00003c80, 0x00003c80, 0x00003c80, 0x00003c80, 0x00003c80,
    0x00003c80, 0x00003c80, 0x00003c80, 0x00003c80, 0x00003c80, 0x00003c80, 0x00003c80, 0x00003c80, 0x00003c80, 0x00003c80,
    0x00003c80, 0x00003c80, 0x00003c80, 0x00003c80, 0x00003c80, 0x00003c80, 0x00003c80, 0x00003c80, 0x00003c80, 0x00003c80,
    0x00003c80, 0x00003c80, 0x3c463c22, 0x3c623bf1, 0x3c753b95, 0x3c7f3ac9, 0x3ac93c7f, 0x3b953c75, 0x3bf13c62, 0x3c223c46,
    0x3c22bc46, 0x3bf1bc62, 0x3b95bc75, 0x3ac9bc7f, 0x3c7fbac9, 0x3c75bb95, 0x3c62bbf1, 0x3c46bc22, 0xbc46bc22, 0xbc62bbf1,
    0xbc75bb95, 0xbc7fbac9, 0xbac9bc7f, 0xbb95bc75, 0xbbf1bc62, 0xbc22bc46, 0xbc223c46, 0xbbf13c62, 0xbb953c75, 0xbac93c7f,
    0xbc7f3ac9, 0xbc753b95, 0xbc623bf1, 0xbc463c22, 0xbb48bc7b, 0xbc0ebc55, 0xbc55bc0e, 0xbc7bbb48, 0xbc7b3b48, 0xbc553c0e,
    0xbc0e3c55, 0xbb483c7b, 0x3b483c7b, 0x3c0e3c55, 0x3c553c0e, 0x3c7b3b48, 0x3c7bbb48, 0x3c55bc0e, 0x3c0ebc55, 0x3b48bc7b,
    0xbb48bc7b, 0xbc0ebc55, 0xbc55bc0e, 0xbc7bbb48, 0xbc7b3b48, 0xbc553c0e, 0xbc0e3c55, 0xbb483c7b, 0x3b483c7b, 0x3c0e3c55,
    0x3c553c0e, 0x3c7b3b48, 0x3c7bbb48, 0x3c55bc0e, 0x3c0ebc55, 0x3b48bc7b, 0x3c623bf1, 0x3c7fbac9, 0x3c46bc22, 0x3b95bc75,
    0xbc753b95, 0xbc223c46, 0xbac93c7f, 0x3bf13c62, 0x3bf1bc62, 0xbac9bc7f, 0xbc22bc46, 0xbc75bb95, 0x3b953c75, 0x3c463c22,
    0x3c7f3ac9, 0x3c62bbf1, 0xbc62bbf1, 0xbc7f3ac9, 0xbc463c22, 0xbb953c75, 0x3c75bb95, 0x3c22bc46, 0x3ac9bc7f, 0xbbf1bc62,
    0xbbf13c62, 0x3ac93c7f, 0x3c223c46, 0x3c753b95, 0xbb95bc75, 0xbc46bc22, 0xbc7fbac9, 0xbc623bf1, 0x3bc43c6d, 0x3c6d3bc4,
    0x3c6dbbc4, 0x3bc4bc6d, 0xbbc4bc6d, 0xbc6dbbc4, 0xbc6d3bc4, 0xbbc43c6d, 0x3bc43c6d, 0x3c6d3bc4, 0x3c6dbbc4, 0x3bc4bc6d,
    0xbbc4bc6d, 0xbc6dbbc4, 0xbc6d3bc4, 0xbbc43c6d, 0x3bc43c6d, 0x3c6d3bc4, 0x3c6dbbc4, 0x3bc4bc6d, 0xbbc4bc6d, 0xbc6dbbc4,
    0xbc6d3bc4, 0xbbc43c6d, 0x3bc43c6d, 0x3c6d3bc4, 0x3c6dbbc4, 0x3bc4bc6d, 0xbbc4bc6d, 0xbc6dbbc4, 0xbc6d3bc4, 0xbbc43c6d,
    0x3c753b95, 0x3c46bc22, 0xbac9bc7f, 0xbc62bbf1, 0xbbf1bc62, 0xbc7fbac9, 0xbc223c46, 0x3b953c75, 0x3b95bc75, 0xbc22bc46,
    0xbc7f3ac9, 0xbbf13c62, 0xbc623bf1, 0xbac93c7f, 0x3c463c22, 0x3c75bb95, 0xbc75bb95, 0xbc463c22, 0x3ac93c7f, 0x3c623bf1,
    0x3bf13c62, 0x3c7f3ac9, 0x3c22bc46, 0xbb95bc75, 0xbb953c75, 0x3c223c46, 0x3c7fbac9, 0x3bf1bc62, 0x3c62bbf1, 0x3ac9bc7f,
    0xbc46bc22, 0xbc753b95, 0xbc0ebc55, 0xbc7b3b48, 0xbb483c7b, 0x3c553c0e, 0x3c55bc0e, 0xbb48bc7b, 0xbc7bbb48, 0xbc0e3c55,
    0x3c0e3c55, 0x3c7bbb48, 0x3b48bc7b, 0xbc55bc0e, 0xbc553c0e, 0x3b483c7b, 0x3c7b3b48, 0x3c0ebc55, 0xbc0ebc55, 0xbc7b3b48,
    0xbb483c7b, 0x3c553c0e, 0x3c55bc0e, 0xbb48bc7b, 0xbc7bbb48, 0xbc0e3c55, 0x3c0e3c55, 0x3c7bbb48, 0x3b48bc7b, 0xbc55bc0e,
    0xbc553c0e, 0x3b483c7b, 0x3c7b3b48, 0x3c0ebc55, 0x3c7f3ac9, 0x3b95bc75, 0xbc62bbf1, 0xbc223c46, 0x3c46bc22, 0xbbf1bc62,
    0xbc753b95, 0x3ac93c7f, 0x3ac9bc7f, 0xbc75bb95, 0xbbf13c62, 0x3c463c22, 0xbc22bc46, 0xbc623bf1, 0x3b953c75, 0x3c7fbac9,
    0xbc7fbac9, 0xbb953c75, 0x3c623bf1, 0x3c22bc46, 0xbc463c22, 0x3bf13c62, 0x3c75bb95, 0xbac9bc7f, 0xbac93c7f, 0x3c753b95,
    0x3bf1bc62, 0xbc46bc22, 0x3c223c46, 0x3c62bbf1, 0xbb95bc75, 0xbc7f3ac9, 0x3a493c80, 0x3b163c7d, 0x3b793c78, 0x3bac3c71,
    0x3bdb3c67, 0x3c043c5c, 0x3c183c4e, 0x3c2c3c3e, 0x3c3e3c2c, 0x3c4e3c18, 0x3c5c3c04, 0x3c673bdb, 0x3c713bac, 0x3c783b79,
    0x3c7d3b16, 0x3c803a49, 0x3c80ba49, 0x3c7dbb16, 0x3c78bb79, 0x3c71bbac, 0x3c67bbdb, 0x3c5cbc04, 0x3c4ebc18, 0x3c3ebc2c,
    0x3c2cbc3e, 0x3c18bc4e, 0x3c04bc5c, 0x3bdbbc67, 0x3bacbc71, 0x3b79bc78, 0x3b16bc7d, 0x3a49bc80, 0x3c783b79, 0x3c80ba49,
    0x3c71bbac, 0x3c4ebc18, 0x3b163c7d, 0x3bdb3c67, 0x3c2c3c3e, 0x3c5c3c04, 0xbc04bc5c, 0xbc3ebc2c, 0xbc67bbdb, 0xbc7dbb16,
    0x3c18bc4e, 0x3bacbc71, 0x3a49bc80, 0xbb79bc78, 0xbb793c78, 0x3a493c80, 0x3bac3c71, 0x3c183c4e, 0xbc7d3b16, 0xbc673bdb,
    0xbc3e3c2c, 0xbc043c5c, 0x3c5cbc04, 0x3c2cbc3e, 0x3bdbbc67, 0x3b16bc7d, 0x3c4e3c18, 0x3c713bac, 0x3c803a49, 0x3c78bb79,
    0xbc5cbc04, 0xbc80ba49, 0xbc673bdb, 0xbc183c4e, 0xbb163c7d, 0x3bac3c71, 0x3c3e3c2c, 0x3c783b79, 0x3b793c78, 0x3c2c3c3e,
    0x3c713bac, 0x3c7dbb16, 0x3c4ebc18, 0x3bdbbc67, 0xba49bc80, 0xbc04bc5c, 0xbc043c5c, 0xba493c80, 0x3bdb3c67, 0x3c4e3c18,
    0x3c7d3b16, 0x3c71bbac, 0x3c2cbc3e, 0x3b79bc78, 0x3c78bb79, 0x3c3ebc2c, 0x3bacbc71, 0xbb16bc7d, 0xbc18bc4e, 0xbc67bbdb,
    0xbc803a49, 0xbc5c3c04, 0x3c3ebc2c, 0x3b16bc7d, 0xbc04bc5c, 0xbc71bbac, 0xbbdb3c67, 0x3b793c78, 0x3c4e3c18, 0x3c80ba49,
    0x3a49bc80, 0xbc18bc4e, 0xbc78bb79, 0xbc673bdb, 0x3bac3c71, 0x3c5c3c04, 0x3c7dbb16, 0x3c2cbc3e, 0x3c2c3c3e, 0x3c7d3b16,
    0x3c5cbc04, 0x3bacbc71, 0xbc67bbdb, 0xbc783b79, 0xbc183c4e, 0x3a493c80, 0x3c803a49, 0x3c4ebc18, 0x3b79bc78, 0xbbdbbc67,
    0xbc713bac, 0xbc043c5c, 0x3b163c7d, 0x3c3e3c2c, 0x3c67bbdb, 0x3b79bc78, 0xbc18bc4e, 0xbc80ba49, 0xbc2c3c3e, 0x3b163c7d,
    0x3c5c3c04, 0x3c71bbac, 0x3bacbc71, 0xbc04bc5c, 0xbc7dbb16, 0xbc3e3c2c, 0x3a493c80, 0x3c4e3c18, 0x3c78bb79, 0x3bdbbc67,
    0x3bdb3c67, 0x3c783b79, 0x3c4ebc18, 0x3a49bc80, 0xbc3ebc2c, 0xbc7d3b16, 0xbc043c5c, 0x3bac3c71, 0x3c713bac, 0x3c5cbc04,
    0x3b16bc7d, 0xbc2cbc3e, 0xbc803a49, 0xbc183c4e, 0x3b793c78, 0x3c673bdb, 0xbb16bc7d, 0xbc71bbac, 0xbc3e3c2c, 0x3b793c78,
    0xbc5c3c04, 0x3a493c80, 0x3c673bdb, 0x3c4ebc18, 0xbc183c4e, 0x3bdb3c67, 0x3c803a49, 0x3c04bc5c, 0x3c783b79, 0x3c2cbc3e,
    0xbbacbc71, 0xbc7dbb16, 0xbc7d3b16, 0xbbac3c71, 0x3c2c3c3e, 0x3c78bb79, 0x3c043c5c, 0x3c80ba49, 0x3bdbbc67, 0xbc18bc4e,
    0x3c4e3c18, 0x3c67bbdb, 0x3a49bc80, 0xbc5cbc04, 0x3b79bc78, 0xbc3ebc2c, 0xbc713bac, 0xbb163c7d, 0xbb163c7d, 0x3c673bdb,
    0x3c2cbc3e, 0xbc04bc5c, 0xbc783b79, 0xba493c80, 0x3c713bac, 0x3c18bc4e, 0x3c4ebc18, 0xbbacbc71, 0xbc803a49, 0xbb793c78,
    0x3c5c3c04, 0x3c3ebc2c, 0xbbdbbc67, 0xbc7d3b16, 0xbc7dbb16, 0xbbdb3c67, 0x3c3e3c2c, 0x3c5cbc04, 0xbb79bc78, 0xbc80ba49,
    0xbbac3c71, 0x3c4e3c18, 0x3c183c4e, 0x3c71bbac, 0xba49bc80, 0xbc78bb79, 0xbc043c5c, 0x3c2c3c3e, 0x3c67bbdb, 0xbb16bc7d,
    0xbc67bbdb, 0xbc043c5c, 0x3c4e3c18, 0x3c2cbc3e, 0xbc80ba49, 0xbb163c7d, 0x3c783b79, 0x3bacbc71, 0xbc713bac, 0x3b793c78,
    0x3c7dbb16, 0xba49bc80, 0xbc3e3c2c, 0x3c183c4e, 0x3c5cbc04, 0xbbdbbc67, 0xbbdb3c67, 0x3c5c3c04, 0x3c18bc4e, 0xbc3ebc2c,
    0xba493c80, 0x3c7d3b16, 0x3b79bc78, 0xbc71bbac, 0x3bac3c71, 0x3c78bb79, 0xbb16bc7d, 0xbc803a49, 0x3c2c3c3e, 0x3c4ebc18,
    0xbc04bc5c, 0xbc673bdb, 0x3c353c35, 0x3c35bc35, 0xbc35bc35, 0xbc353c35, 0x3c353c35, 0x3c35bc35, 0xbc35bc35, 0xbc353c35,
    0x3c353c35, 0x3c35bc35, 0xbc35bc35, 0xbc353c35, 0x3c353c35, 0x3c35bc35, 0xbc35bc35, 0xbc353c35, 0x3c353c35, 0x3c35bc35,
    0xbc35bc35, 0xbc353c35, 0x3c353c35, 0x3c35bc35, 0xbc35bc35, 0xbc353c35, 0x3c353c35, 0x3c35bc35, 0xbc35bc35, 0xbc353c35,
    0x3c353c35, 0x3c35bc35, 0xbc35bc35, 0xbc353c35, 0x3c7fbac9, 0xbb95bc75, 0xbc623bf1, 0x3c223c46, 0x3c463c22, 0x3bf1bc62,
    0xbc75bb95, 0xbac93c7f, 0xbac9bc7f, 0xbc753b95, 0x3bf13c62, 0x3c46bc22, 0x3c22bc46, 0xbc62bbf1, 0xbb953c75, 0x3c7f3ac9,
    0xbc7f3ac9, 0x3b953c75, 0x3c62bbf1, 0xbc22bc46, 0xbc46bc22, 0xbbf13c62, 0x3c753b95, 0x3ac9bc7f, 0x3ac93c7f, 0x3c75bb95,
    0xbbf1bc62, 0xbc463c22, 0xbc223c46, 0x3c623bf1, 0x3b95bc75, 0xbc7fbac9, 0xbc55bc0e, 0xbb483c7b, 0x3c7bbb48, 0xbc0ebc55,
    0xbc0e3c55, 0x3c7b3b48, 0xbb48bc7b, 0xbc553c0e, 0x3c553c0e, 0x3b48bc7b, 0xbc7b3b48, 0x3c0e3c55, 0x3c0ebc55, 0xbc7bbb48,
    0x3b483c7b, 0x3c55bc0e, 0xbc55bc0e, 0xbb483c7b, 0x3c7bbb48, 0xbc0ebc55, 0xbc0e3c55, 0x3c7b3b48, 0xbb48bc7b, 0xbc553c0e,
    0x3c553c0e, 0x3b48bc7b, 0xbc7b3b48, 0x3c0e3c55, 0x3c0ebc55, 0xbc7bbb48, 0x3b483c7b, 0x3c55bc0e, 0x3c75bb95, 0xbc46bc22,
    0xbac93c7f, 0x3c62bbf1, 0xbbf13c62, 0x3c7fbac9, 0xbc22bc46, 0xbb953c75, 0xbb95bc75, 0xbc223c46, 0x3c7f3ac9, 0xbbf1bc62,
    0x3c623bf1, 0xbac9bc7f, 0xbc463c22, 0x3c753b95, 0xbc753b95, 0x3c463c22, 0x3ac9bc7f, 0xbc623bf1, 0x3bf1bc62, 0xbc7f3ac9,
    0x3c223c46, 0x3b95bc75, 0x3b953c75, 0x3c22bc46, 0xbc7fbac9, 0x3bf13c62, 0xbc62bbf1, 0x3ac93c7f, 0x3c46bc22, 0xbc75bb95,
    0x3c6d3bc4, 0xbbc4bc6d, 0xbbc43c6d, 0x3c6dbbc4, 0xbc6dbbc4, 0x3bc43c6d, 0x3bc4bc6d, 0xbc6d3bc4, 0x3c6d3bc4, 0xbbc4bc6d,
    0xbbc43c6d, 0x3c6dbbc4, 0xbc6dbbc4, 0x3bc43c6d, 0x3bc4bc6d, 0xbc6d3bc4, 0x3c6d3bc4, 0xbbc4bc6d, 0xbbc43c6d, 0x3c6dbbc4,
    0xbc6dbbc4, 0x3bc43c6d, 0x3bc4bc6d, 0xbc6d3bc4, 0x3c6d3bc4, 0xbbc4bc6d, 0xbbc43c6d, 0x3c6dbbc4, 0xbc6dbbc4, 0x3bc43c6d,
    0x3bc4bc6d, 0xbc6d3bc4, 0x3c62bbf1, 0xbc7fbac9, 0x3c463c22, 0xbb95bc75, 0xbc75bb95, 0x3c223c46, 0xbac9bc7f, 0xbbf13c62,
    0xbbf1bc62, 0xbac93c7f, 0x3c22bc46, 0xbc753b95, 0xbb953c75, 0x3c46bc22, 0xbc7f3ac9, 0x3c623bf1, 0xbc623bf1, 0x3c7f3ac9,
    0xbc46bc22, 0x3b953c75, 0x3c753b95, 0xbc22bc46, 0x3ac93c7f, 0x3bf1bc62, 0x3bf13c62, 0x3ac9bc7f, 0xbc223c46, 0x3c75bb95,
    0x3b95bc75, 0xbc463c22, 0x3c7fbac9, 0xbc62bbf1, 0xbc7bbb48, 0x3c553c0e, 0xbc0ebc55, 0x3b483c7b, 0x3b48bc7b, 0xbc0e3c55,
    0x3c55bc0e, 0xbc7b3b48, 0x3c7b3b48, 0xbc55bc0e, 0x3c0e3c55, 0xbb48bc7b, 0xbb483c7b, 0x3c0ebc55, 0xbc553c0e, 0x3c7bbb48,
    0xbc7bbb48, 0x3c553c0e, 0xbc0ebc55, 0x3b483c7b, 0x3b48bc7b, 0xbc0e3c55, 0x3c55bc0e, 0xbc7b3b48, 0x3c7b3b48, 0xbc55bc0e,
    0x3c0e3c55, 0xbb48bc7b, 0xbb483c7b, 0x3c0ebc55, 0xbc553c0e, 0x3c7bbb48, 0x3c46bc22, 0xbc623bf1, 0x3c75bb95, 0xbc7f3ac9,
    0x3ac9bc7f, 0xbb953c75, 0x3bf1bc62, 0xbc223c46, 0xbc22bc46, 0x3bf13c62, 0xbb95bc75, 0x3ac93c7f, 0xbc7fbac9, 0x3c753b95,
    0xbc62bbf1, 0x3c463c22, 0xbc463c22, 0x3c62bbf1, 0xbc753b95, 0x3c7fbac9, 0xbac93c7f, 0x3b95bc75, 0xbbf13c62, 0x3c22bc46,
    0x3c223c46, 0xbbf1bc62, 0x3b953c75, 0xbac9bc7f, 0x3c7f3ac9, 0xbc75bb95, 0x3c623bf1, 0xbc46bc22, 0x3c3e3c2c, 0x3c18bc4e,
    0xbc5cbc04, 0xbbdb3c67, 0x3c713bac, 0x3b79bc78, 0xbc7dbb16, 0xba493c80, 0x3c80ba49, 0xbb16bc7d, 0xbc783b79, 0x3bac3c71,
    0x3c67bbdb, 0xbc04bc5c, 0xbc4e3c18, 0x3c2c3c3e, 0x3c2cbc3e, 0xbc4ebc18, 0xbc043c5c, 0x3c673bdb, 0x3bacbc71, 0xbc78bb79,
    0xbb163c7d, 0x3c803a49, 0xba49bc80, 0xbc7d3b16, 0x3b793c78, 0x3c71bbac, 0xbbdbbc67, 0xbc5c3c04, 0x3c183c4e, 0x3c3ebc2c,
    0x3c5cbc04, 0xbc3ebc2c, 0xbbdb3c67, 0x3c7d3b16, 0x3c4e3c18, 0x3bacbc71, 0xbc80ba49, 0x3b793c78, 0xbc78bb79, 0x3a493c80,
    0x3c71bbac, 0xbc18bc4e, 0xbb16bc7d, 0xbc673bdb, 0x3c2c3c3e, 0x3c04bc5c, 0x3c043c5c, 0x3c2cbc3e, 0xbc67bbdb, 0xbb163c7d,
    0xbc183c4e, 0x3c713bac, 0x3a49bc80, 0xbc783b79, 0x3b79bc78, 0xbc803a49, 0x3bac3c71, 0x3c4ebc18, 0x3c7dbb16, 0xbbdbbc67,
    0xbc3e3c2c, 0x3c5c3c04, 0xbc783b79, 0x3c2c3c3e, 0x3bacbc71, 0xbc7d3b16, 0x3c183c4e, 0x3bdbbc67, 0xbc803a49, 0x3c043c5c,
    0x3c5c3c04, 0x3a49bc80, 0xbc673bdb, 0x3c4e3c18, 0x3b16bc7d, 0xbc713bac, 0x3c3e3c2c, 0x3b79bc78, 0x3b793c78, 0x3c3ebc2c,
    0xbc71bbac, 0x3b163c7d, 0x3c4ebc18, 0xbc67bbdb, 0x3a493c80, 0x3c5cbc04, 0x3c04bc5c, 0xbc80ba49, 0x3bdb3c67, 0x3c18bc4e,
    0xbc7dbb16, 0x3bac3c71, 0x3c2cbc3e, 0xbc78bb79, 0x3a49bc80, 0xbc4e3c18, 0x3c783b79, 0xbbdbbc67, 0x3bac3c71, 0x3c04bc5c,
    0xbc7d3b16, 0x3c3e3c2c, 0xbc2cbc3e, 0xbb163c7d, 0x3c5cbc04, 0xbc71bbac, 0x3c673bdb, 0xbb79bc78, 0xbc183c4e, 0x3c80ba49,
    0x3c803a49, 0xbc18bc4e, 0xbb793c78, 0x3c67bbdb, 0xbc713bac, 0x3c5c3c04, 0xbb16bc7d, 0xbc2c3c3e, 0x3c3ebc2c, 0xbc7dbb16,
    0x3c043c5c, 0x3bacbc71, 0xbbdb3c67, 0x3c78bb79, 0xbc4ebc18, 0x3a493c80, 0x3bacbc71, 0xbc5c3c04, 0x3c7d3b16, 0xbc2cbc3e,
    0x3a493c80, 0x3c18bc4e, 0xbc783b79, 0x3c673bdb, 0xbbdbbc67, 0xbb793c78, 0x3c4ebc18, 0xbc80ba49, 0x3c3e3c2c, 0xbb16bc7d,
    0xbc043c5c, 0x3c71bbac, 0x3c713bac, 0xbc04bc5c, 0xbb163c7d, 0x3c3ebc2c, 0xbc803a49, 0x3c4e3c18, 0xbb79bc78, 0xbbdb3c67,
    0x3c67bbdb, 0xbc78bb79, 0x3c183c4e, 0x3a49bc80, 0xbc2c3c3e, 0x3c7dbb16, 0xbc5cbc04, 0x3bac3c71, 0xbc4ebc18, 0x3bdb3c67,
    0x3a49bc80, 0xbc043c5c, 0xbb793c78, 0x3c2cbc3e, 0xbc713bac, 0x3c7d3b16, 0x3b163c7d, 0x3bacbc71, 0xbc3e3c2c, 0x3c78bb79,
    0x3c5cbc04, 0xbc803a49, 0x3c673bdb, 0xbc18bc4e, 0xbc183c4e, 0x3c67bbdb, 0xbc80ba49, 0x3c5c3c04, 0x3c783b79, 0xbc3ebc2c,
    0x3bac3c71, 0x3b16bc7d, 0x3c7dbb16, 0xbc71bbac, 0x3c2c3c3e, 0xbb79bc78, 0xbc04bc5c, 0x3a493c80, 0x3bdbbc67, 0xbc4e3c18,
    0x3c183c4e, 0xbbacbc71, 0x3a493c80, 0x3b79bc78, 0xbc043c5c, 0x3c3ebc2c, 0xbc673bdb, 0x3c7dbb16, 0x3b16bc7d, 0xbbdb3c67,
    0x3c2cbc3e, 0xbc5c3c04, 0x3c78bb79, 0xbc80ba49, 0x3c713bac, 0xbc4ebc18, 0xbc4e3c18, 0x3c71bbac, 0xbc803a49, 0x3c783b79,
    0xbc5cbc04, 0x3c2c3c3e, 0xbbdbbc67, 0x3b163c7d, 0x3c7d3b16, 0xbc67bbdb, 0x3c3e3c2c, 0xbc04bc5c, 0x3b793c78, 0x3a49bc80,
    0xbbac3c71, 0x3c18bc4e, 0xbc713bac, 0x3c78bb79, 0xbc7d3b16, 0x3c80ba49, 0xbc3e3c2c, 0x3c4ebc18, 0xbc5c3c04, 0x3c67bbdb,
    0xbbdb3c67, 0x3c04bc5c, 0xbc183c4e, 0x3c2cbc3e, 0xba493c80, 0x3b16bc7d, 0xbb793c78, 0x3bacbc71, 0x3bac3c71, 0xbb79bc78,
    0x3b163c7d, 0xba49bc80, 0x3c2c3c3e, 0xbc18bc4e, 0x3c043c5c, 0xbbdbbc67, 0x3c673bdb, 0xbc5cbc04, 0x3c4e3c18, 0xbc3ebc2c,
    0x3c803a49, 0xbc7dbb16, 0x3c783b79, 0xbc71bbac, 0x3c800000, 0xbc800000, 0x3c800000, 0xbc800000, 0x3c800000, 0xbc800000,
    0x3c800000, 0xbc800000, 0x3c800000, 0xbc800000, 0x3c800000, 0xbc800000, 0x3c800000, 0xbc800000, 0x3c800000, 0xbc800000,
    0x3c800000, 0xbc800000, 0x3c800000, 0xbc800000, 0x3c800000, 0xbc800000, 0x3c800000, 0xbc800000, 0x3c800000, 0xbc800000,
    0x3c800000, 0xbc800000, 0x3c800000, 0xbc800000, 0x3c800000, 0xbc800000, 0x3c22bc46, 0xbbf13c62, 0x3b95bc75, 0xbac93c7f,
    0x3c7fbac9, 0xbc753b95, 0x3c62bbf1, 0xbc463c22, 0xbc46bc22, 0x3c623bf1, 0xbc75bb95, 0x3c7f3ac9, 0xbac9bc7f, 0x3b953c75,
    0xbbf1bc62, 0x3c223c46, 0xbc223c46, 0x3bf1bc62, 0xbb953c75, 0x3ac9bc7f, 0xbc7f3ac9, 0x3c75bb95, 0xbc623bf1, 0x3c46bc22,
    0x3c463c22, 0xbc62bbf1, 0x3c753b95, 0xbc7fbac9, 0x3ac93c7f, 0xbb95bc75, 0x3bf13c62, 0xbc22bc46, 0xbc7b3b48, 0x3c55bc0e,
    0xbc0e3c55, 0x3b48bc7b, 0x3b483c7b, 0xbc0ebc55, 0x3c553c0e, 0xbc7bbb48, 0x3c7bbb48, 0xbc553c0e, 0x3c0ebc55, 0xbb483c7b,
    0xbb48bc7b, 0x3c0e3c55, 0xbc55bc0e, 0x3c7b3b48, 0xbc7b3b48, 0x3c55bc0e, 0xbc0e3c55, 0x3b48bc7b, 0x3b483c7b, 0xbc0ebc55,
    0x3c553c0e, 0xbc7bbb48, 0x3c7bbb48, 0xbc553c0e, 0x3c0ebc55, 0xbb483c7b, 0xbb48bc7b, 0x3c0e3c55, 0xbc55bc0e, 0x3c7b3b48,
    0x3bf1bc62, 0x3ac93c7f, 0xbc22bc46, 0x3c753b95, 0x3b953c75, 0xbc46bc22, 0x3c7f3ac9, 0xbc623bf1, 0xbc62bbf1, 0x3c7fbac9,
    0xbc463c22, 0x3b95bc75, 0x3c75bb95, 0xbc223c46, 0x3ac9bc7f, 0x3bf13c62, 0xbbf13c62, 0xbac9bc7f, 0x3c223c46, 0xbc75bb95,
    0xbb95bc75, 0x3c463c22, 0xbc7fbac9, 0x3c62bbf1, 0x3c623bf1, 0xbc7f3ac9, 0x3c46bc22, 0xbb953c75, 0xbc753b95, 0x3c22bc46,
    0xbac93c7f, 0xbbf1bc62, 0x3c6dbbc4, 0xbbc43c6d, 0xbbc4bc6d, 0x3c6d3bc4, 0xbc6d3bc4, 0x3bc4bc6d, 0x3bc43c6d, 0xbc6dbbc4,
    0x3c6dbbc4, 0xbbc43c6d, 0xbbc4bc6d, 0x3c6d3bc4, 0xbc6d3bc4, 0x3bc4bc6d, 0x3bc43c6d, 0xbc6dbbc4, 0x3c6dbbc4, 0xbbc43c6d,
    0xbbc4bc6d, 0x3c6d3bc4, 0xbc6d3bc4, 0x3bc4bc6d, 0x3bc43c6d, 0xbc6dbbc4, 0x3c6dbbc4, 0xbbc43c6d, 0xbbc4bc6d, 0x3c6d3bc4,
    0xbc6d3bc4, 0x3bc4bc6d, 0x3bc43c6d, 0xbc6dbbc4, 0x3b95bc75, 0x3c223c46, 0xbc7f3ac9, 0x3bf1bc62, 0xbc623bf1, 0x3ac9bc7f,
    0x3c463c22, 0xbc753b95, 0xbc75bb95, 0x3c46bc22, 0x3ac93c7f, 0xbc62bbf1, 0x3bf13c62, 0xbc7fbac9, 0x3c22bc46, 0x3b953c75,
    0xbb953c75, 0xbc22bc46, 0x3c7fbac9, 0xbbf13c62, 0x3c62bbf1, 0xbac93c7f, 0xbc46bc22, 0x3c75bb95, 0x3c753b95, 0xbc463c22,
    0xbac9bc7f, 0x3c623bf1, 0xbbf1bc62, 0x3c7f3ac9, 0xbc223c46, 0xbb95bc75, 0xbc553c0e, 0xbb48bc7b, 0x3c7b3b48, 0xbc0e3c55,
    0xbc0ebc55, 0x3c7bbb48, 0xbb483c7b, 0xbc55bc0e, 0x3c55bc0e, 0x3b483c7b, 0xbc7bbb48, 0x3c0ebc55, 0x3c0e3c55, 0xbc7b3b48,
    0x3b48bc7b, 0x3c553c0e, 0xbc553c0e, 0xbb48bc7b, 0x3c7b3b48, 0xbc0e3c55, 0xbc0ebc55, 0x3c7bbb48, 0xbb483c7b, 0xbc55bc0e,
    0x3c55bc0e, 0x3b483c7b, 0xbc7bbb48, 0x3c0ebc55, 0x3c0e3c55, 0xbc7b3b48, 0x3b48bc7b, 0x3c553c0e, 0x3ac9bc7f, 0x3c753b95,
    0xbbf13c62, 0xbc46bc22, 0xbc22bc46, 0x3c62bbf1, 0x3b953c75, 0xbc7f3ac9, 0xbc7fbac9, 0x3b95bc75, 0x3c623bf1, 0xbc223c46,
    0xbc463c22, 0xbbf1bc62, 0x3c75bb95, 0x3ac93c7f, 0xbac93c7f, 0xbc75bb95, 0x3bf1bc62, 0x3c463c22, 0x3c223c46, 0xbc623bf1,
    0xbb95bc75, 0x3c7fbac9, 0x3c7f3ac9, 0xbb953c75, 0xbc62bbf1, 0x3c22bc46, 0x3c46bc22, 0x3bf13c62, 0xbc753b95, 0xbac9bc7f,
    0x3c80ba49, 0xbc7d3b16, 0x3c78bb79, 0xbc713bac, 0x3c67bbdb, 0xbc5c3c04, 0x3c4ebc18, 0xbc3e3c2c, 0x3c2cbc3e, 0xbc183c4e,
    0x3c04bc5c, 0xbbdb3c67, 0x3bacbc71, 0xbb793c78, 0x3b16bc7d, 0xba493c80, 0xba49bc80, 0x3b163c7d, 0xbb79bc78, 0x3bac3c71,
    0xbbdbbc67, 0x3c043c5c, 0xbc18bc4e, 0x3c2c3c3e, 0xbc3ebc2c, 0x3c4e3c18, 0xbc5cbc04, 0x3c673bdb, 0xbc71bbac, 0x3c783b79,
    0xbc7dbb16, 0x3c803a49, 0x3b79bc78, 0x3a493c80, 0xbbacbc71, 0x3c183c4e, 0x3c7dbb16, 0xbc673bdb, 0x3c3ebc2c, 0xbc043c5c,
    0xbc5c3c04, 0x3c2cbc3e, 0xbbdb3c67, 0x3b16bc7d, 0xbc4ebc18, 0x3c713bac, 0xbc80ba49, 0x3c78bb79, 0x3c783b79, 0xbc803a49,
    0x3c71bbac, 0xbc4e3c18, 0x3b163c7d, 0xbbdbbc67, 0x3c2c3c3e, 0xbc5cbc04, 0xbc04bc5c, 0x3c3e3c2c, 0xbc67bbdb, 0x3c7d3b16,
    0x3c18bc4e, 0xbbac3c71, 0x3a49bc80, 0x3b793c78, 0xbc043c5c, 0x3a49bc80, 0x3bdb3c67, 0xbc4ebc18, 0x3c7d3b16, 0xbc713bac,
    0x3c2cbc3e, 0xbb793c78, 0x3c78bb79, 0xbc3e3c2c, 0x3bacbc71, 0x3b163c7d, 0xbc18bc4e, 0x3c673bdb, 0xbc803a49, 0x3c5cbc04,
    0x3c5c3c04, 0xbc80ba49, 0x3c67bbdb, 0xbc183c4e, 0x3b16bc7d, 0x3bac3c71, 0xbc3ebc2c, 0x3c783b79, 0xbb79bc78, 0x3c2c3c3e,
    0xbc71bbac, 0x3c7dbb16, 0xbc4e3c18, 0x3bdbbc67, 0x3a493c80, 0xbc04bc5c, 0xbc2cbc3e, 0x3c7d3b16, 0xbc5c3c04, 0x3bacbc71,
    0x3c673bdb, 0xbc783b79, 0x3c18bc4e, 0x3a493c80, 0xbc80ba49, 0x3c4ebc18, 0xbb793c78, 0xbbdbbc67, 0x3c71bbac, 0xbc043c5c,
    0xbb16bc7d, 0x3c3e3c2c, 0x3c3ebc2c, 0xbb163c7d, 0xbc04bc5c, 0x3c713bac, 0xbbdb3c67, 0xbb79bc78, 0x3c4e3c18, 0xbc803a49,
    0x3a49bc80, 0x3c183c4e, 0xbc78bb79, 0x3c67bbdb, 0x3bac3c71, 0xbc5cbc04, 0x3c7dbb16, 0xbc2c3c3e, 0xbbdbbc67, 0x3c783b79,
    0xbc4e3c18, 0x3a49bc80, 0x3c3e3c2c, 0xbc7d3b16, 0x3c04bc5c, 0x3bac3c71, 0xbc71bbac, 0x3c5cbc04, 0xbb163c7d, 0xbc2cbc3e,
    0x3c80ba49, 0xbc183c4e, 0xbb79bc78, 0x3c673bdb, 0x3c67bbdb, 0xbb793c78, 0xbc18bc4e, 0x3c803a49, 0xbc2c3c3e, 0xbb16bc7d,
    0x3c5c3c04, 0xbc713bac, 0x3bacbc71, 0x3c043c5c, 0xbc7dbb16, 0x3c3ebc2c, 0x3a493c80, 0xbc4ebc18, 0x3c78bb79, 0xbbdb3c67,
    0xbc7d3b16, 0x3bacbc71, 0x3c2c3c3e, 0xbc783b79, 0x3c043c5c, 0xbc803a49, 0x3bdbbc67, 0x3c183c4e, 0x3c4e3c18, 0xbc673bdb,
    0x3a49bc80, 0x3c5c3c04, 0x3b79bc78, 0x3c3e3c2c, 0xbc713bac, 0x3b16bc7d, 0x3b163c7d, 0xbc71bbac, 0x3c3ebc2c, 0x3b793c78,
    0x3c5cbc04, 0x3a493c80, 0xbc67bbdb, 0x3c4ebc18, 0x3c18bc4e, 0x3bdb3c67, 0xbc80ba49, 0x3c04bc5c, 0xbc78bb79, 0x3c2cbc3e,
    0x3bac3c71, 0xbc7dbb16, 0x3c7d3b16, 0xbbdb3c67, 0xbc3ebc2c, 0x3c5cbc04, 0x3b793c78, 0xbc80ba49, 0x3bacbc71, 0x3c4e3c18,
    0xbc18bc4e, 0x3c71bbac, 0x3a493c80, 0xbc78bb79, 0x3c04bc5c, 0x3c2c3c3e, 0xbc673bdb, 0xbb16bc7d, 0xbb163c7d, 0xbc67bbdb,
    0x3c2cbc3e, 0x3c043c5c, 0xbc783b79, 0x3a49bc80, 0x3c713bac, 0xbc183c4e, 0x3c4ebc18, 0x3bac3c71, 0xbc803a49, 0x3b79bc78,
    0x3c5c3c04, 0xbc3e3c2c, 0xbbdbbc67, 0x3c7dbb16, 0xbbdb3c67, 0xbc5cbc04, 0x3c18bc4e, 0x3c3e3c2c, 0xba493c80, 0xbc7dbb16,
    0x3b79bc78, 0x3c713bac, 0x3bac3c71, 0xbc783b79, 0xbb16bc7d, 0x3c80ba49, 0x3c2c3c3e, 0xbc4e3c18, 0xbc04bc5c, 0x3c67bbdb,
    0x3c673bdb, 0xbc043c5c, 0xbc4ebc18, 0x3c2cbc3e, 0x3c803a49, 0xbb163c7d, 0xbc78bb79, 0x3bacbc71, 0x3c71bbac, 0x3b793c78,
    0xbc7d3b16, 0xba49bc80, 0x3c3ebc2c, 0x3c183c4e, 0xbc5c3c04, 0xbbdbbc67, 0x3f803f80, 0x3f7d3f7f, 0x3f783f7b, 0x3f713f75,
    0x3f673f6d, 0x3f5c3f62, 0x3f4e3f55, 0x3f3e3f46, 0x3f2c3f35, 0x3f183f22, 0x3f043f0e, 0x3edb3ef1, 0x3eac3ec4, 0x3e793e95,
    0x3e163e48, 0x3d493dc9, 0xbd490000, 0xbe16bdc9, 0xbe79be48, 0xbeacbe95, 0xbedbbec4, 0xbf04bef1, 0xbf18bf0e, 0xbf2cbf22,
    0xbf3ebf35, 0xbf4ebf46, 0xbf5cbf55, 0xbf67bf62, 0xbf71bf6d, 0xbf78bf75, 0xbf7dbf7b, 0xbf80bf7f, 0x3edb3ec4, 0x3f043ef1,
    0x3f183f0e, 0x3f2c3f22, 0x3d490000, 0x3e163dc9, 0x3e793e48, 0x3eac3e95, 0x3f713f6d, 0x3f783f75, 0x3f7d3f7b, 0x3f803f7f,
    0x3f3e3f35, 0x3f4e3f46, 0x3f5c3f55, 0x3f673f62, 0x3f673f6d, 0x3f5c3f62, 0x3f4e3f55, 0x3f3e3f46, 0x3f803f80, 0x3f7d3f7f,
    0x3f783f7b, 0x3f713f75, 0x3eac3ec4, 0x3e793e95, 0x3e163e48, 0x3d493dc9, 0x3f2c3f35, 0x3f183f22, 0x3f043f0e, 0x3edb3ef1,
    0xbf4ebf35, 0xbf71bf62, 0xbf80bf7b, 0xbf78bf7f, 0xbf5cbf6d, 0xbf2cbf46, 0xbedbbf0e, 0xbe16be95, 0x3f7d3f80, 0x3f673f75,
    0x3f3e3f55, 0x3f043f22, 0x3e793ec4, 0xbd493dc9, 0xbeacbe48, 0xbf18bef1, 0x3f183f35, 0x3eac3ef1, 0x3d493e48, 0xbe79bdc9,
    0xbf04bec4, 0xbf3ebf22, 0xbf67bf55, 0xbf7dbf75, 0x3e160000, 0x3edb3e95, 0x3f2c3f0e, 0x3f5c3f46, 0x3f783f6d, 0x3f803f7f,
    0x3f713f7b, 0x3f4e3f62, 0xbf04bec4, 0xbf3ebf22, 0xbf67bf55, 0xbf7dbf75, 0x3f183f35, 0x3eac3ef1, 0x3d493e48, 0xbe79bdc9,
    0x3f783f6d, 0x3f803f7f, 0x3f713f7b, 0x3f4e3f62, 0x3e160000, 0x3edb3e95, 0x3f2c3f0e, 0x3f5c3f46, 0x3f5c3f6d, 0x3f2c3f46,
    0x3edb3f0e, 0x3e163e95, 0x3f4e3f35, 0x3f713f62, 0x3f803f7b, 0x3f783f7f, 0xbe79bec4, 0x3d49bdc9, 0x3eac3e48, 0x3f183ef1,
    0xbf7dbf80, 0xbf67bf75, 0xbf3ebf55, 0xbf04bf22, 0xbe790000, 0xbf2cbef1, 0xbf71bf55, 0xbf7dbf7f, 0xbf4ebf6d, 0xbedbbf22,
    0x3d49be48, 0x3f043e95, 0x3f5c3f35, 0x3f803f75, 0x3f673f7b, 0x3f183f46, 0x3e163ec4, 0xbeacbdc9, 0xbf3ebf0e, 0xbf78bf62,
    0x3f783f80, 0x3f3e3f62, 0x3eac3f0e, 0xbe163dc9, 0xbf18bec4, 0xbf67bf46, 0xbf80bf7b, 0xbf5cbf75, 0xbf04bf35, 0xbd49be95,
    0x3edb3e48, 0x3f4e3f22, 0x3f7d3f6d, 0x3f713f7f, 0x3f2c3f55, 0x3e793ef1, 0xbf18bec4, 0xbf67bf46, 0xbf80bf7b, 0xbf5cbf75,
    0x3f783f80, 0x3f3e3f62, 0x3eac3f0e, 0xbe163dc9, 0x3f7d3f6d, 0x3f713f7f, 0x3f2c3f55, 0x3e793ef1, 0xbf04bf35, 0xbd49be95,
    0x3edb3e48, 0x3f4e3f22, 0x3f4e3f6d, 0x3edb3f22, 0xbd493e48, 0xbf04be95, 0x3e790000, 0x3f2c3ef1, 0x3f713f55, 0x3f7d3f7f,
    0xbe16bec4, 0x3eac3dc9, 0x3f3e3f0e, 0x3f783f62, 0xbf5cbf35, 0xbf80bf75, 0xbf67bf7b, 0xbf18bf46, 0xbedbbf35, 0x3e79bdc9,
    0x3f4e3f0e, 0x3f803f75, 0x3f3e3f6d, 0x3e163ef1, 0xbf04be48, 0xbf71bf46, 0x3eac0000, 0x3f5c3f22, 0x3f7d3f7b, 0x3f2c3f62,
    0x3d493ec4, 0xbf18be95, 0xbf78bf55, 0xbf67bf7f, 0x3f673f35, 0x3f783f7f, 0x3f183f55, 0xbd493e95, 0xbf2cbec4, 0xbf7dbf62,
    0xbf5cbf7b, 0xbeacbf22, 0x3f713f80, 0x3f043f46, 0xbe163e48, 0xbf3ebef1, 0xbf80bf6d, 0xbf4ebf75, 0xbe79bf0e, 0x3edb3dc9,
    0x3f2c3ec4, 0x3f7d3f62, 0x3f5c3f7b, 0x3eac3f22, 0xbf67bf35, 0xbf78bf7f, 0xbf18bf55, 0x3d49be95, 0x3f803f6d, 0x3f4e3f75,
    0x3e793f0e, 0xbedbbdc9, 0xbf71bf80, 0xbf04bf46, 0x3e16be48, 0x3f3e3ef1, 0x3f3e3f6d, 0x3e163ef1, 0xbf04be48, 0xbf71bf46,
    0xbedbbf35, 0x3e79bdc9, 0x3f4e3f0e, 0x3f803f75, 0x3d493ec4, 0xbf18be95, 0xbf78bf55, 0xbf67bf7f, 0x3eac0000, 0x3f5c3f22,
    0x3f7d3f7b, 0x3f2c3f62, 0x3f673f80, 0x3e793f22, 0xbf18be48, 0xbf80bf62, 0xbf2cbf6d, 0x3e16be95, 0x3f5c3f0e, 0x3f713f7f,
    0x3eac3f35, 0xbf04bdc9, 0xbf7dbf55, 0xbf3ebf75, 0x3d49bec4, 0x3f4e3ef1, 0x3f783f7b, 0x3edb3f46, 0xbedb0000, 0xbf78bf46,
    0xbf4ebf7b, 0xbd49bef1, 0x3f3e3ec4, 0x3f7d3f75, 0x3f043f55, 0xbeac3dc9, 0xbf71bf35, 0xbf5cbf7f, 0xbe16bf0e, 0x3f2c3e95,
    0x3f803f6d, 0x3f183f62, 0xbe793e48, 0xbf67bf22, 0xbf3ebec4, 0xbf7dbf75, 0xbf04bf55, 0x3eacbdc9, 0x3edb0000, 0x3f783f46,
    0x3f4e3f7b, 0x3d493ef1, 0xbf80bf6d, 0xbf18bf62, 0x3e79be48, 0x3f673f22, 0x3f713f35, 0x3f5c3f7f, 0x3e163f0e, 0xbf2cbe95,
    0xbf2cbf6d, 0x3e16be95, 0x3f5c3f0e, 0x3f713f7f, 0x3f673f80, 0x3e793f22, 0xbf18be48, 0xbf80bf62, 0x3d49bec4, 0x3f4e3ef1,
    0x3f783f7b, 0x3edb3f46, 0x3eac3f35, 0xbf04bdc9, 0xbf7dbf55, 0xbf3ebf75, 0xbf78bf35, 0xbf2cbf75, 0x3eacbe48, 0x3f7d3f46,
    0x3f183f6d, 0xbedb3dc9, 0xbf80bf55, 0xbf04bf62, 0x3f5c3f80, 0xbd493ef1, 0xbf67bf0e, 0xbf4ebf7f, 0x3e16bec4, 0x3f713f22,
    0x3f3e3f7b, 0xbe793e95, 0x3e793f35, 0xbf3ebe95, 0xbf71bf7b, 0xbe16bf22, 0x3f4e3ec4, 0x3f673f7f, 0x3d493f0e, 0xbf5cbef1,
    0x3f040000, 0x3f803f62, 0x3edb3f55, 0xbf18bdc9, 0xbf7dbf6d, 0xbeacbf46, 0x3f2c3e48, 0x3f783f75, 0x3f4e3ec4, 0x3f673f7f,
    0x3d493f0e, 0xbf5cbef1, 0x3e793f35, 0xbf3ebe95, 0xbf71bf7b, 0xbe16bf22, 0xbf7dbf6d, 0xbeacbf46, 0x3f2c3e48, 0x3f783f75,
    0x3f040000, 0x3f803f62, 0x3edb3f55, 0xbf18bdc9, 0xbf18bf6d, 0x3edbbdc9, 0x3f803f55, 0x3f043f62, 0x3f783f35, 0x3f2c3f75,
    0xbeac3e48, 0xbf7dbf46, 0xbe163ec4, 0xbf71bf22, 0xbf3ebf7b, 0x3e79be95, 0xbf5cbf80, 0x3d49bef1, 0x3f673f0e, 0x3f4e3f7f,
    0xbf180000, 0xbf71bf75, 0x3d49bf0e, 0x3f783f22, 0x3f043f6d, 0xbf2cbdc9, 0xbf67bf7b, 0x3e16bef1, 0x3f7d3f35, 0x3edb3f62,
    0xbf3ebe48, 0xbf5cbf7f, 0x3e79bec4, 0x3f803f46, 0x3eac3f55, 0xbf4ebe95, 0x3f4e3f80, 0xbeac3e95, 0xbf80bf55, 0xbe79bf46,
    0x3f5c3ec4, 0x3f3e3f7f, 0xbedb3e48, 0xbf7dbf62, 0xbe16bf35, 0x3f673ef1, 0x3f2c3f7b, 0xbf043dc9, 0xbf78bf6d, 0xbd49bf22,
    0x3f713f0e, 0x3f183f75, 0x3f5c3ec4, 0x3f3e3f7f, 0xbedb3e48, 0xbf7dbf62, 0x3f4e3f80, 0xbeac3e95, 0xbf80bf55, 0xbe79bf46,
    0xbf78bf6d, 0xbd49bf22, 0x3f713f0e, 0x3f183f75, 0xbe16bf35, 0x3f673ef1, 0x3f2c3f7b, 0xbf043dc9, 0xbf04bf6d, 0x3f2c3dc9,
    0x3f673f7b, 0xbe163ef1, 0x3f180000, 0x3f713f75, 0xbd493f0e, 0xbf78bf22, 0xbe793ec4, 0xbf80bf46, 0xbeacbf55, 0x3f4e3e95,
    0xbf7dbf35, 0xbedbbf62, 0x3f3e3e48, 0x3f5c3f7f, 0xbd49bf35, 0x3f7d3f22, 0x3e793f55, 0xbf71bef1, 0xbedbbf6d, 0x3f5c3e95,
    0x3f183f7b, 0xbf3ebdc9, 0x3f2c0000, 0x3f4e3f7f, 0xbf043e48, 0xbf67bf75, 0x3eacbec4, 0x3f783f62, 0xbe163f0e, 0xbf80bf46,
    0x3f803f35, 0x3e163f46, 0xbf78bf0e, 0xbeacbf62, 0x3f673ec4, 0x3f043f75, 0xbf4ebe48, 0xbf2cbf7f, 0x3f3e3f80, 0xbf183dc9,
    0xbf5cbf7b, 0x3edbbe95, 0x3f713f6d, 0xbe793ef1, 0xbf7dbf55, 0x3d49bf22, 0xbf67bec4, 0xbf04bf75, 0x3f4e3e48, 0x3f2c3f7f,
    0xbf80bf35, 0xbe16bf46, 0x3f783f0e, 0x3eac3f62, 0xbf71bf6d, 0x3e79bef1, 0x3f7d3f55, 0xbd493f22, 0xbf3ebf80, 0x3f18bdc9,
    0x3f5c3f7b, 0xbedb3e95, 0xbedbbf6d, 0x3f5c3e95, 0x3f183f7b, 0xbf3ebdc9, 0xbd49bf35, 0x3f7d3f22, 0x3e793f55, 0xbf71bef1,
    0x3eacbec4, 0x3f783f62, 0xbe163f0e, 0xbf80bf46, 0x3f2c0000, 0x3f4e3f7f, 0xbf043e48, 0xbf67bf75, 0x3f2c3f80, 0xbf4ebdc9,
    0xbf04bf7b, 0x3f673e95, 0x3eac3f6d, 0xbf78bef1, 0xbe16bf55, 0x3f803f22, 0xbd493f35, 0xbf7dbf46, 0x3e79bf0e, 0x3f713f62,
    0xbedb3ec4, 0xbf5cbf75, 0x3f18be48, 0x3f3e3f7f, 0xbf3e0000, 0xbf18bf7f, 0x3f5c3e48, 0x3edb3f75, 0xbf71bec4, 0xbe79bf62,
    0x3f7d3f0e, 0x3d493f46, 0xbf80bf35, 0x3e16bf22, 0x3f783f55, 0xbeac3ef1, 0xbf67bf6d, 0x3f04be95, 0x3f4e3f7b, 0xbf2c3dc9,
    0x3f713ec4, 0x3e793f62, 0xbf7dbf0e, 0xbd49bf46, 0x3f3e0000, 0x3f183f7f, 0xbf5cbe48, 0xbedbbf75, 0x3f673f6d, 0xbf043e95,
    0xbf4ebf7b, 0x3f2cbdc9, 0x3f803f35, 0xbe163f22, 0xbf78bf55, 0x3eacbef1, 0x3eac3f6d, 0xbf78bef1, 0xbe16bf55, 0x3f803f22,
    0x3f2c3f80, 0xbf4ebdc9, 0xbf04bf7b, 0x3f673e95, 0xbedb3ec4, 0xbf5cbf75, 0x3f18be48, 0x3f3e3f7f, 0xbd493f35, 0xbf7dbf46,
    0x3e79bf0e, 0x3f713f62, 0xbf7dbf35, 0x3edbbef1, 0x3f3e3f7b, 0xbf5cbdc9, 0xbe79bf6d, 0x3f803f22, 0xbeac3f0e, 0xbf4ebf75,
    0x3f183f80, 0xbf71be95, 0xbd49bf55, 0x3f783f46, 0xbf043ec4, 0xbf2cbf7f, 0x3f673e48, 0x3e163f62, 0xbe163f35, 0xbf67bf62,
    0x3f2cbe48, 0x3f043f7f, 0xbf78bec4, 0x3d49bf46, 0x3f713f55, 0xbf183e95, 0x3f4e0000, 0x3eac3f75, 0xbf80bf0e, 0x3e79bf22,
    0x3f5c3f6d, 0xbf3e3dc9, 0xbedbbf7b, 0x3f7d3ef1, 0xbf78bec4, 0x3d49bf46, 0x3f713f55, 0xbf183e95, 0xbe163f35, 0xbf67bf62,
    0x3f2cbe48, 0x3f043f7f, 0x3f5c3f6d, 0xbf3e3dc9, 0xbedbbf7b, 0x3f7d3ef1, 0x3f4e0000, 0x3eac3f75, 0xbf80bf0e, 0x3e79bf22,
    0x3e793f6d, 0xbf80bf22, 0x3eacbf0e, 0x3f4e3f75, 0x3f7d3f35, 0xbedb3ef1, 0xbf3ebf7b, 0x3f5c3dc9, 0x3f04bec4, 0x3f2c3f7f,
    0xbf67be48, 0xbe16bf62, 0xbf18bf80, 0x3f713e95, 0x3d493f55, 0xbf78bf46, 0xbf5c0000, 0xbd49bf62, 0x3f673f55, 0xbf4e3dc9,
    0xbe16bf6d, 0x3f713f46, 0xbf3e3e48, 0xbe79bf75, 0x3f783f35, 0xbf2c3e95, 0xbeacbf7b, 0x3f7d3f22, 0xbf183ec4, 0xbedbbf7f,
    0x3f803f0e, 0xbf043ef1, 0x3f043f80, 0xbf80bef1, 0x3edbbf0e, 0x3f183f7f, 0xbf7dbec4, 0x3eacbf22, 0x3f2c3f7b, 0xbf78be95,
    0x3e79bf35, 0x3f3e3f75, 0xbf71be48, 0x3e16bf46, 0x3f4e3f6d, 0xbf67bdc9, 0x3d49bf55, 0x3f5c3f62, 0xbf7dbec4, 0x3eacbf22,
    0x3f2c3f7b, 0xbf78be95, 0x3f043f80, 0xbf80bef1, 0x3edbbf0e, 0x3f183f7f, 0x3f4e3f6d, 0xbf67bdc9, 0x3d49bf55, 0x3f5c3f62,
    0x3e79bf35, 0x3f3e3f75, 0xbf71be48, 0x3e16bf46, 0x3e163f6d, 0xbf71bf46, 0x3f3ebe48, 0x3e793f75, 0x3f5c0000, 0x3d493f62,
    0xbf67bf55, 0x3f4ebdc9, 0x3f18bec4, 0x3edb3f7f, 0xbf80bf0e, 0x3f04bef1, 0xbf78bf35, 0x3f2cbe95, 0x3eac3f7b, 0xbf7dbf22,
    0x3eacbf35, 0x3f043f7f, 0xbf7dbf0e, 0x3f3ebe95, 0x3d493f6d, 0xbf4ebf62, 0x3f783e48, 0xbedb3f22, 0x3f670000, 0xbe793f46,
    0xbf18bf7b, 0x3f803ef1, 0xbf2c3ec4, 0xbe16bf75, 0x3f5c3f55, 0xbf71bdc9, 0x3f713f35, 0xbf5c3dc9, 0x3e16bf55, 0x3f2c3f75,
    0xbf80bec4, 0x3f18bef1, 0x3e793f7b, 0xbf67bf46, 0x3edb3f80, 0xbf78bf22, 0x3f4ebe48, 0xbd493f62, 0xbf3ebf6d, 0x3f7d3e95,
    0xbf043f0e, 0xbeacbf7f, 0x3f803ec4, 0xbf183ef1, 0xbe79bf7b, 0x3f673f46, 0xbf71bf35, 0x3f5cbdc9, 0xbe163f55, 0xbf2cbf75,
    0x3f3e3f6d, 0xbf7dbe95, 0x3f04bf0e, 0x3eac3f7f, 0xbedbbf80, 0x3f783f22, 0xbf4e3e48, 0x3d49bf62, 0x3d493f6d, 0xbf4ebf62,
    0x3f783e48, 0xbedb3f22, 0x3eacbf35, 0x3f043f7f, 0xbf7dbf0e, 0x3f3ebe95, 0xbf2c3ec4, 0xbe16bf75, 0x3f5c3f55, 0xbf71bdc9,
    0x3f670000, 0xbe793f46, 0xbf18bf7b, 0x3f803ef1, 0x3eac3f80, 0xbf5cbf46, 0x3f7d3e48, 0xbf2c3ef1, 0x3d49bf6d, 0x3f183f75,
    0xbf78bf0e, 0x3f67bdc9, 0xbedb3f35, 0xbe79bf7f, 0x3f4e3f55, 0xbf80be95, 0x3f3ebec4, 0xbe163f62, 0xbf04bf7b, 0x3f713f22,
    0xbf710000, 0x3f04bf22, 0x3e163f7b, 0xbf3ebf62, 0x3f803ec4, 0xbf4e3e95, 0x3e79bf55, 0x3edb3f7f, 0xbf67bf35, 0x3f783dc9,
    0xbf183f0e, 0xbd49bf75, 0x3f2c3f6d, 0xbf7dbef1, 0x3f5cbe48, 0xbeac3f46, 0xbf80bec4, 0x3f4ebe95, 0xbe793f55, 0xbedbbf7f,
    0x3f710000, 0xbf043f22, 0xbe16bf7b, 0x3f3e3f62, 0xbf2cbf6d, 0x3f7d3ef1, 0xbf5c3e48, 0x3eacbf46, 0x3f673f35, 0xbf78bdc9,
    0x3f18bf0e, 0x3d493f75, 0x3d49bf6d, 0x3f183f75, 0xbf78bf0e, 0x3f67bdc9, 0x3eac3f80, 0xbf5cbf46, 0x3f7d3e48, 0xbf2c3ef1,
    0x3f3ebec4, 0xbe163f62, 0xbf04bf7b, 0x3f713f22, 0xbedb3f35, 0xbe79bf7f, 0x3f4e3f55, 0xbf80be95, 0xbf5cbf35, 0x3f803e95,
    0xbf673e48, 0x3f18bf22, 0xbe163f6d, 0xbeacbf7f, 0x3f3e3f55, 0xbf78bef1, 0x3e793f80, 0xbf2cbf62, 0x3f713f0e, 0xbf7dbdc9,
    0x3f4ebec4, 0xbedb3f46, 0xbd49bf7b, 0x3f043f75, 0xbf043f35, 0x3d49bf75, 0x3edb3f7b, 0xbf4ebf46, 0x3f7d3ec4, 0xbf713dc9,
    0x3f2cbf0e, 0xbe793f62, 0x3f780000, 0xbf3e3ef1, 0x3eacbf55, 0x3e163f7f, 0xbf18bf6d, 0x3f673f22, 0xbf80be48, 0x3f5cbe95,
    0x3f7d3ec4, 0xbf713dc9, 0x3f2cbf0e, 0xbe793f62, 0xbf043f35, 0x3d49bf75, 0x3edb3f7b, 0xbf4ebf46, 0xbf18bf6d, 0x3f673f22,
    0xbf80be48, 0x3f5cbe95, 0x3f780000, 0xbf3e3ef1, 0x3eacbf55, 0x3e163f7f, 0x3e16bf6d, 0x3eac3f7f, 0xbf3ebf55, 0x3f783ef1,
    0x3f5c3f35, 0xbf80be95, 0x3f67be48, 0xbf183f22, 0xbf4e3ec4, 0x3edbbf46, 0x3d493f7b, 0xbf04bf75, 0xbe79bf80, 0x3f2c3f62,
    0xbf71bf0e, 0x3f7d3dc9, 0xbf7d0000, 0x3f67be95, 0xbf3e3f0e, 0x3f04bf46, 0xbe793f6d, 0xbd49bf7f, 0x3eac3f7b, 0xbf18bf62,
    0x3f4e3f35, 0xbf71bef1, 0x3f803e48, 0xbf783dc9, 0x3f5cbec4, 0xbf2c3f22, 0x3edbbf55, 0xbe163f75, 0x3e163f80, 0xbedbbf75,
    0x3f2c3f55, 0xbf5cbf22, 0x3f783ec4, 0xbf80bdc9, 0x3f71be48, 0xbf4e3ef1, 0x3f18bf35, 0xbeac3f62, 0x3d49bf7b, 0x3e793f7f,
    0xbf04bf6d, 0x3f3e3f46, 0xbf67bf0e, 0x3f7d3e95, 0x3f783ec4, 0xbf80bdc9, 0x3f71be48, 0xbf4e3ef1, 0x3e163f80, 0xbedbbf75,
    0x3f2c3f55, 0xbf5cbf22, 0xbf04bf6d, 0x3f3e3f46, 0xbf67bf0e, 0x3f7d3e95, 0x3f18bf35, 0xbeac3f62, 0x3d49bf7b, 0x3e793f7f,
    0x3e79bf6d, 0x3d493f7f, 0xbeacbf7b, 0x3f183f62, 0x3f7d0000, 0xbf673e95, 0x3f3ebf0e, 0xbf043f46, 0xbf5c3ec4, 0x3f2cbf22,
    0xbedb3f55, 0x3e16bf75, 0xbf4ebf35, 0x3f713ef1, 0xbf80be48, 0x3f78bdc9, 0x3f2cbf35, 0xbf183f46, 0x3f04bf55, 0xbedb3f62,
    0x3eacbf6d, 0xbe793f75, 0x3e16bf7b, 0xbd493f7f, 0x3f800000, 0xbf7d3dc9, 0x3f78be48, 0xbf713e95, 0x3f67bec4, 0xbf5c3ef1,
    0x3f4ebf0e, 0xbf3e3f22, 0x3f3e3f35, 0xbf4ebf22, 0x3f5c3f0e, 0xbf67bef1, 0x3f713ec4, 0xbf78be95, 0x3f7d3e48, 0xbf80bdc9,
    0x3d493f80, 0xbe16bf7f, 0x3e793f7b, 0xbeacbf75, 0x3edb3f6d, 0xbf04bf62, 0x3f183f55, 0xbf2cbf46, 0xbf71bec4, 0x3f783e95,
    0xbf7dbe48, 0x3f803dc9, 0xbf3ebf35, 0x3f4e3f22, 0xbf5cbf0e, 0x3f673ef1, 0xbedbbf6d, 0x3f043f62, 0xbf18bf55, 0x3f2c3f46,
    0xbd49bf80, 0x3e163f7f, 0xbe79bf7b, 0x3eac3f75, 0x3eacbf6d, 0xbe793f75, 0x3e16bf7b, 0xbd493f7f, 0x3f2cbf35, 0xbf183f46,
    0x3f04bf55, 0xbedb3f62, 0x3f67bec4, 0xbf5c3ef1, 0x3f4ebf0e, 0xbf3e3f22, 0x3f800000, 0xbf7d3dc9, 0x3f78be48, 0xbf713e95,
    0xbd493f80, 0x3e16bf7f, 0xbe793f7b, 0x3eacbf75, 0xbedb3f6d, 0x3f04bf62, 0xbf183f55, 0x3f2cbf46, 0xbf3e3f35, 0x3f4ebf22,
    0xbf5c3f0e, 0x3f67bef1, 0xbf713ec4, 0x3f78be95, 0xbf7d3e48, 0x3f80bdc9, 0xbf800000, 0x3f7d3dc9, 0xbf78be48, 0x3f713e95,
    0xbf67bec4, 0x3f5c3ef1, 0xbf4ebf0e, 0x3f3e3f22, 0xbf2cbf35, 0x3f183f46, 0xbf04bf55, 0x3edb3f62, 0xbeacbf6d, 0x3e793f75,
    0xbe16bf7b, 0x3d493f7f, 0x3f673ec4, 0xbf5cbef1, 0x3f4e3f0e, 0xbf3ebf22, 0x3f800000, 0xbf7dbdc9, 0x3f783e48, 0xbf71be95,
    0x3eac3f6d, 0xbe79bf75, 0x3e163f7b, 0xbd49bf7f, 0x3f2c3f35, 0xbf18bf46, 0x3f043f55, 0xbedbbf62, 0xbedb3f6d, 0x3f04bf62,
    0xbf183f55, 0x3f2cbf46, 0xbd493f80, 0x3e16bf7f, 0xbe793f7b, 0x3eacbf75, 0xbf713ec4, 0x3f78be95, 0xbf7d3e48, 0x3f80bdc9,
    0xbf3e3f35, 0x3f4ebf22, 0xbf5c3f0e, 0x3f67bef1, 0xbf18bf35, 0x3eac3f62, 0xbd49bf7b, 0xbe793f7f, 0x3f04bf6d, 0xbf3e3f46,
    0x3f67bf0e, 0xbf7d3e95, 0xbe163f80, 0x3edbbf75, 0xbf2c3f55, 0x3f5cbf22, 0xbf783ec4, 0x3f80bdc9, 0xbf71be48, 0x3f4e3ef1,
    0xbf4e3f35, 0x3f71bef1, 0xbf803e48, 0x3f783dc9, 0xbf5cbec4, 0x3f2c3f22, 0xbedbbf55, 0x3e163f75, 0x3f7d0000, 0xbf67be95,
    0x3f3e3f0e, 0xbf04bf46, 0x3e793f6d, 0x3d49bf7f, 0xbeac3f7b, 0x3f18bf62, 0xbf5cbec4, 0x3f2c3f22, 0xbedbbf55, 0x3e163f75,
    0xbf4e3f35, 0x3f71bef1, 0xbf803e48, 0x3f783dc9, 0x3e793f6d, 0x3d49bf7f, 0xbeac3f7b, 0x3f18bf62, 0x3f7d0000, 0xbf67be95,
    0x3f3e3f0e, 0xbf04bf46, 0xbf043f6d, 0x3f3ebf46, 0xbf673f0e, 0x3f7dbe95, 0x3f183f35, 0xbeacbf62, 0x3d493f7b, 0x3e79bf7f,
    0x3f78bec4, 0xbf803dc9, 0x3f713e48, 0xbf4ebef1, 0x3e16bf80, 0xbedb3f75, 0x3f2cbf55, 0xbf5c3f22, 0xbf780000, 0x3f3e3ef1,
    0xbeacbf55, 0xbe163f7f, 0x3f18bf6d, 0xbf673f22, 0x3f80be48, 0xbf5cbe95, 0x3f043f35, 0xbd49bf75, 0xbedb3f7b, 0x3f4ebf46,
    0xbf7d3ec4, 0x3f713dc9, 0xbf2cbf0e, 0x3e793f62, 0xbe793f80, 0x3f2cbf62, 0xbf713f0e, 0x3f7dbdc9, 0xbf4ebec4, 0x3edb3f46,
    0x3d49bf7b, 0xbf043f75, 0x3f5cbf35, 0xbf803e95, 0x3f673e48, 0xbf18bf22, 0x3e163f6d, 0x3eacbf7f, 0xbf3e3f55, 0x3f78bef1,
    0xbf4ebec4, 0x3edb3f46, 0x3d49bf7b, 0xbf043f75, 0xbe793f80, 0x3f2cbf62, 0xbf713f0e, 0x3f7dbdc9, 0x3e163f6d, 0x3eacbf7f,
    0xbf3e3f55, 0x3f78bef1, 0x3f5cbf35, 0xbf803e95, 0x3f673e48, 0xbf18bf22, 0xbf183f6d, 0x3f67bf22, 0xbf803e48, 0x3f5c3e95,
    0x3f780000, 0xbf3ebef1, 0x3eac3f55, 0x3e16bf7f, 0x3f7dbec4, 0xbf71bdc9, 0x3f2c3f0e, 0xbe79bf62, 0xbf04bf35, 0x3d493f75,
    0x3edbbf7b, 0xbf4e3f46, 0x3f67bf35, 0xbf783dc9, 0x3f183f0e, 0x3d49bf75, 0xbf2c3f6d, 0x3f7dbef1, 0xbf5cbe48, 0x3eac3f46,
    0x3f710000, 0xbf04bf22, 0xbe163f7b, 0x3f3ebf62, 0xbf803ec4, 0x3f4e3e95, 0xbe79bf55, 0xbedb3f7f, 0x3edb3f35, 0x3e79bf7f,
    0xbf4e3f55, 0x3f80be95, 0xbf3ebec4, 0x3e163f62, 0x3f04bf7b, 0xbf713f22, 0xbeac3f80, 0x3f5cbf46, 0xbf7d3e48, 0x3f2c3ef1,
    0xbd49bf6d, 0xbf183f75, 0x3f78bf0e, 0xbf67bdc9, 0x3f3e3ec4, 0xbe16bf62, 0xbf043f7b, 0x3f71bf22, 0xbedbbf35, 0xbe793f7f,
    0x3f4ebf55, 0xbf803e95, 0x3d493f6d, 0x3f18bf75, 0xbf783f0e, 0x3f673dc9, 0x3eacbf80, 0xbf5c3f46, 0x3f7dbe48, 0xbf2cbef1,
    0xbf2c3f6d, 0x3f7dbef1, 0xbf5cbe48, 0x3eac3f46, 0x3f67bf35, 0xbf783dc9, 0x3f183f0e, 0x3d49bf75, 0xbf803ec4, 0x3f4e3e95,
    0xbe79bf55, 0xbedb3f7f, 0x3f710000, 0xbf04bf22, 0xbe163f7b, 0x3f3ebf62, 0xbedb3f80, 0x3f78bf22, 0xbf4ebe48, 0x3d493f62,
    0x3f3ebf6d, 0xbf7d3e95, 0x3f043f0e, 0x3eacbf7f, 0xbf713f35, 0x3f5c3dc9, 0xbe16bf55, 0xbf2c3f75, 0x3f80bec4, 0xbf18bef1,
    0xbe793f7b, 0x3f67bf46, 0xbf670000, 0x3e793f46, 0x3f18bf7b, 0xbf803ef1, 0x3f2c3ec4, 0x3e16bf75, 0xbf5c3f55, 0x3f71bdc9,
    0xbeacbf35, 0xbf043f7f, 0x3f7dbf0e, 0xbf3ebe95, 0xbd493f6d, 0x3f4ebf62, 0xbf783e48, 0x3edb3f22, 0xbf2cbec4, 0xbe163f75,
    0x3f5cbf55, 0xbf713dc9, 0x3f670000, 0xbe79bf46, 0xbf183f7b, 0x3f80bef1, 0x3d49bf6d, 0xbf4e3f62, 0x3f78be48, 0xbedbbf22,
    0x3eac3f35, 0x3f04bf7f, 0xbf7d3f0e, 0x3f3e3e95, 0x3f3ebf6d, 0xbf7d3e95, 0x3f043f0e, 0x3eacbf7f, 0xbedb3f80, 0x3f78bf22,
    0xbf4ebe48, 0x3d493f62, 0x3f80bec4, 0xbf18bef1, 0xbe793f7b, 0x3f67bf46, 0xbf713f35, 0x3f5c3dc9, 0xbe16bf55, 0xbf2c3f75,
    0xbe79bf35, 0xbf3e3f75, 0x3f71be48, 0xbe16bf46, 0xbf4e3f6d, 0x3f67bdc9, 0xbd49bf55, 0xbf5c3f62, 0xbf043f80, 0x3f80bef1,
    0xbedbbf0e, 0xbf183f7f, 0x3f7dbec4, 0xbeacbf22, 0xbf2c3f7b, 0x3f78be95, 0xbf783f35, 0x3f2c3e95, 0x3eacbf7b, 0xbf7d3f22,
    0x3f183ec4, 0x3edbbf7f, 0xbf803f0e, 0x3f043ef1, 0x3f5c0000, 0x3d49bf62, 0xbf673f55, 0x3f4e3dc9, 0x3e16bf6d, 0xbf713f46,
    0x3f3e3e48, 0x3e79bf75, 0x3f183ec4, 0x3edbbf7f, 0xbf803f0e, 0x3f043ef1, 0xbf783f35, 0x3f2c3e95, 0x3eacbf7b, 0xbf7d3f22,
    0x3e16bf6d, 0xbf713f46, 0x3f3e3e48, 0x3e79bf75, 0x3f5c0000, 0x3d49bf62, 0xbf673f55, 0x3f4e3dc9, 0x3f4ebf6d, 0xbf673dc9,
    0x3d493f55, 0x3f5cbf62, 0x3e793f35, 0x3f3ebf75, 0xbf713e48, 0x3e163f46, 0xbf7d3ec4, 0x3eac3f22, 0x3f2cbf7b, 0xbf783e95,
    0x3f04bf80, 0xbf803ef1, 0x3edb3f0e, 0x3f18bf7f, 0xbf4e0000, 0xbeac3f75, 0x3f80bf0e, 0xbe79bf22, 0xbf5c3f6d, 0x3f3e3dc9,
    0x3edbbf7b, 0xbf7d3ef1, 0x3e163f35, 0x3f67bf62, 0xbf2cbe48, 0xbf043f7f, 0x3f78bec4, 0xbd49bf46, 0xbf713f55, 0x3f183e95,
    0xbf183f80, 0x3f71be95, 0x3d49bf55, 0xbf783f46, 0x3f043ec4, 0x3f2cbf7f, 0xbf673e48, 0xbe163f62, 0x3f7dbf35, 0xbedbbef1,
    0xbf3e3f7b, 0x3f5cbdc9, 0x3e79bf6d, 0xbf803f22, 0x3eac3f0e, 0x3f4ebf75, 0x3f043ec4, 0x3f2cbf7f, 0xbf673e48, 0xbe163f62,
    0xbf183f80, 0x3f71be95, 0x3d49bf55, 0xbf783f46, 0x3e79bf6d, 0xbf803f22, 0x3eac3f0e, 0x3f4ebf75, 0x3f7dbf35, 0xbedbbef1,
    0xbf3e3f7b, 0x3f5cbdc9, 0x3f5cbf6d, 0xbf3ebdc9, 0xbedb3f7b, 0x3f7dbef1, 0x3f4e0000, 0x3eacbf75, 0xbf803f0e, 0x3e793f22,
    0xbf783ec4, 0x3d493f46, 0x3f71bf55, 0xbf18be95, 0xbe16bf35, 0xbf673f62, 0x3f2c3e48, 0x3f04bf7f, 0x3f80bf35, 0xbe16bf22,
    0xbf783f55, 0x3eac3ef1, 0x3f67bf6d, 0xbf04be95, 0xbf4e3f7b, 0x3f2c3dc9, 0x3f3e0000, 0x3f18bf7f, 0xbf5c3e48, 0xbedb3f75,
    0x3f71bec4, 0x3e79bf62, 0xbf7d3f0e, 0xbd493f46, 0x3d493f35, 0x3f7dbf46, 0xbe79bf0e, 0xbf713f62, 0x3edb3ec4, 0x3f5cbf75,
    0xbf18be48, 0xbf3e3f7f, 0xbf2c3f80, 0x3f4ebdc9, 0x3f04bf7b, 0xbf673e95, 0xbeac3f6d, 0x3f78bef1, 0x3e16bf55, 0xbf803f22,
    0xbedbbec4, 0xbf5c3f75, 0x3f183e48, 0x3f3ebf7f, 0xbd49bf35, 0xbf7d3f46, 0x3e793f0e, 0x3f71bf62, 0x3eacbf6d, 0xbf783ef1,
    0xbe163f55, 0x3f80bf22, 0x3f2cbf80, 0xbf4e3dc9, 0xbf043f7b, 0x3f67be95, 0x3f67bf6d, 0xbf04be95, 0xbf4e3f7b, 0x3f2c3dc9,
    0x3f80bf35, 0xbe16bf22, 0xbf783f55, 0x3eac3ef1, 0x3f71bec4, 0x3e79bf62, 0xbf7d3f0e, 0xbd493f46, 0x3f3e0000, 0x3f18bf7f,
    0xbf5c3e48, 0xbedb3f75, 0xbf3e3f80, 0x3f183dc9, 0x3f5cbf7b, 0xbedbbe95, 0xbf713f6d, 0x3e793ef1, 0x3f7dbf55, 0xbd49bf22,
    0xbf803f35, 0xbe163f46, 0x3f78bf0e, 0x3eacbf62, 0xbf673ec4, 0xbf043f75, 0x3f4ebe48, 0x3f2cbf7f, 0xbf2c0000, 0xbf4e3f7f,
    0x3f043e48, 0x3f67bf75, 0xbeacbec4, 0xbf783f62, 0x3e163f0e, 0x3f80bf46, 0x3d49bf35, 0xbf7d3f22, 0xbe793f55, 0x3f71bef1,
    0x3edbbf6d, 0xbf5c3e95, 0xbf183f7b, 0x3f3ebdc9, 0x3eac3ec4, 0x3f78bf62, 0xbe16bf0e, 0xbf803f46, 0x3f2c0000, 0x3f4ebf7f,
    0xbf04be48, 0xbf673f75, 0xbedb3f6d, 0x3f5cbe95, 0x3f18bf7b, 0xbf3e3dc9, 0xbd493f35, 0x3f7dbf22, 0x3e79bf55, 0xbf713ef1,
    0xbf713f6d, 0x3e793ef1, 0x3f7dbf55, 0xbd49bf22, 0xbf3e3f80, 0x3f183dc9, 0x3f5cbf7b, 0xbedbbe95, 0xbf673ec4, 0xbf043f75,
    0x3f4ebe48, 0x3f2cbf7f, 0xbf803f35, 0xbe163f46, 0x3f78bf0e, 0x3eacbf62, 0x3e16bf35, 0xbf673ef1, 0xbf2c3f7b, 0x3f043dc9,
    0x3f78bf6d, 0x3d49bf22, 0xbf713f0e, 0xbf183f75, 0xbf4e3f80, 0x3eac3e95, 0x3f80bf55, 0x3e79bf46, 0xbf5c3ec4, 0xbf3e3f7f,
    0x3edb3e48, 0x3f7dbf62, 0xbf7d3f35, 0xbedb3f62, 0x3f3ebe48, 0x3f5cbf7f, 0xbe79bec4, 0xbf803f46, 0xbeac3f55, 0x3f4ebe95,
    0x3f180000, 0x3f71bf75, 0xbd49bf0e, 0xbf783f22, 0xbf043f6d, 0x3f2cbdc9, 0x3f67bf7b, 0xbe16bef1, 0xbe79bec4, 0xbf803f46,
    0xbeac3f55, 0x3f4ebe95, 0xbf7d3f35, 0xbedb3f62, 0x3f3ebe48, 0x3f5cbf7f, 0xbf043f6d, 0x3f2cbdc9, 0x3f67bf7b, 0xbe16bef1,
    0x3f180000, 0x3f71bf75, 0xbd49bf0e, 0xbf783f22, 0xbf783f6d, 0xbd493f22, 0x3f71bf0e, 0x3f18bf75, 0xbe163f35, 0x3f67bef1,
    0x3f2cbf7b, 0xbf04bdc9, 0x3f5cbec4, 0x3f3ebf7f, 0xbedbbe48, 0xbf7d3f62, 0x3f4ebf80, 0xbeacbe95, 0xbf803f55, 0xbe793f46,
    0xbf040000, 0xbf803f62, 0xbedb3f55, 0x3f18bdc9, 0x3f7dbf6d, 0x3eacbf46, 0xbf2c3e48, 0xbf783f75, 0xbe793f35, 0x3f3ebe95,
    0x3f71bf7b, 0x3e16bf22, 0xbf4e3ec4, 0xbf673f7f, 0xbd493f0e, 0x3f5cbef1, 0xbf5c3f80, 0x3d493ef1, 0x3f67bf0e, 0x3f4ebf7f,
    0xbe16bec4, 0xbf713f22, 0xbf3e3f7b, 0x3e793e95, 0x3f78bf35, 0x3f2cbf75, 0xbeacbe48, 0xbf7d3f46, 0xbf183f6d, 0x3edb3dc9,
    0x3f80bf55, 0x3f04bf62, 0xbe16bec4, 0xbf713f22, 0xbf3e3f7b, 0x3e793e95, 0xbf5c3f80, 0x3d493ef1, 0x3f67bf0e, 0x3f4ebf7f,
    0xbf183f6d, 0x3edb3dc9, 0x3f80bf55, 0x3f04bf62, 0x3f78bf35, 0x3f2cbf75, 0xbeacbe48, 0xbf7d3f46, 0xbf7d3f6d, 0xbeac3f46,
    0x3f2cbe48, 0x3f78bf75, 0x3f040000, 0x3f80bf62, 0x3edbbf55, 0xbf183dc9, 0x3f4ebec4, 0x3f67bf7f, 0x3d49bf0e, 0xbf5c3ef1,
    0x3e79bf35, 0xbf3e3e95, 0xbf713f7b, 0xbe163f22, 0x3f71bf35, 0x3f5cbf7f, 0x3e16bf0e, 0xbf2c3e95, 0xbf803f6d, 0xbf183f62,
    0x3e793e48, 0x3f67bf22, 0x3edb0000, 0x3f78bf46, 0x3f4ebf7b, 0x3d49bef1, 0xbf3e3ec4, 0xbf7d3f75, 0xbf043f55, 0x3eac3dc9,
    0xbeac3f35, 0x3f04bdc9, 0x3f7dbf55, 0x3f3ebf75, 0xbd49bec4, 0xbf4e3ef1, 0xbf783f7b, 0xbedb3f46, 0xbf673f80, 0xbe793f22,
    0x3f18be48, 0x3f80bf62, 0x3f2cbf6d, 0xbe16be95, 0xbf5c3f0e, 0xbf713f7f, 0x3d493ec4, 0x3f4ebef1, 0x3f78bf7b, 0x3edbbf46,
    0x3eacbf35, 0xbf043dc9, 0xbf7d3f55, 0xbf3e3f75, 0xbf2c3f6d, 0x3e163e95, 0x3f5cbf0e, 0x3f71bf7f, 0x3f67bf80, 0x3e79bf22,
    0xbf183e48, 0xbf803f62, 0xbf803f6d, 0xbf183f62, 0x3e793e48, 0x3f67bf22, 0x3f71bf35, 0x3f5cbf7f, 0x3e16bf0e, 0xbf2c3e95,
    0xbf3e3ec4, 0xbf7d3f75, 0xbf043f55, 0x3eac3dc9, 0x3edb0000, 0x3f78bf46, 0x3f4ebf7b, 0x3d49bef1, 0xbf713f80, 0xbf043f46,
    0x3e163e48, 0x3f3ebef1, 0x3f80bf6d, 0x3f4ebf75, 0x3e79bf0e, 0xbedb3dc9, 0xbf673f35, 0xbf783f7f, 0xbf183f55, 0x3d493e95,
    0x3f2cbec4, 0x3f7dbf62, 0x3f5cbf7b, 0x3eacbf22, 0xbeac0000, 0xbf5c3f22, 0xbf7d3f7b, 0xbf2c3f62, 0xbd493ec4, 0x3f18be95,
    0x3f78bf55, 0x3f67bf7f, 0x3edbbf35, 0xbe79bdc9, 0xbf4e3f0e, 0xbf803f75, 0xbf3e3f6d, 0xbe163ef1, 0x3f04be48, 0x3f71bf46,
    0x3d49bec4, 0xbf183e95, 0xbf783f55, 0xbf673f7f, 0x3eac0000, 0x3f5cbf22, 0x3f7dbf7b, 0x3f2cbf62, 0x3f3ebf6d, 0x3e16bef1,
    0xbf043e48, 0xbf713f46, 0xbedb3f35, 0x3e793dc9, 0x3f4ebf0e, 0x3f80bf75, 0x3f80bf6d, 0x3f4ebf75, 0x3e79bf0e, 0xbedb3dc9,
    0xbf713f80, 0xbf043f46, 0x3e163e48, 0x3f3ebef1, 0x3f2cbec4, 0x3f7dbf62, 0x3f5cbf7b, 0x3eacbf22, 0xbf673f35, 0xbf783f7f,
    0xbf183f55, 0x3d493e95, 0x3f04bf35, 0x3d49be95, 0xbedb3e48, 0xbf4e3f22, 0xbf7d3f6d, 0xbf713f7f, 0xbf2c3f55, 0xbe793ef1,
    0xbf783f80, 0xbf3e3f62, 0xbeac3f0e, 0x3e163dc9, 0x3f18bec4, 0x3f67bf46, 0x3f80bf7b, 0x3f5cbf75, 0xbf5c3f35, 0xbf803f75,
    0xbf673f7b, 0xbf183f46, 0xbe163ec4, 0x3eacbdc9, 0x3f3ebf0e, 0x3f78bf62, 0x3e790000, 0x3f2cbef1, 0x3f71bf55, 0x3f7dbf7f,
    0x3f4ebf6d, 0x3edbbf22, 0xbd49be48, 0xbf043e95, 0xbe163ec4, 0x3eacbdc9, 0x3f3ebf0e, 0x3f78bf62, 0xbf5c3f35, 0xbf803f75,
    0xbf673f7b, 0xbf183f46, 0x3f4ebf6d, 0x3edbbf22, 0xbd49be48, 0xbf043e95, 0x3e790000, 0x3f2cbef1, 0x3f71bf55, 0x3f7dbf7f,
    0x3f7dbf6d, 0x3f71bf7f, 0x3f2cbf55, 0x3e79bef1, 0xbf043f35, 0xbd493e95, 0x3edbbe48, 0x3f4ebf22, 0xbf183ec4, 0xbf673f46,
    0xbf803f7b, 0xbf5c3f75, 0x3f78bf80, 0x3f3ebf62, 0x3eacbf0e, 0xbe16bdc9, 0xbe160000, 0xbedb3e95, 0xbf2c3f0e, 0xbf5c3f46,
    0xbf783f6d, 0xbf803f7f, 0xbf713f7b, 0xbf4e3f62, 0xbf183f35, 0xbeac3ef1, 0xbd493e48, 0x3e79bdc9, 0x3f04bec4, 0x3f3ebf22,
    0x3f67bf55, 0x3f7dbf75, 0xbf7d3f80, 0xbf673f75, 0xbf3e3f55, 0xbf043f22, 0xbe793ec4, 0x3d493dc9, 0x3eacbe48, 0x3f18bef1,
    0x3f4ebf35, 0x3f71bf62, 0x3f80bf7b, 0x3f78bf7f, 0x3f5cbf6d, 0x3f2cbf46, 0x3edbbf0e, 0x3e16be95, 0xbe793ec4, 0x3d493dc9,
    0x3eacbe48, 0x3f18bef1, 0xbf7d3f80, 0xbf673f75, 0xbf3e3f55, 0xbf043f22, 0x3f5cbf6d, 0x3f2cbf46, 0x3edbbf0e, 0x3e16be95,
    0x3f4ebf35, 0x3f71bf62, 0x3f80bf7b, 0x3f78bf7f, 0x3f78bf6d, 0x3f80bf7f, 0x3f71bf7b, 0x3f4ebf62, 0x3e160000, 0x3edbbe95,
    0x3f2cbf0e, 0x3f5cbf46, 0xbf043ec4, 0xbf3e3f22, 0xbf673f55, 0xbf7d3f75, 0x3f18bf35, 0x3eacbef1, 0x3d49be48, 0xbe793dc9,
    0x3f3ebf35, 0x3f4ebf46, 0x3f5cbf55, 0x3f67bf62, 0x3f71bf6d, 0x3f78bf75, 0x3f7dbf7b, 0x3f80bf7f, 0x3d490000, 0x3e16bdc9,
    0x3e79be48, 0x3eacbe95, 0x3edbbec4, 0x3f04bef1, 0x3f18bf0e, 0x3f2cbf22, 0xbf2c3f35, 0xbf183f22, 0xbf043f0e, 0xbedb3ef1,
    0xbeac3ec4, 0xbe793e95, 0xbe163e48, 0xbd493dc9, 0xbf803f80, 0xbf7d3f7f, 0xbf783f7b, 0xbf713f75, 0xbf673f6d, 0xbf5c3f62,
    0xbf4e3f55, 0xbf3e3f46, 0x3eacbec4, 0x3e79be95, 0x3e16be48, 0x3d49bdc9, 0x3f2cbf35, 0x3f18bf22, 0x3f04bf0e, 0x3edbbef1,
    0x3f67bf6d, 0x3f5cbf62, 0x3f4ebf55, 0x3f3ebf46, 0x3f80bf80, 0x3f7dbf7f, 0x3f78bf7b, 0x3f71bf75, 0x3f71bf6d, 0x3f78bf75,
    0x3f7dbf7b, 0x3f80bf7f, 0x3f3ebf35, 0x3f4ebf46, 0x3f5cbf55, 0x3f67bf62, 0x3edbbec4, 0x3f04bef1, 0x3f18bf0e, 0x3f2cbf22,
    0x3d490000, 0x3e16bdc9, 0x3e79be48, 0x3eacbe95,
};
__device__ const __align__(128) uint32_t c_ga[1536] = {
    0x00003c80, 0x3bc43c6d, 0x00003c80, 0xbbc4bc6d, 0x00003c80, 0x3c6d3bc4, 0x00003c80, 0xbc6dbbc4, 0x00003c80, 0x3c6dbbc4,
    0x00003c80, 0xbc6d3bc4, 0x00003c80, 0x3bc4bc6d, 0x00003c80, 0xbbc43c6d, 0x3a493c80, 0x3bdb3c67, 0x3bdb3c67, 0xbc3ebc2c,
    0x3b163c7d, 0x3c783b79, 0x3c043c5c, 0xbc7d3b16, 0x3b793c78, 0x3c4ebc18, 0x3c183c4e, 0xbc043c5c, 0x3bac3c71, 0x3a49bc80,
    0x3c2c3c3e, 0x3bac3c71, 0x3ac93c7f, 0x3bf13c62, 0x3c463c22, 0xbc75bb95, 0x3b953c75, 0x3c7f3ac9, 0x3c623bf1, 0xbc463c22,
    0x3bf13c62, 0x3c22bc46, 0x3c753b95, 0x3ac93c7f, 0x3c223c46, 0xbb95bc75, 0x3c7f3ac9, 0x3c623bf1, 0x3b163c7d, 0x3c043c5c,
    0x3c783b79, 0xbc7d3b16, 0x3bdb3c67, 0x3c80ba49, 0x3c80ba49, 0xbbac3c71, 0x3c2c3c3e, 0x3bdbbc67, 0x3c71bbac, 0x3c2c3c3e,
    0x3c5c3c04, 0xbc18bc4e, 0x3c4ebc18, 0x3c78bb79, 0x3b483c7b, 0x3c0e3c55, 0x3c7bbb48, 0xbc553c0e, 0x3c0e3c55, 0x3c7bbb48,
    0x3c55bc0e, 0x3b483c7b, 0x3c553c0e, 0x3b48bc7b, 0x3c0ebc55, 0x3c7b3b48, 0x3c7b3b48, 0xbc55bc0e, 0x3b48bc7b, 0x3c0ebc55,
    0x3b793c78, 0x3c183c4e, 0x3c4ebc18, 0xbc043c5c, 0x3c2c3c3e, 0x3c71bbac, 0x3bdbbc67, 0x3c2c3c3e, 0x3c713bac, 0xba49bc80,
    0xba49bc80, 0x3c67bbdb, 0x3c7dbb16, 0xbc78bb79, 0xbc04bc5c, 0xbb16bc7d, 0x3b953c75, 0x3c223c46, 0x3bf1bc62, 0xbac93c7f,
    0x3c463c22, 0x3c62bbf1, 0xbac9bc7f, 0x3c753b95, 0x3c7f3ac9, 0xbb95bc75, 0xbc22bc46, 0x3bf1bc62, 0x3c62bbf1, 0xbc7f3ac9,
    0xbc75bb95, 0xbc46bc22, 0x3bac3c71, 0x3c2c3c3e, 0x3a49bc80, 0x3bac3c71, 0x3c5c3c04, 0x3c4ebc18, 0xbc18bc4e, 0x3c78bb79,
    0x3c7dbb16, 0xbc04bc5c, 0xbc78bb79, 0xbb16bc7d, 0x3c2cbc3e, 0xbc673bdb, 0xbc673bdb, 0xbc803a49, 0x00003c80, 0x3bc43c6d,
    0x00003c80, 0xbbc4bc6d, 0x00003c80, 0x3c6d3bc4, 0x00003c80, 0xbc6dbbc4, 0x00003c80, 0x3c6dbbc4, 0x00003c80, 0xbc6d3bc4,
    0x00003c80, 0x3bc4bc6d, 0x00003c80, 0xbbc43c6d, 0x3c3e3c2c, 0x3c713bac, 0x3c713bac, 0xbc803a49, 0x3c4e3c18, 0x3c5cbc04,
    0x3c783b79, 0xbc183c4e, 0x3c5c3c04, 0x3b16bc7d, 0x3c7d3b16, 0x3b793c78, 0x3c673bdb, 0xbc2cbc3e, 0x3c803a49, 0x3c673bdb,
    0x3c7fbac9, 0x3c62bbf1, 0x3c22bc46, 0xbb953c75, 0x3c75bb95, 0x3ac9bc7f, 0x3bf1bc62, 0x3c223c46, 0x3c62bbf1, 0xbc46bc22,
    0x3b95bc75, 0x3c7fbac9, 0x3c46bc22, 0xbc753b95, 0x3ac9bc7f, 0x3bf1bc62, 0x3c18bc4e, 0x3b79bc78, 0xbc04bc5c, 0x3c4e3c18,
    0x3bacbc71, 0xbc3ebc2c, 0xbc3ebc2c, 0x3c67bbdb, 0x3a49bc80, 0xbc713bac, 0xbc67bbdb, 0x3a49bc80, 0xbb79bc78, 0xbb163c7d,
    0xbc7dbb16, 0xbc5cbc04, 0xbb48bc7b, 0xbc0ebc55, 0xbc7b3b48, 0x3c55bc0e, 0xbc0ebc55, 0xbc7b3b48, 0xbc553c0e, 0xbb48bc7b,
    0xbc55bc0e, 0xbb483c7b, 0xbc0e3c55, 0xbc7bbb48, 0xbc7bbb48, 0x3c553c0e, 0xbb483c7b, 0xbc0e3c55, 0xbc5cbc04, 0xbc7dbb16,
    0xbb163c7d, 0xbb79bc78, 0xbc80ba49, 0xbbdb3c67, 0x3bac3c71, 0xbc80ba49, 0xbc673bdb, 0x3c3e3c2c, 0x3c3e3c2c, 0xbbac3c71,
    0xbc183c4e, 0x3c5cbc04, 0x3c783b79, 0x3c4e3c18, 0xbc753b95, 0xbc463c22, 0x3c623bf1, 0xbc7fbac9, 0xbc223c46, 0x3bf13c62,
    0x3c7fbac9, 0xbb953c75, 0xbac93c7f, 0x3c75bb95, 0x3c46bc22, 0x3c623bf1, 0x3bf13c62, 0xbac9bc7f, 0x3b95bc75, 0x3c22bc46,
    0xbbdb3c67, 0xba493c80, 0x3c3ebc2c, 0xbbdb3c67, 0x3b793c78, 0x3c7d3b16, 0x3b16bc7d, 0x3c5c3c04, 0x3c4e3c18, 0x3b79bc78,
    0xbc04bc5c, 0x3c18bc4e, 0x3c80ba49, 0xbc71bbac, 0xbc71bbac, 0xbc3ebc2c, 0x00003c80, 0x3bc43c6d, 0x00003c80, 0xbbc4bc6d,
    0x00003c80, 0x3c6d3bc4, 0x00003c80, 0xbc6dbbc4, 0x00003c80, 0x3c6dbbc4, 0x00003c80, 0xbc6d3bc4, 0x00003c80, 0x3bc4bc6d,
    0x00003c80, 0xbbc43c6d, 0x3c80ba49, 0x3c67bbdb, 0x3c67bbdb, 0xbc2c3c3e, 0x3c7dbb16, 0x3b79bc78, 0x3c5cbc04, 0x3b163c7d,
    0x3c78bb79, 0xbc18bc4e, 0x3c4ebc18, 0x3c5c3c04, 0x3c71bbac, 0xbc80ba49, 0x3c3ebc2c, 0x3c71bbac, 0xbac9bc7f, 0xbbf1bc62,
    0xbc46bc22, 0x3c753b95, 0xbb95bc75, 0xbc7fbac9, 0xbc62bbf1, 0x3c46bc22, 0xbbf1bc62, 0xbc223c46, 0xbc75bb95, 0xbac9bc7f,
    0xbc22bc46, 0x3b953c75, 0xbc7fbac9, 0xbc62bbf1, 0xbc7d3b16, 0xbc5c3c04, 0xbb793c78, 0xbb16bc7d, 0xbc673bdb, 0x3a493c80,
    0x3a493c80, 0xbc71bbac, 0xbc3e3c2c, 0x3c673bdb, 0x3bac3c71, 0xbc3e3c2c, 0xbc043c5c, 0x3c4ebc18, 0x3c183c4e, 0x3b793c78,
    0x3b483c7b, 0x3c0e3c55, 0x3c7bbb48, 0xbc553c0e, 0x3c0e3c55, 0x3c7bbb48, 0x3c55bc0e, 0x3b483c7b, 0x3c553c0e, 0x3b48bc7b,
    0x3c0ebc55, 0x3c7b3b48, 0x3c7b3b48, 0xbc55bc0e, 0x3b48bc7b, 0x3c0ebc55, 0x3c78bb79, 0x3c4ebc18, 0xbc18bc4e, 0x3c5c3c04,
    0x3c3ebc2c, 0xbbacbc71, 0xbc67bbdb, 0x3c3ebc2c, 0x3bacbc71, 0xbc803a49, 0xbc803a49, 0xbbdbbc67, 0xbb16bc7d, 0xbb793c78,
    0xbc5c3c04, 0xbc7d3b16, 0xbb95bc75, 0xbc22bc46, 0xbbf13c62, 0x3ac9bc7f, 0xbc46bc22, 0xbc623bf1, 0x3ac93c7f, 0xbc75bb95,
    0xbc7fbac9, 0x3b953c75, 0x3c223c46, 0xbbf13c62, 0xbc623bf1, 0x3c7fbac9, 0x3c753b95, 0x3c463c22, 0xbc713bac, 0xbc3e3c2c,
    0x3c803a49, 0xbc713bac, 0xbc043c5c, 0x3c183c4e, 0x3c4ebc18, 0x3b793c78, 0x3b163c7d, 0x3c5cbc04, 0x3b79bc78, 0x3c7dbb16,
    0x3c3e3c2c, 0xbbdbbc67, 0xbbdbbc67, 0xba49bc80, 0x00003c80, 0x3bc43c6d, 0x00003c80, 0xbbc4bc6d, 0x00003c80, 0x3c6d3bc4,
    0x00003c80, 0xbc6dbbc4, 0x00003c80, 0x3c6dbbc4, 0x00003c80, 0xbc6d3bc4, 0x00003c80, 0x3bc4bc6d, 0x00003c80, 0xbbc43c6d,
    0x3c2cbc3e, 0x3bacbc71, 0x3bacbc71, 0x3a493c80, 0x3c18bc4e, 0xbc04bc5c, 0x3b79bc78, 0x3c4e3c18, 0x3c04bc5c, 0xbc7dbb16,
    0x3b16bc7d, 0x3c78bb79, 0x3bdbbc67, 0xbc3e3c2c, 0x3a49bc80, 0x3bdbbc67, 0xbc7f3ac9, 0xbc623bf1, 0xbc223c46, 0x3b95bc75,
    0xbc753b95, 0xbac93c7f, 0xbbf13c62, 0xbc22bc46, 0xbc623bf1, 0x3c463c22, 0xbb953c75, 0xbc7f3ac9, 0xbc463c22, 0x3c75bb95,
    0xbac93c7f, 0xbbf13c62, 0x3c4e3c18, 0x3c783b79, 0x3c5cbc04, 0xbc183c4e, 0x3c713bac, 0x3c2cbc3e, 0x3c2cbc3e, 0x3bdb3c67,
    0x3c803a49, 0xbbacbc71, 0x3bdbbc67, 0x3c803a49, 0x3c78bb79, 0xbc7dbb16, 0x3b16bc7d, 0x3c04bc5c, 0xbb48bc7b, 0xbc0ebc55,
    0xbc7b3b48, 0x3c55bc0e, 0xbc0ebc55, 0xbc7b3b48, 0xbc553c0e, 0xbb48bc7b, 0xbc55bc0e, 0xbb483c7b, 0xbc0e3c55, 0xbc7bbb48,
    0xbc7bbb48, 0x3c553c0e, 0xbb483c7b, 0xbc0e3c55, 0xbc043c5c, 0xbb163c7d, 0x3c7d3b16, 0xbc783b79, 0xba493c80, 0x3c673bdb,
    0x3c71bbac, 0xba493c80, 0x3bdb3c67, 0x3c2cbc3e, 0x3c2cbc3e, 0x3c713bac, 0x3c4e3c18, 0xbc04bc5c, 0x3b79bc78, 0x3c18bc4e,
    0x3c75bb95, 0x3c46bc22, 0xbc62bbf1, 0x3c7f3ac9, 0x3c22bc46, 0xbbf1bc62, 0xbc7f3ac9, 0x3b95bc75, 0x3ac9bc7f, 0xbc753b95,
    0xbc463c22, 0xbc62bbf1, 0xbbf1bc62, 0x3ac93c7f, 0xbb953c75, 0xbc223c46, 0xbc67bbdb, 0xbc80ba49, 0x3c2c3c3e, 0xbc67bbdb,
    0xbc783b79, 0xbb163c7d, 0x3c7d3b16, 0xbc043c5c, 0xbc183c4e, 0x3c783b79, 0x3c5cbc04, 0x3c4e3c18, 0x3a493c80, 0x3bacbc71,
    0x3bacbc71, 0x3c2cbc3e, 0x3c353c35, 0x3c6d3bc4, 0x3c353c35, 0xbc6dbbc4, 0x3c35bc35, 0xbbc4bc6d, 0x3c35bc35, 0x3bc43c6d,
    0xbc35bc35, 0xbbc43c6d, 0xbc35bc35, 0x3bc4bc6d, 0xbc353c35, 0x3c6dbbc4, 0xbc353c35, 0xbc6d3bc4, 0x3c3e3c2c, 0x3c713bac,
    0x3c713bac, 0xbc803a49, 0x3c18bc4e, 0xbc04bc5c, 0x3b79bc78, 0x3c4e3c18, 0xbc5cbc04, 0xbb163c7d, 0xbc7dbb16, 0xbb79bc78,
    0xbbdb3c67, 0x3c3ebc2c, 0xba493c80, 0xbbdb3c67, 0x3c463c22, 0x3c753b95, 0x3c7fbac9, 0xbc623bf1, 0x3bf1bc62, 0xbc22bc46,
    0xbb95bc75, 0x3c7f3ac9, 0xbc75bb95, 0x3ac93c7f, 0xbc623bf1, 0xbc46bc22, 0xbac93c7f, 0x3bf1bc62, 0x3c223c46, 0x3b953c75,
    0x3c4e3c18, 0x3c783b79, 0x3c5cbc04, 0xbc183c4e, 0x3bacbc71, 0xbc3ebc2c, 0xbc3ebc2c, 0x3c67bbdb, 0xbc80ba49, 0x3bac3c71,
    0xbbdb3c67, 0xbc80ba49, 0x3b793c78, 0x3b16bc7d, 0x3c7d3b16, 0x3c5c3c04, 0x3c553c0e, 0x3c7b3b48, 0x3c0ebc55, 0xbb483c7b,
    0x3b48bc7b, 0xbc55bc0e, 0xbc7bbb48, 0x3c0ebc55, 0xbc7b3b48, 0x3c0e3c55, 0x3b483c7b, 0xbc553c0e, 0x3c0e3c55, 0xbb48bc7b,
    0x3c55bc0e, 0x3c7bbb48, 0x3c5c3c04, 0x3c7d3b16, 0x3b16bc7d, 0x3b793c78, 0x3a49bc80, 0xbc67bbdb, 0xbc713bac, 0x3a49bc80,
    0xbc673bdb, 0x3c3e3c2c, 0x3c3e3c2c, 0xbbac3c71, 0x3c4e3c18, 0xbc04bc5c, 0x3b79bc78, 0x3c18bc4e, 0x3c623bf1, 0x3c7f3ac9,
    0xbb95bc75, 0x3c223c46, 0xbac9bc7f, 0xbc75bb95, 0xbc223c46, 0xbbf1bc62, 0xbc463c22, 0x3c623bf1, 0x3c7f3ac9, 0x3b953c75,
    0x3c753b95, 0xbc46bc22, 0xbbf1bc62, 0xbac9bc7f, 0x3c673bdb, 0x3c803a49, 0xbc2cbc3e, 0x3c673bdb, 0xbb79bc78, 0xbc7dbb16,
    0xbb163c7d, 0xbc5cbc04, 0xbc183c4e, 0x3c783b79, 0x3c5cbc04, 0x3c4e3c18, 0x3c80ba49, 0xbc71bbac, 0xbc71bbac, 0xbc3ebc2c,
    0x3c353c35, 0x3c6d3bc4, 0x3c353c35, 0xbc6dbbc4, 0x3c35bc35, 0xbbc4bc6d, 0x3c35bc35, 0x3bc43c6d, 0xbc35bc35, 0xbbc43c6d,
    0xbc35bc35, 0x3bc4bc6d, 0xbc353c35, 0x3c6dbbc4, 0xbc353c35, 0xbc6d3bc4, 0x3c80ba49, 0x3c67bbdb, 0x3c67bbdb, 0xbc2c3c3e,
    0xbb16bc7d, 0xbc78bb79, 0xbc04bc5c, 0x3c7dbb16, 0xbc783b79, 0x3c183c4e, 0xbc4e3c18, 0xbc5cbc04, 0x3bac3c71, 0x3a49bc80,
    0x3c2c3c3e, 0x3bac3c71, 0x3c22bc46, 0x3b95bc75, 0xbac9bc7f, 0x3bf13c62, 0xbc62bbf1, 0xbc463c22, 0xbc753b95, 0x3ac9bc7f,
    0xbb953c75, 0x3c7fbac9, 0x3bf13c62, 0xbc223c46, 0x3c7f3ac9, 0xbc62bbf1, 0x3c46bc22, 0x3c75bb95, 0xbb16bc7d, 0xbc04bc5c,
    0xbc78bb79, 0x3c7dbb16, 0xbc673bdb, 0x3a493c80, 0x3a493c80, 0xbc71bbac, 0x3c2c3c3e, 0x3bdbbc67, 0x3c71bbac, 0x3c2c3c3e,
    0x3c04bc5c, 0xbc4e3c18, 0xbc18bc4e, 0xbb79bc78, 0xbc55bc0e, 0xbc7bbb48, 0xbc0e3c55, 0x3b48bc7b, 0xbb483c7b, 0x3c553c0e,
    0x3c7b3b48, 0xbc0e3c55, 0x3c7bbb48, 0xbc0ebc55, 0xbb48bc7b, 0x3c55bc0e, 0xbc0ebc55, 0x3b483c7b, 0xbc553c0e, 0xbc7b3b48,
    0xbc783b79, 0xbc4e3c18, 0x3c183c4e, 0xbc5cbc04, 0x3c2c3c3e, 0x3c71bbac, 0x3bdbbc67, 0x3c2c3c3e, 0x3bacbc71, 0xbc803a49,
    0xbc803a49, 0xbbdbbc67, 0xbc7d3b16, 0x3c783b79, 0x3c043c5c, 0x3b163c7d, 0xbbf13c62, 0xbac93c7f, 0x3c75bb95, 0xbc463c22,
    0x3c7fbac9, 0x3b95bc75, 0xbc46bc22, 0x3c62bbf1, 0xbc22bc46, 0xbbf13c62, 0xbac93c7f, 0xbc753b95, 0xbb953c75, 0x3c22bc46,
    0x3c62bbf1, 0x3c7fbac9, 0x3bac3c71, 0x3c2c3c3e, 0x3a49bc80, 0x3bac3c71, 0x3c04bc5c, 0xbc18bc4e, 0xbc4e3c18, 0xbb79bc78,
    0xbc7d3b16, 0x3c043c5c, 0x3c783b79, 0x3b163c7d, 0x3c3e3c2c, 0xbbdbbc67, 0xbbdbbc67, 0xba49bc80, 0x3c353c35, 0x3c6d3bc4,
    0x3c353c35, 0xbc6dbbc4, 0x3c35bc35, 0xbbc4bc6d, 0x3c35bc35, 0x3bc43c6d, 0xbc35bc35, 0xbbc43c6d, 0xbc35bc35, 0x3bc4bc6d,
    0xbc353c35, 0x3c6dbbc4, 0xbc353c35, 0xbc6d3bc4, 0x3c2cbc3e, 0x3bacbc71, 0x3bacbc71, 0x3a493c80, 0xbc4ebc18, 0xbc5c3c04,
    0xbc78bb79, 0x3c18bc4e, 0xbc043c5c, 0x3c7d3b16, 0xbb163c7d, 0xbc783b79, 0x3c673bdb, 0xbc2cbc3e, 0x3c803a49, 0x3c673bdb,
    0xbc46bc22, 0xbc75bb95, 0xbc7f3ac9, 0x3c62bbf1, 0xbbf13c62, 0x3c223c46, 0x3b953c75, 0xbc7fbac9, 0x3c753b95, 0xbac9bc7f,
    0x3c62bbf1, 0x3c463c22, 0x3ac9bc7f, 0xbbf13c62, 0xbc22bc46, 0xbb95bc75, 0xbc183c4e, 0xbb793c78, 0x3c043c5c, 0xbc4ebc18,
    0x3c713bac, 0x3c2cbc3e, 0x3c2cbc3e, 0x3bdb3c67, 0x3a49bc80, 0xbc713bac, 0xbc67bbdb, 0x3a49bc80, 0xbc783b79, 0x3c7d3b16,
    0xbb163c7d, 0xbc043c5c, 0x3c553c0e, 0x3c7b3b48, 0x3c0ebc55, 0xbb483c7b, 0x3b48bc7b, 0xbc55bc0e, 0xbc7bbb48, 0x3c0ebc55,
    0xbc7b3b48, 0x3c0e3c55, 0x3b483c7b, 0xbc553c0e, 0x3c0e3c55, 0xbb48bc7b, 0x3c55bc0e, 0x3c7bbb48, 0x3c04bc5c, 0x3b16bc7d,
    0xbc7dbb16, 0x3c78bb79, 0xbc80ba49, 0xbbdb3c67, 0x3bac3c71, 0xbc80ba49, 0x3bdb3c67, 0x3c2cbc3e, 0x3c2cbc3e, 0x3c713bac,
    0x3c18bc4e, 0xbc5c3c04, 0xbc78bb79, 0xbc4ebc18, 0xbc62bbf1, 0xbc7fbac9, 0x3b953c75, 0xbc22bc46, 0x3ac93c7f, 0x3c753b95,
    0x3c22bc46, 0x3bf13c62, 0x3c46bc22, 0xbc62bbf1, 0xbc7fbac9, 0xbb95bc75, 0xbc75bb95, 0x3c463c22, 0x3bf13c62, 0x3ac93c7f,
    0xbbdb3c67, 0xba493c80, 0x3c3ebc2c, 0xbbdb3c67, 0x3c78bb79, 0x3b16bc7d, 0xbc7dbb16, 0x3c04bc5c, 0xbc4ebc18, 0xbb793c78,
    0x3c043c5c, 0xbc183c4e, 0x3a493c80, 0x3bacbc71, 0x3bacbc71, 0x3c2cbc3e, 0x3c353c35, 0x3c6d3bc4, 0x3c353c35, 0xbc6dbbc4,
    0x3c35bc35, 0xbbc4bc6d, 0x3c35bc35, 0x3bc43c6d, 0xbc35bc35, 0xbbc43c6d, 0xbc35bc35, 0x3bc4bc6d, 0xbc353c35, 0x3c6dbbc4,
    0xbc353c35, 0xbc6d3bc4, 0xba49bc80, 0xbbdbbc67, 0xbbdbbc67, 0x3c3e3c2c, 0xbc7d3b16, 0xbb793c78, 0xbc5c3c04, 0xbb16bc7d,
    0x3b793c78, 0x3c4ebc18, 0x3c183c4e, 0xbc043c5c, 0x3c71bbac, 0xbc80ba49, 0x3c3ebc2c, 0x3c71bbac, 0xbc223c46, 0xbb953c75,
    0x3ac93c7f, 0xbbf1bc62, 0x3c623bf1, 0x3c46bc22, 0x3c75bb95, 0xbac93c7f, 0x3b95bc75, 0xbc7f3ac9, 0xbbf1bc62, 0x3c22bc46,
    0xbc7fbac9, 0x3c623bf1, 0xbc463c22, 0xbc753b95, 0x3c7dbb16, 0x3c5cbc04, 0x3b79bc78, 0x3b163c7d, 0xbbdbbc67, 0xbc803a49,
    0xbc803a49, 0x3bacbc71, 0xbc3e3c2c, 0x3c673bdb, 0x3bac3c71, 0xbc3e3c2c, 0x3c5c3c04, 0xbc18bc4e, 0x3c4ebc18, 0x3c78bb79,
    0xbc55bc0e, 0xbc7bbb48, 0xbc0e3c55, 0x3b48bc7b, 0xbb483c7b, 0x3c553c0e, 0x3c7b3b48, 0xbc0e3c55, 0x3c7bbb48, 0xbc0ebc55,
    0xbb48bc7b, 0x3c55bc0e, 0xbc0ebc55, 0x3b483c7b, 0xbc553c0e, 0xbc7b3b48, 0x3b793c78, 0x3c183c4e, 0x3c4ebc18, 0xbc043c5c,
    0x3c3ebc2c, 0xbbacbc71, 0xbc67bbdb, 0x3c3ebc2c, 0xbc71bbac, 0x3a493c80, 0x3a493c80, 0xbc673bdb, 0x3b163c7d, 0x3b79bc78,
    0x3c5cbc04, 0x3c7dbb16, 0x3bf1bc62, 0x3ac9bc7f, 0xbc753b95, 0x3c46bc22, 0xbc7f3ac9, 0xbb953c75, 0x3c463c22, 0xbc623bf1,
    0x3c223c46, 0x3bf1bc62, 0x3ac9bc7f, 0x3c75bb95, 0x3b95bc75, 0xbc223c46, 0xbc623bf1, 0xbc7f3ac9, 0xbc713bac, 0xbc3e3c2c,
    0x3c803a49, 0xbc713bac, 0x3c5c3c04, 0x3c4ebc18, 0xbc18bc4e, 0x3c78bb79, 0xbb16bc7d, 0xbc5c3c04, 0xbb793c78, 0xbc7d3b16,
    0xbc2c3c3e, 0x3c67bbdb, 0x3c67bbdb, 0x3c80ba49, 0x3c800000, 0x3c6dbbc4, 0x3c800000, 0xbc6d3bc4, 0xbc800000, 0xbbc43c6d,
    0xbc800000, 0x3bc4bc6d, 0x3c800000, 0xbbc4bc6d, 0x3c800000, 0x3bc43c6d, 0xbc800000, 0x3c6d3bc4, 0xbc800000, 0xbc6dbbc4,
    0x3c80ba49, 0x3c67bbdb, 0x3c67bbdb, 0xbc2c3c3e, 0xbc7d3b16, 0xbb793c78, 0xbc5c3c04, 0xbb16bc7d, 0x3c78bb79, 0xbc18bc4e,
    0x3c4ebc18, 0x3c5c3c04, 0xbc713bac, 0x3c803a49, 0xbc3e3c2c, 0xbc713bac, 0x3c7fbac9, 0x3c62bbf1, 0x3c22bc46, 0xbb953c75,
    0xbc753b95, 0xbac93c7f, 0xbbf13c62, 0xbc22bc46, 0x3c62bbf1, 0xbc46bc22, 0x3b95bc75, 0x3c7fbac9, 0xbc463c22, 0x3c75bb95,
    0xbac93c7f, 0xbbf13c62, 0x3c7dbb16, 0x3c5cbc04, 0x3b79bc78, 0x3b163c7d, 0xbc673bdb, 0x3a493c80, 0x3a493c80, 0xbc71bbac,
    0x3c3ebc2c, 0xbc67bbdb, 0xbbacbc71, 0x3c3ebc2c, 0xbc043c5c, 0x3c4ebc18, 0x3c183c4e, 0x3b793c78, 0x3c7bbb48, 0x3c55bc0e,
    0xbb48bc7b, 0x3c0e3c55, 0xbc553c0e, 0x3b483c7b, 0x3c0e3c55, 0xbc7b3b48, 0x3c0ebc55, 0xbc7bbb48, 0xbc55bc0e, 0x3b48bc7b,
    0xbb483c7b, 0x3c0ebc55, 0x3c7b3b48, 0x3c553c0e, 0x3c78bb79, 0x3c4ebc18, 0xbc18bc4e, 0x3c5c3c04, 0xbc3e3c2c, 0x3bac3c71,
    0x3c673bdb, 0xbc3e3c2c, 0x3bacbc71, 0xbc803a49, 0xbc803a49, 0xbbdbbc67, 0x3b163c7d, 0x3b79bc78, 0x3c5cbc04, 0x3c7dbb16,
    0x3c75bb95, 0x3c46bc22, 0xbc62bbf1, 0x3c7f3ac9, 0xbc223c46, 0x3bf13c62, 0x3c7fbac9, 0xbb953c75, 0x3ac9bc7f, 0xbc753b95,
    0xbc463c22, 0xbc62bbf1, 0x3bf13c62, 0xbac9bc7f, 0x3b95bc75, 0x3c22bc46, 0x3c71bbac, 0x3c3ebc2c, 0xbc80ba49, 0x3c71bbac,
    0xbc043c5c, 0x3c183c4e, 0x3c4ebc18, 0x3b793c78, 0xbb16bc7d, 0xbc5c3c04, 0xbb793c78, 0xbc7d3b16, 0x3c3e3c2c, 0xbbdbbc67,
    0xbbdbbc67, 0xba49bc80, 0x3c800000, 0x3c6dbbc4, 0x3c800000, 0xbc6d3bc4, 0xbc800000, 0xbbc43c6d, 0xbc800000, 0x3bc4bc6d,
    0x3c800000, 0xbbc4bc6d, 0x3c800000, 0x3bc43c6d, 0xbc800000, 0x3c6d3bc4, 0xbc800000, 0xbc6dbbc4, 0x3c2cbc3e, 0x3bacbc71,
    0x3bacbc71, 0x3a493c80, 0xbc183c4e, 0x3c043c5c, 0xbb793c78, 0xbc4ebc18, 0x3c04bc5c, 0xbc7dbb16, 0x3b16bc7d, 0x3c78bb79,
    0xbbdb3c67, 0x3c3ebc2c, 0xba493c80, 0xbbdb3c67, 0xbac9bc7f, 0xbbf1bc62, 0xbc46bc22, 0x3c753b95, 0x3b953c75, 0x3c7f3ac9,
    0x3c623bf1, 0xbc463c22, 0xbbf1bc62, 0xbc223c46, 0xbc75bb95, 0xbac9bc7f, 0x3c223c46, 0xbb95bc75, 0x3c7f3ac9, 0x3c623bf1,
    0xbc4ebc18, 0xbc78bb79, 0xbc5c3c04, 0x3c18bc4e, 0x3c713bac, 0x3c2cbc3e, 0x3c2cbc3e, 0x3bdb3c67, 0xbc80ba49, 0x3bac3c71,
    0xbbdb3c67, 0xbc80ba49, 0x3c78bb79, 0xbc7dbb16, 0x3b16bc7d, 0x3c04bc5c, 0xbc7b3b48, 0xbc553c0e, 0x3b483c7b, 0xbc0ebc55,
    0x3c55bc0e, 0xbb48bc7b, 0xbc0ebc55, 0x3c7bbb48, 0xbc0e3c55, 0x3c7b3b48, 0x3c553c0e, 0xbb483c7b, 0x3b48bc7b, 0xbc0e3c55,
    0xbc7bbb48, 0xbc55bc0e, 0xbc043c5c, 0xbb163c7d, 0x3c7d3b16, 0xbc783b79, 0x3a49bc80, 0xbc67bbdb, 0xbc713bac, 0x3a49bc80,
    0x3bdb3c67, 0x3c2cbc3e, 0x3c2cbc3e, 0x3c713bac, 0xbc4ebc18, 0x3c043c5c, 0xbb793c78, 0xbc183c4e, 0x3b953c75, 0x3c223c46,
    0x3bf1bc62, 0xbac93c7f, 0xbc46bc22, 0xbc623bf1, 0x3ac93c7f, 0xbc75bb95, 0x3c7f3ac9, 0xbb95bc75, 0xbc22bc46, 0x3bf1bc62,
    0xbc623bf1, 0x3c7fbac9, 0x3c753b95, 0x3c463c22, 0x3c673bdb, 0x3c803a49, 0xbc2cbc3e, 0x3c673bdb, 0xbc783b79, 0xbb163c7d,
    0x3c7d3b16, 0xbc043c5c, 0x3c18bc4e, 0xbc78bb79, 0xbc5c3c04, 0xbc4ebc18, 0x3a493c80, 0x3bacbc71, 0x3bacbc71, 0x3c2cbc3e,
    0x3c800000, 0x3c6dbbc4, 0x3c800000, 0xbc6d3bc4, 0xbc800000, 0xbbc43c6d, 0xbc800000, 0x3bc4bc6d, 0x3c800000, 0xbbc4bc6d,
    0x3c800000, 0x3bc43c6d, 0xbc800000, 0x3c6d3bc4, 0xbc800000, 0xbc6dbbc4, 0xba49bc80, 0xbbdbbc67, 0xbbdbbc67, 0x3c3e3c2c,
    0x3b163c7d, 0x3c783b79, 0x3c043c5c, 0xbc7d3b16, 0xbb79bc78, 0xbc4e3c18, 0xbc18bc4e, 0x3c04bc5c, 0x3bac3c71, 0x3a49bc80,
    0x3c2c3c3e, 0x3bac3c71, 0xbc7f3ac9, 0xbc623bf1, 0xbc223c46, 0x3b95bc75, 0x3c75bb95, 0x3ac9bc7f, 0x3bf1bc62, 0x3c223c46,
    0xbc623bf1, 0x3c463c22, 0xbb953c75, 0xbc7f3ac9, 0x3c46bc22, 0xbc753b95, 0x3ac9bc7f, 0x3bf1bc62, 0x3b163c7d, 0x3c043c5c,
    0x3c783b79, 0xbc7d3b16, 0xbbdbbc67, 0xbc803a49, 0xbc803a49, 0x3bacbc71, 0x3c2c3c3e, 0x3bdbbc67, 0x3c71bbac, 0x3c2c3c3e,
    0xbc5cbc04, 0x3c183c4e, 0xbc4e3c18, 0xbc783b79, 0x3c7bbb48, 0x3c55bc0e, 0xbb48bc7b, 0x3c0e3c55, 0xbc553c0e, 0x3b483c7b,
    0x3c0e3c55, 0xbc7b3b48, 0x3c0ebc55, 0xbc7bbb48, 0xbc55bc0e, 0x3b48bc7b, 0xbb483c7b, 0x3c0ebc55, 0x3c7b3b48, 0x3c553c0e,
    0xbb79bc78, 0xbc18bc4e, 0xbc4e3c18, 0x3c04bc5c, 0x3c2c3c3e, 0x3c71bbac, 0x3bdbbc67, 0x3c2c3c3e, 0xbc71bbac, 0x3a493c80,
    0x3a493c80, 0xbc673bdb, 0x3c7dbb16, 0xbc78bb79, 0xbc04bc5c, 0xbb16bc7d, 0xbc753b95, 0xbc463c22, 0x3c623bf1, 0xbc7fbac9,
    0x3c22bc46, 0xbbf1bc62, 0xbc7f3ac9, 0x3b95bc75, 0xbac93c7f, 0x3c75bb95, 0x3c46bc22, 0x3c623bf1, 0xbbf1bc62, 0x3ac93c7f,
    0xbb953c75, 0xbc223c46, 0x3bac3c71, 0x3c2c3c3e, 0x3a49bc80, 0x3bac3c71, 0xbc5cbc04, 0xbc4e3c18, 0x3c183c4e, 0xbc783b79,
    0x3c7dbb16, 0xbc04bc5c, 0xbc78bb79, 0xbb16bc7d, 0xbc2c3c3e, 0x3c67bbdb, 0x3c67bbdb, 0x3c80ba49, 0x3c800000, 0x3c6dbbc4,
    0x3c800000, 0xbc6d3bc4, 0xbc800000, 0xbbc43c6d, 0xbc800000, 0x3bc4bc6d, 0x3c800000, 0xbbc4bc6d, 0x3c800000, 0x3bc43c6d,
    0xbc800000, 0x3c6d3bc4, 0xbc800000, 0xbc6dbbc4, 0xbc3ebc2c, 0xbc71bbac, 0xbc71bbac, 0x3c80ba49, 0x3c4e3c18, 0x3c5cbc04,
    0x3c783b79, 0xbc183c4e, 0xbc5cbc04, 0xbb163c7d, 0xbc7dbb16, 0xbb79bc78, 0x3c673bdb, 0xbc2cbc3e, 0x3c803a49, 0x3c673bdb,
    0x3ac93c7f, 0x3bf13c62, 0x3c463c22, 0xbc75bb95, 0xbb95bc75, 0xbc7fbac9, 0xbc62bbf1, 0x3c46bc22, 0x3bf13c62, 0x3c22bc46,
    0x3c753b95, 0x3ac93c7f, 0xbc22bc46, 0x3b953c75, 0xbc7fbac9, 0xbc62bbf1, 0x3c18bc4e, 0x3b79bc78, 0xbc04bc5c, 0x3c4e3c18,
    0xbbac3c71, 0x3c3e3c2c, 0x3c3e3c2c, 0xbc673bdb, 0x3a49bc80, 0xbc713bac, 0xbc67bbdb, 0x3a49bc80, 0x3b793c78, 0x3b16bc7d,
    0x3c7d3b16, 0x3c5c3c04, 0xbc7b3b48, 0xbc553c0e, 0x3b483c7b, 0xbc0ebc55, 0x3c55bc0e, 0xbb48bc7b, 0xbc0ebc55, 0x3c7bbb48,
    0xbc0e3c55, 0x3c7b3b48, 0x3c553c0e, 0xbb483c7b, 0x3b48bc7b, 0xbc0e3c55, 0xbc7bbb48, 0xbc55bc0e, 0x3c5c3c04, 0x3c7d3b16,
    0x3b16bc7d, 0x3b793c78, 0xbc80ba49, 0xbbdb3c67, 0x3bac3c71, 0xbc80ba49, 0x3c67bbdb, 0xbc3ebc2c, 0xbc3ebc2c, 0x3bacbc71,
    0xbc183c4e, 0x3c5cbc04, 0x3c783b79, 0x3c4e3c18, 0xbb95bc75, 0xbc22bc46, 0xbbf13c62, 0x3ac9bc7f, 0x3c463c22, 0x3c62bbf1,
    0xbac9bc7f, 0x3c753b95, 0xbc7fbac9, 0x3b953c75, 0x3c223c46, 0xbbf13c62, 0x3c62bbf1, 0xbc7f3ac9, 0xbc75bb95, 0xbc46bc22,
    0xbbdb3c67, 0xba493c80, 0x3c3ebc2c, 0xbbdb3c67, 0xbb79bc78, 0xbc7dbb16, 0xbb163c7d, 0xbc5cbc04, 0x3c4e3c18, 0x3b79bc78,
    0xbc04bc5c, 0x3c18bc4e, 0xbc803a49, 0x3c713bac, 0x3c713bac, 0x3c3e3c2c,
};

template <int G = 1024> __device__ __forceinline__ void store_tile_64(const float (&d)[32], uint32_t base, int warp, int lane) {
  const uint32_t rb = base + (warp * 2 + ((lane >> 3) & 1)) * G + (lane & 7) * 128;
#pragma unroll
  for (int j = 0; j < 8; j += 2) {
    const int jj = j + (lane >> 4);
    stsm4(rb + ((jj ^ (lane & 7)) << 4), pack2(d[4 * j], d[4 * j + 1]), pack2(d[4 * j + 2], d[4 * j + 3]),
          pack2(d[4 * j + 4], d[4 * j + 5]), pack2(d[4 * j + 6], d[4 * j + 7]));
  }
}

#define A_XM0 0xEB5C
#define A_XM1 0xDCBC
#define A_REL 0x22910
#define G_WPOLK 12
#define A_LDW 0x242
#define A_W2PF 0
#define A_POLL 0
#define A_X0 1
#define A_FREE 0x3F000
#define A_RELS 0x8A88
#define A_ACQ 0x1511
#define A_DEP 3
#define A_PACE0 1000
#define A_PACE1 A_PACE0
#define A_PACE_N 8
#define G_TMASK 0x0FB0
constexpr int A_IN = 112 * 128, A_OUT = 16384, A_NIN = 5, A_NOUT = 6;
constexpr int A_NREL = __builtin_popcount(A_REL);
constexpr int G_XP = NB1 * 64;
constexpr int G_STAGE = 16384 + 2 * G_XP, G_NST = 5;
constexpr int G_TIN = G_NST * G_STAGE, G_TOUT = G_TIN + 8192, G_SMEM = G_TOUT + 32768 + 1024;
#define G_SLOTS 0x1032410324103210ull
__host__ __device__ constexpr int g_slot(int k) { return (G_SLOTS >> (4 * k)) & 7; }
constexpr uint32_t g_parities() {
  uint32_t m = 0;
  for (int k = 0; k < 16; k++)
    for (int j = 0; j < k; j++)
      if (g_slot(j) == g_slot(k)) m ^= 1u << k;
  return m;
}
constexpr uint32_t G_PAR = g_parities();
constexpr int G_KS = 12;
__device__ __align__(128) int g_cnt[3 * 32];

__device__ __forceinline__ int x_decode(int r, int cta) {
  const int v = r * 64 + ((cta >> 2) << 1) + (cta & 1);
  return cta < 128 ? ((7 - v / 80) << 7) | (v % 80) : ((7 - (r >> 1)) << 7) | (80 + 2 * (cta & 1) + (r & 1));
}
__device__ __forceinline__ uint32_t a_out(int n) {
  const int p = n % A_NOUT;
  return (p < 4 ? (3 + (p >> 1)) * G_STAGE : G_TOUT) + (p & 1) * A_OUT;
}
__device__ __forceinline__ uint32_t x1_addr(int L, int b, uint32_t flips) {
  const int p = L >> 4, sel = (b ^ __popc(L & 15) ^ (flips >> p)) & 1;
  return (p << 21) | (sel << 12) | ((L & 1) << 13) | ((L & 6) << 15) | ((L & 8) << 16);
}
__device__ __forceinline__ uint32_t spread16(int i) { return ((i & 3) << 14) | ((i & 4) << 16) | ((i & 8) << 17); }
constexpr int NPG = 19 + W_SHIFT, NVOTE = 6;
__device__ __forceinline__ uint32_t w_addr(int P, int f, int c, int dhalf, uint32_t flips) {
  return x1_addr(16 * P + (c >> 5) + 2 * (f >> 3), dhalf, flips >> 12) + spread16(2 * f) + (c & 31) * 128;
}
__device__ __forceinline__ void w_store(const CUtensorMap* m, uint32_t src, uint32_t a) {
#pragma unroll
  for (int j = 0; j < 8; j++)
    tma_st5<0>(m, src + j * 2048, ((a & 16383) >> 1) ^ ((__popc(j) & 1) << 11), (j & 3) << 1, (j >> 2) << 1, a >> 20, 0);
}
__device__ __forceinline__ uint32_t read_votes(const int* cnt, int lane, int& side, int v = 0) {
  for (int it = 0; it < (1 << 20) && (__ballot_sync(0xffffffffu, v < NVOTE * 256) & ((2 << NPG) - 2)); it++)
    asm volatile("ld.relaxed.gpu.global.s32 %0, [%1];" : "=r"(v) : "l"(cnt + 32 + lane) : "memory");
  uint32_t smid;
  asm("mov.u32 %0, %%smid;" : "=r"(smid));
  side = (__shfl_sync(0xffffffffu, v, 24 + ((smid >> 5) & 7)) >> (smid & 31)) & 1;
  return __ballot_sync(0xffffffffu, (v & 255) > NVOTE / 2);
}
__device__ __forceinline__ int take_ticket(int* p) {
  int v;
  asm volatile("atom.relaxed.gpu.global.inc.u32 %0, [%1], 0xffffffff;" : "=r"(v) : "l"(p) : "memory");
  return v;
}
__device__ __forceinline__ void send_role(uint32_t dst, uint32_t bar, int v) {
  for (int c = 0; c < 2; c++)
    asm volatile("{\n.reg .b32 a, b;\nmapa.shared::cluster.u32 a, %0, %2;\nmapa.shared::cluster.u32 b, %1, %2;\n"
                 "st.async.shared::cluster.mbarrier::complete_tx::bytes.u32 [a], %3, [b];\n}" ::"r"(dst), "r"(bar), "r"(c), "r"(v) : "memory");
}
struct GMaps {
  CUtensorMap in[5];
  CUtensorMap ws, xs, w, y;
};

__global__ void __cluster_dims__(2, 1, 1) __launch_bounds__(384, 1)
kG(int* __restrict__ cnt, char* __restrict__ x1, char* __restrict__ wt, const __nv_bfloat16* __restrict__ g,
   const __nv_bfloat16* __restrict__ wgt, float* __restrict__ ge, const uint32_t* __restrict__ img, const __grid_constant__ GMaps m) {
  extern __shared__ uint8_t smem_raw[];
  __shared__ __align__(8) uint64_t bars[20 + A_NIN + 2 * A_NOUT + 2 * G_NST + 16 + 2 * A_NREL];
  __shared__ uint16_t tab[128];
  __shared__ uint32_t lat[8], s_role, s_flips;
  const uint32_t sb = pin((s2u(smem_raw) + 1023) & ~1023u);
  const int tid = threadIdx.x, wg = __shfl_sync(0xffffffffu, tid >> 7, 0), t = tid & 127;
  const int warp = __shfl_sync(0xffffffffu, t >> 5, 0), lane = t & 31;
  const int blk = blockIdx.x, hf = blk & 1, page = 1 + blk % NPG;
  const bool spare = blk >= 128, voter = blk >= 128 - NPG * NVOTE && !spare;
  const int nu = spare ? 16 : 18;
  const uint32_t xm = spare ? 0xFFFF : hf ? A_XM1 : A_XM0;
  const uint32_t wf0 = pin(s2u(&bars[0])), xf0 = wf0 + 32, xe0 = xf0 + 128, aof0 = xe0 + 8 * A_NIN, aoe0 = aof0 + 8 * A_NOUT;
  const uint32_t full0 = aoe0 + 8 * A_NOUT, empty0 = full0 + 8 * G_NST;
  const uint32_t sf0 = empty0 + 8 * G_NST, se0 = sf0 + 16, inf0 = se0 + 16, roleb = inf0 + 16, flipb = roleb + 8;
  const uint32_t rel0 = flipb + 8, got0 = rel0 + 8 * A_NREL, acq0 = got0 + 64;
  auto role = [&]() {
    if (spare) return blk;
    mbar_wait(roleb, 0);
    return 2 * (int)*(volatile uint32_t*)&s_role + hf;
  };
  auto flips = [&]() {
    mbar_wait(flipb, 0);
    return *(volatile uint32_t*)&s_flips;
  };
  auto w_unit = [&](int cta) { return (cta & ~3) | (hf << 1) | ((cta >> 1) & 1); };
  auto w_code = [](int w2, int s, int i) { return (-(s < 4) << 16) | ((2 * w2 + (s >> 2)) << 11) | ((s & 3) << 9) | ((i >> 1) << 3) | ((i & 1) << 1); };
  auto in_load = [&](int c, uint32_t dst, uint32_t bar) {
    tma_ld5<1>(dst, &m.in[(c >> 11) & 7], bar, 0, c >> 16, c & 7, (c >> 3) & 63, (c >> 9) & 3);
  };
  if (wg < 2) {
    if (lane == 0) {
      const uint32_t h = blk & 0x59, par = h ^ (h >> 3) ^ (h >> 4) ^ (h >> 6);
      char* p = x1 + (blk << 13) + (((warp ^ par) & 1) << 12) + 3584 + (warp >> 1) * 128;
      if (wg) {
        if (!voter) p += 256;
        else if (page < 12) p += page << 21;
        else p = wt + w_addr(page - 12, warp >> 1, blk >> 1, warp & 1, 0);
      }
      uint32_t c0, c1;
      asm volatile("{\n.reg .u32 v;\n.reg .pred q;\n"
                   "st.global.v4.u32 [%2], {0, 0, 0, 0};\nst.global.v4.u32 [%2 + 16], {0, 0, 0, 0};\n"
                   "mov.u32 %0, %%clock;\nmov.u32 %1, %0;\natom.relaxed.gpu.global.exch.b32 v, [%2], 1;\n"
                   "setp.eq.u32 q, v, 0;\n@q mov.u32 %1, %%clock;\n}\n" : "=r"(c0), "=r"(c1) : "l"(p) : "memory");
      lat[wg * 4 + warp] = c1 - c0;
    }
    __syncwarp();
    if (wg == 0 && hf == 0 && !spare) bar_arrive(10, 160);
    bar_arrive(9, 288);
  }
  if (wg == 2) {
    if (t == 32) {
      mbar_init(wf0 + 24, 1);
      mbar_expect(wf0 + 24, 8192);
      fence_async();
      if (!spare) tma_ld5<1>(sb + 2 * G_STAGE + 3 * 8192, &m.in[1], wf0 + 24, 0, 0, 2 * hf, blk >> 1, 2);
    }
    __syncwarp();
    int votes = 0;
    if (warp == 3 && !voter) asm volatile("ld.relaxed.gpu.global.s32 %0, [%1];" : "=r"(votes) : "l"(cnt + 32 + lane) : "memory");
    asm volatile("setmaxnreg.dec.sync.aligned.u32 40;");
    if (lane == 0 && warp > 0) {
      if (warp == 1) {
        for (int i = 0; i < 3; i++) {
          mbar_init(wf0 + 8 * i, 1);
          mbar_expect(wf0 + 8 * i, 8192);
        }
      } else if (warp == 2) {
        prefetch_map(&m.in[4]);
        for (int i = 0; i < A_NIN + A_NOUT; i++) mbar_init(xe0 + 8 * i, 4);
        for (int i = 0; i < A_NOUT; i++) mbar_init(aoe0 + 8 * i, 1);
      } else {
        for (int i = 0; i < 2; i++) mbar_init(sf0 + 8 * i, 8);
        for (int i = 0; i < 6 + A_NREL; i++) mbar_init(se0 + 8 * i, 1);
        for (int i = 0; i < 3; i++) mbar_expect(inf0 + 8 * i, i < 2 ? 4096 : 4);
      }
      fence_bar_init();
    }
    __syncwarp();
    asm volatile("barrier.cluster.arrive.relaxed.aligned;" ::: "memory");
    int role_w = warp;
    if (role_w == 0) {
      int cta = blk;
      if (hf == 0 && !spare) {
        bar_sync(10, 160);
        const int side = min(lat[0], lat[2]) > min(lat[1], lat[3]);
        if (lane == 0) cta = take_ticket(cnt + 54 + side);
        __syncwarp();
        asm volatile("barrier.cluster.wait.aligned;" ::: "memory");
        cta = 2 * __shfl_sync(0xffffffffu, cta, 0) + side;
        if (cta >= 64) cta = 127 - cta;
        if (lane == 0) send_role(s2u(&s_role), roleb, cta);
        cta *= 2;
      } else {
        asm volatile("barrier.cluster.wait.aligned;" ::: "memory");
        cta = role();
      }
      const int b = (cta >> 1) & 1;
      if (lane == 0 && !spare) {
        const int c = ((cta >> 2) << 1) + hf;
#pragma unroll
        for (int r = 0; r < A_X0; r++) {
          const bool lo = c < 16 * r;
          tma_ld5<1>(sb + r * A_IN, &m.in[4], xf0 + 8 * r, 0, 96 * (c - 16 * r + (lo ? 80 : 0)) - 24, 7 - r + lo, 0, b);
        }
      }
      __syncwarp();
      const uint32_t wm = spare ? 0 : A_LDW | 0x6000;
      const int nw = __popc(wm & ((1 << lane) - 1)), r = lane - nw, np = r + A_NIN - (spare ? A_NIN : A_DEP);
      const bool isw = (wm >> lane) & 1;
      const uint32_t dst = sb + (!isw ? (r % A_NIN) * A_IN : nw < 3 ? 2 * G_STAGE + (2 - nw) * 8192 : G_TIN + (nw - 3) * 4096);
      const uint32_t bf = !isw ? xf0 + 8 * r : nw < 3 ? wf0 + 8 * (2 - nw) : inf0 + 8 * (nw - 3);
      const uint32_t be = isw ? roleb : xe0 + 8 * (np % A_NIN) + ((np / A_NIN - 1) & 1);
      const int xc = x_decode(r, cta);
      const int code = isw ? w_code(nw >= 3, nw < 3 ? 4 - 2 * nw : 10 - nw, w_unit(cta)) : ((96 * (xc & 127) - 24) << 16) | (4 << 11) | (b << 9) | (xc >> 7);
#pragma unroll 1
      for (int p = spare ? 0 : A_X0; p < (spare ? 16 : 15); p++) {
        const int c = __shfl_sync(0xffffffffu, code, p);
        const uint32_t d = __shfl_sync(0xffffffffu, dst, p), f = __shfl_sync(0xffffffffu, bf, p), e = __shfl_sync(0xffffffffu, be, p);
        mbar_wait(e & ~1u, e & 1);
        if (lane == 0) in_load(c, d, f);
        __syncwarp();
      }
      if (!spare) {
        const int bin = cta >> 2, f = 2 * bin + hf;
        if (lane == 0) {
          for (int s = 5; s >= A_W2PF; s--) {
            const int c = w_code(1, s, w_unit(cta));
            asm volatile("cp.async.bulk.prefetch.tensor.5d.L2.global [%0, {0, %1, %2, %3, %4}];" ::"l"(&m.in[(c >> 11) & 7]), "r"(c >> 16), "r"(c & 7), "r"((c >> 3) & 63), "r"((c >> 9) & 3) : "memory");
          }
          prefetch_map(&m.w);
          prefetch_map(&m.y);
          prefetch_map(&m.in[2]);
        }
        const uint32_t xa = x1_addr((21 - lane + 2 * (lane % 3)) * 8 + (f >> 4), b, flips()) + spread16(f);
        const uint32_t wa = w_addr(7 - (lane >> 1), 2 * bin, (lane & 1) * 32, hf, s_flips & ~0xC0000u);
#pragma unroll 1
        for (int k = 0; k < 16; k++) {
          const int st = g_slot(k);
          uint32_t a[3];
#pragma unroll
          for (int th = 0; th < 3; th++) a[th] = __shfl_sync(0xffffffffu, xa, 3 * (k >> 1) + th) ^ ((k & 1) * 0x21000);
          const uint32_t w = __shfl_sync(0xffffffffu, wa, k);
          if ((A_ACQ >> k) & 1) {
            mbar_wait(acq0 + 8 * __popc(A_ACQ & ((1 << k) - 1)), 0);
            asm volatile("fence.proxy.async.global;" ::: "memory");
          }
          mbar_wait(empty0 + 8 * st, (G_PAR >> k) & 1);
          if (lane == 0) {
            const uint32_t base = sb + st * G_STAGE, bar = full0 + 8 * st;
            mbar_expect(bar, G_STAGE);
#pragma unroll
            for (int th = 0; th < 3; th++)
              asm volatile("cp.async.bulk.shared::cluster.global.mbarrier::complete_tx::bytes.multicast::cluster.L2::cache_hint [%0], [%1], %2, [%3], %4, %5;"
                           ::"r"(base + 16384 + hf * G_XP + th * 3584), "l"(x1 + a[th]), "n"(3584), "r"(bar), "h"((uint16_t)3), "l"(policy<1>()) : "memory");
            if (k >= G_WPOLK) tma_ld3<1>(base, &m.w, bar, 0, (w >> 7) & 127, w >> 14);
            else tma_ld3<0>(base, &m.w, bar, 0, (w >> 7) & 127, w >> 14);
          }
          __syncwarp();
        }
        if (blk == 0 && lane == 0) asm volatile("cp.async.bulk.prefetch.L2.global [%0], 14336;" ::"l"(img) : "memory");
      }
    } else if (pin(warp) == 1) {
      if (lane == 0) {
        prefetch_map(&m.ws);
        prefetch_map(&m.xs);
        prefetch_map(&m.in[0]);
        prefetch_map(&m.in[3]);
      }
      __syncwarp();
      asm volatile("barrier.cluster.wait.aligned;" ::: "memory");
      if (lane == 0) {
#pragma unroll 1
        for (int r = 0; r < A_NREL; r++) {
          mbar_wait(rel0 + 8 * r, 0);
          asm volatile("fence.acq_rel.gpu;\nred.relaxed.gpu.global.inc.u32 [%0], 0xffffffff;" ::"l"(cnt + 8 + r) : "memory");
        }
      }
    } else if (warp == 2) {
      asm volatile("barrier.cluster.wait.aligned;" ::: "memory");
      const uint32_t relm = spare ? A_RELS : A_REL;
      const int xr = __popc(xm & ((1 << lane) - 1));
      const uint32_t srcs = sb + a_out(lane), bars = aof0 + 8 * (lane % A_NOUT);
      const uint32_t done = lane < 16 ? bars + 8 * A_NOUT : se0 + 8 * (lane & 1), relb = rel0 + 8 * __popc(relm & ((1 << lane) - 1));
      const int cta = role(), xc = x_decode(xr, cta), q = xc & 127, th = q / 28, wi = lane < 2 ? blk : w_unit(cta);
      int code = (xm >> lane) & 1 ? 0x80000000u + x1_addr(((xc >> 7) * 3 + th) * 8, (cta >> 1) & 1, 0) + (q - 28 * th) * 128
                                  : w_addr(7 - lane + xr, 0, wi >> 1, wi & 1, 0);
      uint32_t fl = 0;
      auto tables = [&]() {
        fl = flips();
        code ^= ((fl >> (((code >> 21) & 15) + (code < 0 ? 0 : 12))) & 1) << 12;
      };
      if (spare) tables();
      uint32_t tnext = clock(), src = __shfl_sync(0xffffffffu, srcs, 0), bar = aof0;
      int c = __shfl_sync(0xffffffffu, code, 0);
#pragma unroll 1
      for (int n = 0; n < nu; n++) {
        mbar_wait(bar, (n >= A_NOUT) ^ (n >= 2 * A_NOUT));
        while ((int)(clock() - tnext) < 0);
        tnext = clock() + (spare ? 0 : n < A_PACE_N ? A_PACE0 : A_PACE1);
        if (lane == n) {
          if (c >= 0) {
            w_store(&m.ws, src, c);
          } else {
#pragma unroll
            for (int j = 0; j < 8; j++)
              tma_st4<0>(&m.xs, src + j * 2048, ((c & 16383) >> 1) ^ ((__popc(j) & 1) << 11) ^ ((j & 1) << 12), (j >> 1) << 2, (c >> 18) & 3, (c >> 20) & 31);
          }
          bulk_commit();
        }
        __syncwarp();
        if (n == 1 && !spare) tables();
        c = __shfl_sync(0xffffffffu, code, n + 1);
        src = __shfl_sync(0xffffffffu, srcs, n + 1);
        bar = __shfl_sync(0xffffffffu, bars, n + 1);
        bulk_wait<0>();
        if (lane == n) {
          mbar_arrive(done);
          if ((relm >> lane) & 1) mbar_arrive(relb);
        }
        __syncwarp();
        if (!spare && (n == 13 || n == 15) && lane < 16) mbar_arrive_cta(empty0 + 8 * ((n - 7) >> 1), lane & 1);
      }
      if (!spare) {
        const int i = w_unit(cta), wc = w_code(1, 5 - lane, i);
        const uint32_t wa = w_addr(7 + W_SHIFT - lane, 0, i >> 1, i & 1, fl);
#pragma unroll 1
        for (int it = 0; it < 8; it++) {
          const uint32_t a = __shfl_sync(0xffffffffu, wa, it), j = it & 1;
          const int c2 = __shfl_sync(0xffffffffu, wc, it);
          mbar_wait(sf0 + 8 * j, (it >> 1) & 1);
          if (lane == 0 && it < 6) {
            mbar_expect(inf0 + 8 * j, 4096);
            in_load(c2, sb + G_TIN + j * 4096, inf0 + 8 * j);
          }
          if (it >= W_SHIFT) mbar_wait(got0 + 8 * (it - W_SHIFT), 0);
          if (lane == 0) {
            w_store(&m.ws, sb + G_TOUT + j * A_OUT, a);
            bulk_commit();
            bulk_wait_read<0>();
            mbar_arrive(se0 + 8 * j);
          }
          __syncwarp();
        }
      }
    } else {
      int side;
      bar_sync(9, 288);
      const int near = min(lat[0], lat[2]) > min(lat[1], lat[3]);
      if (lane == 0 && voter)
        asm volatile("red.relaxed.gpu.global.add.s32 [%0], %1;" ::"l"(cnt + 32 + page), "r"(256 + (near ^ (min(lat[4], lat[6]) > min(lat[5], lat[7])))) : "memory");
      __syncwarp();
      asm volatile("barrier.cluster.wait.aligned;" ::: "memory");
      if (A_POLL && !spare) mbar_wait(roleb, 0);
      const uint32_t fl = read_votes(cnt, lane, side, votes);
      if (lane == 0) {
        s_flips = fl;
        mbar_arrive(flipb);
        uint32_t smid;
        asm("mov.u32 %0, %%smid;" : "=r"(smid));
        if (near) asm volatile("red.relaxed.gpu.global.or.b32 [%0], %1;" ::"l"(cnt + 56 + ((smid >> 5) & 7)), "r"(1 << (smid & 31)) : "memory");
      }
      __syncwarp();
      if (!spare) {
        bool open = lane < 8 - W_SHIFT || (lane >= 8 && lane < 8 + A_NREL);
        int k = 0;
        mbar_wait(rel0, 0);
#pragma unroll 1
        for (int p = 0; p < (1 << 16) && (k < 14 || __any_sync(0xffffffffu, open)); p++) {
          int v;
          asm volatile("ld.relaxed.gpu.global.s32 %0, [%1];" : "=r"(v) : "l"(cnt + (lane & 15)) : "memory");
          while (k < 14 && mbar_test(full0 + 8 * g_slot(k), (G_PAR >> k) & 1)) {
            if (lane == 0) mbar_arrive(empty0 + 8 * g_slot(k));
            if ((k & 1) && lane == 0) asm volatile("red.relaxed.gpu.global.inc.u32 [%0], 0xffffffff;" ::"l"(cnt + (k >> 1)) : "memory");
            k++;
          }
          if (open && v >= (lane < 8 ? 128 : 132)) {
            asm volatile("fence.acquire.gpu;" ::: "memory");
            mbar_arrive(got0 + 8 * lane);
            open = false;
          }
        }
      }
    }
  } else {
    if (lane == 0) {
      const int w8 = 4 * wg + warp;
      for (int i = 0; i < 2; i++) {
        mbar_init(xf0 + 16 * w8 + 8 * i, 1);
        mbar_expect(xf0 + 16 * w8 + 8 * i, A_IN);
      }
      mbar_init(got0 + 8 * w8, 1);
      if (w8 >= 8 - A_NREL) mbar_init(acq0 + 8 * (7 - w8), 1);
      if (w8 < G_NST) {
        mbar_init(full0 + 8 * w8, 1);
        mbar_init(empty0 + 8 * w8, 17);
        mbar_arrive(empty0 + 8 * w8);
      }
      fence_bar_init();
    }
    __syncwarp();
    asm volatile("barrier.cluster.arrive.relaxed.aligned;" ::: "memory");
    if (wg == 1) tab[t] = __bfloat16_as_ushort(__float2bfloat16_rn(-__cosf((float)(t - 64) * 0.04908738521234052f)));
    bar_sync(1, 256);
    asm volatile("setmaxnreg.inc.sync.aligned.u32 232;");
    uint32_t fa[16];
    auto frag = [&](int i, int l) {
      const int f = warp * 16 + (l >> 2) + 8 * (i & 1), r = 8 * (i >> 1) + (l & 3) * 2;
      const int k0 = (f | 1) * r - ((f & 1) << 5);
      return tab[k0 & 127] | ((uint32_t)tab[(k0 + (f | 1)) & 127] << 16);
    };
#pragma unroll
    for (int i = 0; i < 16; i++) fa[i] = i < 4 ? frag(i, lane) : 0;
    reg_fence(fa);
    asm volatile("barrier.cluster.wait.aligned;" ::: "memory");
    int cta = blk, qs = 2 * hf + wg;
#pragma unroll 1
    for (int n = wg; n < nu; n += 2) {
      float e[64];
      if ((n >> 1) == !spare) {
        pdl_launch();
        int l = lane;
        asm volatile("" : "+r"(l));
#pragma unroll
        for (int i = 4; i < 16; i++) fa[i] = frag(i, l);
        reg_fence(fa);
        cta = role();
        if (!spare) qs = ((cta >> 1) & 2) + hf;
      }
      const bool isx = (xm >> n) & 1;
      const int r = __popc(xm & ((1 << n) - 1)), s = 7 - n + r;
      const uint32_t in = isx ? sb + (r % A_NIN) * A_IN : sb + 2 * G_STAGE + s * 4096;
      mbar_wait(isx ? xf0 + 8 * r : wf0 + 8 * (s >> 1), 0);
      if (!isx) {
        wg_fence();
        wgmma_rs_128<1, 1, 1>(e, fa[0], fa[1], fa[2], fa[3], mk_desc(in, 0, 2048, 1024, 1), 0);
        wg_commit();
      } else {
        wg_fence();
#pragma unroll
        for (int k = 0; k < 4; k++)
          wgmma_rs_128<1, 1, 1>(e, fa[4 * k], fa[4 * k + 1], fa[4 * k + 2], fa[4 * k + 3], mk_desc(in, k * 2048, 6144, 1024, 1), k);
        wg_commit();
      }
      wg_wait<0>();
      reg_fence(e);
      if (isx && lane == 0) mbar_arrive(xe0 + 8 * (r % A_NIN));
      if (((A_FREE >> n) & 1) && !spare && lane < 2) mbar_arrive_cta(empty0 + 8 * (__popc(A_FREE & ((1 << n) - 1)) >> 1), lane);
      if (n >= A_NOUT) mbar_wait(aoe0 + 8 * (n % A_NOUT), (n / A_NOUT - 1) & 1);
      const int row = warp * 16 + (lane & 7) + ((lane >> 3) & 1) * 8, hi = lane >> 4;
      const uint32_t rb = sb + a_out(n) + (isx ? row : row + (row & ~7)) * 128, ts = isx ? 8192 : 1024, xr = (lane & 7) ^ (isx ? qs : 0);
#pragma unroll
      for (int j = 0; j < 16; j += 2) {
        const uint32_t tile = isx ? (j >> 2) & 1 : j >> 3, pos = (isx ? (j >> 3) * 4 + (j & 3) : (j & 7)) + hi;
        stsm4(rb + tile * ts + ((pos ^ xr) << 4), pack2(e[4 * j], e[4 * j + 1]), pack2(e[4 * j + 2], e[4 * j + 3]),
              pack2(e[4 * j + 4], e[4 * j + 5]), pack2(e[4 * j + 6], e[4 * j + 7]));
      }
      fence_async();
      __syncwarp();
      if (lane == 0) mbar_arrive(aof0 + 8 * (n % A_NOUT));
    }
    if (spare) {
      float* sg = reinterpret_cast<float*>(smem_raw + (sb - s2u(smem_raw)));
      __nv_bfloat16* sw = reinterpret_cast<__nv_bfloat16*>(sg + 16 * 256);
      const int c0 = (cta - 128) * 64;
      uint4 vw[8], vg[2];
#pragma unroll
      for (int i = 0; i < 8; i++) vw[i] = __ldg(reinterpret_cast<const uint4*>(wgt + ((i * 256 + tid) >> 3) * 256 + c0 + (tid & 7) * 8));
#pragma unroll
      for (int i = 0; i < 2; i++) vg[i] = __ldg(reinterpret_cast<const uint4*>(g) + i * 256 + tid);
      bar_sync(3, 256);
#pragma unroll
      for (int i = 0; i < 8; i++) reinterpret_cast<uint4*>(sw)[i * 256 + tid] = vw[i];
#pragma unroll
      for (int i = 0; i < 2; i++) {
        const uint32_t w4[4] = {vg[i].x, vg[i].y, vg[i].z, vg[i].w};
#pragma unroll
        for (int e = 0; e < 4; e++) {
          sg[(i * 256 + tid) * 8 + 2 * e] = __uint_as_float(w4[e] << 16);
          sg[(i * 256 + tid) * 8 + 2 * e + 1] = __uint_as_float(w4[e] & 0xffff0000u);
        }
      }
      bar_sync(3, 256);
      const int col = tid & 63, r0 = (tid >> 6) * 4;
      float a0 = 0.f, a1 = 0.f, a2 = 0.f, a3 = 0.f;
#pragma unroll 8
      for (int k = 0; k < 256; k++) {
        const float w = __bfloat162float(sw[k * 64 + col]);
        a0 = fmaf(sg[(r0 + 0) * 256 + k], w, a0);
        a1 = fmaf(sg[(r0 + 1) * 256 + k], w, a1);
        a2 = fmaf(sg[(r0 + 2) * 256 + k], w, a2);
        a3 = fmaf(sg[(r0 + 3) * 256 + k], w, a3);
      }
      const int cc = c0 + col;
      const int pos = (cc & ~15) + ((cc >> 1) & 3) * 4 + ((cc >> 3) & 1) * 2 + (cc & 1);
      ge[(r0 + 0) * 256 + pos] = __bfloat162float(__float2bfloat16_rn(a0));
      ge[(r0 + 1) * 256 + pos] = __bfloat162float(__float2bfloat16_rn(a1));
      ge[(r0 + 2) * 256 + pos] = __bfloat162float(__float2bfloat16_rn(a2));
      ge[(r0 + 3) * 256 + pos] = __bfloat162float(__float2bfloat16_rn(a3));
      return;
    }
    const int b = (cta >> 1) & 1, bin = cta >> 2;
    float d[32];
    auto t_begin = [&](int it, int hh) {
      mbar_wait(inf0 + 8 * (it & 1), (it >> 1) & 1);
      wg_fence();
      wgmma_rs_64<1, 1, 1>(d, fa[0], fa[1], fa[2], fa[3], mk_desc(sb + G_TIN + (it & 1) * 4096 + hh * 2048, 0, 0, 1024, 1), 0);
      wg_commit();
    };
    auto t_end = [&](int it, int hh) {
      reg_fence(d);
      const int j = it & 1;
      mbar_wait(se0 + 8 * j, (it >> 1) & 1);
      store_tile_64<2048>(d, sb + G_TOUT + j * A_OUT + hh * 1024, warp, lane);
      fence_async();
      __syncwarp();
      if (lane == 0) mbar_arrive(sf0 + 8 * j);
    };
    float re[NB1 / 2], im[NB1 / 2];
#pragma unroll 1
    for (int k = 0; k < G_KS; k++) {
      const int st = g_slot(k);
      const int it = __popc(G_TMASK & ((1 << k) - 1));
      const bool T = (G_TMASK >> k) & 1;
      mbar_wait(full0 + 8 * st, (G_PAR >> k) & 1);
      const uint32_t base = sb + st * G_STAGE;
      const uint32_t wb = base + wg * 4096;
      if (T) t_begin(it, wg);
      wg_fence();
#pragma unroll
      for (int s = 0; s < 2; s++) {
        const int acc = (k | s) != 0;
        const uint64_t dP = mk_desc(wb, s * 2048, 0, 1024, 1), dQ = mk_desc(wb, 8192 + s * 2048, 0, 1024, 1);
        const uint64_t dA = mk_desc(base, 16384 + s * 32, 0, 512, 2), dB = mk_desc(base, 16384 + G_XP + s * 32, 0, 512, 2);
        wgmma_ss_168<1, 1, 1, 0>(re, dP, dA, acc);
        wgmma_ss_168<1, 1, 1, 0>(im, dP, dB, acc);
        wgmma_ss_168<1, 1, 1, 0>(re, dQ, dB, 1);
        wgmma_ss_168<-1, 1, 1, 0>(im, dQ, dA, 1);
      }
      wg_commit();
      wg_wait<1>();
      if (k > 0 && lane < 2) mbar_arrive_cta(empty0 + 8 * g_slot(k - 1), lane);
      if (T) t_end(it, wg);
    }
    auto tail = [&](auto part, bool wait) {
      constexpr int PART = decltype(part)::value;
#pragma unroll
      for (int k = G_KS; k < 16; k++) {
        if (wait) mbar_wait(full0 + 8 * g_slot(k), (G_PAR >> k) & 1);
        const uint32_t base = sb + g_slot(k) * G_STAGE, wb = base + wg * 4096;
        wg_fence();
#pragma unroll
        for (int s = 0; s < 2; s++) {
          const uint64_t dP = mk_desc(wb, s * 2048, 0, 1024, 1), dQ = mk_desc(wb, 8192 + s * 2048, 0, 1024, 1);
          const uint64_t dA = mk_desc(base, 16384 + s * 32, 0, 512, 2), dB = mk_desc(base, 16384 + G_XP + s * 32, 0, 512, 2);
          if (PART == 0) {
            wgmma_ss_168<1, 1, 1, 0>(re, dP, dA, 1);
            wgmma_ss_168<1, 1, 1, 0>(re, dQ, dB, 1);
          } else {
            wgmma_ss_168<1, 1, 1, 0>(im, dP, dB, 1);
            wgmma_ss_168<-1, 1, 1, 0>(im, dQ, dA, 1);
          }
        }
      }
      wg_commit();
    };
    auto put = [&](const float (&v)[NB1 / 2], uint32_t stg, int f) {
      const int mi = lane >> 3, i = lane & 7;
      const uint32_t a0 = stg + (mi >> 1) * 1024 + i * 128 + (((2 * warp + (mi & 1)) ^ i) << 4);
      const uint32_t ya = x1_addr(96 + 8 * lane + 4 * hf + 2 * wg + (f >> 5), b, s_flips) + (f & 31) * 128;
#pragma unroll
      for (int c = 0; c < 3; c++) {
#pragma unroll
        for (int j = 8 * c; j < 8 * c + 8 && j < 20; j += 2)
          stsm4t(a0 + j * 1024, pack2(v[4 * j], v[4 * j + 1]), pack2(v[4 * j + 2], v[4 * j + 3]),
                 pack2(v[4 * j + 4], v[4 * j + 5]), pack2(v[4 * j + 6], v[4 * j + 7]));
        if (c == 2)
          asm volatile("stmatrix.sync.aligned.m8n8.x2.trans.shared.b16 [%0], {%1, %2};" ::"r"(a0 + 20 * 1024),
                       "r"(pack2(v[80], v[81])), "r"(pack2(v[82], v[83])) : "memory");
        const uint32_t a = __shfl_sync(0xffffffffu, ya, 4 * c + warp);
        fence_async();
        bar_sync(2 + wg, 128);
        if (lane == 0 && (c < 2 || warp < 3)) {
          tma_st4<0>(c == 2 && warp == 2 ? &m.y : &m.xs, stg + (4 * c + warp) * 2048, (a & 16383) >> 1, (a >> 14) & 15, (a >> 18) & 3, a >> 20);
          bulk_commit();
        }
      }
    };
    if (wg == 0) {
      tail(std::integral_constant<int, 0>(), true);
      bar_arrive(4, 256);
      bar_sync(5, 256);
      wg_wait<0>();
      reg_fence(re);
      put(re, sb + 4 * G_STAGE, 2 * bin);
      bar_sync(7, 256);
      tail(std::integral_constant<int, 1>(), false);
      bar_arrive(8, 256);
      wg_wait<0>();
      reg_fence(im);
      bar_arrive(6, 256);
      put(im, sb + 4 * G_STAGE + NB1 * 128, 2 * bin + 1);
    } else {
#pragma unroll 1
      for (int h2 = 2 * __popc(G_TMASK); h2 < 16; h2++) {
        t_begin(h2 >> 1, h2 & 1);
        wg_wait<0>();
        t_end(h2 >> 1, h2 & 1);
      }
      wg_wait<0>();
      bar_arrive(5, 256);
      bar_sync(4, 256);
      tail(std::integral_constant<int, 0>(), true);
      bar_arrive(7, 256);
      mbar_wait(se0, 0);
      mbar_wait(se0 + 8, 0);
      wg_wait<0>();
      reg_fence(re);
      put(re, sb + G_TOUT, 2 * bin);
      bar_sync(8, 256);
      tail(std::integral_constant<int, 1>(), false);
      wg_wait<0>();
      reg_fence(im);
      bar_sync(6, 256);
      put(im, sb, 2 * bin + 1);
    }
    bulk_wait_read<0>();
  }
}

#define G_WPRE 2
#define H_EPI 3
#define H_KS 11
constexpr int H_XP = 168 * 64, H_STAGE = 8192 + 2 * H_XP, H_NST = 7, H_SMEM = H_NST * H_STAGE + 21504 + 1024;

template <int WG>
__device__ __forceinline__ void h_loop(float (&acc)[84], uint32_t sb, uint32_t full0, uint32_t empty0, int lane) {
#pragma unroll 1
  for (int k = 0; k < 16; k++) {
    const int st = k % H_NST;
    if (WG == 1 && k == H_KS) bar_sync(4, 256);
    mbar_wait(full0 + 8 * st, (k / H_NST) & 1);
    const uint32_t base = sb + st * H_STAGE;
    wg_fence();
#pragma unroll
    for (int s = 0; s < 2; s++) {
      const uint64_t dP = mk_desc(base, s * 2048, 0, 1024, 1), dQ = mk_desc(base, 4096 + s * 2048, 0, 1024, 1);
      const uint64_t dA = mk_desc(base, 8192 + s * 32, 0, 512, 2), dB = mk_desc(base, 8192 + H_XP + s * 32, 0, 512, 2);
      wgmma_ss_168<1, 1, 1, 0>(acc, dP, WG == 0 ? dA : dB, k | s);
      wgmma_ss_168<WG == 0 ? 1 : -1, 1, 1, 0>(acc, dQ, WG == 0 ? dB : dA, 1);
    }
    wg_commit();
    if (WG == 0 && k == 15) bar_arrive(4, 256);
    if (k <= 10) {
      wg_wait<1>();
      if (k > 0 && k - 1 + H_NST < 16 && lane < 2) mbar_arrive_cta(empty0 + 8 * ((k - 1) % H_NST), lane);
    }
  }
  wg_wait<0>();
  reg_fence(acc);
}

__global__ void __cluster_dims__(2, 1, 1) __launch_bounds__(288, 1)
kH(int* __restrict__ cnt, const __nv_bfloat16* __restrict__ wf, const __nv_bfloat16* __restrict__ wo, const uint32_t* __restrict__ gat,
   const __grid_constant__ CUtensorMap mx, const __grid_constant__ CUtensorMap mw, const __grid_constant__ CUtensorMap my) {
  extern __shared__ uint8_t smem_raw[];
  __shared__ __align__(8) uint64_t bars[2 * H_NST];
  const uint32_t sb = pin((s2u(smem_raw) + 1023) & ~1023u);
  const int tid = threadIdx.x, wg = __shfl_sync(0xffffffffu, tid >> 7, 0), t = tid & 127;
  const int warp = __shfl_sync(0xffffffffu, t >> 5, 0), lane = t & 31;
  __shared__ __align__(8) uint64_t role_bar;
  __shared__ uint32_t s_role;
  const int rank = blockIdx.x & 1;
  const uint32_t full0 = pin(s2u(&bars[0])), empty0 = full0 + 8 * H_NST, roleb = s2u(&role_bar);
  pdl_launch();
  if (tid == 32) {
    for (int i = 0; i < H_NST; i++) {
      mbar_init(full0 + 8 * i, 1);
      mbar_init(empty0 + 8 * i, 16);
    }
    mbar_init(roleb, 1);
    mbar_expect(roleb, 4);
    fence_bar_init();
    fence_async();
  } else if (tid == 64) {
    prefetch_map(&mw);
    prefetch_map(&mx);
    prefetch_map(&my);
  }
  __syncwarp();
  asm volatile("barrier.cluster.arrive.relaxed.aligned;" ::: "memory");
  uint32_t fl = 0;
  int ticket = 0;
  if (warp == 0 && wg != 1) {
    int side;
    fl = read_votes(cnt, lane, side);
    if (tid == 256 && rank == 0) ticket = 2 * take_ticket(cnt + 66 + side) + side;
    __syncwarp();
  }
  asm volatile("barrier.cluster.wait.aligned;" ::: "memory");
  if (tid == 256 && rank == 0) send_role(s2u(&s_role), roleb, ticket < 64 ? ticket : 127 - ticket);
  __syncwarp();
  mbar_wait(roleb, 0);
  __syncwarp();
  const int cta = 2 * *(volatile uint32_t*)&s_role + rank, dc = cta & 3, bin = cta >> 2;
  const uint32_t wa = w_addr((lane >> 1) + W_SHIFT, 2 * bin, (lane & 1) * 32, dc >> 1, fl) + (rank << 14);
  if (wg == 0 && warp == 0) {
#pragma unroll
    for (int k = 0; k < G_WPRE; k++) {
      const uint32_t w = __shfl_sync(0xffffffffu, wa, k);
      if (lane == 0) tma_ld3<1>(sb + k * H_STAGE, &mw, full0 + 8 * k, 0, (w >> 7) & 255, w >> 15);
    }
    __syncwarp();
  }
  if (wg == 2) {
    if (lane < H_NST) mbar_expect(full0 + 8 * lane, H_STAGE);
    pdl_wait();
    int st = 0;
#pragma unroll 1
    for (int k = 0; k < 16; k++) {
      const uint32_t w = __shfl_sync(0xffffffffu, wa, k);
      if (k >= H_NST) mbar_wait(empty0 + 8 * st, k >= 2 * H_NST);
      if (lane == 0) {
        const uint32_t base = sb + st * H_STAGE, bar = full0 + 8 * st;
        if (k >= H_NST) mbar_expect(bar, H_STAGE);
        tma_ld3mc<0>(base + 8192 + rank * H_XP, &mx, bar, (k & 1) * 32, 0, (k >> 1) * 64 + 2 * bin + rank);
        if (k >= G_WPRE) tma_ld3<1>(base, &mw, bar, 0, (w >> 7) & 255, w >> 15);
        if (k == H_NST - 1) {
          if (cta == 0) asm volatile("cp.async.bulk.prefetch.L2.global [%0], 6144;" ::"l"(gat) : "memory");
          asm volatile("cp.async.bulk.prefetch.L2.global [%0], 1024;" ::"l"(wf + cta * 512) : "memory");
          asm volatile("cp.async.bulk.prefetch.L2.global [%0], 1024;" ::"l"(wo + cta * 512) : "memory");
        }
      }
      __syncwarp();
      if (++st == H_NST) st = 0;
    }
  } else {
    float acc[84];
    if (wg == 0) {
      h_loop<0>(acc, sb, full0, empty0, lane);
    } else {
      h_loop<1>(acc, sb, full0, empty0, lane);
      bar_sync(3, 128);
    }
    const uint32_t stg = sb + (wg == 0 ? H_NST : 9 % H_NST) * H_STAGE;
    const int mi = lane >> 3, i = lane & 7;
    const uint32_t a0 = stg + (mi >> 1) * 1024 + i * 128 + (((2 * warp + (mi & 1)) ^ i) << 4);
    constexpr int J = 21 / H_EPI;
#pragma unroll
    for (int c = 0; c < H_EPI; c++) {
#pragma unroll
      for (int j = c * J; j + 1 < (c + 1) * J; j += 2)
        stsm4t(a0 + j * 1024, pack2(acc[4 * j], acc[4 * j + 1]), pack2(acc[4 * j + 2], acc[4 * j + 3]),
               pack2(acc[4 * j + 4], acc[4 * j + 5]), pack2(acc[4 * j + 6], acc[4 * j + 7]));
      const int j = (c + 1) * J - 1;
      asm volatile("stmatrix.sync.aligned.m8n8.x2.trans.shared.b16 [%0], {%1, %2};" ::"r"(a0 + j * 1024),
                   "r"(pack2(acc[4 * j], acc[4 * j + 1])), "r"(pack2(acc[4 * j + 2], acc[4 * j + 3])) : "memory");
      fence_async();
      bar_sync(2 + wg, 128);
      if (t == 0) {
        tma_st4<0>(&my, stg + c * J * 1024, 0, c * J * 8, 2 * bin + wg, dc);
        bulk_commit();
      }
    }
    if (t == 0) {
      bulk_wait_read<0>();
    }
  }
}

#define C_TOK 1
constexpr int C_OUT = 13 * 8192, C_GI = C_OUT + 6 * 16384, C_F = C_GI + 6144;
constexpr int C_SMEM = C_F + 8192 + 1024;

template <int NC> __device__ __forceinline__ void gelu_pack(uint32_t (&hp)[32], const float (&h)[4 * NC], int rc0, bool zero_first, bool zero_all) {
#pragma unroll
  for (int c = 0; c < NC; c++) {
    const uint32_t lo = pack2(gelu(h[4 * c]), gelu(h[4 * c + 1])), hi = pack2(gelu(h[4 * c + 2]), gelu(h[4 * c + 3]));
    const bool z = zero_all || (zero_first && c < 2);
    hp[(c & 1) * 16 + (rc0 + (c >> 1)) * 2] = z ? 0u : lo;
    hp[(c & 1) * 16 + (rc0 + (c >> 1)) * 2 + 1] = z ? 0u : hi;
  }
}

__global__ void __launch_bounds__(512, 1)
kC(int* __restrict__ ctr, const uint32_t* __restrict__ img, const __grid_constant__ CUtensorMap my0, const __grid_constant__ CUtensorMap my1, const __grid_constant__ CUtensorMap mxs) {
  extern __shared__ uint8_t smem_raw[];
  __shared__ __align__(8) uint64_t bars[14];
  __shared__ int s_role;
  const uint32_t sb = pin((s2u(smem_raw) + 1023) & ~1023u);
  const int tid = threadIdx.x, wg = __shfl_sync(0xffffffffu, tid >> 7, 0), t = tid & 127, warp = t >> 5, lane = t & 31;
  const bool loader = __shfl_sync(0xffffffffu, tid >> 5, 0) == 15;
  const uint32_t sGi = sb + C_GI, sF = sb + C_F, barc = pin(s2u(&bars[0]));
  uint32_t fl = 0;
  if (loader) {
    int side;
    fl = read_votes(ctr, lane, side);
    if (lane == 0) {
      const int ticket = 2 * take_ticket(ctr + 64 + side) + side;
      s_role = ticket < 128 ? ticket : 255 - ticket;
    }
  } else if (tid == 384) {
    prefetch_map(&my0);
    prefetch_map(&my1);
    for (int i = 0; i < 14; i++) mbar_init(barc + 8 * i, 1);
    fence_bar_init();
    fence_async();
    mbar_expect(barc + 8 * 13, 14336);
    asm volatile("cp.async.bulk.shared::cluster.global.mbarrier::complete_tx::bytes [%0], [%1], 14336, [%2];"
                 ::"r"(sGi), "l"(img), "r"(barc + 8 * 13) : "memory");
  }
  __syncthreads();
  const int b = s_role & 1, cs = (s_role >> 1) & 3, j = s_role >> 3;
  const int n0 = 5 * j + min(j, 4), cnt = j < 4 ? 6 : 5;
  if (loader) {
    const int blk = min(2 * n0 + lane, NB1 - 1);
    const uint32_t ya = x1_addr(96 + 8 * (blk >> 4) + 2 * cs, b, fl) + spread16(blk);
    if (lane <= 2 * cnt) mbar_expect(barc + 8 * lane, 8192);
    pdl_wait();
#pragma unroll 1
    for (int i = 0; i <= 2 * cnt; i++) {
      const uint32_t a = __shfl_sync(0xffffffffu, ya, i);
      if (lane == 0) tma_ld3<1>(sb + i * 8192, (a & 4096) ? &my1 : &my0, barc + 8 * i, 0, a >> 7, 0);
      __syncwarp();
    }
    pdl_launch();
    if (lane == 0) prefetch_map(&mxs);
  }
  mbar_wait(barc + 8 * 13, 0);
#pragma unroll 1
  for (int i = wg; i < cnt; i += 4) {
    const int n2 = n0 + i;
    const uint32_t in = sb + i * 16384, bar = barc + i * 16, outb = sb + C_OUT + i * 16384;
    float h0[24], h1[24], h2[16];
    uint32_t hp[32];
    mbar_wait(bar, 0);
    wg_fence();
#pragma unroll
    for (int k = 0; k < 4; k++) wgmma_ss_48<1, 1, 1, 0>(h0, mk_desc(in, k * 2048, 0, 1024, 1), mk_desc(sGi, k * 32, 0, 1024, 1), k);
    wg_commit();
    mbar_wait(bar + 8, 0);
    wg_fence();
#pragma unroll
    for (int k = 0; k < 4; k++) wgmma_ss_48<1, 1, 1, 0>(h1, mk_desc(in, 8192 + k * 2048, 0, 1024, 1), mk_desc(sGi, k * 32, 0, 1024, 1), k);
    wg_commit();
    if (C_TOK && i > 0) bar_sync(5 + wg, 256);
    wg_wait<1>();
    reg_fence(h0);
    gelu_pack<6>(hp, h0, 0, n2 == 0, false);
    mbar_wait(bar + 16, 0);
    wg_fence();
#pragma unroll
    for (int k = 0; k < 4; k++) wgmma_ss_32<1, 1, 1, 0>(h2, mk_desc(in, 16384 + k * 2048, 0, 1024, 1), mk_desc(sGi, k * 32, 0, 1024, 1), k);
    wg_commit();
    if (C_TOK == 1 && i + 1 < cnt) bar_arrive(5 + ((wg + 1) & 3), 256);
    wg_wait<1>();
    reg_fence(h1);
    gelu_pack<6>(hp, h1, 3, false, n2 == NB2 - 1);
    if (C_TOK == 2 && i + 1 < cnt) bar_arrive(5 + ((wg + 1) & 3), 256);
    wg_wait<0>();
    reg_fence(h2);
    gelu_pack<4>(hp, h2, 6, false, n2 == NB2 - 1);
    float e0[32], e1[32];
    reg_fence(hp);
    if (C_TOK == 3 && i + 1 < cnt) bar_arrive(5 + ((wg + 1) & 3), 256);
    wg_fence();
#pragma unroll
    for (int k = 0; k < 4; k++) {
      const uint64_t db = mk_desc(sF, k * 32, 0, 1024, 1);
      wgmma_rs_64<1, 1, 0>(e0, hp[4 * k], hp[4 * k + 1], hp[4 * k + 2], hp[4 * k + 3], db, k);
      wgmma_rs_64<1, 1, 0>(e1, hp[16 + 4 * k], hp[16 + 4 * k + 1], hp[16 + 4 * k + 2], hp[16 + 4 * k + 3], db, k);
    }
    wg_commit();
    wg_wait<0>();
    reg_fence(e0);
    reg_fence(e1);
    {
      const int mi = lane >> 3, r = lane & 7;
      const uint32_t a0 = outb + (mi >> 1) * 8192 + r * 128 + (((2 * warp + (mi & 1)) ^ r) << 4);
#pragma unroll
      for (int q = 0; q < 8; q++)
        stsm4t(a0 + q * 1024, pack2(e0[4 * q], e0[4 * q + 1]), pack2(e0[4 * q + 2], e0[4 * q + 3]),
               pack2(e1[4 * q], e1[4 * q + 1]), pack2(e1[4 * q + 2], e1[4 * q + 3]));
    }
    fence_async();
    bar_sync(1 + wg, 128);
    if (t == 0) {
      tma_st3<0>(&mxs, outb, 0, cs * 64, b * NB2 + n2);
      tma_st3<0>(&mxs, outb + 8192, 0, (4 + cs) * 64, b * NB2 + n2);
      bulk_commit();
    }
  }
  if (t == 0) bulk_wait_read<0>();
}

#define E_WPRE 2
#define E_EARLY0 2
#define E_CHUNK 1
#define E_EARLY 2
constexpr int E_SMEM = 65536 + 131072 + 32768 + 1024;

__device__ __forceinline__ uint32_t joint2(uint32_t fe, uint32_t g0, uint32_t g1) {
  uint32_t s0, s1;
  asm("{\n.reg .b16 l, h;\n.reg .b32 ll;\nmov.b32 {l, h}, %2;\nmov.b32 ll, {l, l};\n"
      "fma.rn.bf16x2 %0, ll, %5, %3;\nfma.rn.bf16x2 %1, %2, %5, %4;\n}"
      : "=r"(s0), "=r"(s1) : "r"(fe), "r"(g0), "r"(g1), "r"(0x3F800000u));
  return pack2(tanh_f32(__uint_as_float(s0)), tanh_f32(__uint_as_float(s1)));
}
__device__ __forceinline__ uint4 lds128(uint32_t a) {
  uint4 v;
  asm volatile("ld.shared.v4.u32 {%0, %1, %2, %3}, [%4];" : "=r"(v.x), "=r"(v.y), "=r"(v.z), "=r"(v.w) : "r"(a));
  return v;
}
__device__ __forceinline__ void joint_group(uint32_t (&ja)[8], const uint32_t* fe, uint4& g0, uint4& g1, uint32_t gnext) {
  const uint4 c0 = g0, c1 = g1;
  g0 = lds128(gnext);
  g1 = lds128(gnext + 64);
  ja[0] = joint2(fe[0], c0.x, c0.y);
  ja[1] = joint2(fe[1], c0.x, c0.y);
  ja[2] = joint2(fe[2], c0.z, c0.w);
  ja[3] = joint2(fe[3], c0.z, c0.w);
  ja[4] = joint2(fe[4], c1.x, c1.y);
  ja[5] = joint2(fe[5], c1.x, c1.y);
  ja[6] = joint2(fe[6], c1.z, c1.w);
  ja[7] = joint2(fe[7], c1.z, c1.w);
  reg_fence(ja);
}

__global__ void __launch_bounds__(256, 1)
kE(int* __restrict__ cnt, const uint32_t* __restrict__ gat, const float* __restrict__ ge, const __grid_constant__ CUtensorMap my, const __grid_constant__ CUtensorMap mwf, const __grid_constant__ CUtensorMap mwo,
   const __grid_constant__ CUtensorMap mout) {
  extern __shared__ uint8_t smem_raw[];
  __shared__ __align__(8) uint64_t bars[13];
  const uint32_t sb = (s2u(smem_raw) + 1023) & ~1023u;
  const int tid = threadIdx.x, wg = __shfl_sync(0xffffffffu, tid >> 7, 0), t = tid & 127, warp = t >> 5, lane = t & 31;
  const uint32_t R0 = sb, R1 = sb + 65536, R2 = sb + 65536 + 131072;
  const uint32_t barY = s2u(&bars[0]), barF = barY + 32, barO = barY + 64, barA = barY + 96;
  const int b = blockIdx.x / 63, t0 = (blockIdx.x % 63) * 64;
  const int a = t0 / 48, o = t0 % 48;
  const int qw = o + 16 * warp, sel = qw >= 48;
  uint32_t ga[16];
#pragma unroll
  for (int s = 0; s < 4; s++)
    ldg128(reinterpret_cast<const uint4*>(gat) + ((qw >> 4) - 3 * sel) * 128 + s * 32 + lane, ga[4 * s], ga[4 * s + 1], ga[4 * s + 2], ga[4 * s + 3]);
  uint4 gev0, gev1;
  asm volatile("ld.global.cg.v4.u32 {%0, %1, %2, %3}, [%4];" : "=r"(gev0.x), "=r"(gev0.y), "=r"(gev0.z), "=r"(gev0.w)
               : "l"(reinterpret_cast<const uint4*>(ge) + (b * 8 + wg * 4) * 64 + t));
  asm volatile("ld.global.cg.v4.u32 {%0, %1, %2, %3}, [%4];" : "=r"(gev1.x), "=r"(gev1.y), "=r"(gev1.z), "=r"(gev1.w)
               : "l"(reinterpret_cast<const uint4*>(ge) + (b * 8 + wg * 4) * 64 + 128 + t));
  if (tid == 0) {
    prefetch_map(&my);
    for (int i = 0; i < 12; i++) mbar_init(barY + 8 * i, 1);
    mbar_init(barA, 8);
    fence_bar_init();
    fence_async();
    for (int i = 0; i < E_WPRE; i++) {
      const int kc = (i >> 1) | ((i & 1) << 1);
      mbar_expect(barF + 8 * kc, 32768);
      tma_ld3<0>(R1 + kc * 32768, &mwf, barF + 8 * kc, 0, kc * 64, 0);
    }
    pdl_wait();
    for (int i = 0; i < 4; i++) {
      mbar_expect(barY + 8 * i, 16384);
      tma_ld5<0>(R0 + i * 16384, &my, barY + 8 * i, 0, 0, 2 * (i & 1) + (i >> 1), a, b);
    }
    for (int i = E_WPRE; i < 4; i++) {
      const int kc = (i >> 1) | ((i & 1) << 1);
      mbar_expect(barF + 8 * kc, 32768);
      tma_ld3<0>(R1 + kc * 32768, &mwf, barF + 8 * kc, 0, kc * 64, 0);
    }
    prefetch_map(&mwo);
    prefetch_map(&mout);
  }
  uint32_t gs[32];
#pragma unroll
  for (int i = 0; i < 16; i++) {
    gs[i] = sel ? 0u : ga[i];
    gs[16 + i] = sel ? ga[i] : 0u;
  }
  __syncthreads();
  if (blockIdx.x == 125 && tid < 96) cnt[tid] = 0;
  reg_fence(gs);
  uint32_t gp = R2 + wg * 4096 + (lane & 3) * 16;
  uint4 g0, g1;
  uint32_t fe[64];
  {
    float d0[32], d1[32], e[64];
    mbar_wait(barY + 8 * wg, 0);
    wg_fence();
#pragma unroll
    for (int k = 0; k < 8; k++)
      wgmma_rs_64<1, 1, 1>(d0, gs[4 * k], gs[4 * k + 1], gs[4 * k + 2], gs[4 * k + 3], mk_desc(R0 + wg * 16384, k * 2048, 0, 1024, 1), k);
    wg_commit();
    wg_wait<0>();
    reg_fence(d0);
#pragma unroll
    for (int i = 0; i < 32; i++) d0[i] = gelu(d0[i]);
    store_tile_64(d0, R2 + wg * 16384, warp, lane);
    mbar_wait(barY + 8 * (2 + wg), 0);
    wg_fence();
#pragma unroll
    for (int k = 0; k < 8; k++)
      wgmma_rs_64<1, 1, 1>(d1, gs[4 * k], gs[4 * k + 1], gs[4 * k + 2], gs[4 * k + 3], mk_desc(R0 + wg * 16384, 32768 + k * 2048, 0, 1024, 1), k);
    wg_commit();
    fence_async();
    mbar_wait(barF, 0);
    mbar_wait(barF + 16, 0);
    __syncthreads();
    wg_fence();
#pragma unroll
    for (int i = 0; i < 8; i++) {
      const int kc = (i >> 2) * 2, s = i & 3;
      wgmma_ss_128<1, 1, 0, 1>(e, mk_desc(R2, kc * 8192 + s * 32, 0, 1024, 1),
                               mk_desc(R1 + wg * 16384, kc * 32768 + s * 2048, 8192, 1024, 1), i);
    }
    wg_commit();
    if (tid == 128) {
      mbar_expect(barO, 32768);
      tma_ld3<0>(R0, &mwo, barO, 0, 0, 0);
    }
    wg_wait<1>();
    reg_fence(d1);
#pragma unroll
    for (int i = 0; i < 32; i++) d1[i] = gelu(d1[i]);
    store_tile_64(d1, R2 + wg * 16384 + 8192, warp, lane);
    fence_async();
    mbar_wait(barF + 8, 0);
    mbar_wait(barF + 24, 0);
    __syncthreads();
    if (tid == 128) {
      mbar_expect(barO + 8, 32768);
      tma_ld3<0>(R0 + 32768, &mwo, barO + 8, 0, 64, 0);
    }
    if (wg == 1) bar_sync(4, 256);
    wg_fence();
#pragma unroll
    for (int i = 0; i < 8; i++) {
      const int kc = (i >> 2) * 2 + 1, s = i & 3;
      wgmma_ss_128<1, 1, 0, 1>(e, mk_desc(R2, kc * 8192 + s * 32, 0, 1024, 1),
                               mk_desc(R1 + wg * 16384, kc * 32768 + s * 2048, 8192, 1024, 1), 1);
    }
    wg_commit();
    if (wg == 0) bar_arrive(4, 256);
    wg_wait<1>();
    if (lane == 0) mbar_arrive(barA);
    if (tid == 128) {
      mbar_wait(barA, 0);
      for (int kc = 2; kc < 4; kc++) {
        mbar_expect(barO + 8 * kc, 32768);
        tma_ld3<0>(R1 + (kc - 2) * 65536, &mwo, barO + 8 * kc, 0, kc * 64, 0);
      }
    }
    mbar_wait(barA, 0);
    asm volatile("st.shared.v4.u32 [%0], {%1, %2, %3, %4};" ::"r"(R2 + wg * 4096 + ((t * 16) ^ (wg * 512))), "r"(gev0.x), "r"(gev0.y), "r"(gev0.z), "r"(gev0.w) : "memory");
    asm volatile("st.shared.v4.u32 [%0], {%1, %2, %3, %4};" ::"r"(R2 + wg * 4096 + 2048 + ((t * 16) ^ (wg * 512))), "r"(gev1.x), "r"(gev1.y), "r"(gev1.z), "r"(gev1.w) : "memory");
    bar_sync(1 + wg, 128);
    g0 = lds128(gp);
    g1 = lds128(gp + 64);
    wg_wait<0>();
    reg_fence(e);
#pragma unroll
    for (int i = 0; i < 32; i++) fe[i] = pack2(e[2 * i], e[2 * i + 1]);
  }
  auto publish = [&]() {
    bar_sync(1 + wg, 128);
    const int row = warp * 16 + (lane & 7) + ((lane >> 3) & 1) * 8;
    const uint32_t xb = R1 + (wg == 0 ? 3 * 32768 : 32768 + 16384) + row * 128;
#pragma unroll
    for (int s = 0; s < 8; s++) {
      const int jj = 2 * s + (lane >> 4);
      stsm4(xb + (s >> 2) * 8192 + (((jj & 7) ^ (lane & 7)) << 4), fe[4 * s], fe[4 * s + 1], fe[4 * s + 2], fe[4 * s + 3]);
    }
    bar_arrive(5 + wg, 256);
  };
  if (wg == 1) publish();
  const uint32_t stg = R1 + 32768 + wg * 65536;
  const uint32_t w0 = sb + wg * 65536, w1 = sb + 32768 + wg * 98304, w2 = sb + 65536 - wg * 65536, w3 = sb + 131072 - wg * 98304;
  float acc[128];
  uint32_t j0[8], j1[8], j2[8], j3[8];
  joint_group(j0, fe, g0, g1, gp + 128);
  mbar_wait(barO + 16 * wg, 0);
  joint_group(j1, fe + 8, g0, g1, gp + 256);
#define E_MMA4(J, K, W, FIRSTK, G, NEXTBAR)                                                     \
  wg_fence();                                                                                   \
  wgmma_rs_256<1, 1, 1>(acc, J[0], J[1], J[2], J[3], mk_desc(W, 0, 8192, 1024, 1), FIRSTK);     \
  wgmma_rs_256<1, 1, 1>(acc, J[4], J[5], J[6], J[7], mk_desc(W, 2048, 8192, 1024, 1), 1);       \
  wgmma_rs_256<1, 1, 1>(acc, K[0], K[1], K[2], K[3], mk_desc(W, 4096, 8192, 1024, 1), 1);       \
  wgmma_rs_256<1, 1, 1>(acc, K[4], K[5], K[6], K[7], mk_desc(W, 6144, 8192, 1024, 1), 1);       \
  wg_commit();                                                                                  \
  if ((ui + wg == 0 ? E_EARLY0 : E_EARLY) == (G) && (ui < 3 || wg == 0)) bar_arrive(4 - wg, 256); \
  wg_wait<1>();                                                                                 \
  if (ui == 0) mbar_wait(NEXTBAR, 0);
  const uint32_t bo0 = barO + 16 * wg, bo2 = barO + 16 * (1 - wg);
#pragma unroll 1
  for (int ui = 0; ui < 4; ui++) {
    if (ui > 0 || wg == 1) bar_sync(3 + wg, 256);
    E_MMA4(j0, j1, w0, 0, 0, bo0)
    joint_group(j2, fe + 16, g0, g1, gp + 384);
    if (ui == 0) mbar_wait(bo0 + 8, 0);
    joint_group(j3, fe + 24, g0, g1, gp + 512);
    E_MMA4(j2, j3, w1, 1, 1, bo0 + 8)
    if (ui == 0) {
      if (wg == 0) publish();
      bar_sync(6 - wg, 256);
      const int row = warp * 16 + (lane & 7) + ((lane >> 3) & 1) * 8;
      const uint32_t xb = R1 + (wg == 1 ? 3 * 32768 : 32768 + 16384) + row * 128;
#pragma unroll
      for (int s = 0; s < 8; s++) {
        const int jj = 2 * s + (lane >> 4);
        ldsm4(xb + (s >> 2) * 8192 + (((jj & 7) ^ (lane & 7)) << 4), fe[32 + 4 * s], fe[33 + 4 * s], fe[34 + 4 * s], fe[35 + 4 * s]);
      }
    }
    joint_group(j0, fe + 32, g0, g1, gp + 640);
    if (ui == 0) mbar_wait(bo2, 0);
    joint_group(j1, fe + 40, g0, g1, gp + 768);
    E_MMA4(j0, j1, w2, 1, 2, bo2)
    joint_group(j2, fe + 48, g0, g1, gp + 896);
    if (ui == 0) mbar_wait(bo2 + 8, 0);
    joint_group(j3, fe + 56, g0, g1, gp + 1024);
    E_MMA4(j2, j3, w3, 1, 3, bo2 + 8)
    gp += 1024;
    if (ui < 3) {
      joint_group(j0, fe, g0, g1, gp + 128);
      if (ui == 0) mbar_wait(bo2 + 8, 0);
      joint_group(j1, fe + 8, g0, g1, gp + 256);
    }
    if (t == 0) bulk_wait_read<0>();
    wg_wait<0>();
    reg_fence(acc);
    bar_sync(1 + wg, 128);
    const uint32_t rb = stg + (warp * 16 + (lane & 7) + ((lane >> 3) & 1) * 8) * 128;
#pragma unroll
    for (int h = 0; h < 2; h++) {
#pragma unroll
      for (int j = 16 * h; j < 16 * h + 16; j += 2) {
        const int jj = j + (lane >> 4);
        stsm4(rb + (j >> 3) * 8192 + (((jj & 7) ^ (lane & 7)) << 4), pack2(acc[4 * j], acc[4 * j + 1]), pack2(acc[4 * j + 2], acc[4 * j + 3]),
              pack2(acc[4 * j + 4], acc[4 * j + 5]), pack2(acc[4 * j + 6], acc[4 * j + 7]));
      }
      const bool split = E_CHUNK == 2 || (E_CHUNK == 1 && ui == 3);
      if (h == 1 || split) {
        fence_async();
        bar_sync(1 + wg, 128);
        if (t == 0) {
          if (h == 1 && !split) tma_st5<1>(&mout, stg, 0, t0, 0, wg * 4 + ui, b);
          tma_st5<1>(&mout, stg + h * 16384, 0, t0, 2 * h, wg * 4 + ui, b);
          bulk_commit();
        }
      }
    }
  }
  if (t == 0) bulk_wait_read<0>();
}

typedef CUresult (*EncodeFn)(CUtensorMap*, CUtensorMapDataType, cuuint32_t, void*, const cuuint64_t*, const cuuint64_t*,
                             const cuuint32_t*, const cuuint32_t*, CUtensorMapInterleave, CUtensorMapSwizzle,
                             CUtensorMapL2promotion, CUtensorMapFloatOOBfill);

CUtensorMap make_map(EncodeFn fn, const void* base, int rank, const uint64_t* dims, const uint64_t* strides, const uint32_t* box,
                     CUtensorMapSwizzle swz) {
  CUtensorMap m;
  cuuint64_t gd[5], gs[4];
  cuuint32_t bx[5], es[5];
  for (int i = 0; i < rank; i++) { gd[i] = dims[i]; bx[i] = box[i]; es[i] = 1; }
  for (int i = 0; i + 1 < rank; i++) gs[i] = strides[i];
  fn(&m, CU_TENSOR_MAP_DATA_TYPE_BFLOAT16, rank, const_cast<void*>(base), gd, gs, bx, es, CU_TENSOR_MAP_INTERLEAVE_NONE, swz,
     CU_TENSOR_MAP_L2_PROMOTION_NONE, CU_TENSOR_MAP_FLOAT_OOB_FILL_NONE);
  return m;
}

template <typename... KArgs, typename... Args>
void launch(void (*k)(KArgs...), int grid, int block, int smem, bool pdl, Args... args) {
  cudaLaunchConfig_t c = {};
  c.gridDim = dim3(grid);
  c.blockDim = dim3(block);
  c.dynamicSmemBytes = smem;
  c.stream = cudaStreamPerThread;
  cudaLaunchAttribute at[1];
  at[0].id = cudaLaunchAttributeProgrammaticStreamSerialization;
  at[0].val.programmaticStreamSerializationAllowed = 1;
  c.attrs = at;
  c.numAttrs = pdl ? 1 : 0;
  cudaLaunchKernelEx(&c, k, args...);
}

}

extern "C" void kernel_launch(void* const* d_in, const int* in_sizes, int n_in, void* d_out, int out_size) {
  const __nv_bfloat16* x = (const __nv_bfloat16*)d_in[0];
  const __nv_bfloat16* w1 = (const __nv_bfloat16*)d_in[1];
  const __nv_bfloat16* w2 = (const __nv_bfloat16*)d_in[2];
  const __nv_bfloat16* g = (const __nv_bfloat16*)d_in[3];
  const __nv_bfloat16* wf = (const __nv_bfloat16*)d_in[4];
  const __nv_bfloat16* wgt = (const __nv_bfloat16*)d_in[5];
  const __nv_bfloat16* wo = (const __nv_bfloat16*)d_in[6];

  void* fp = nullptr;
  cudaDriverEntryPointQueryResult qr;
  cudaGetDriverEntryPoint("cuTensorMapEncodeTiled", &fp, cudaEnableDefault, &qr);
  EncodeFn fn = (EncodeFn)fp;
  void *W, *Y2, *cnt, *ge, *img, *gat;
  cudaGetSymbolAddress(&cnt, g_cnt);
  cudaGetSymbolAddress(&ge, g_ge);
  cudaGetSymbolAddress(&img, c_img);
  cudaGetSymbolAddress(&gat, c_ga);
  cudaGetSymbolAddress(&W, g_W);
  cudaGetSymbolAddress(&Y2, g_Y2);
  cudaFuncSetAttribute(kG, cudaFuncAttributeMaxDynamicSharedMemorySize, G_SMEM);
  cudaFuncSetAttribute(kC, cudaFuncAttributeMaxDynamicSharedMemorySize, C_SMEM);
  cudaFuncSetAttribute(kH, cudaFuncAttributeMaxDynamicSharedMemorySize, H_SMEM);
  cudaFuncSetAttribute(kE, cudaFuncAttributeMaxDynamicSharedMemorySize, E_SMEM);
  auto page_up = [](void* p) { return (void*)(((uintptr_t)p + (1 << 21) - 1) & ~(uintptr_t)((1 << 21) - 1)); };
  void *X1 = page_up(d_out), *X2 = X1;
  W = page_up(W);
  const CUtensorMapSwizzle S128 = CU_TENSOR_MAP_SWIZZLE_128B, S64 = CU_TENSOR_MAP_SWIZZLE_64B;

  auto map_x = [&]() {
    uint64_t d[] = {64, 8000, 8, 1, 2}, s[] = {1024, 128, 8000ull * 1024, 8000ull * 1024};
    uint32_t bx[] = {64, 112, 1, 1, 1};
    return make_map(fn, x, 5, d, s, bx, S128);
  };
  auto map_w_in = [&](const __nv_bfloat16* w, int odd, uint32_t n) {
    uint64_t d[] = {64, (uint64_t)(odd ? 15 : 16), 4, 64, 4}, s[] = {2ull * 65536 * 2, 128, 512, 32768};
    uint32_t bx[] = {64, 16, 2, 1, n};
    return make_map(fn, w + (odd ? 65536 : 0), 5, d, s, bx, S128);
  };
  auto map_X_st = [&](void* p, int nb, int boxb) {
    uint64_t d[] = {64, 512, (uint64_t)(2 * nb)}, s[] = {2ull * nb * 128, 128};
    uint32_t bx[] = {64, 64, (uint32_t)boxb};
    return make_map(fn, p, 3, d, s, bx, S128);
  };
  auto map_X1_st = [&](uint32_t rows) {
    uint64_t d[] = {8192, 16, 4, 24}, s[] = {16384, 262144, 1048576};
    uint32_t bx[] = {64, 4, 2, rows / 8};
    return make_map(fn, X1, 4, d, s, bx, S128);
  };
  auto map_Y1_ld = [&](uint64_t step) {
    uint64_t d[] = {64, 12 << 14, 2}, s[] = {128, step};
    uint32_t bx[] = {64, 32, 2};
    return make_map(fn, X1, 3, d, s, bx, S128);
  };
  auto map_W_st = [&]() {
    uint64_t d[] = {8192, 8, 4, 2 * (8 + W_SHIFT), 2}, s[] = {32768, 262144, 1048576, 16384};
    uint32_t bx[] = {64, 2, 2, 2, 2};
    return make_map(fn, W, 5, d, s, bx, S128);
  };
  auto map_X_ld = [&](void* p, int nb, int boxb) {
    uint64_t d[] = {64, (uint64_t)(2 * nb), 512}, s[] = {128, 2ull * nb * 128};
    uint32_t bx[] = {32, (uint32_t)boxb, 1};
    return make_map(fn, p, 3, d, s, bx, S64);
  };
  auto map_W_ld = [&](uint32_t n) {
    uint64_t d[] = {64, 512 / n, (8ull + W_SHIFT) * 32 * n}, s[] = {128, 65536 / n};
    uint32_t bx[] = {64, 32, n};
    return make_map(fn, W, 3, d, s, bx, S128);
  };
  auto map_Y_st = [&](void* p, int nb, int rows) {
    uint64_t d[] = {64, (uint64_t)(2 * nb), 64, 4}, s[] = {32768, 128, 8192};
    uint32_t bx[] = {64, (uint32_t)rows, 1, 1};
    return make_map(fn, p, 4, d, s, bx, S128);
  };
  auto map_Y_ld = [&](void* p, int nb, int boxc, int boxb) {
    uint64_t d[] = {64, 64, 4, (uint64_t)nb, 2}, s[] = {128, 8192, 32768, (uint64_t)nb * 32768};
    uint32_t bx[] = {64, 64, (uint32_t)boxc, (uint32_t)boxb, 1};
    return make_map(fn, p, 5, d, s, bx, S128);
  };
  auto map_wsq = [&](const __nv_bfloat16* w) {
    uint64_t d[] = {64, 256, 4}, s[] = {512, 128};
    uint32_t bx[] = {64, 64, 4};
    return make_map(fn, w, 3, d, s, bx, S128);
  };
  auto map_out = [&]() {
    uint64_t d[] = {64, 4000, 4, 8, 2}, s[] = {4096, 128, 512, 4000ull * 4096};
    uint32_t bx[] = {64, 64, 2, 1, 1};
    return make_map(fn, d_out, 5, d, s, bx, S128);
  };

  GMaps g1;
  g1.w = map_W_ld(4);
  g1.y = map_X1_st(8);
  g1.in[0] = map_w_in(w1, 1, 2);
  g1.in[1] = map_w_in(w1, 0, 2);
  g1.in[2] = map_w_in(w2, 1, 1);
  g1.in[3] = map_w_in(w2, 0, 1);
  g1.in[4] = map_x();
  g1.xs = map_X1_st(16);
  g1.ws = map_W_st();
  launch(kG, 132, 384, G_SMEM, false, (int*)cnt, (char*)X1, (char*)W, g, wgt, (float*)ge, (const uint32_t*)img, g1);
  launch(kC, 128, 512, C_SMEM, true, (int*)cnt, (const uint32_t*)img, map_Y1_ld(0x3000), map_Y1_ld(0x1000), map_X_st(X2, NB2, 1));
  launch(kH, 128, 288, H_SMEM, true, (int*)cnt, wf, wo, (const uint32_t*)gat, map_X_ld(X2, NB2, 168), map_W_ld(2), map_Y_st(Y2, NB2, 168 / H_EPI));
  launch(kE, 126, 256, E_SMEM, true, (int*)cnt, (const uint32_t*)gat, (const float*)ge, map_Y_ld(Y2, NB2, 1, 2), map_wsq(wf), map_wsq(wo), map_out());
}
```

```cpp
#include <cuda_runtime.h>
#include <cuda_bf16.h>
#include <cuda.h>
#include <stdint.h>
#include <type_traits>

#define W_SHIFT 1
namespace {

constexpr int NB1 = 168;
constexpr int NB2 = 84;

__device__ __align__(1024) __nv_bfloat16 g_W[(9 + W_SHIFT) * 64 * 4 * 64 * 64];
__device__ __align__(1024) __nv_bfloat16 g_Y2[2 * NB2 * 4 * 64 * 64];
__device__ __align__(1024) float g_ge[16 * 256];

__device__ __forceinline__ uint32_t s2u(const void* p) { return (uint32_t)__cvta_generic_to_shared(p); }
__device__ __forceinline__ uint32_t pin(uint32_t v) {
  return __shfl_sync(0xffffffffu, v, 0);
}
__device__ __forceinline__ void mbar_init(uint32_t b, int c) {
  asm volatile("mbarrier.init.shared::cta.b64 [%0], %1;" ::"r"(b), "r"(c) : "memory");
}
__device__ __forceinline__ void mbar_expect(uint32_t b, int bytes) {
  asm volatile("mbarrier.arrive.expect_tx.shared::cta.b64 _, [%0], %1;" ::"r"(b), "r"(bytes) : "memory");
}
__device__ __forceinline__ void mbar_arrive(uint32_t b) {
  asm volatile("mbarrier.arrive.shared::cta.b64 _, [%0];" ::"r"(b) : "memory");
}
__device__ __forceinline__ void mbar_arrive_cta(uint32_t b, uint32_t cta) {
  asm volatile("{\n.reg .b32 r;\nmapa.shared::cluster.u32 r, %0, %1;\nmbarrier.arrive.shared::cluster.b64 _, [r];\n}" ::"r"(b), "r"(cta) : "memory");
}
__device__ __forceinline__ void mbar_wait(uint32_t b, int ph) {
  asm volatile(
      "{\n.reg .pred p;\n.reg .u32 n;\n"
      "mov.u32 n, 0;\n"
      "MBW_LOOP:\n"
      "mbarrier.try_wait.parity.shared::cta.b64 p, [%0], %1;\n"
      "@p bra MBW_DONE;\n"
      "add.u32 n, n, 1;\n"
      "setp.lt.u32 p, n, 1048576;\n"
      "@p bra MBW_LOOP;\n"
      "MBW_DONE:\n}" ::"r"(b), "r"(ph) : "memory");
}
__device__ __forceinline__ bool mbar_test(uint32_t b, int ph) {
  uint32_t ok;
  asm volatile("{\n.reg .pred p;\nmbarrier.test_wait.parity.shared::cta.b64 p, [%1], %2;\nselp.u32 %0, 1, 0, p;\n}" : "=r"(ok) : "r"(b), "r"(ph) : "memory");
  return __all_sync(0xffffffffu, ok);
}
__device__ __forceinline__ void fence_bar_init() { asm volatile("fence.mbarrier_init.release.cluster;" ::: "memory"); }
__device__ __forceinline__ void fence_async() { asm volatile("fence.proxy.async.shared::cta;" ::: "memory"); }
__device__ __forceinline__ void bar_sync(int id, int n) { asm volatile("bar.sync %0, %1;" ::"r"(id), "r"(n) : "memory"); }
__device__ __forceinline__ void bar_arrive(int id, int n) { asm volatile("bar.arrive %0, %1;" ::"r"(id), "r"(n) : "memory"); }
__device__ __forceinline__ void pdl_wait() { asm volatile("griddepcontrol.wait;" ::: "memory"); }
__device__ __forceinline__ void pdl_launch() { asm volatile("griddepcontrol.launch_dependents;" ::: "memory"); }
__device__ __forceinline__ void prefetch_map(const CUtensorMap* m) {
  asm volatile("prefetch.tensormap [%0];" ::"l"(m) : "memory");
}
template <int P> __device__ __forceinline__ uint64_t policy() {
  uint64_t p;
  asm("createpolicy.fractional.L2::evict_first.b64 %0, 1.0;" : "=l"(p));
  return p;
}
template <int P> __device__ __forceinline__ void tma_ld3(uint32_t dst, const CUtensorMap* m, uint32_t bar, int c0, int c1, int c2) {
  if constexpr (P == 0)
    asm volatile("cp.async.bulk.tensor.3d.shared::cluster.global.mbarrier::complete_tx::bytes [%0], [%1, {%3, %4, %5}], [%2];"
                 ::"r"(dst), "l"(m), "r"(bar), "r"(c0), "r"(c1), "r"(c2) : "memory");
  else
    asm volatile("cp.async.bulk.tensor.3d.shared::cluster.global.mbarrier::complete_tx::bytes.L2::cache_hint [%0], [%1, {%3, %4, %5}], [%2], %6;"
                 ::"r"(dst), "l"(m), "r"(bar), "r"(c0), "r"(c1), "r"(c2), "l"(policy<P>()) : "memory");
}
template <int P> __device__ __forceinline__ void tma_ld3mc(uint32_t dst, const CUtensorMap* m, uint32_t bar, int c0, int c1, int c2) {
  if constexpr (P == 0)
    asm volatile("cp.async.bulk.tensor.3d.shared::cluster.global.mbarrier::complete_tx::bytes.multicast::cluster [%0], [%1, {%3, %4, %5}], [%2], %6;"
                 ::"r"(dst), "l"(m), "r"(bar), "r"(c0), "r"(c1), "r"(c2), "h"((uint16_t)3) : "memory");
  else
    asm volatile("cp.async.bulk.tensor.3d.shared::cluster.global.mbarrier::complete_tx::bytes.multicast::cluster.L2::cache_hint [%0], [%1, {%3, %4, %5}], [%2], %6, %7;"
                 ::"r"(dst), "l"(m), "r"(bar), "r"(c0), "r"(c1), "r"(c2), "h"((uint16_t)3), "l"(policy<P>()) : "memory");
}
template <int P> __device__ __forceinline__ void tma_ld4(uint32_t dst, const CUtensorMap* m, uint32_t bar, int c0, int c1, int c2, int c3) {
  if constexpr (P == 0)
    asm volatile("cp.async.bulk.tensor.4d.shared::cluster.global.mbarrier::complete_tx::bytes [%0], [%1, {%3, %4, %5, %6}], [%2];"
                 ::"r"(dst), "l"(m), "r"(bar), "r"(c0), "r"(c1), "r"(c2), "r"(c3) : "memory");
  else
    asm volatile("cp.async.bulk.tensor.4d.shared::cluster.global.mbarrier::complete_tx::bytes.L2::cache_hint [%0], [%1, {%3, %4, %5, %6}], [%2], %7;"
                 ::"r"(dst), "l"(m), "r"(bar), "r"(c0), "r"(c1), "r"(c2), "r"(c3), "l"(policy<P>()) : "memory");
}
template <int P> __device__ __forceinline__ void tma_ld4mc(uint32_t dst, const CUtensorMap* m, uint32_t bar, int c0, int c1, int c2, int c3) {
  if constexpr (P == 0)
    asm volatile("cp.async.bulk.tensor.4d.shared::cluster.global.mbarrier::complete_tx::bytes.multicast::cluster [%0], [%1, {%3, %4, %5, %6}], [%2], %7;"
                 ::"r"(dst), "l"(m), "r"(bar), "r"(c0), "r"(c1), "r"(c2), "r"(c3), "h"((uint16_t)3) : "memory");
  else
    asm volatile("cp.async.bulk.tensor.4d.shared::cluster.global.mbarrier::complete_tx::bytes.multicast::cluster.L2::cache_hint [%0], [%1, {%3, %4, %5, %6}], [%2], %7, %8;"
                 ::"r"(dst), "l"(m), "r"(bar), "r"(c0), "r"(c1), "r"(c2), "r"(c3), "h"((uint16_t)3), "l"(policy<P>()) : "memory");
}
template <int P> __device__ __forceinline__ void tma_ld5(uint32_t dst, const CUtensorMap* m, uint32_t bar, int c0, int c1, int c2, int c3, int c4) {
  if constexpr (P == 0)
    asm volatile("cp.async.bulk.tensor.5d.shared::cluster.global.mbarrier::complete_tx::bytes [%0], [%1, {%3, %4, %5, %6, %7}], [%2];"
                 ::"r"(dst), "l"(m), "r"(bar), "r"(c0), "r"(c1), "r"(c2), "r"(c3), "r"(c4) : "memory");
  else
    asm volatile("cp.async.bulk.tensor.5d.shared::cluster.global.mbarrier::complete_tx::bytes.L2::cache_hint [%0], [%1, {%3, %4, %5, %6, %7}], [%2], %8;"
                 ::"r"(dst), "l"(m), "r"(bar), "r"(c0), "r"(c1), "r"(c2), "r"(c3), "r"(c4), "l"(policy<P>()) : "memory");
}
template <int P> __device__ __forceinline__ void tma_st3(const CUtensorMap* m, uint32_t src, int c0, int c1, int c2) {
  if constexpr (P == 0)
    asm volatile("cp.async.bulk.tensor.3d.global.shared::cta.bulk_group [%0, {%2, %3, %4}], [%1];" ::"l"(m), "r"(src), "r"(c0), "r"(c1), "r"(c2) : "memory");
  else
    asm volatile("cp.async.bulk.tensor.3d.global.shared::cta.bulk_group.L2::cache_hint [%0, {%2, %3, %4}], [%1], %5;" ::"l"(m), "r"(src), "r"(c0), "r"(c1), "r"(c2), "l"(policy<P>()) : "memory");
}
template <int P> __device__ __forceinline__ void tma_st4(const CUtensorMap* m, uint32_t src, int c0, int c1, int c2, int c3) {
  if constexpr (P == 0)
    asm volatile("cp.async.bulk.tensor.4d.global.shared::cta.bulk_group [%0, {%2, %3, %4, %5}], [%1];" ::"l"(m), "r"(src), "r"(c0), "r"(c1), "r"(c2), "r"(c3) : "memory");
  else
    asm volatile("cp.async.bulk.tensor.4d.global.shared::cta.bulk_group.L2::cache_hint [%0, {%2, %3, %4, %5}], [%1], %6;" ::"l"(m), "r"(src), "r"(c0), "r"(c1), "r"(c2), "r"(c3), "l"(policy<P>()) : "memory");
}
template <int P> __device__ __forceinline__ void tma_st5(const CUtensorMap* m, uint32_t src, int c0, int c1, int c2, int c3, int c4) {
  if constexpr (P == 0)
    asm volatile("cp.async.bulk.tensor.5d.global.shared::cta.bulk_group [%0, {%2, %3, %4, %5, %6}], [%1];" ::"l"(m), "r"(src), "r"(c0), "r"(c1), "r"(c2), "r"(c3), "r"(c4) : "memory");
  else
    asm volatile("cp.async.bulk.tensor.5d.global.shared::cta.bulk_group.L2::cache_hint [%0, {%2, %3, %4, %5, %6}], [%1], %7;" ::"l"(m), "r"(src), "r"(c0), "r"(c1), "r"(c2), "r"(c3), "r"(c4), "l"(policy<P>()) : "memory");
}
__device__ __forceinline__ void bulk_commit() { asm volatile("cp.async.bulk.commit_group;" ::: "memory"); }
template <int N> __device__ __forceinline__ void bulk_wait() { asm volatile("cp.async.bulk.wait_group %0;" ::"n"(N) : "memory"); }
template <int N> __device__ __forceinline__ void bulk_wait_read() { asm volatile("cp.async.bulk.wait_group.read %0;" ::"n"(N) : "memory"); }
__device__ __forceinline__ void wg_fence() { asm volatile("wgmma.fence.sync.aligned;" ::: "memory"); }
__device__ __forceinline__ void wg_commit() { asm volatile("wgmma.commit_group.sync.aligned;" ::: "memory"); }
template <int N> __device__ __forceinline__ void wg_wait() { asm volatile("wgmma.wait_group.sync.aligned %0;" ::"n"(N) : "memory"); }
template <int R> __device__ __forceinline__ void reg_fence(float (&d)[R]) {
#pragma unroll
  for (int i = 0; i < R; i++) asm volatile("" : "+f"(d[i])::"memory");
}
template <int R> __device__ __forceinline__ void reg_fence(uint32_t (&d)[R]) {
#pragma unroll
  for (int i = 0; i < R; i++) asm volatile("" : "+r"(d[i])::"memory");
}
__device__ __forceinline__ void stsm4(uint32_t a, uint32_t r0, uint32_t r1, uint32_t r2, uint32_t r3) {
  asm volatile("stmatrix.sync.aligned.m8n8.x4.shared.b16 [%0], {%1, %2, %3, %4};" ::"r"(a), "r"(r0), "r"(r1), "r"(r2), "r"(r3) : "memory");
}
__device__ __forceinline__ void stsm4t(uint32_t a, uint32_t r0, uint32_t r1, uint32_t r2, uint32_t r3) {
  asm volatile("stmatrix.sync.aligned.m8n8.x4.trans.shared.b16 [%0], {%1, %2, %3, %4};" ::"r"(a), "r"(r0), "r"(r1), "r"(r2), "r"(r3) : "memory");
}
__device__ __forceinline__ void ldsm4(uint32_t a, uint32_t& r0, uint32_t& r1, uint32_t& r2, uint32_t& r3) {
  asm volatile("ldmatrix.sync.aligned.m8n8.x4.shared.b16 {%0, %1, %2, %3}, [%4];" : "=r"(r0), "=r"(r1), "=r"(r2), "=r"(r3) : "r"(a) : "memory");
}
__device__ __forceinline__ void ldg128(const uint4* p, uint32_t& a, uint32_t& b, uint32_t& c, uint32_t& d) {
  asm volatile("ld.global.nc.v4.u32 {%0, %1, %2, %3}, [%4];" : "=r"(a), "=r"(b), "=r"(c), "=r"(d) : "l"(p));
}
__device__ __forceinline__ uint32_t pack2(float lo, float hi) {
  uint32_t r;
  asm("cvt.rn.bf16x2.f32 %0, %1, %2;" : "=r"(r) : "f"(hi), "f"(lo));
  return r;
}
__device__ __forceinline__ float tanh_f32(float x) {
  float y;
  asm("tanh.approx.f32 %0, %1;" : "=f"(y) : "f"(x));
  return y;
}
__device__ __forceinline__ float gelu(float hx) {
  const float u = hx * fmaf(hx * hx, 8.0f * 0.044715f * 0.7978845608028654f, 2.0f * 0.7978845608028654f);
  return fmaf(hx, tanh_f32(u), hx);
}
__device__ __forceinline__ uint64_t mk_desc4(uint32_t addr4, uint32_t lbo, uint32_t sbo, uint32_t swz) {
  const uint32_t lo = addr4 + ((lbo >> 4) << 16), hi = (sbo >> 4) | (swz << 30);
  uint64_t d;
  asm("mov.b64 %0, {%1, %2};" : "=l"(d) : "r"(lo), "r"(hi));
  return d;
}
#define mk_desc(base, off, lbo, sbo, swz) mk_desc4((((base) & 0x3FFFF) >> 4) + ((off) >> 4), lbo, sbo, swz)

template <int SA, int SB, int TA, int TB>
__device__ __forceinline__ void wgmma_ss_32(float (&d)[16], uint64_t da, uint64_t db, int sd) {
  asm volatile("{\n.reg .pred p;\nsetp.ne.b32 p, %18, 0;\n"
      "wgmma.mma_async.sync.aligned.m64n32k16.f32.bf16.bf16 {"
      "%0, %1, %2, %3, %4, %5, %6, %7, %8, %9, %10, %11, %12, %13, %14, %15"
      "}, %16, %17, p, %19, %20, %21, %22;\n}\n"
      : "+f"(d[0]), "+f"(d[1]), "+f"(d[2]), "+f"(d[3]), "+f"(d[4]), "+f"(d[5]), "+f"(d[6]), "+f"(d[7]), "+f"(d[8]),
        "+f"(d[9]), "+f"(d[10]), "+f"(d[11]), "+f"(d[12]), "+f"(d[13]), "+f"(d[14]), "+f"(d[15])
      : "l"(da), "l"(db), "r"(sd), "n"(SA), "n"(SB), "n"(TA), "n"(TB));
}
template <int SA, int SB, int TA, int TB>
__device__ __forceinline__ void wgmma_ss_48(float (&d)[24], uint64_t da, uint64_t db, int sd) {
  asm volatile("{\n.reg .pred p;\nsetp.ne.b32 p, %26, 0;\n"
      "wgmma.mma_async.sync.aligned.m64n48k16.f32.bf16.bf16 {"
      "%0, %1, %2, %3, %4, %5, %6, %7, %8, %9, %10, %11, %12, %13, %14, %15, %16, %17, %18, %19, %20, %21, %22, %23"
      "}, %24, %25, p, %27, %28, %29, %30;\n}\n"
      : "+f"(d[0]), "+f"(d[1]), "+f"(d[2]), "+f"(d[3]), "+f"(d[4]), "+f"(d[5]), "+f"(d[6]), "+f"(d[7]), "+f"(d[8]),
        "+f"(d[9]), "+f"(d[10]), "+f"(d[11]), "+f"(d[12]), "+f"(d[13]), "+f"(d[14]), "+f"(d[15]), "+f"(d[16]),
        "+f"(d[17]), "+f"(d[18]), "+f"(d[19]), "+f"(d[20]), "+f"(d[21]), "+f"(d[22]), "+f"(d[23])
      : "l"(da), "l"(db), "r"(sd), "n"(SA), "n"(SB), "n"(TA), "n"(TB));
}
template <int SA, int SB, int TA, int TB>
__device__ __forceinline__ void wgmma_ss_128(float (&d)[64], uint64_t da, uint64_t db, int sd) {
  asm volatile("{\n.reg .pred p;\nsetp.ne.b32 p, %66, 0;\n"
      "wgmma.mma_async.sync.aligned.m64n128k16.f32.bf16.bf16 {"
      "%0, %1, %2, %3, %4, %5, %6, %7, %8, %9, %10, %11, %12, %13, %14, %15, %16, %17, %18, %19, %20, %21, %22, %23, "
      "%24, %25, %26, %27, %28, %29, %30, %31, %32, %33, %34, %35, %36, %37, %38, %39, %40, %41, %42, %43, %44, %45, "
      "%46, %47, %48, %49, %50, %51, %52, %53, %54, %55, %56, %57, %58, %59, %60, %61, %62, %63"
      "}, %64, %65, p, %67, %68, %69, %70;\n}\n"
      : "+f"(d[0]), "+f"(d[1]), "+f"(d[2]), "+f"(d[3]), "+f"(d[4]), "+f"(d[5]), "+f"(d[6]), "+f"(d[7]), "+f"(d[8]),
        "+f"(d[9]), "+f"(d[10]), "+f"(d[11]), "+f"(d[12]), "+f"(d[13]), "+f"(d[14]), "+f"(d[15]), "+f"(d[16]),
        "+f"(d[17]), "+f"(d[18]), "+f"(d[19]), "+f"(d[20]), "+f"(d[21]), "+f"(d[22]), "+f"(d[23]), "+f"(d[24]),
        "+f"(d[25]), "+f"(d[26]), "+f"(d[27]), "+f"(d[28]), "+f"(d[29]), "+f"(d[30]), "+f"(d[31]), "+f"(d[32]),
        "+f"(d[33]), "+f"(d[34]), "+f"(d[35]), "+f"(d[36]), "+f"(d[37]), "+f"(d[38]), "+f"(d[39]), "+f"(d[40]),
        "+f"(d[41]), "+f"(d[42]), "+f"(d[43]), "+f"(d[44]), "+f"(d[45]), "+f"(d[46]), "+f"(d[47]), "+f"(d[48]),
        "+f"(d[49]), "+f"(d[50]), "+f"(d[51]), "+f"(d[52]), "+f"(d[53]), "+f"(d[54]), "+f"(d[55]), "+f"(d[56]),
        "+f"(d[57]), "+f"(d[58]), "+f"(d[59]), "+f"(d[60]), "+f"(d[61]), "+f"(d[62]), "+f"(d[63])
      : "l"(da), "l"(db), "r"(sd), "n"(SA), "n"(SB), "n"(TA), "n"(TB));
}
template <int SA, int SB, int TA, int TB>
__device__ __forceinline__ void wgmma_ss_168(float (&d)[84], uint64_t da, uint64_t db, int sd) {
  asm volatile("{\n.reg .pred p;\nsetp.ne.b32 p, %86, 0;\n"
      "wgmma.mma_async.sync.aligned.m64n168k16.f32.bf16.bf16 {"
      "%0, %1, %2, %3, %4, %5, %6, %7, %8, %9, %10, %11, %12, %13, %14, %15, %16, %17, %18, %19, %20, %21, %22, %23, "
      "%24, %25, %26, %27, %28, %29, %30, %31, %32, %33, %34, %35, %36, %37, %38, %39, %40, %41, %42, %43, %44, %45, "
      "%46, %47, %48, %49, %50, %51, %52, %53, %54, %55, %56, %57, %58, %59, %60, %61, %62, %63, %64, %65, %66, %67, "
      "%68, %69, %70, %71, %72, %73, %74, %75, %76, %77, %78, %79, %80, %81, %82, %83"
      "}, %84, %85, p, %87, %88, %89, %90;\n}\n"
      : "+f"(d[0]), "+f"(d[1]), "+f"(d[2]), "+f"(d[3]), "+f"(d[4]), "+f"(d[5]), "+f"(d[6]), "+f"(d[7]), "+f"(d[8]),
        "+f"(d[9]), "+f"(d[10]), "+f"(d[11]), "+f"(d[12]), "+f"(d[13]), "+f"(d[14]), "+f"(d[15]), "+f"(d[16]),
        "+f"(d[17]), "+f"(d[18]), "+f"(d[19]), "+f"(d[20]), "+f"(d[21]), "+f"(d[22]), "+f"(d[23]), "+f"(d[24]),
        "+f"(d[25]), "+f"(d[26]), "+f"(d[27]), "+f"(d[28]), "+f"(d[29]), "+f"(d[30]), "+f"(d[31]), "+f"(d[32]),
        "+f"(d[33]), "+f"(d[34]), "+f"(d[35]), "+f"(d[36]), "+f"(d[37]), "+f"(d[38]), "+f"(d[39]), "+f"(d[40]),
        "+f"(d[41]), "+f"(d[42]), "+f"(d[43]), "+f"(d[44]), "+f"(d[45]), "+f"(d[46]), "+f"(d[47]), "+f"(d[48]),
        "+f"(d[49]), "+f"(d[50]), "+f"(d[51]), "+f"(d[52]), "+f"(d[53]), "+f"(d[54]), "+f"(d[55]), "+f"(d[56]),
        "+f"(d[57]), "+f"(d[58]), "+f"(d[59]), "+f"(d[60]), "+f"(d[61]), "+f"(d[62]), "+f"(d[63]), "+f"(d[64]),
        "+f"(d[65]), "+f"(d[66]), "+f"(d[67]), "+f"(d[68]), "+f"(d[69]), "+f"(d[70]), "+f"(d[71]), "+f"(d[72]),
        "+f"(d[73]), "+f"(d[74]), "+f"(d[75]), "+f"(d[76]), "+f"(d[77]), "+f"(d[78]), "+f"(d[79]), "+f"(d[80]),
        "+f"(d[81]), "+f"(d[82]), "+f"(d[83])
      : "l"(da), "l"(db), "r"(sd), "n"(SA), "n"(SB), "n"(TA), "n"(TB));
}
template <int SA, int SB, int TB>
__device__ __forceinline__ void wgmma_rs_64(float (&d)[32], uint32_t a0, uint32_t a1, uint32_t a2, uint32_t a3, uint64_t db, int sd) {
  asm volatile("{\n.reg .pred p;\nsetp.ne.b32 p, %37, 0;\n"
      "wgmma.mma_async.sync.aligned.m64n64k16.f32.bf16.bf16 {"
      "%0, %1, %2, %3, %4, %5, %6, %7, %8, %9, %10, %11, %12, %13, %14, %15, %16, %17, %18, %19, %20, %21, %22, %23, "
      "%24, %25, %26, %27, %28, %29, %30, %31"
      "}, {%32, %33, %34, %35}, %36, p, %38, %39, %40;\n}\n"
      : "+f"(d[0]), "+f"(d[1]), "+f"(d[2]), "+f"(d[3]), "+f"(d[4]), "+f"(d[5]), "+f"(d[6]), "+f"(d[7]), "+f"(d[8]),
        "+f"(d[9]), "+f"(d[10]), "+f"(d[11]), "+f"(d[12]), "+f"(d[13]), "+f"(d[14]), "+f"(d[15]), "+f"(d[16]),
        "+f"(d[17]), "+f"(d[18]), "+f"(d[19]), "+f"(d[20]), "+f"(d[21]), "+f"(d[22]), "+f"(d[23]), "+f"(d[24]),
        "+f"(d[25]), "+f"(d[26]), "+f"(d[27]), "+f"(d[28]), "+f"(d[29]), "+f"(d[30]), "+f"(d[31])
      : "r"(a0), "r"(a1), "r"(a2), "r"(a3), "l"(db), "r"(sd), "n"(SA), "n"(SB), "n"(TB));
}
template <int SA, int SB, int TB>
__device__ __forceinline__ void wgmma_rs_128(float (&d)[64], uint32_t a0, uint32_t a1, uint32_t a2, uint32_t a3, uint64_t db, int sd) {
  asm volatile("{\n.reg .pred p;\nsetp.ne.b32 p, %69, 0;\n"
      "wgmma.mma_async.sync.aligned.m64n128k16.f32.bf16.bf16 {"
      "%0, %1, %2, %3, %4, %5, %6, %7, %8, %9, %10, %11, %12, %13, %14, %15, %16, %17, %18, %19, %20, %21, %22, %23, "
      "%24, %25, %26, %27, %28, %29, %30, %31, %32, %33, %34, %35, %36, %37, %38, %39, %40, %41, %42, %43, %44, %45, "
      "%46, %47, %48, %49, %50, %51, %52, %53, %54, %55, %56, %57, %58, %59, %60, %61, %62, %63"
      "}, {%64, %65, %66, %67}, %68, p, %70, %71, %72;\n}\n"
      : "+f"(d[0]), "+f"(d[1]), "+f"(d[2]), "+f"(d[3]), "+f"(d[4]), "+f"(d[5]), "+f"(d[6]), "+f"(d[7]), "+f"(d[8]),
        "+f"(d[9]), "+f"(d[10]), "+f"(d[11]), "+f"(d[12]), "+f"(d[13]), "+f"(d[14]), "+f"(d[15]), "+f"(d[16]),
        "+f"(d[17]), "+f"(d[18]), "+f"(d[19]), "+f"(d[20]), "+f"(d[21]), "+f"(d[22]), "+f"(d[23]), "+f"(d[24]),
        "+f"(d[25]), "+f"(d[26]), "+f"(d[27]), "+f"(d[28]), "+f"(d[29]), "+f"(d[30]), "+f"(d[31]), "+f"(d[32]),
        "+f"(d[33]), "+f"(d[34]), "+f"(d[35]), "+f"(d[36]), "+f"(d[37]), "+f"(d[38]), "+f"(d[39]), "+f"(d[40]),
        "+f"(d[41]), "+f"(d[42]), "+f"(d[43]), "+f"(d[44]), "+f"(d[45]), "+f"(d[46]), "+f"(d[47]), "+f"(d[48]),
        "+f"(d[49]), "+f"(d[50]), "+f"(d[51]), "+f"(d[52]), "+f"(d[53]), "+f"(d[54]), "+f"(d[55]), "+f"(d[56]),
        "+f"(d[57]), "+f"(d[58]), "+f"(d[59]), "+f"(d[60]), "+f"(d[61]), "+f"(d[62]), "+f"(d[63])
      : "r"(a0), "r"(a1), "r"(a2), "r"(a3), "l"(db), "r"(sd), "n"(SA), "n"(SB), "n"(TB));
}
template <int SA, int SB, int TB>
__device__ __forceinline__ void wgmma_rs_256(float (&d)[128], uint32_t a0, uint32_t a1, uint32_t a2, uint32_t a3, uint64_t db, int sd) {
  asm volatile("{\n.reg .pred p;\nsetp.ne.b32 p, %133, 0;\n"
      "wgmma.mma_async.sync.aligned.m64n256k16.f32.bf16.bf16 {"
      "%0, %1, %2, %3, %4, %5, %6, %7, %8, %9, %10, %11, %12, %13, %14, %15, %16, %17, %18, %19, %20, %21, %22, %23, "
      "%24, %25, %26, %27, %28, %29, %30, %31, %32, %33, %34, %35, %36, %37, %38, %39, %40, %41, %42, %43, %44, %45, "
      "%46, %47, %48, %49, %50, %51, %52, %53, %54, %55, %56, %57, %58, %59, %60, %61, %62, %63, %64, %65, %66, %67, "
      "%68, %69, %70, %71, %72, %73, %74, %75, %76, %77, %78, %79, %80, %81, %82, %83, %84, %85, %86, %87, %88, %89, "
      "%90, %91, %92, %93, %94, %95, %96, %97, %98, %99, %100, %101, %102, %103, %104, %105, %106, %107, %108, %109, "
      "%110, %111, %112, %113, %114, %115, %116, %117, %118, %119, %120, %121, %122, %123, %124, %125, %126, %127"
      "}, {%128, %129, %130, %131}, %132, p, %134, %135, %136;\n}\n"
      : "+f"(d[0]), "+f"(d[1]), "+f"(d[2]), "+f"(d[3]), "+f"(d[4]), "+f"(d[5]), "+f"(d[6]), "+f"(d[7]), "+f"(d[8]),
        "+f"(d[9]), "+f"(d[10]), "+f"(d[11]), "+f"(d[12]), "+f"(d[13]), "+f"(d[14]), "+f"(d[15]), "+f"(d[16]),
        "+f"(d[17]), "+f"(d[18]), "+f"(d[19]), "+f"(d[20]), "+f"(d[21]), "+f"(d[22]), "+f"(d[23]), "+f"(d[24]),
        "+f"(d[25]), "+f"(d[26]), "+f"(d[27]), "+f"(d[28]), "+f"(d[29]), "+f"(d[30]), "+f"(d[31]), "+f"(d[32]),
        "+f"(d[33]), "+f"(d[34]), "+f"(d[35]), "+f"(d[36]), "+f"(d[37]), "+f"(d[38]), "+f"(d[39]), "+f"(d[40]),
        "+f"(d[41]), "+f"(d[42]), "+f"(d[43]), "+f"(d[44]), "+f"(d[45]), "+f"(d[46]), "+f"(d[47]), "+f"(d[48]),
        "+f"(d[49]), "+f"(d[50]), "+f"(d[51]), "+f"(d[52]), "+f"(d[53]), "+f"(d[54]), "+f"(d[55]), "+f"(d[56]),
        "+f"(d[57]), "+f"(d[58]), "+f"(d[59]), "+f"(d[60]), "+f"(d[61]), "+f"(d[62]), "+f"(d[63]), "+f"(d[64]),
        "+f"(d[65]), "+f"(d[66]), "+f"(d[67]), "+f"(d[68]), "+f"(d[69]), "+f"(d[70]), "+f"(d[71]), "+f"(d[72]),
        "+f"(d[73]), "+f"(d[74]), "+f"(d[75]), "+f"(d[76]), "+f"(d[77]), "+f"(d[78]), "+f"(d[79]), "+f"(d[80]),
        "+f"(d[81]), "+f"(d[82]), "+f"(d[83]), "+f"(d[84]), "+f"(d[85]), "+f"(d[86]), "+f"(d[87]), "+f"(d[88]),
        "+f"(d[89]), "+f"(d[90]), "+f"(d[91]), "+f"(d[92]), "+f"(d[93]), "+f"(d[94]), "+f"(d[95]), "+f"(d[96]),
        "+f"(d[97]), "+f"(d[98]), "+f"(d[99]), "+f"(d[100]), "+f"(d[101]), "+f"(d[102]), "+f"(d[103]), "+f"(d[104]),
        "+f"(d[105]), "+f"(d[106]), "+f"(d[107]), "+f"(d[108]), "+f"(d[109]), "+f"(d[110]), "+f"(d[111]),
        "+f"(d[112]), "+f"(d[113]), "+f"(d[114]), "+f"(d[115]), "+f"(d[116]), "+f"(d[117]), "+f"(d[118]),
        "+f"(d[119]), "+f"(d[120]), "+f"(d[121]), "+f"(d[122]), "+f"(d[123]), "+f"(d[124]), "+f"(d[125]),
        "+f"(d[126]), "+f"(d[127])
      : "r"(a0), "r"(a1), "r"(a2), "r"(a3), "l"(db), "r"(sd), "n"(SA), "n"(SB), "n"(TB));
}

__device__ const __align__(128) uint32_t c_img[3584] = {
    0x00003c80, 0x00003c80, 0x00003c80, 0x00003c80, 0x00003c80, 0x00003c80, 0x00003c80, 0x00003c80, 0x00003c80, 0x00003c80,
    0x00003c80, 0x00003c80, 0x00003c80, 0x00003c80, 0x00003c80, 0x00003c80, 0x00003c80, 0x00003c80, 0x00003c80, 0x00003c80,
    0x00003c80, 0x00003c80, 0x00003c80, 0x00003c80, 0x00003c80, 0x00003c80, 0x00003c80, 0x00003c80, 0x00003c80, 0x00003c80,
    0x00003c80, 0x00003c80, 0x3c463c22, 0x3c623bf1, 0x3c753b95, 0x3c7f3ac9, 0x3ac93c7f, 0x3b953c75, 0x3bf13c62, 0x3c223c46,
    0x3c22bc46, 0x3bf1bc62, 0x3b95bc75, 0x3ac9bc7f, 0x3c7fbac9, 0x3c75bb95, 0x3c62bbf1, 0x3c46bc22, 0xbc46bc22, 0xbc62bbf1,
    0xbc75bb95, 0xbc7fbac9, 0xbac9bc7f, 0xbb95bc75, 0xbbf1bc62, 0xbc22bc46, 0xbc223c46, 0xbbf13c62, 0xbb953c75, 0xbac93c7f,
    0xbc7f3ac9, 0xbc753b95, 0xbc623bf1, 0xbc463c22, 0xbb48bc7b, 0xbc0ebc55, 0xbc55bc0e, 0xbc7bbb48, 0xbc7b3b48, 0xbc553c0e,
    0xbc0e3c55, 0xbb483c7b, 0x3b483c7b, 0x3c0e3c55, 0x3c553c0e, 0x3c7b3b48, 0x3c7bbb48, 0x3c55bc0e, 0x3c0ebc55, 0x3b48bc7b,
    0xbb48bc7b, 0xbc0ebc55, 0xbc55bc0e, 0xbc7bbb48, 0xbc7b3b48, 0xbc553c0e, 0xbc0e3c55, 0xbb483c7b, 0x3b483c7b, 0x3c0e3c55,
    0x3c553c0e, 0x3c7b3b48, 0x3c7bbb48, 0x3c55bc0e, 0x3c0ebc55, 0x3b48bc7b, 0x3c623bf1, 0x3c7fbac9, 0x3c46bc22, 0x3b95bc75,
    0xbc753b95, 0xbc223c46, 0xbac93c7f, 0x3bf13c62, 0x3bf1bc62, 0xbac9bc7f, 0xbc22bc46, 0xbc75bb95, 0x3b953c75, 0x3c463c22,
    0x3c7f3ac9, 0x3c62bbf1, 0xbc62bbf1, 0xbc7f3ac9, 0xbc463c22, 0xbb953c75, 0x3c75bb95, 0x3c22bc46, 0x3ac9bc7f, 0xbbf1bc62,
    0xbbf13c62, 0x3ac93c7f, 0x3c223c46, 0x3c753b95, 0xbb95bc75, 0xbc46bc22, 0xbc7fbac9, 0xbc623bf1, 0x3bc43c6d, 0x3c6d3bc4,
    0x3c6dbbc4, 0x3bc4bc6d, 0xbbc4bc6d, 0xbc6dbbc4, 0xbc6d3bc4, 0xbbc43c6d, 0x3bc43c6d, 0x3c6d3bc4, 0x3c6dbbc4, 0x3bc4bc6d,
    0xbbc4bc6d, 0xbc6dbbc4, 0xbc6d3bc4, 0xbbc43c6d, 0x3bc43c6d, 0x3c6d3bc4, 0x3c6dbbc4, 0x3bc4bc6d, 0xbbc4bc6d, 0xbc6dbbc4,
    0xbc6d3bc4, 0xbbc43c6d, 0x3bc43c6d, 0x3c6d3bc4, 0x3c6dbbc4, 0x3bc4bc6d, 0xbbc4bc6d, 0xbc6dbbc4, 0xbc6d3bc4, 0xbbc43c6d,
    0x3c753b95, 0x3c46bc22, 0xbac9bc7f, 0xbc62bbf1, 0xbbf1bc62, 0xbc7fbac9, 0xbc223c46, 0x3b953c75, 0x3b95bc75, 0xbc22bc46,
    0xbc7f3ac9, 0xbbf13c62, 0xbc623bf1, 0xbac93c7f, 0x3c463c22, 0x3c75bb95, 0xbc75bb95, 0xbc463c22, 0x3ac93c7f, 0x3c623bf1,
    0x3bf13c62, 0x3c7f3ac9, 0x3c22bc46, 0xbb95bc75, 0xbb953c75, 0x3c223c46, 0x3c7fbac9, 0x3bf1bc62, 0x3c62bbf1, 0x3ac9bc7f,
    0xbc46bc22, 0xbc753b95, 0xbc0ebc55, 0xbc7b3b48, 0xbb483c7b, 0x3c553c0e, 0x3c55bc0e, 0xbb48bc7b, 0xbc7bbb48, 0xbc0e3c55,
    0x3c0e3c55, 0x3c7bbb48, 0x3b48bc7b, 0xbc55bc0e, 0xbc553c0e, 0x3b483c7b, 0x3c7b3b48, 0x3c0ebc55, 0xbc0ebc55, 0xbc7b3b48,
    0xbb483c7b, 0x3c553c0e, 0x3c55bc0e, 0xbb48bc7b, 0xbc7bbb48, 0xbc0e3c55, 0x3c0e3c55, 0x3c7bbb48, 0x3b48bc7b, 0xbc55bc0e,
    0xbc553c0e, 0x3b483c7b, 0x3c7b3b48, 0x3c0ebc55, 0x3c7f3ac9, 0x3b95bc75, 0xbc62bbf1, 0xbc223c46, 0x3c46bc22, 0xbbf1bc62,
    0xbc753b95, 0x3ac93c7f, 0x3ac9bc7f, 0xbc75bb95, 0xbbf13c62, 0x3c463c22, 0xbc22bc46, 0xbc623bf1, 0x3b953c75, 0x3c7fbac9,
    0xbc7fbac9, 0xbb953c75, 0x3c623bf1, 0x3c22bc46, 0xbc463c22, 0x3bf13c62, 0x3c75bb95, 0xbac9bc7f, 0xbac93c7f, 0x3c753b95,
    0x3bf1bc62, 0xbc46bc22, 0x3c223c46, 0x3c62bbf1, 0xbb95bc75, 0xbc7f3ac9, 0x3a493c80, 0x3b163c7d, 0x3b793c78, 0x3bac3c71,
    0x3bdb3c67, 0x3c043c5c, 0x3c183c4e, 0x3c2c3c3e, 0x3c3e3c2c, 0x3c4e3c18, 0x3c5c3c04, 0x3c673bdb, 0x3c713bac, 0x3c783b79,
    0x3c7d3b16, 0x3c803a49, 0x3c80ba49, 0x3c7dbb16, 0x3c78bb79, 0x3c71bbac, 0x3c67bbdb, 0x3c5cbc04, 0x3c4ebc18, 0x3c3ebc2c,
    0x3c2cbc3e, 0x3c18bc4e, 0x3c04bc5c, 0x3bdbbc67, 0x3bacbc71, 0x3b79bc78, 0x3b16bc7d, 0x3a49bc80, 0x3c783b79, 0x3c80ba49,
    0x3c71bbac, 0x3c4ebc18, 0x3b163c7d, 0x3bdb3c67, 0x3c2c3c3e, 0x3c5c3c04, 0xbc04bc5c, 0xbc3ebc2c, 0xbc67bbdb, 0xbc7dbb16,
    0x3c18bc4e, 0x3bacbc71, 0x3a49bc80, 0xbb79bc78, 0xbb793c78, 0x3a493c80, 0x3bac3c71, 0x3c183c4e, 0xbc7d3b16, 0xbc673bdb,
    0xbc3e3c2c, 0xbc043c5c, 0x3c5cbc04, 0x3c2cbc3e, 0x3bdbbc67, 0x3b16bc7d, 0x3c4e3c18, 0x3c713bac, 0x3c803a49, 0x3c78bb79,
    0xbc5cbc04, 0xbc80ba49, 0xbc673bdb, 0xbc183c4e, 0xbb163c7d, 0x3bac3c71, 0x3c3e3c2c, 0x3c783b79, 0x3b793c78, 0x3c2c3c3e,
    0x3c713bac, 0x3c7dbb16, 0x3c4ebc18, 0x3bdbbc67, 0xba49bc80, 0xbc04bc5c, 0xbc043c5c, 0xba493c80, 0x3bdb3c67, 0x3c4e3c18,
    0x3c7d3b16, 0x3c71bbac, 0x3c2cbc3e, 0x3b79bc78, 0x3c78bb79, 0x3c3ebc2c, 0x3bacbc71, 0xbb16bc7d, 0xbc18bc4e, 0xbc67bbdb,
    0xbc803a49, 0xbc5c3c04, 0x3c3ebc2c, 0x3b16bc7d, 0xbc04bc5c, 0xbc71bbac, 0xbbdb3c67, 0x3b793c78, 0x3c4e3c18, 0x3c80ba49,
    0x3a49bc80, 0xbc18bc4e, 0xbc78bb79, 0xbc673bdb, 0x3bac3c71, 0x3c5c3c04, 0x3c7dbb16, 0x3c2cbc3e, 0x3c2c3c3e, 0x3c7d3b16,
    0x3c5cbc04, 0x3bacbc71, 0xbc67bbdb, 0xbc783b79, 0xbc183c4e, 0x3a493c80, 0x3c803a49, 0x3c4ebc18, 0x3b79bc78, 0xbbdbbc67,
    0xbc713bac, 0xbc043c5c, 0x3b163c7d, 0x3c3e3c2c, 0x3c67bbdb, 0x3b79bc78, 0xbc18bc4e, 0xbc80ba49, 0xbc2c3c3e, 0x3b163c7d,
    0x3c5c3c04, 0x3c71bbac, 0x3bacbc71, 0xbc04bc5c, 0xbc7dbb16, 0xbc3e3c2c, 0x3a493c80, 0x3c4e3c18, 0x3c78bb79, 0x3bdbbc67,
    0x3bdb3c67, 0x3c783b79, 0x3c4ebc18, 0x3a49bc80, 0xbc3ebc2c, 0xbc7d3b16, 0xbc043c5c, 0x3bac3c71, 0x3c713bac, 0x3c5cbc04,
    0x3b16bc7d, 0xbc2cbc3e, 0xbc803a49, 0xbc183c4e, 0x3b793c78, 0x3c673bdb, 0xbb16bc7d, 0xbc71bbac, 0xbc3e3c2c, 0x3b793c78,
    0xbc5c3c04, 0x3a493c80, 0x3c673bdb, 0x3c4ebc18, 0xbc183c4e, 0x3bdb3c67, 0x3c803a49, 0x3c04bc5c, 0x3c783b79, 0x3c2cbc3e,
    0xbbacbc71, 0xbc7dbb16, 0xbc7d3b16, 0xbbac3c71, 0x3c2c3c3e, 0x3c78bb79, 0x3c043c5c, 0x3c80ba49, 0x3bdbbc67, 0xbc18bc4e,
    0x3c4e3c18, 0x3c67bbdb, 0x3a49bc80, 0xbc5cbc04, 0x3b79bc78, 0xbc3ebc2c, 0xbc713bac, 0xbb163c7d, 0xbb163c7d, 0x3c673bdb,
    0x3c2cbc3e, 0xbc04bc5c, 0xbc783b79, 0xba493c80, 0x3c713bac, 0x3c18bc4e, 0x3c4ebc18, 0xbbacbc71, 0xbc803a49, 0xbb793c78,
    0x3c5c3c04, 0x3c3ebc2c, 0xbbdbbc67, 0xbc7d3b16, 0xbc7dbb16, 0xbbdb3c67, 0x3c3e3c2c, 0x3c5cbc04, 0xbb79bc78, 0xbc80ba49,
    0xbbac3c71, 0x3c4e3c18, 0x3c183c4e, 0x3c71bbac, 0xba49bc80, 0xbc78bb79, 0xbc043c5c, 0x3c2c3c3e, 0x3c67bbdb, 0xbb16bc7d,
    0xbc67bbdb, 0xbc043c5c, 0x3c4e3c18, 0x3c2cbc3e, 0xbc80ba49, 0xbb163c7d, 0x3c783b79, 0x3bacbc71, 0xbc713bac, 0x3b793c78,
    0x3c7dbb16, 0xba49bc80, 0xbc3e3c2c, 0x3c183c4e, 0x3c5cbc04, 0xbbdbbc67, 0xbbdb3c67, 0x3c5c3c04, 0x3c18bc4e, 0xbc3ebc2c,
    0xba493c80, 0x3c7d3b16, 0x3b79bc78, 0xbc71bbac, 0x3bac3c71, 0x3c78bb79, 0xbb16bc7d, 0xbc803a49, 0x3c2c3c3e, 0x3c4ebc18,
    0xbc04bc5c, 0xbc673bdb, 0x3c353c35, 0x3c35bc35, 0xbc35bc35, 0xbc353c35, 0x3c353c35, 0x3c35bc35, 0xbc35bc35, 0xbc353c35,
    0x3c353c35, 0x3c35bc35, 0xbc35bc35, 0xbc353c35, 0x3c353c35, 0x3c35bc35, 0xbc35bc35, 0xbc353c35, 0x3c353c35, 0x3c35bc35,
    0xbc35bc35, 0xbc353c35, 0x3c353c35, 0x3c35bc35, 0xbc35bc35, 0xbc353c35, 0x3c353c35, 0x3c35bc35, 0xbc35bc35, 0xbc353c35,
    0x3c353c35, 0x3c35bc35, 0xbc35bc35, 0xbc353c35, 0x3c7fbac9, 0xbb95bc75, 0xbc623bf1, 0x3c223c46, 0x3c463c22, 0x3bf1bc62,
    0xbc75bb95, 0xbac93c7f, 0xbac9bc7f, 0xbc753b95, 0x3bf13c62, 0x3c46bc22, 0x3c22bc46, 0xbc62bbf1, 0xbb953c75, 0x3c7f3ac9,
    0xbc7f3ac9, 0x3b953c75, 0x3c62bbf1, 0xbc22bc46, 0xbc46bc22, 0xbbf13c62, 0x3c753b95, 0x3ac9bc7f, 0x3ac93c7f, 0x3c75bb95,
    0xbbf1bc62, 0xbc463c22, 0xbc223c46, 0x3c623bf1, 0x3b95bc75, 0xbc7fbac9, 0xbc55bc0e, 0xbb483c7b, 0x3c7bbb48, 0xbc0ebc55,
    0xbc0e3c55, 0x3c7b3b48, 0xbb48bc7b, 0xbc553c0e, 0x3c553c0e, 0x3b48bc7b, 0xbc7b3b48, 0x3c0e3c55, 0x3c0ebc55, 0xbc7bbb48,
    0x3b483c7b, 0x3c55bc0e, 0xbc55bc0e, 0xbb483c7b, 0x3c7bbb48, 0xbc0ebc55, 0xbc0e3c55, 0x3c7b3b48, 0xbb48bc7b, 0xbc553c0e,
    0x3c553c0e, 0x3b48bc7b, 0xbc7b3b48, 0x3c0e3c55, 0x3c0ebc55, 0xbc7bbb48, 0x3b483c7b, 0x3c55bc0e, 0x3c75bb95, 0xbc46bc22,
    0xbac93c7f, 0x3c62bbf1, 0xbbf13c62, 0x3c7fbac9, 0xbc22bc46, 0xbb953c75, 0xbb95bc75, 0xbc223c46, 0x3c7f3ac9, 0xbbf1bc62,
    0x3c623bf1, 0xbac9bc7f, 0xbc463c22, 0x3c753b95, 0xbc753b95, 0x3c463c22, 0x3ac9bc7f, 0xbc623bf1, 0x3bf1bc62, 0xbc7f3ac9,
    0x3c223c46, 0x3b95bc75, 0x3b953c75, 0x3c22bc46, 0xbc7fbac9, 0x3bf13c62, 0xbc62bbf1, 0x3ac93c7f, 0x3c46bc22, 0xbc75bb95,
    0x3c6d3bc4, 0xbbc4bc6d, 0xbbc43c6d, 0x3c6dbbc4, 0xbc6dbbc4, 0x3bc43c6d, 0x3bc4bc6d, 0xbc6d3bc4, 0x3c6d3bc4, 0xbbc4bc6d,
    0xbbc43c6d, 0x3c6dbbc4, 0xbc6dbbc4, 0x3bc43c6d, 0x3bc4bc6d, 0xbc6d3bc4, 0x3c6d3bc4, 0xbbc4bc6d, 0xbbc43c6d, 0x3c6dbbc4,
    0xbc6dbbc4, 0x3bc43c6d, 0x3bc4bc6d, 0xbc6d3bc4, 0x3c6d3bc4, 0xbbc4bc6d, 0xbbc43c6d, 0x3c6dbbc4, 0xbc6dbbc4, 0x3bc43c6d,
    0x3bc4bc6d, 0xbc6d3bc4, 0x3c62bbf1, 0xbc7fbac9, 0x3c463c22, 0xbb95bc75, 0xbc75bb95, 0x3c223c46, 0xbac9bc7f, 0xbbf13c62,
    0xbbf1bc62, 0xbac93c7f, 0x3c22bc46, 0xbc753b95, 0xbb953c75, 0x3c46bc22, 0xbc7f3ac9, 0x3c623bf1, 0xbc623bf1, 0x3c7f3ac9,
    0xbc46bc22, 0x3b953c75, 0x3c753b95, 0xbc22bc46, 0x3ac93c7f, 0x3bf1bc62, 0x3bf13c62, 0x3ac9bc7f, 0xbc223c46, 0x3c75bb95,
    0x3b95bc75, 0xbc463c22, 0x3c7fbac9, 0xbc62bbf1, 0xbc7bbb48, 0x3c553c0e, 0xbc0ebc55, 0x3b483c7b, 0x3b48bc7b, 0xbc0e3c55,
    0x3c55bc0e, 0xbc7b3b48, 0x3c7b3b48, 0xbc55bc0e, 0x3c0e3c55, 0xbb48bc7b, 0xbb483c7b, 0x3c0ebc55, 0xbc553c0e, 0x3c7bbb48,
    0xbc7bbb48, 0x3c553c0e, 0xbc0ebc55, 0x3b483c7b, 0x3b48bc7b, 0xbc0e3c55, 0x3c55bc0e, 0xbc7b3b48, 0x3c7b3b48, 0xbc55bc0e,
    0x3c0e3c55, 0xbb48bc7b, 0xbb483c7b, 0x3c0ebc55, 0xbc553c0e, 0x3c7bbb48, 0x3c46bc22, 0xbc623bf1, 0x3c75bb95, 0xbc7f3ac9,
    0x3ac9bc7f, 0xbb953c75, 0x3bf1bc62, 0xbc223c46, 0xbc22bc46, 0x3bf13c62, 0xbb95bc75, 0x3ac93c7f, 0xbc7fbac9, 0x3c753b95,
    0xbc62bbf1, 0x3c463c22, 0xbc463c22, 0x3c62bbf1, 0xbc753b95, 0x3c7fbac9, 0xbac93c7f, 0x3b95bc75, 0xbbf13c62, 0x3c22bc46,
    0x3c223c46, 0xbbf1bc62, 0x3b953c75, 0xbac9bc7f, 0x3c7f3ac9, 0xbc75bb95, 0x3c623bf1, 0xbc46bc22, 0x3c3e3c2c, 0x3c18bc4e,
    0xbc5cbc04, 0xbbdb3c67, 0x3c713bac, 0x3b79bc78, 0xbc7dbb16, 0xba493c80, 0x3c80ba49, 0xbb16bc7d, 0xbc783b79, 0x3bac3c71,
    0x3c67bbdb, 0xbc04bc5c, 0xbc4e3c18, 0x3c2c3c3e, 0x3c2cbc3e, 0xbc4ebc18, 0xbc043c5c, 0x3c673bdb, 0x3bacbc71, 0xbc78bb79,
    0xbb163c7d, 0x3c803a49, 0xba49bc80, 0xbc7d3b16, 0x3b793c78, 0x3c71bbac, 0xbbdbbc67, 0xbc5c3c04, 0x3c183c4e, 0x3c3ebc2c,
    0x3c5cbc04, 0xbc3ebc2c, 0xbbdb3c67, 0x3c7d3b16, 0x3c4e3c18, 0x3bacbc71, 0xbc80ba49, 0x3b793c78, 0xbc78bb79, 0x3a493c80,
    0x3c71bbac, 0xbc18bc4e, 0xbb16bc7d, 0xbc673bdb, 0x3c2c3c3e, 0x3c04bc5c, 0x3c043c5c, 0x3c2cbc3e, 0xbc67bbdb, 0xbb163c7d,
    0xbc183c4e, 0x3c713bac, 0x3a49bc80, 0xbc783b79, 0x3b79bc78, 0xbc803a49, 0x3bac3c71, 0x3c4ebc18, 0x3c7dbb16, 0xbbdbbc67,
    0xbc3e3c2c, 0x3c5c3c04, 0xbc783b79, 0x3c2c3c3e, 0x3bacbc71, 0xbc7d3b16, 0x3c183c4e, 0x3bdbbc67, 0xbc803a49, 0x3c043c5c,
    0x3c5c3c04, 0x3a49bc80, 0xbc673bdb, 0x3c4e3c18, 0x3b16bc7d, 0xbc713bac, 0x3c3e3c2c, 0x3b79bc78, 0x3b793c78, 0x3c3ebc2c,
    0xbc71bbac, 0x3b163c7d, 0x3c4ebc18, 0xbc67bbdb, 0x3a493c80, 0x3c5cbc04, 0x3c04bc5c, 0xbc80ba49, 0x3bdb3c67, 0x3c18bc4e,
    0xbc7dbb16, 0x3bac3c71, 0x3c2cbc3e, 0xbc78bb79, 0x3a49bc80, 0xbc4e3c18, 0x3c783b79, 0xbbdbbc67, 0x3bac3c71, 0x3c04bc5c,
    0xbc7d3b16, 0x3c3e3c2c, 0xbc2cbc3e, 0xbb163c7d, 0x3c5cbc04, 0xbc71bbac, 0x3c673bdb, 0xbb79bc78, 0xbc183c4e, 0x3c80ba49,
    0x3c803a49, 0xbc18bc4e, 0xbb793c78, 0x3c67bbdb, 0xbc713bac, 0x3c5c3c04, 0xbb16bc7d, 0xbc2c3c3e, 0x3c3ebc2c, 0xbc7dbb16,
    0x3c043c5c, 0x3bacbc71, 0xbbdb3c67, 0x3c78bb79, 0xbc4ebc18, 0x3a493c80, 0x3bacbc71, 0xbc5c3c04, 0x3c7d3b16, 0xbc2cbc3e,
    0x3a493c80, 0x3c18bc4e, 0xbc783b79, 0x3c673bdb, 0xbbdbbc67, 0xbb793c78, 0x3c4ebc18, 0xbc80ba49, 0x3c3e3c2c, 0xbb16bc7d,
    0xbc043c5c, 0x3c71bbac, 0x3c713bac, 0xbc04bc5c, 0xbb163c7d, 0x3c3ebc2c, 0xbc803a49, 0x3c4e3c18, 0xbb79bc78, 0xbbdb3c67,
    0x3c67bbdb, 0xbc78bb79, 0x3c183c4e, 0x3a49bc80, 0xbc2c3c3e, 0x3c7dbb16, 0xbc5cbc04, 0x3bac3c71, 0xbc4ebc18, 0x3bdb3c67,
    0x3a49bc80, 0xbc043c5c, 0xbb793c78, 0x3c2cbc3e, 0xbc713bac, 0x3c7d3b16, 0x3b163c7d, 0x3bacbc71, 0xbc3e3c2c, 0x3c78bb79,
    0x3c5cbc04, 0xbc803a49, 0x3c673bdb, 0xbc18bc4e, 0xbc183c4e, 0x3c67bbdb, 0xbc80ba49, 0x3c5c3c04, 0x3c783b79, 0xbc3ebc2c,
    0x3bac3c71, 0x3b16bc7d, 0x3c7dbb16, 0xbc71bbac, 0x3c2c3c3e, 0xbb79bc78, 0xbc04bc5c, 0x3a493c80, 0x3bdbbc67, 0xbc4e3c18,
    0x3c183c4e, 0xbbacbc71, 0x3a493c80, 0x3b79bc78, 0xbc043c5c, 0x3c3ebc2c, 0xbc673bdb, 0x3c7dbb16, 0x3b16bc7d, 0xbbdb3c67,
    0x3c2cbc3e, 0xbc5c3c04, 0x3c78bb79, 0xbc80ba49, 0x3c713bac, 0xbc4ebc18, 0xbc4e3c18, 0x3c71bbac, 0xbc803a49, 0x3c783b79,
    0xbc5cbc04, 0x3c2c3c3e, 0xbbdbbc67, 0x3b163c7d, 0x3c7d3b16, 0xbc67bbdb, 0x3c3e3c2c, 0xbc04bc5c, 0x3b793c78, 0x3a49bc80,
    0xbbac3c71, 0x3c18bc4e, 0xbc713bac, 0x3c78bb79, 0xbc7d3b16, 0x3c80ba49, 0xbc3e3c2c, 0x3c4ebc18, 0xbc5c3c04, 0x3c67bbdb,
    0xbbdb3c67, 0x3c04bc5c, 0xbc183c4e, 0x3c2cbc3e, 0xba493c80, 0x3b16bc7d, 0xbb793c78, 0x3bacbc71, 0x3bac3c71, 0xbb79bc78,
    0x3b163c7d, 0xba49bc80, 0x3c2c3c3e, 0xbc18bc4e, 0x3c043c5c, 0xbbdbbc67, 0x3c673bdb, 0xbc5cbc04, 0x3c4e3c18, 0xbc3ebc2c,
    0x3c803a49, 0xbc7dbb16, 0x3c783b79, 0xbc71bbac, 0x3c800000, 0xbc800000, 0x3c800000, 0xbc800000, 0x3c800000, 0xbc800000,
    0x3c800000, 0xbc800000, 0x3c800000, 0xbc800000, 0x3c800000, 0xbc800000, 0x3c800000, 0xbc800000, 0x3c800000, 0xbc800000,
    0x3c800000, 0xbc800000, 0x3c800000, 0xbc800000, 0x3c800000, 0xbc800000, 0x3c800000, 0xbc800000, 0x3c800000, 0xbc800000,
    0x3c800000, 0xbc800000, 0x3c800000, 0xbc800000, 0x3c800000, 0xbc800000, 0x3c22bc46, 0xbbf13c62, 0x3b95bc75, 0xbac93c7f,
    0x3c7fbac9, 0xbc753b95, 0x3c62bbf1, 0xbc463c22, 0xbc46bc22, 0x3c623bf1, 0xbc75bb95, 0x3c7f3ac9, 0xbac9bc7f, 0x3b953c75,
    0xbbf1bc62, 0x3c223c46, 0xbc223c46, 0x3bf1bc62, 0xbb953c75, 0x3ac9bc7f, 0xbc7f3ac9, 0x3c75bb95, 0xbc623bf1, 0x3c46bc22,
    0x3c463c22, 0xbc62bbf1, 0x3c753b95, 0xbc7fbac9, 0x3ac93c7f, 0xbb95bc75, 0x3bf13c62, 0xbc22bc46, 0xbc7b3b48, 0x3c55bc0e,
    0xbc0e3c55, 0x3b48bc7b, 0x3b483c7b, 0xbc0ebc55, 0x3c553c0e, 0xbc7bbb48, 0x3c7bbb48, 0xbc553c0e, 0x3c0ebc55, 0xbb483c7b,
    0xbb48bc7b, 0x3c0e3c55, 0xbc55bc0e, 0x3c7b3b48, 0xbc7b3b48, 0x3c55bc0e, 0xbc0e3c55, 0x3b48bc7b, 0x3b483c7b, 0xbc0ebc55,
    0x3c553c0e, 0xbc7bbb48, 0x3c7bbb48, 0xbc553c0e, 0x3c0ebc55, 0xbb483c7b, 0xbb48bc7b, 0x3c0e3c55, 0xbc55bc0e, 0x3c7b3b48,
    0x3bf1bc62, 0x3ac93c7f, 0xbc22bc46, 0x3c753b95, 0x3b953c75, 0xbc46bc22, 0x3c7f3ac9, 0xbc623bf1, 0xbc62bbf1, 0x3c7fbac9,
    0xbc463c22, 0x3b95bc75, 0x3c75bb95, 0xbc223c46, 0x3ac9bc7f, 0x3bf13c62, 0xbbf13c62, 0xbac9bc7f, 0x3c223c46, 0xbc75bb95,
    0xbb95bc75, 0x3c463c22, 0xbc7fbac9, 0x3c62bbf1, 0x3c623bf1, 0xbc7f3ac9, 0x3c46bc22, 0xbb953c75, 0xbc753b95, 0x3c22bc46,
    0xbac93c7f, 0xbbf1bc62, 0x3c6dbbc4, 0xbbc43c6d, 0xbbc4bc6d, 0x3c6d3bc4, 0xbc6d3bc4, 0x3bc4bc6d, 0x3bc43c6d, 0xbc6dbbc4,
    0x3c6dbbc4, 0xbbc43c6d, 0xbbc4bc6d, 0x3c6d3bc4, 0xbc6d3bc4, 0x3bc4bc6d, 0x3bc43c6d, 0xbc6dbbc4, 0x3c6dbbc4, 0xbbc43c6d,
    0xbbc4bc6d, 0x3c6d3bc4, 0xbc6d3bc4, 0x3bc4bc6d, 0x3bc43c6d, 0xbc6dbbc4, 0x3c6dbbc4, 0xbbc43c6d, 0xbbc4bc6d, 0x3c6d3bc4,
    0xbc6d3bc4, 0x3bc4bc6d, 0x3bc43c6d, 0xbc6dbbc4, 0x3b95bc75, 0x3c223c46, 0xbc7f3ac9, 0x3bf1bc62, 0xbc623bf1, 0x3ac9bc7f,
    0x3c463c22, 0xbc753b95, 0xbc75bb95, 0x3c46bc22, 0x3ac93c7f, 0xbc62bbf1, 0x3bf13c62, 0xbc7fbac9, 0x3c22bc46, 0x3b953c75,
    0xbb953c75, 0xbc22bc46, 0x3c7fbac9, 0xbbf13c62, 0x3c62bbf1, 0xbac93c7f, 0xbc46bc22, 0x3c75bb95, 0x3c753b95, 0xbc463c22,
    0xbac9bc7f, 0x3c623bf1, 0xbbf1bc62, 0x3c7f3ac9, 0xbc223c46, 0xbb95bc75, 0xbc553c0e, 0xbb48bc7b, 0x3c7b3b48, 0xbc0e3c55,
    0xbc0ebc55, 0x3c7bbb48, 0xbb483c7b, 0xbc55bc0e, 0x3c55bc0e, 0x3b483c7b, 0xbc7bbb48, 0x3c0ebc55, 0x3c0e3c55, 0xbc7b3b48,
    0x3b48bc7b, 0x3c553c0e, 0xbc553c0e, 0xbb48bc7b, 0x3c7b3b48, 0xbc0e3c55, 0xbc0ebc55, 0x3c7bbb48, 0xbb483c7b, 0xbc55bc0e,
    0x3c55bc0e, 0x3b483c7b, 0xbc7bbb48, 0x3c0ebc55, 0x3c0e3c55, 0xbc7b3b48, 0x3b48bc7b, 0x3c553c0e, 0x3ac9bc7f, 0x3c753b95,
    0xbbf13c62, 0xbc46bc22, 0xbc22bc46, 0x3c62bbf1, 0x3b953c75, 0xbc7f3ac9, 0xbc7fbac9, 0x3b95bc75, 0x3c623bf1, 0xbc223c46,
    0xbc463c22, 0xbbf1bc62, 0x3c75bb95, 0x3ac93c7f, 0xbac93c7f, 0xbc75bb95, 0x3bf1bc62, 0x3c463c22, 0x3c223c46, 0xbc623bf1,
    0xbb95bc75, 0x3c7fbac9, 0x3c7f3ac9, 0xbb953c75, 0xbc62bbf1, 0x3c22bc46, 0x3c46bc22, 0x3bf13c62, 0xbc753b95, 0xbac9bc7f,
    0x3c80ba49, 0xbc7d3b16, 0x3c78bb79, 0xbc713bac, 0x3c67bbdb, 0xbc5c3c04, 0x3c4ebc18, 0xbc3e3c2c, 0x3c2cbc3e, 0xbc183c4e,
    0x3c04bc5c, 0xbbdb3c67, 0x3bacbc71, 0xbb793c78, 0x3b16bc7d, 0xba493c80, 0xba49bc80, 0x3b163c7d, 0xbb79bc78, 0x3bac3c71,
    0xbbdbbc67, 0x3c043c5c, 0xbc18bc4e, 0x3c2c3c3e, 0xbc3ebc2c, 0x3c4e3c18, 0xbc5cbc04, 0x3c673bdb, 0xbc71bbac, 0x3c783b79,
    0xbc7dbb16, 0x3c803a49, 0x3b79bc78, 0x3a493c80, 0xbbacbc71, 0x3c183c4e, 0x3c7dbb16, 0xbc673bdb, 0x3c3ebc2c, 0xbc043c5c,
    0xbc5c3c04, 0x3c2cbc3e, 0xbbdb3c67, 0x3b16bc7d, 0xbc4ebc18, 0x3c713bac, 0xbc80ba49, 0x3c78bb79, 0x3c783b79, 0xbc803a49,
    0x3c71bbac, 0xbc4e3c18, 0x3b163c7d, 0xbbdbbc67, 0x3c2c3c3e, 0xbc5cbc04, 0xbc04bc5c, 0x3c3e3c2c, 0xbc67bbdb, 0x3c7d3b16,
    0x3c18bc4e, 0xbbac3c71, 0x3a49bc80, 0x3b793c78, 0xbc043c5c, 0x3a49bc80, 0x3bdb3c67, 0xbc4ebc18, 0x3c7d3b16, 0xbc713bac,
    0x3c2cbc3e, 0xbb793c78, 0x3c78bb79, 0xbc3e3c2c, 0x3bacbc71, 0x3b163c7d, 0xbc18bc4e, 0x3c673bdb, 0xbc803a49, 0x3c5cbc04,
    0x3c5c3c04, 0xbc80ba49, 0x3c67bbdb, 0xbc183c4e, 0x3b16bc7d, 0x3bac3c71, 0xbc3ebc2c, 0x3c783b79, 0xbb79bc78, 0x3c2c3c3e,
    0xbc71bbac, 0x3c7dbb16, 0xbc4e3c18, 0x3bdbbc67, 0x3a493c80, 0xbc04bc5c, 0xbc2cbc3e, 0x3c7d3b16, 0xbc5c3c04, 0x3bacbc71,
    0x3c673bdb, 0xbc783b79, 0x3c18bc4e, 0x3a493c80, 0xbc80ba49, 0x3c4ebc18, 0xbb793c78, 0xbbdbbc67, 0x3c71bbac, 0xbc043c5c,
    0xbb16bc7d, 0x3c3e3c2c, 0x3c3ebc2c, 0xbb163c7d, 0xbc04bc5c, 0x3c713bac, 0xbbdb3c67, 0xbb79bc78, 0x3c4e3c18, 0xbc803a49,
    0x3a49bc80, 0x3c183c4e, 0xbc78bb79, 0x3c67bbdb, 0x3bac3c71, 0xbc5cbc04, 0x3c7dbb16, 0xbc2c3c3e, 0xbbdbbc67, 0x3c783b79,
    0xbc4e3c18, 0x3a49bc80, 0x3c3e3c2c, 0xbc7d3b16, 0x3c04bc5c, 0x3bac3c71, 0xbc71bbac, 0x3c5cbc04, 0xbb163c7d, 0xbc2cbc3e,
    0x3c80ba49, 0xbc183c4e, 0xbb79bc78, 0x3c673bdb, 0x3c67bbdb, 0xbb793c78, 0xbc18bc4e, 0x3c803a49, 0xbc2c3c3e, 0xbb16bc7d,
    0x3c5c3c04, 0xbc713bac, 0x3bacbc71, 0x3c043c5c, 0xbc7dbb16, 0x3c3ebc2c, 0x3a493c80, 0xbc4ebc18, 0x3c78bb79, 0xbbdb3c67,
    0xbc7d3b16, 0x3bacbc71, 0x3c2c3c3e, 0xbc783b79, 0x3c043c5c, 0xbc803a49, 0x3bdbbc67, 0x3c183c4e, 0x3c4e3c18, 0xbc673bdb,
    0x3a49bc80, 0x3c5c3c04, 0x3b79bc78, 0x3c3e3c2c, 0xbc713bac, 0x3b16bc7d, 0x3b163c7d, 0xbc71bbac, 0x3c3ebc2c, 0x3b793c78,
    0x3c5cbc04, 0x3a493c80, 0xbc67bbdb, 0x3c4ebc18, 0x3c18bc4e, 0x3bdb3c67, 0xbc80ba49, 0x3c04bc5c, 0xbc78bb79, 0x3c2cbc3e,
    0x3bac3c71, 0xbc7dbb16, 0x3c7d3b16, 0xbbdb3c67, 0xbc3ebc2c, 0x3c5cbc04, 0x3b793c78, 0xbc80ba49, 0x3bacbc71, 0x3c4e3c18,
    0xbc18bc4e, 0x3c71bbac, 0x3a493c80, 0xbc78bb79, 0x3c04bc5c, 0x3c2c3c3e, 0xbc673bdb, 0xbb16bc7d, 0xbb163c7d, 0xbc67bbdb,
    0x3c2cbc3e, 0x3c043c5c, 0xbc783b79, 0x3a49bc80, 0x3c713bac, 0xbc183c4e, 0x3c4ebc18, 0x3bac3c71, 0xbc803a49, 0x3b79bc78,
    0x3c5c3c04, 0xbc3e3c2c, 0xbbdbbc67, 0x3c7dbb16, 0xbbdb3c67, 0xbc5cbc04, 0x3c18bc4e, 0x3c3e3c2c, 0xba493c80, 0xbc7dbb16,
    0x3b79bc78, 0x3c713bac, 0x3bac3c71, 0xbc783b79, 0xbb16bc7d, 0x3c80ba49, 0x3c2c3c3e, 0xbc4e3c18, 0xbc04bc5c, 0x3c67bbdb,
    0x3c673bdb, 0xbc043c5c, 0xbc4ebc18, 0x3c2cbc3e, 0x3c803a49, 0xbb163c7d, 0xbc78bb79, 0x3bacbc71, 0x3c71bbac, 0x3b793c78,
    0xbc7d3b16, 0xba49bc80, 0x3c3ebc2c, 0x3c183c4e, 0xbc5c3c04, 0xbbdbbc67, 0x3f803f80, 0x3f7d3f7f, 0x3f783f7b, 0x3f713f75,
    0x3f673f6d, 0x3f5c3f62, 0x3f4e3f55, 0x3f3e3f46, 0x3f2c3f35, 0x3f183f22, 0x3f043f0e, 0x3edb3ef1, 0x3eac3ec4, 0x3e793e95,
    0x3e163e48, 0x3d493dc9, 0xbd490000, 0xbe16bdc9, 0xbe79be48, 0xbeacbe95, 0xbedbbec4, 0xbf04bef1, 0xbf18bf0e, 0xbf2cbf22,
    0xbf3ebf35, 0xbf4ebf46, 0xbf5cbf55, 0xbf67bf62, 0xbf71bf6d, 0xbf78bf75, 0xbf7dbf7b, 0xbf80bf7f, 0x3edb3ec4, 0x3f043ef1,
    0x3f183f0e, 0x3f2c3f22, 0x3d490000, 0x3e163dc9, 0x3e793e48, 0x3eac3e95, 0x3f713f6d, 0x3f783f75, 0x3f7d3f7b, 0x3f803f7f,
    0x3f3e3f35, 0x3f4e3f46, 0x3f5c3f55, 0x3f673f62, 0x3f673f6d, 0x3f5c3f62, 0x3f4e3f55, 0x3f3e3f46, 0x3f803f80, 0x3f7d3f7f,
    0x3f783f7b, 0x3f713f75, 0x3eac3ec4, 0x3e793e95, 0x3e163e48, 0x3d493dc9, 0x3f2c3f35, 0x3f183f22, 0x3f043f0e, 0x3edb3ef1,
    0xbf4ebf35, 0xbf71bf62, 0xbf80bf7b, 0xbf78bf7f, 0xbf5cbf6d, 0xbf2cbf46, 0xbedbbf0e, 0xbe16be95, 0x3f7d3f80, 0x3f673f75,
    0x3f3e3f55, 0x3f043f22, 0x3e793ec4, 0xbd493dc9, 0xbeacbe48, 0xbf18bef1, 0x3f183f35, 0x3eac3ef1, 0x3d493e48, 0xbe79bdc9,
    0xbf04bec4, 0xbf3ebf22, 0xbf67bf55, 0xbf7dbf75, 0x3e160000, 0x3edb3e95, 0x3f2c3f0e, 0x3f5c3f46, 0x3f783f6d, 0x3f803f7f,
    0x3f713f7b, 0x3f4e3f62, 0xbf04bec4, 0xbf3ebf22, 0xbf67bf55, 0xbf7dbf75, 0x3f183f35, 0x3eac3ef1, 0x3d493e48, 0xbe79bdc9,
    0x3f783f6d, 0x3f803f7f, 0x3f713f7b, 0x3f4e3f62, 0x3e160000, 0x3edb3e95, 0x3f2c3f0e, 0x3f5c3f46, 0x3f5c3f6d, 0x3f2c3f46,
    0x3edb3f0e, 0x3e163e95, 0x3f4e3f35, 0x3f713f62, 0x3f803f7b, 0x3f783f7f, 0xbe79bec4, 0x3d49bdc9, 0x3eac3e48, 0x3f183ef1,
    0xbf7dbf80, 0xbf67bf75, 0xbf3ebf55, 0xbf04bf22, 0xbe790000, 0xbf2cbef1, 0xbf71bf55, 0xbf7dbf7f, 0xbf4ebf6d, 0xbedbbf22,
    0x3d49be48, 0x3f043e95, 0x3f5c3f35, 0x3f803f75, 0x3f673f7b, 0x3f183f46, 0x3e163ec4, 0xbeacbdc9, 0xbf3ebf0e, 0xbf78bf62,
    0x3f783f80, 0x3f3e3f62, 0x3eac3f0e, 0xbe163dc9, 0xbf18bec4, 0xbf67bf46, 0xbf80bf7b, 0xbf5cbf75, 0xbf04bf35, 0xbd49be95,
    0x3edb3e48, 0x3f4e3f22, 0x3f7d3f6d, 0x3f713f7f, 0x3f2c3f55, 0x3e793ef1, 0xbf18bec4, 0xbf67bf46, 0xbf80bf7b, 0xbf5cbf75,
    0x3f783f80, 0x3f3e3f62, 0x3eac3f0e, 0xbe163dc9, 0x3f7d3f6d, 0x3f713f7f, 0x3f2c3f55, 0x3e793ef1, 0xbf04bf35, 0xbd49be95,
    0x3edb3e48, 0x3f4e3f22, 0x3f4e3f6d, 0x3edb3f22, 0xbd493e48, 0xbf04be95, 0x3e790000, 0x3f2c3ef1, 0x3f713f55, 0x3f7d3f7f,
    0xbe16bec4, 0x3eac3dc9, 0x3f3e3f0e, 0x3f783f62, 0xbf5cbf35, 0xbf80bf75, 0xbf67bf7b, 0xbf18bf46, 0xbedbbf35, 0x3e79bdc9,
    0x3f4e3f0e, 0x3f803f75, 0x3f3e3f6d, 0x3e163ef1, 0xbf04be48, 0xbf71bf46, 0x3eac0000, 0x3f5c3f22, 0x3f7d3f7b, 0x3f2c3f62,
    0x3d493ec4, 0xbf18be95, 0xbf78bf55, 0xbf67bf7f, 0x3f673f35, 0x3f783f7f, 0x3f183f55, 0xbd493e95, 0xbf2cbec4, 0xbf7dbf62,
    0xbf5cbf7b, 0xbeacbf22, 0x3f713f80, 0x3f043f46, 0xbe163e48, 0xbf3ebef1, 0xbf80bf6d, 0xbf4ebf75, 0xbe79bf0e, 0x3edb3dc9,
    0x3f2c3ec4, 0x3f7d3f62, 0x3f5c3f7b, 0x3eac3f22, 0xbf67bf35, 0xbf78bf7f, 0xbf18bf55, 0x3d49be95, 0x3f803f6d, 0x3f4e3f75,
    0x3e793f0e, 0xbedbbdc9, 0xbf71bf80, 0xbf04bf46, 0x3e16be48, 0x3f3e3ef1, 0x3f3e3f6d, 0x3e163ef1, 0xbf04be48, 0xbf71bf46,
    0xbedbbf35, 0x3e79bdc9, 0x3f4e3f0e, 0x3f803f75, 0x3d493ec4, 0xbf18be95, 0xbf78bf55, 0xbf67bf7f, 0x3eac0000, 0x3f5c3f22,
    0x3f7d3f7b, 0x3f2c3f62, 0x3f673f80, 0x3e793f22, 0xbf18be48, 0xbf80bf62, 0xbf2cbf6d, 0x3e16be95, 0x3f5c3f0e, 0x3f713f7f,
    0x3eac3f35, 0xbf04bdc9, 0xbf7dbf55, 0xbf3ebf75, 0x3d49bec4, 0x3f4e3ef1, 0x3f783f7b, 0x3edb3f46, 0xbedb0000, 0xbf78bf46,
    0xbf4ebf7b, 0xbd49bef1, 0x3f3e3ec4, 0x3f7d3f75, 0x3f043f55, 0xbeac3dc9, 0xbf71bf35, 0xbf5cbf7f, 0xbe16bf0e, 0x3f2c3e95,
    0x3f803f6d, 0x3f183f62, 0xbe793e48, 0xbf67bf22, 0xbf3ebec4, 0xbf7dbf75, 0xbf04bf55, 0x3eacbdc9, 0x3edb0000, 0x3f783f46,
    0x3f4e3f7b, 0x3d493ef1, 0xbf80bf6d, 0xbf18bf62, 0x3e79be48, 0x3f673f22, 0x3f713f35, 0x3f5c3f7f, 0x3e163f0e, 0xbf2cbe95,
    0xbf2cbf6d, 0x3e16be95, 0x3f5c3f0e, 0x3f713f7f, 0x3f673f80, 0x3e793f22, 0xbf18be48, 0xbf80bf62, 0x3d49bec4, 0x3f4e3ef1,
    0x3f783f7b, 0x3edb3f46, 0x3eac3f35, 0xbf04bdc9, 0xbf7dbf55, 0xbf3ebf75, 0xbf78bf35, 0xbf2cbf75, 0x3eacbe48, 0x3f7d3f46,
    0x3f183f6d, 0xbedb3dc9, 0xbf80bf55, 0xbf04bf62, 0x3f5c3f80, 0xbd493ef1, 0xbf67bf0e, 0xbf4ebf7f, 0x3e16bec4, 0x3f713f22,
    0x3f3e3f7b, 0xbe793e95, 0x3e793f35, 0xbf3ebe95, 0xbf71bf7b, 0xbe16bf22, 0x3f4e3ec4, 0x3f673f7f, 0x3d493f0e, 0xbf5cbef1,
    0x3f040000, 0x3f803f62, 0x3edb3f55, 0xbf18bdc9, 0xbf7dbf6d, 0xbeacbf46, 0x3f2c3e48, 0x3f783f75, 0x3f4e3ec4, 0x3f673f7f,
    0x3d493f0e, 0xbf5cbef1, 0x3e793f35, 0xbf3ebe95, 0xbf71bf7b, 0xbe16bf22, 0xbf7dbf6d, 0xbeacbf46, 0x3f2c3e48, 0x3f783f75,
    0x3f040000, 0x3f803f62, 0x3edb3f55, 0xbf18bdc9, 0xbf18bf6d, 0x3edbbdc9, 0x3f803f55, 0x3f043f62, 0x3f783f35, 0x3f2c3f75,
    0xbeac3e48, 0xbf7dbf46, 0xbe163ec4, 0xbf71bf22, 0xbf3ebf7b, 0x3e79be95, 0xbf5cbf80, 0x3d49bef1, 0x3f673f0e, 0x3f4e3f7f,
    0xbf180000, 0xbf71bf75, 0x3d49bf0e, 0x3f783f22, 0x3f043f6d, 0xbf2cbdc9, 0xbf67bf7b, 0x3e16bef1, 0x3f7d3f35, 0x3edb3f62,
    0xbf3ebe48, 0xbf5cbf7f, 0x3e79bec4, 0x3f803f46, 0x3eac3f55, 0xbf4ebe95, 0x3f4e3f80, 0xbeac3e95, 0xbf80bf55, 0xbe79bf46,
    0x3f5c3ec4, 0x3f3e3f7f, 0xbedb3e48, 0xbf7dbf62, 0xbe16bf35, 0x3f673ef1, 0x3f2c3f7b, 0xbf043dc9, 0xbf78bf6d, 0xbd49bf22,
    0x3f713f0e, 0x3f183f75, 0x3f5c3ec4, 0x3f3e3f7f, 0xbedb3e48, 0xbf7dbf62, 0x3f4e3f80, 0xbeac3e95, 0xbf80bf55, 0xbe79bf46,
    0xbf78bf6d, 0xbd49bf22, 0x3f713f0e, 0x3f183f75, 0xbe16bf35, 0x3f673ef1, 0x3f2c3f7b, 0xbf043dc9, 0xbf04bf6d, 0x3f2c3dc9,
    0x3f673f7b, 0xbe163ef1, 0x3f180000, 0x3f713f75, 0xbd493f0e, 0xbf78bf22, 0xbe793ec4, 0xbf80bf46, 0xbeacbf55, 0x3f4e3e95,
    0xbf7dbf35, 0xbedbbf62, 0x3f3e3e48, 0x3f5c3f7f, 0xbd49bf35, 0x3f7d3f22, 0x3e793f55, 0xbf71bef1, 0xbedbbf6d, 0x3f5c3e95,
    0x3f183f7b, 0xbf3ebdc9, 0x3f2c0000, 0x3f4e3f7f, 0xbf043e48, 0xbf67bf75, 0x3eacbec4, 0x3f783f62, 0xbe163f0e, 0xbf80bf46,
    0x3f803f35, 0x3e163f46, 0xbf78bf0e, 0xbeacbf62, 0x3f673ec4, 0x3f043f75, 0xbf4ebe48, 0xbf2cbf7f, 0x3f3e3f80, 0xbf183dc9,
    0xbf5cbf7b, 0x3edbbe95, 0x3f713f6d, 0xbe793ef1, 0xbf7dbf55, 0x3d49bf22, 0xbf67bec4, 0xbf04bf75, 0x3f4e3e48, 0x3f2c3f7f,
    0xbf80bf35, 0xbe16bf46, 0x3f783f0e, 0x3eac3f62, 0xbf71bf6d, 0x3e79bef1, 0x3f7d3f55, 0xbd493f22, 0xbf3ebf80, 0x3f18bdc9,
    0x3f5c3f7b, 0xbedb3e95, 0xbedbbf6d, 0x3f5c3e95, 0x3f183f7b, 0xbf3ebdc9, 0xbd49bf35, 0x3f7d3f22, 0x3e793f55, 0xbf71bef1,
    0x3eacbec4, 0x3f783f62, 0xbe163f0e, 0xbf80bf46, 0x3f2c0000, 0x3f4e3f7f, 0xbf043e48, 0xbf67bf75, 0x3f2c3f80, 0xbf4ebdc9,
    0xbf04bf7b, 0x3f673e95, 0x3eac3f6d, 0xbf78bef1, 0xbe16bf55, 0x3f803f22, 0xbd493f35, 0xbf7dbf46, 0x3e79bf0e, 0x3f713f62,
    0xbedb3ec4, 0xbf5cbf75, 0x3f18be48, 0x3f3e3f7f, 0xbf3e0000, 0xbf18bf7f, 0x3f5c3e48, 0x3edb3f75, 0xbf71bec4, 0xbe79bf62,
    0x3f7d3f0e, 0x3d493f46, 0xbf80bf35, 0x3e16bf22, 0x3f783f55, 0xbeac3ef1, 0xbf67bf6d, 0x3f04be95, 0x3f4e3f7b, 0xbf2c3dc9,
    0x3f713ec4, 0x3e793f62, 0xbf7dbf0e, 0xbd49bf46, 0x3f3e0000, 0x3f183f7f, 0xbf5cbe48, 0xbedbbf75, 0x3f673f6d, 0xbf043e95,
    0xbf4ebf7b, 0x3f2cbdc9, 0x3f803f35, 0xbe163f22, 0xbf78bf55, 0x3eacbef1, 0x3eac3f6d, 0xbf78bef1, 0xbe16bf55, 0x3f803f22,
    0x3f2c3f80, 0xbf4ebdc9, 0xbf04bf7b, 0x3f673e95, 0xbedb3ec4, 0xbf5cbf75, 0x3f18be48, 0x3f3e3f7f, 0xbd493f35, 0xbf7dbf46,
    0x3e79bf0e, 0x3f713f62, 0xbf7dbf35, 0x3edbbef1, 0x3f3e3f7b, 0xbf5cbdc9, 0xbe79bf6d, 0x3f803f22, 0xbeac3f0e, 0xbf4ebf75,
    0x3f183f80, 0xbf71be95, 0xbd49bf55, 0x3f783f46, 0xbf043ec4, 0xbf2cbf7f, 0x3f673e48, 0x3e163f62, 0xbe163f35, 0xbf67bf62,
    0x3f2cbe48, 0x3f043f7f, 0xbf78bec4, 0x3d49bf46, 0x3f713f55, 0xbf183e95, 0x3f4e0000, 0x3eac3f75, 0xbf80bf0e, 0x3e79bf22,
    0x3f5c3f6d, 0xbf3e3dc9, 0xbedbbf7b, 0x3f7d3ef1, 0xbf78bec4, 0x3d49bf46, 0x3f713f55, 0xbf183e95, 0xbe163f35, 0xbf67bf62,
    0x3f2cbe48, 0x3f043f7f, 0x3f5c3f6d, 0xbf3e3dc9, 0xbedbbf7b, 0x3f7d3ef1, 0x3f4e0000, 0x3eac3f75, 0xbf80bf0e, 0x3e79bf22,
    0x3e793f6d, 0xbf80bf22, 0x3eacbf0e, 0x3f4e3f75, 0x3f7d3f35, 0xbedb3ef1, 0xbf3ebf7b, 0x3f5c3dc9, 0x3f04bec4, 0x3f2c3f7f,
    0xbf67be48, 0xbe16bf62, 0xbf18bf80, 0x3f713e95, 0x3d493f55, 0xbf78bf46, 0xbf5c0000, 0xbd49bf62, 0x3f673f55, 0xbf4e3dc9,
    0xbe16bf6d, 0x3f713f46, 0xbf3e3e48, 0xbe79bf75, 0x3f783f35, 0xbf2c3e95, 0xbeacbf7b, 0x3f7d3f22, 0xbf183ec4, 0xbedbbf7f,
    0x3f803f0e, 0xbf043ef1, 0x3f043f80, 0xbf80bef1, 0x3edbbf0e, 0x3f183f7f, 0xbf7dbec4, 0x3eacbf22, 0x3f2c3f7b, 0xbf78be95,
    0x3e79bf35, 0x3f3e3f75, 0xbf71be48, 0x3e16bf46, 0x3f4e3f6d, 0xbf67bdc9, 0x3d49bf55, 0x3f5c3f62, 0xbf7dbec4, 0x3eacbf22,
    0x3f2c3f7b, 0xbf78be95, 0x3f043f80, 0xbf80bef1, 0x3edbbf0e, 0x3f183f7f, 0x3f4e3f6d, 0xbf67bdc9, 0x3d49bf55, 0x3f5c3f62,
    0x3e79bf35, 0x3f3e3f75, 0xbf71be48, 0x3e16bf46, 0x3e163f6d, 0xbf71bf46, 0x3f3ebe48, 0x3e793f75, 0x3f5c0000, 0x3d493f62,
    0xbf67bf55, 0x3f4ebdc9, 0x3f18bec4, 0x3edb3f7f, 0xbf80bf0e, 0x3f04bef1, 0xbf78bf35, 0x3f2cbe95, 0x3eac3f7b, 0xbf7dbf22,
    0x3eacbf35, 0x3f043f7f, 0xbf7dbf0e, 0x3f3ebe95, 0x3d493f6d, 0xbf4ebf62, 0x3f783e48, 0xbedb3f22, 0x3f670000, 0xbe793f46,
    0xbf18bf7b, 0x3f803ef1, 0xbf2c3ec4, 0xbe16bf75, 0x3f5c3f55, 0xbf71bdc9, 0x3f713f35, 0xbf5c3dc9, 0x3e16bf55, 0x3f2c3f75,
    0xbf80bec4, 0x3f18bef1, 0x3e793f7b, 0xbf67bf46, 0x3edb3f80, 0xbf78bf22, 0x3f4ebe48, 0xbd493f62, 0xbf3ebf6d, 0x3f7d3e95,
    0xbf043f0e, 0xbeacbf7f, 0x3f803ec4, 0xbf183ef1, 0xbe79bf7b, 0x3f673f46, 0xbf71bf35, 0x3f5cbdc9, 0xbe163f55, 0xbf2cbf75,
    0x3f3e3f6d, 0xbf7dbe95, 0x3f04bf0e, 0x3eac3f7f, 0xbedbbf80, 0x3f783f22, 0xbf4e3e48, 0x3d49bf62, 0x3d493f6d, 0xbf4ebf62,
    0x3f783e48, 0xbedb3f22, 0x3eacbf35, 0x3f043f7f, 0xbf7dbf0e, 0x3f3ebe95, 0xbf2c3ec4, 0xbe16bf75, 0x3f5c3f55, 0xbf71bdc9,
    0x3f670000, 0xbe793f46, 0xbf18bf7b, 0x3f803ef1, 0x3eac3f80, 0xbf5cbf46, 0x3f7d3e48, 0xbf2c3ef1, 0x3d49bf6d, 0x3f183f75,
    0xbf78bf0e, 0x3f67bdc9, 0xbedb3f35, 0xbe79bf7f, 0x3f4e3f55, 0xbf80be95, 0x3f3ebec4, 0xbe163f62, 0xbf04bf7b, 0x3f713f22,
    0xbf710000, 0x3f04bf22, 0x3e163f7b, 0xbf3ebf62, 0x3f803ec4, 0xbf4e3e95, 0x3e79bf55, 0x3edb3f7f, 0xbf67bf35, 0x3f783dc9,
    0xbf183f0e, 0xbd49bf75, 0x3f2c3f6d, 0xbf7dbef1, 0x3f5cbe48, 0xbeac3f46, 0xbf80bec4, 0x3f4ebe95, 0xbe793f55, 0xbedbbf7f,
    0x3f710000, 0xbf043f22, 0xbe16bf7b, 0x3f3e3f62, 0xbf2cbf6d, 0x3f7d3ef1, 0xbf5c3e48, 0x3eacbf46, 0x3f673f35, 0xbf78bdc9,
    0x3f18bf0e, 0x3d493f75, 0x3d49bf6d, 0x3f183f75, 0xbf78bf0e, 0x3f67bdc9, 0x3eac3f80, 0xbf5cbf46, 0x3f7d3e48, 0xbf2c3ef1,
    0x3f3ebec4, 0xbe163f62, 0xbf04bf7b, 0x3f713f22, 0xbedb3f35, 0xbe79bf7f, 0x3f4e3f55, 0xbf80be95, 0xbf5cbf35, 0x3f803e95,
    0xbf673e48, 0x3f18bf22, 0xbe163f6d, 0xbeacbf7f, 0x3f3e3f55, 0xbf78bef1, 0x3e793f80, 0xbf2cbf62, 0x3f713f0e, 0xbf7dbdc9,
    0x3f4ebec4, 0xbedb3f46, 0xbd49bf7b, 0x3f043f75, 0xbf043f35, 0x3d49bf75, 0x3edb3f7b, 0xbf4ebf46, 0x3f7d3ec4, 0xbf713dc9,
    0x3f2cbf0e, 0xbe793f62, 0x3f780000, 0xbf3e3ef1, 0x3eacbf55, 0x3e163f7f, 0xbf18bf6d, 0x3f673f22, 0xbf80be48, 0x3f5cbe95,
    0x3f7d3ec4, 0xbf713dc9, 0x3f2cbf0e, 0xbe793f62, 0xbf043f35, 0x3d49bf75, 0x3edb3f7b, 0xbf4ebf46, 0xbf18bf6d, 0x3f673f22,
    0xbf80be48, 0x3f5cbe95, 0x3f780000, 0xbf3e3ef1, 0x3eacbf55, 0x3e163f7f, 0x3e16bf6d, 0x3eac3f7f, 0xbf3ebf55, 0x3f783ef1,
    0x3f5c3f35, 0xbf80be95, 0x3f67be48, 0xbf183f22, 0xbf4e3ec4, 0x3edbbf46, 0x3d493f7b, 0xbf04bf75, 0xbe79bf80, 0x3f2c3f62,
    0xbf71bf0e, 0x3f7d3dc9, 0xbf7d0000, 0x3f67be95, 0xbf3e3f0e, 0x3f04bf46, 0xbe793f6d, 0xbd49bf7f, 0x3eac3f7b, 0xbf18bf62,
    0x3f4e3f35, 0xbf71bef1, 0x3f803e48, 0xbf783dc9, 0x3f5cbec4, 0xbf2c3f22, 0x3edbbf55, 0xbe163f75, 0x3e163f80, 0xbedbbf75,
    0x3f2c3f55, 0xbf5cbf22, 0x3f783ec4, 0xbf80bdc9, 0x3f71be48, 0xbf4e3ef1, 0x3f18bf35, 0xbeac3f62, 0x3d49bf7b, 0x3e793f7f,
    0xbf04bf6d, 0x3f3e3f46, 0xbf67bf0e, 0x3f7d3e95, 0x3f783ec4, 0xbf80bdc9, 0x3f71be48, 0xbf4e3ef1, 0x3e163f80, 0xbedbbf75,
    0x3f2c3f55, 0xbf5cbf22, 0xbf04bf6d, 0x3f3e3f46, 0xbf67bf0e, 0x3f7d3e95, 0x3f18bf35, 0xbeac3f62, 0x3d49bf7b, 0x3e793f7f,
    0x3e79bf6d, 0x3d493f7f, 0xbeacbf7b, 0x3f183f62, 0x3f7d0000, 0xbf673e95, 0x3f3ebf0e, 0xbf043f46, 0xbf5c3ec4, 0x3f2cbf22,
    0xbedb3f55, 0x3e16bf75, 0xbf4ebf35, 0x3f713ef1, 0xbf80be48, 0x3f78bdc9, 0x3f2cbf35, 0xbf183f46, 0x3f04bf55, 0xbedb3f62,
    0x3eacbf6d, 0xbe793f75, 0x3e16bf7b, 0xbd493f7f, 0x3f800000, 0xbf7d3dc9, 0x3f78be48, 0xbf713e95, 0x3f67bec4, 0xbf5c3ef1,
    0x3f4ebf0e, 0xbf3e3f22, 0x3f3e3f35, 0xbf4ebf22, 0x3f5c3f0e, 0xbf67bef1, 0x3f713ec4, 0xbf78be95, 0x3f7d3e48, 0xbf80bdc9,
    0x3d493f80, 0xbe16bf7f, 0x3e793f7b, 0xbeacbf75, 0x3edb3f6d, 0xbf04bf62, 0x3f183f55, 0xbf2cbf46, 0xbf71bec4, 0x3f783e95,
    0xbf7dbe48, 0x3f803dc9, 0xbf3ebf35, 0x3f4e3f22, 0xbf5cbf0e, 0x3f673ef1, 0xbedbbf6d, 0x3f043f62, 0xbf18bf55, 0x3f2c3f46,
    0xbd49bf80, 0x3e163f7f, 0xbe79bf7b, 0x3eac3f75, 0x3eacbf6d, 0xbe793f75, 0x3e16bf7b, 0xbd493f7f, 0x3f2cbf35, 0xbf183f46,
    0x3f04bf55, 0xbedb3f62, 0x3f67bec4, 0xbf5c3ef1, 0x3f4ebf0e, 0xbf3e3f22, 0x3f800000, 0xbf7d3dc9, 0x3f78be48, 0xbf713e95,
    0xbd493f80, 0x3e16bf7f, 0xbe793f7b, 0x3eacbf75, 0xbedb3f6d, 0x3f04bf62, 0xbf183f55, 0x3f2cbf46, 0xbf3e3f35, 0x3f4ebf22,
    0xbf5c3f0e, 0x3f67bef1, 0xbf713ec4, 0x3f78be95, 0xbf7d3e48, 0x3f80bdc9, 0xbf800000, 0x3f7d3dc9, 0xbf78be48, 0x3f713e95,
    0xbf67bec4, 0x3f5c3ef1, 0xbf4ebf0e, 0x3f3e3f22, 0xbf2cbf35, 0x3f183f46, 0xbf04bf55, 0x3edb3f62, 0xbeacbf6d, 0x3e793f75,
    0xbe16bf7b, 0x3d493f7f, 0x3f673ec4, 0xbf5cbef1, 0x3f4e3f0e, 0xbf3ebf22, 0x3f800000, 0xbf7dbdc9, 0x3f783e48, 0xbf71be95,
    0x3eac3f6d, 0xbe79bf75, 0x3e163f7b, 0xbd49bf7f, 0x3f2c3f35, 0xbf18bf46, 0x3f043f55, 0xbedbbf62, 0xbedb3f6d, 0x3f04bf62,
    0xbf183f55, 0x3f2cbf46, 0xbd493f80, 0x3e16bf7f, 0xbe793f7b, 0x3eacbf75, 0xbf713ec4, 0x3f78be95, 0xbf7d3e48, 0x3f80bdc9,
    0xbf3e3f35, 0x3f4ebf22, 0xbf5c3f0e, 0x3f67bef1, 0xbf18bf35, 0x3eac3f62, 0xbd49bf7b, 0xbe793f7f, 0x3f04bf6d, 0xbf3e3f46,
    0x3f67bf0e, 0xbf7d3e95, 0xbe163f80, 0x3edbbf75, 0xbf2c3f55, 0x3f5cbf22, 0xbf783ec4, 0x3f80bdc9, 0xbf71be48, 0x3f4e3ef1,
    0xbf4e3f35, 0x3f71bef1, 0xbf803e48, 0x3f783dc9, 0xbf5cbec4, 0x3f2c3f22, 0xbedbbf55, 0x3e163f75, 0x3f7d0000, 0xbf67be95,
    0x3f3e3f0e, 0xbf04bf46, 0x3e793f6d, 0x3d49bf7f, 0xbeac3f7b, 0x3f18bf62, 0xbf5cbec4, 0x3f2c3f22, 0xbedbbf55, 0x3e163f75,
    0xbf4e3f35, 0x3f71bef1, 0xbf803e48, 0x3f783dc9, 0x3e793f6d, 0x3d49bf7f, 0xbeac3f7b, 0x3f18bf62, 0x3f7d0000, 0xbf67be95,
    0x3f3e3f0e, 0xbf04bf46, 0xbf043f6d, 0x3f3ebf46, 0xbf673f0e, 0x3f7dbe95, 0x3f183f35, 0xbeacbf62, 0x3d493f7b, 0x3e79bf7f,
    0x3f78bec4, 0xbf803dc9, 0x3f713e48, 0xbf4ebef1, 0x3e16bf80, 0xbedb3f75, 0x3f2cbf55, 0xbf5c3f22, 0xbf780000, 0x3f3e3ef1,
    0xbeacbf55, 0xbe163f7f, 0x3f18bf6d, 0xbf673f22, 0x3f80be48, 0xbf5cbe95, 0x3f043f35, 0xbd49bf75, 0xbedb3f7b, 0x3f4ebf46,
    0xbf7d3ec4, 0x3f713dc9, 0xbf2cbf0e, 0x3e793f62, 0xbe793f80, 0x3f2cbf62, 0xbf713f0e, 0x3f7dbdc9, 0xbf4ebec4, 0x3edb3f46,
    0x3d49bf7b, 0xbf043f75, 0x3f5cbf35, 0xbf803e95, 0x3f673e48, 0xbf18bf22, 0x3e163f6d, 0x3eacbf7f, 0xbf3e3f55, 0x3f78bef1,
    0xbf4ebec4, 0x3edb3f46, 0x3d49bf7b, 0xbf043f75, 0xbe793f80, 0x3f2cbf62, 0xbf713f0e, 0x3f7dbdc9, 0x3e163f6d, 0x3eacbf7f,
    0xbf3e3f55, 0x3f78bef1, 0x3f5cbf35, 0xbf803e95, 0x3f673e48, 0xbf18bf22, 0xbf183f6d, 0x3f67bf22, 0xbf803e48, 0x3f5c3e95,
    0x3f780000, 0xbf3ebef1, 0x3eac3f55, 0x3e16bf7f, 0x3f7dbec4, 0xbf71bdc9, 0x3f2c3f0e, 0xbe79bf62, 0xbf04bf35, 0x3d493f75,
    0x3edbbf7b, 0xbf4e3f46, 0x3f67bf35, 0xbf783dc9, 0x3f183f0e, 0x3d49bf75, 0xbf2c3f6d, 0x3f7dbef1, 0xbf5cbe48, 0x3eac3f46,
    0x3f710000, 0xbf04bf22, 0xbe163f7b, 0x3f3ebf62, 0xbf803ec4, 0x3f4e3e95, 0xbe79bf55, 0xbedb3f7f, 0x3edb3f35, 0x3e79bf7f,
    0xbf4e3f55, 0x3f80be95, 0xbf3ebec4, 0x3e163f62, 0x3f04bf7b, 0xbf713f22, 0xbeac3f80, 0x3f5cbf46, 0xbf7d3e48, 0x3f2c3ef1,
    0xbd49bf6d, 0xbf183f75, 0x3f78bf0e, 0xbf67bdc9, 0x3f3e3ec4, 0xbe16bf62, 0xbf043f7b, 0x3f71bf22, 0xbedbbf35, 0xbe793f7f,
    0x3f4ebf55, 0xbf803e95, 0x3d493f6d, 0x3f18bf75, 0xbf783f0e, 0x3f673dc9, 0x3eacbf80, 0xbf5c3f46, 0x3f7dbe48, 0xbf2cbef1,
    0xbf2c3f6d, 0x3f7dbef1, 0xbf5cbe48, 0x3eac3f46, 0x3f67bf35, 0xbf783dc9, 0x3f183f0e, 0x3d49bf75, 0xbf803ec4, 0x3f4e3e95,
    0xbe79bf55, 0xbedb3f7f, 0x3f710000, 0xbf04bf22, 0xbe163f7b, 0x3f3ebf62, 0xbedb3f80, 0x3f78bf22, 0xbf4ebe48, 0x3d493f62,
    0x3f3ebf6d, 0xbf7d3e95, 0x3f043f0e, 0x3eacbf7f, 0xbf713f35, 0x3f5c3dc9, 0xbe16bf55, 0xbf2c3f75, 0x3f80bec4, 0xbf18bef1,
    0xbe793f7b, 0x3f67bf46, 0xbf670000, 0x3e793f46, 0x3f18bf7b, 0xbf803ef1, 0x3f2c3ec4, 0x3e16bf75, 0xbf5c3f55, 0x3f71bdc9,
    0xbeacbf35, 0xbf043f7f, 0x3f7dbf0e, 0xbf3ebe95, 0xbd493f6d, 0x3f4ebf62, 0xbf783e48, 0x3edb3f22, 0xbf2cbec4, 0xbe163f75,
    0x3f5cbf55, 0xbf713dc9, 0x3f670000, 0xbe79bf46, 0xbf183f7b, 0x3f80bef1, 0x3d49bf6d, 0xbf4e3f62, 0x3f78be48, 0xbedbbf22,
    0x3eac3f35, 0x3f04bf7f, 0xbf7d3f0e, 0x3f3e3e95, 0x3f3ebf6d, 0xbf7d3e95, 0x3f043f0e, 0x3eacbf7f, 0xbedb3f80, 0x3f78bf22,
    0xbf4ebe48, 0x3d493f62, 0x3f80bec4, 0xbf18bef1, 0xbe793f7b, 0x3f67bf46, 0xbf713f35, 0x3f5c3dc9, 0xbe16bf55, 0xbf2c3f75,
    0xbe79bf35, 0xbf3e3f75, 0x3f71be48, 0xbe16bf46, 0xbf4e3f6d, 0x3f67bdc9, 0xbd49bf55, 0xbf5c3f62, 0xbf043f80, 0x3f80bef1,
    0xbedbbf0e, 0xbf183f7f, 0x3f7dbec4, 0xbeacbf22, 0xbf2c3f7b, 0x3f78be95, 0xbf783f35, 0x3f2c3e95, 0x3eacbf7b, 0xbf7d3f22,
    0x3f183ec4, 0x3edbbf7f, 0xbf803f0e, 0x3f043ef1, 0x3f5c0000, 0x3d49bf62, 0xbf673f55, 0x3f4e3dc9, 0x3e16bf6d, 0xbf713f46,
    0x3f3e3e48, 0x3e79bf75, 0x3f183ec4, 0x3edbbf7f, 0xbf803f0e, 0x3f043ef1, 0xbf783f35, 0x3f2c3e95, 0x3eacbf7b, 0xbf7d3f22,
    0x3e16bf6d, 0xbf713f46, 0x3f3e3e48, 0x3e79bf75, 0x3f5c0000, 0x3d49bf62, 0xbf673f55, 0x3f4e3dc9, 0x3f4ebf6d, 0xbf673dc9,
    0x3d493f55, 0x3f5cbf62, 0x3e793f35, 0x3f3ebf75, 0xbf713e48, 0x3e163f46, 0xbf7d3ec4, 0x3eac3f22, 0x3f2cbf7b, 0xbf783e95,
    0x3f04bf80, 0xbf803ef1, 0x3edb3f0e, 0x3f18bf7f, 0xbf4e0000, 0xbeac3f75, 0x3f80bf0e, 0xbe79bf22, 0xbf5c3f6d, 0x3f3e3dc9,
    0x3edbbf7b, 0xbf7d3ef1, 0x3e163f35, 0x3f67bf62, 0xbf2cbe48, 0xbf043f7f, 0x3f78bec4, 0xbd49bf46, 0xbf713f55, 0x3f183e95,
    0xbf183f80, 0x3f71be95, 0x3d49bf55, 0xbf783f46, 0x3f043ec4, 0x3f2cbf7f, 0xbf673e48, 0xbe163f62, 0x3f7dbf35, 0xbedbbef1,
    0xbf3e3f7b, 0x3f5cbdc9, 0x3e79bf6d, 0xbf803f22, 0x3eac3f0e, 0x3f4ebf75, 0x3f043ec4, 0x3f2cbf7f, 0xbf673e48, 0xbe163f62,
    0xbf183f80, 0x3f71be95, 0x3d49bf55, 0xbf783f46, 0x3e79bf6d, 0xbf803f22, 0x3eac3f0e, 0x3f4ebf75, 0x3f7dbf35, 0xbedbbef1,
    0xbf3e3f7b, 0x3f5cbdc9, 0x3f5cbf6d, 0xbf3ebdc9, 0xbedb3f7b, 0x3f7dbef1, 0x3f4e0000, 0x3eacbf75, 0xbf803f0e, 0x3e793f22,
    0xbf783ec4, 0x3d493f46, 0x3f71bf55, 0xbf18be95, 0xbe16bf35, 0xbf673f62, 0x3f2c3e48, 0x3f04bf7f, 0x3f80bf35, 0xbe16bf22,
    0xbf783f55, 0x3eac3ef1, 0x3f67bf6d, 0xbf04be95, 0xbf4e3f7b, 0x3f2c3dc9, 0x3f3e0000, 0x3f18bf7f, 0xbf5c3e48, 0xbedb3f75,
    0x3f71bec4, 0x3e79bf62, 0xbf7d3f0e, 0xbd493f46, 0x3d493f35, 0x3f7dbf46, 0xbe79bf0e, 0xbf713f62, 0x3edb3ec4, 0x3f5cbf75,
    0xbf18be48, 0xbf3e3f7f, 0xbf2c3f80, 0x3f4ebdc9, 0x3f04bf7b, 0xbf673e95, 0xbeac3f6d, 0x3f78bef1, 0x3e16bf55, 0xbf803f22,
    0xbedbbec4, 0xbf5c3f75, 0x3f183e48, 0x3f3ebf7f, 0xbd49bf35, 0xbf7d3f46, 0x3e793f0e, 0x3f71bf62, 0x3eacbf6d, 0xbf783ef1,
    0xbe163f55, 0x3f80bf22, 0x3f2cbf80, 0xbf4e3dc9, 0xbf043f7b, 0x3f67be95, 0x3f67bf6d, 0xbf04be95, 0xbf4e3f7b, 0x3f2c3dc9,
    0x3f80bf35, 0xbe16bf22, 0xbf783f55, 0x3eac3ef1, 0x3f71bec4, 0x3e79bf62, 0xbf7d3f0e, 0xbd493f46, 0x3f3e0000, 0x3f18bf7f,
    0xbf5c3e48, 0xbedb3f75, 0xbf3e3f80, 0x3f183dc9, 0x3f5cbf7b, 0xbedbbe95, 0xbf713f6d, 0x3e793ef1, 0x3f7dbf55, 0xbd49bf22,
    0xbf803f35, 0xbe163f46, 0x3f78bf0e, 0x3eacbf62, 0xbf673ec4, 0xbf043f75, 0x3f4ebe48, 0x3f2cbf7f, 0xbf2c0000, 0xbf4e3f7f,
    0x3f043e48, 0x3f67bf75, 0xbeacbec4, 0xbf783f62, 0x3e163f0e, 0x3f80bf46, 0x3d49bf35, 0xbf7d3f22, 0xbe793f55, 0x3f71bef1,
    0x3edbbf6d, 0xbf5c3e95, 0xbf183f7b, 0x3f3ebdc9, 0x3eac3ec4, 0x3f78bf62, 0xbe16bf0e, 0xbf803f46, 0x3f2c0000, 0x3f4ebf7f,
    0xbf04be48, 0xbf673f75, 0xbedb3f6d, 0x3f5cbe95, 0x3f18bf7b, 0xbf3e3dc9, 0xbd493f35, 0x3f7dbf22, 0x3e79bf55, 0xbf713ef1,
    0xbf713f6d, 0x3e793ef1, 0x3f7dbf55, 0xbd49bf22, 0xbf3e3f80, 0x3f183dc9, 0x3f5cbf7b, 0xbedbbe95, 0xbf673ec4, 0xbf043f75,
    0x3f4ebe48, 0x3f2cbf7f, 0xbf803f35, 0xbe163f46, 0x3f78bf0e, 0x3eacbf62, 0x3e16bf35, 0xbf673ef1, 0xbf2c3f7b, 0x3f043dc9,
    0x3f78bf6d, 0x3d49bf22, 0xbf713f0e, 0xbf183f75, 0xbf4e3f80, 0x3eac3e95, 0x3f80bf55, 0x3e79bf46, 0xbf5c3ec4, 0xbf3e3f7f,
    0x3edb3e48, 0x3f7dbf62, 0xbf7d3f35, 0xbedb3f62, 0x3f3ebe48, 0x3f5cbf7f, 0xbe79bec4, 0xbf803f46, 0xbeac3f55, 0x3f4ebe95,
    0x3f180000, 0x3f71bf75, 0xbd49bf0e, 0xbf783f22, 0xbf043f6d, 0x3f2cbdc9, 0x3f67bf7b, 0xbe16bef1, 0xbe79bec4, 0xbf803f46,
    0xbeac3f55, 0x3f4ebe95, 0xbf7d3f35, 0xbedb3f62, 0x3f3ebe48, 0x3f5cbf7f, 0xbf043f6d, 0x3f2cbdc9, 0x3f67bf7b, 0xbe16bef1,
    0x3f180000, 0x3f71bf75, 0xbd49bf0e, 0xbf783f22, 0xbf783f6d, 0xbd493f22, 0x3f71bf0e, 0x3f18bf75, 0xbe163f35, 0x3f67bef1,
    0x3f2cbf7b, 0xbf04bdc9, 0x3f5cbec4, 0x3f3ebf7f, 0xbedbbe48, 0xbf7d3f62, 0x3f4ebf80, 0xbeacbe95, 0xbf803f55, 0xbe793f46,
    0xbf040000, 0xbf803f62, 0xbedb3f55, 0x3f18bdc9, 0x3f7dbf6d, 0x3eacbf46, 0xbf2c3e48, 0xbf783f75, 0xbe793f35, 0x3f3ebe95,
    0x3f71bf7b, 0x3e16bf22, 0xbf4e3ec4, 0xbf673f7f, 0xbd493f0e, 0x3f5cbef1, 0xbf5c3f80, 0x3d493ef1, 0x3f67bf0e, 0x3f4ebf7f,
    0xbe16bec4, 0xbf713f22, 0xbf3e3f7b, 0x3e793e95, 0x3f78bf35, 0x3f2cbf75, 0xbeacbe48, 0xbf7d3f46, 0xbf183f6d, 0x3edb3dc9,
    0x3f80bf55, 0x3f04bf62, 0xbe16bec4, 0xbf713f22, 0xbf3e3f7b, 0x3e793e95, 0xbf5c3f80, 0x3d493ef1, 0x3f67bf0e, 0x3f4ebf7f,
    0xbf183f6d, 0x3edb3dc9, 0x3f80bf55, 0x3f04bf62, 0x3f78bf35, 0x3f2cbf75, 0xbeacbe48, 0xbf7d3f46, 0xbf7d3f6d, 0xbeac3f46,
    0x3f2cbe48, 0x3f78bf75, 0x3f040000, 0x3f80bf62, 0x3edbbf55, 0xbf183dc9, 0x3f4ebec4, 0x3f67bf7f, 0x3d49bf0e, 0xbf5c3ef1,
    0x3e79bf35, 0xbf3e3e95, 0xbf713f7b, 0xbe163f22, 0x3f71bf35, 0x3f5cbf7f, 0x3e16bf0e, 0xbf2c3e95, 0xbf803f6d, 0xbf183f62,
    0x3e793e48, 0x3f67bf22, 0x3edb0000, 0x3f78bf46, 0x3f4ebf7b, 0x3d49bef1, 0xbf3e3ec4, 0xbf7d3f75, 0xbf043f55, 0x3eac3dc9,
    0xbeac3f35, 0x3f04bdc9, 0x3f7dbf55, 0x3f3ebf75, 0xbd49bec4, 0xbf4e3ef1, 0xbf783f7b, 0xbedb3f46, 0xbf673f80, 0xbe793f22,
    0x3f18be48, 0x3f80bf62, 0x3f2cbf6d, 0xbe16be95, 0xbf5c3f0e, 0xbf713f7f, 0x3d493ec4, 0x3f4ebef1, 0x3f78bf7b, 0x3edbbf46,
    0x3eacbf35, 0xbf043dc9, 0xbf7d3f55, 0xbf3e3f75, 0xbf2c3f6d, 0x3e163e95, 0x3f5cbf0e, 0x3f71bf7f, 0x3f67bf80, 0x3e79bf22,
    0xbf183e48, 0xbf803f62, 0xbf803f6d, 0xbf183f62, 0x3e793e48, 0x3f67bf22, 0x3f71bf35, 0x3f5cbf7f, 0x3e16bf0e, 0xbf2c3e95,
    0xbf3e3ec4, 0xbf7d3f75, 0xbf043f55, 0x3eac3dc9, 0x3edb0000, 0x3f78bf46, 0x3f4ebf7b, 0x3d49bef1, 0xbf713f80, 0xbf043f46,
    0x3e163e48, 0x3f3ebef1, 0x3f80bf6d, 0x3f4ebf75, 0x3e79bf0e, 0xbedb3dc9, 0xbf673f35, 0xbf783f7f, 0xbf183f55, 0x3d493e95,
    0x3f2cbec4, 0x3f7dbf62, 0x3f5cbf7b, 0x3eacbf22, 0xbeac0000, 0xbf5c3f22, 0xbf7d3f7b, 0xbf2c3f62, 0xbd493ec4, 0x3f18be95,
    0x3f78bf55, 0x3f67bf7f, 0x3edbbf35, 0xbe79bdc9, 0xbf4e3f0e, 0xbf803f75, 0xbf3e3f6d, 0xbe163ef1, 0x3f04be48, 0x3f71bf46,
    0x3d49bec4, 0xbf183e95, 0xbf783f55, 0xbf673f7f, 0x3eac0000, 0x3f5cbf22, 0x3f7dbf7b, 0x3f2cbf62, 0x3f3ebf6d, 0x3e16bef1,
    0xbf043e48, 0xbf713f46, 0xbedb3f35, 0x3e793dc9, 0x3f4ebf0e, 0x3f80bf75, 0x3f80bf6d, 0x3f4ebf75, 0x3e79bf0e, 0xbedb3dc9,
    0xbf713f80, 0xbf043f46, 0x3e163e48, 0x3f3ebef1, 0x3f2cbec4, 0x3f7dbf62, 0x3f5cbf7b, 0x3eacbf22, 0xbf673f35, 0xbf783f7f,
    0xbf183f55, 0x3d493e95, 0x3f04bf35, 0x3d49be95, 0xbedb3e48, 0xbf4e3f22, 0xbf7d3f6d, 0xbf713f7f, 0xbf2c3f55, 0xbe793ef1,
    0xbf783f80, 0xbf3e3f62, 0xbeac3f0e, 0x3e163dc9, 0x3f18bec4, 0x3f67bf46, 0x3f80bf7b, 0x3f5cbf75, 0xbf5c3f35, 0xbf803f75,
    0xbf673f7b, 0xbf183f46, 0xbe163ec4, 0x3eacbdc9, 0x3f3ebf0e, 0x3f78bf62, 0x3e790000, 0x3f2cbef1, 0x3f71bf55, 0x3f7dbf7f,
    0x3f4ebf6d, 0x3edbbf22, 0xbd49be48, 0xbf043e95, 0xbe163ec4, 0x3eacbdc9, 0x3f3ebf0e, 0x3f78bf62, 0xbf5c3f35, 0xbf803f75,
    0xbf673f7b, 0xbf183f46, 0x3f4ebf6d, 0x3edbbf22, 0xbd49be48, 0xbf043e95, 0x3e790000, 0x3f2cbef1, 0x3f71bf55, 0x3f7dbf7f,
    0x3f7dbf6d, 0x3f71bf7f, 0x3f2cbf55, 0x3e79bef1, 0xbf043f35, 0xbd493e95, 0x3edbbe48, 0x3f4ebf22, 0xbf183ec4, 0xbf673f46,
    0xbf803f7b, 0xbf5c3f75, 0x3f78bf80, 0x3f3ebf62, 0x3eacbf0e, 0xbe16bdc9, 0xbe160000, 0xbedb3e95, 0xbf2c3f0e, 0xbf5c3f46,
    0xbf783f6d, 0xbf803f7f, 0xbf713f7b, 0xbf4e3f62, 0xbf183f35, 0xbeac3ef1, 0xbd493e48, 0x3e79bdc9, 0x3f04bec4, 0x3f3ebf22,
    0x3f67bf55, 0x3f7dbf75, 0xbf7d3f80, 0xbf673f75, 0xbf3e3f55, 0xbf043f22, 0xbe793ec4, 0x3d493dc9, 0x3eacbe48, 0x3f18bef1,
    0x3f4ebf35, 0x3f71bf62, 0x3f80bf7b, 0x3f78bf7f, 0x3f5cbf6d, 0x3f2cbf46, 0x3edbbf0e, 0x3e16be95, 0xbe793ec4, 0x3d493dc9,
    0x3eacbe48, 0x3f18bef1, 0xbf7d3f80, 0xbf673f75, 0xbf3e3f55, 0xbf043f22, 0x3f5cbf6d, 0x3f2cbf46, 0x3edbbf0e, 0x3e16be95,
    0x3f4ebf35, 0x3f71bf62, 0x3f80bf7b, 0x3f78bf7f, 0x3f78bf6d, 0x3f80bf7f, 0x3f71bf7b, 0x3f4ebf62, 0x3e160000, 0x3edbbe95,
    0x3f2cbf0e, 0x3f5cbf46, 0xbf043ec4, 0xbf3e3f22, 0xbf673f55, 0xbf7d3f75, 0x3f18bf35, 0x3eacbef1, 0x3d49be48, 0xbe793dc9,
    0x3f3ebf35, 0x3f4ebf46, 0x3f5cbf55, 0x3f67bf62, 0x3f71bf6d, 0x3f78bf75, 0x3f7dbf7b, 0x3f80bf7f, 0x3d490000, 0x3e16bdc9,
    0x3e79be48, 0x3eacbe95, 0x3edbbec4, 0x3f04bef1, 0x3f18bf0e, 0x3f2cbf22, 0xbf2c3f35, 0xbf183f22, 0xbf043f0e, 0xbedb3ef1,
    0xbeac3ec4, 0xbe793e95, 0xbe163e48, 0xbd493dc9, 0xbf803f80, 0xbf7d3f7f, 0xbf783f7b, 0xbf713f75, 0xbf673f6d, 0xbf5c3f62,
    0xbf4e3f55, 0xbf3e3f46, 0x3eacbec4, 0x3e79be95, 0x3e16be48, 0x3d49bdc9, 0x3f2cbf35, 0x3f18bf22, 0x3f04bf0e, 0x3edbbef1,
    0x3f67bf6d, 0x3f5cbf62, 0x3f4ebf55, 0x3f3ebf46, 0x3f80bf80, 0x3f7dbf7f, 0x3f78bf7b, 0x3f71bf75, 0x3f71bf6d, 0x3f78bf75,
    0x3f7dbf7b, 0x3f80bf7f, 0x3f3ebf35, 0x3f4ebf46, 0x3f5cbf55, 0x3f67bf62, 0x3edbbec4, 0x3f04bef1, 0x3f18bf0e, 0x3f2cbf22,
    0x3d490000, 0x3e16bdc9, 0x3e79be48, 0x3eacbe95,
};
__device__ const __align__(128) uint32_t c_ga[1536] = {
    0x00003c80, 0x3bc43c6d, 0x00003c80, 0xbbc4bc6d, 0x00003c80, 0x3c6d3bc4, 0x00003c80, 0xbc6dbbc4, 0x00003c80, 0x3c6dbbc4,
    0x00003c80, 0xbc6d3bc4, 0x00003c80, 0x3bc4bc6d, 0x00003c80, 0xbbc43c6d, 0x3a493c80, 0x3bdb3c67, 0x3bdb3c67, 0xbc3ebc2c,
    0x3b163c7d, 0x3c783b79, 0x3c043c5c, 0xbc7d3b16, 0x3b793c78, 0x3c4ebc18, 0x3c183c4e, 0xbc043c5c, 0x3bac3c71, 0x3a49bc80,
    0x3c2c3c3e, 0x3bac3c71, 0x3ac93c7f, 0x3bf13c62, 0x3c463c22, 0xbc75bb95, 0x3b953c75, 0x3c7f3ac9, 0x3c623bf1, 0xbc463c22,
    0x3bf13c62, 0x3c22bc46, 0x3c753b95, 0x3ac93c7f, 0x3c223c46, 0xbb95bc75, 0x3c7f3ac9, 0x3c623bf1, 0x3b163c7d, 0x3c043c5c,
    0x3c783b79, 0xbc7d3b16, 0x3bdb3c67, 0x3c80ba49, 0x3c80ba49, 0xbbac3c71, 0x3c2c3c3e, 0x3bdbbc67, 0x3c71bbac, 0x3c2c3c3e,
    0x3c5c3c04, 0xbc18bc4e, 0x3c4ebc18, 0x3c78bb79, 0x3b483c7b, 0x3c0e3c55, 0x3c7bbb48, 0xbc553c0e, 0x3c0e3c55, 0x3c7bbb48,
    0x3c55bc0e, 0x3b483c7b, 0x3c553c0e, 0x3b48bc7b, 0x3c0ebc55, 0x3c7b3b48, 0x3c7b3b48, 0xbc55bc0e, 0x3b48bc7b, 0x3c0ebc55,
    0x3b793c78, 0x3c183c4e, 0x3c4ebc18, 0xbc043c5c, 0x3c2c3c3e, 0x3c71bbac, 0x3bdbbc67, 0x3c2c3c3e, 0x3c713bac, 0xba49bc80,
    0xba49bc80, 0x3c67bbdb, 0x3c7dbb16, 0xbc78bb79, 0xbc04bc5c, 0xbb16bc7d, 0x3b953c75, 0x3c223c46, 0x3bf1bc62, 0xbac93c7f,
    0x3c463c22, 0x3c62bbf1, 0xbac9bc7f, 0x3c753b95, 0x3c7f3ac9, 0xbb95bc75, 0xbc22bc46, 0x3bf1bc62, 0x3c62bbf1, 0xbc7f3ac9,
    0xbc75bb95, 0xbc46bc22, 0x3bac3c71, 0x3c2c3c3e, 0x3a49bc80, 0x3bac3c71, 0x3c5c3c04, 0x3c4ebc18, 0xbc18bc4e, 0x3c78bb79,
    0x3c7dbb16, 0xbc04bc5c, 0xbc78bb79, 0xbb16bc7d, 0x3c2cbc3e, 0xbc673bdb, 0xbc673bdb, 0xbc803a49, 0x00003c80, 0x3bc43c6d,
    0x00003c80, 0xbbc4bc6d, 0x00003c80, 0x3c6d3bc4, 0x00003c80, 0xbc6dbbc4, 0x00003c80, 0x3c6dbbc4, 0x00003c80, 0xbc6d3bc4,
    0x00003c80, 0x3bc4bc6d, 0x00003c80, 0xbbc43c6d, 0x3c3e3c2c, 0x3c713bac, 0x3c713bac, 0xbc803a49, 0x3c4e3c18, 0x3c5cbc04,
    0x3c783b79, 0xbc183c4e, 0x3c5c3c04, 0x3b16bc7d, 0x3c7d3b16, 0x3b793c78, 0x3c673bdb, 0xbc2cbc3e, 0x3c803a49, 0x3c673bdb,
    0x3c7fbac9, 0x3c62bbf1, 0x3c22bc46, 0xbb953c75, 0x3c75bb95, 0x3ac9bc7f, 0x3bf1bc62, 0x3c223c46, 0x3c62bbf1, 0xbc46bc22,
    0x3b95bc75, 0x3c7fbac9, 0x3c46bc22, 0xbc753b95, 0x3ac9bc7f, 0x3bf1bc62, 0x3c18bc4e, 0x3b79bc78, 0xbc04bc5c, 0x3c4e3c18,
    0x3bacbc71, 0xbc3ebc2c, 0xbc3ebc2c, 0x3c67bbdb, 0x3a49bc80, 0xbc713bac, 0xbc67bbdb, 0x3a49bc80, 0xbb79bc78, 0xbb163c7d,
    0xbc7dbb16, 0xbc5cbc04, 0xbb48bc7b, 0xbc0ebc55, 0xbc7b3b48, 0x3c55bc0e, 0xbc0ebc55, 0xbc7b3b48, 0xbc553c0e, 0xbb48bc7b,
    0xbc55bc0e, 0xbb483c7b, 0xbc0e3c55, 0xbc7bbb48, 0xbc7bbb48, 0x3c553c0e, 0xbb483c7b, 0xbc0e3c55, 0xbc5cbc04, 0xbc7dbb16,
    0xbb163c7d, 0xbb79bc78, 0xbc80ba49, 0xbbdb3c67, 0x3bac3c71, 0xbc80ba49, 0xbc673bdb, 0x3c3e3c2c, 0x3c3e3c2c, 0xbbac3c71,
    0xbc183c4e, 0x3c5cbc04, 0x3c783b79, 0x3c4e3c18, 0xbc753b95, 0xbc463c22, 0x3c623bf1, 0xbc7fbac9, 0xbc223c46, 0x3bf13c62,
    0x3c7fbac9, 0xbb953c75, 0xbac93c7f, 0x3c75bb95, 0x3c46bc22, 0x3c623bf1, 0x3bf13c62, 0xbac9bc7f, 0x3b95bc75, 0x3c22bc46,
    0xbbdb3c67, 0xba493c80, 0x3c3ebc2c, 0xbbdb3c67, 0x3b793c78, 0x3c7d3b16, 0x3b16bc7d, 0x3c5c3c04, 0x3c4e3c18, 0x3b79bc78,
    0xbc04bc5c, 0x3c18bc4e, 0x3c80ba49, 0xbc71bbac, 0xbc71bbac, 0xbc3ebc2c, 0x00003c80, 0x3bc43c6d, 0x00003c80, 0xbbc4bc6d,
    0x00003c80, 0x3c6d3bc4, 0x00003c80, 0xbc6dbbc4, 0x00003c80, 0x3c6dbbc4, 0x00003c80, 0xbc6d3bc4, 0x00003c80, 0x3bc4bc6d,
    0x00003c80, 0xbbc43c6d, 0x3c80ba49, 0x3c67bbdb, 0x3c67bbdb, 0xbc2c3c3e, 0x3c7dbb16, 0x3b79bc78, 0x3c5cbc04, 0x3b163c7d,
    0x3c78bb79, 0xbc18bc4e, 0x3c4ebc18, 0x3c5c3c04, 0x3c71bbac, 0xbc80ba49, 0x3c3ebc2c, 0x3c71bbac, 0xbac9bc7f, 0xbbf1bc62,
    0xbc46bc22, 0x3c753b95, 0xbb95bc75, 0xbc7fbac9, 0xbc62bbf1, 0x3c46bc22, 0xbbf1bc62, 0xbc223c46, 0xbc75bb95, 0xbac9bc7f,
    0xbc22bc46, 0x3b953c75, 0xbc7fbac9, 0xbc62bbf1, 0xbc7d3b16, 0xbc5c3c04, 0xbb793c78, 0xbb16bc7d, 0xbc673bdb, 0x3a493c80,
    0x3a493c80, 0xbc71bbac, 0xbc3e3c2c, 0x3c673bdb, 0x3bac3c71, 0xbc3e3c2c, 0xbc043c5c, 0x3c4ebc18, 0x3c183c4e, 0x3b793c78,
    0x3b483c7b, 0x3c0e3c55, 0x3c7bbb48, 0xbc553c0e, 0x3c0e3c55, 0x3c7bbb48, 0x3c55bc0e, 0x3b483c7b, 0x3c553c0e, 0x3b48bc7b,
    0x3c0ebc55, 0x3c7b3b48, 0x3c7b3b48, 0xbc55bc0e, 0x3b48bc7b, 0x3c0ebc55, 0x3c78bb79, 0x3c4ebc18, 0xbc18bc4e, 0x3c5c3c04,
    0x3c3ebc2c, 0xbbacbc71, 0xbc67bbdb, 0x3c3ebc2c, 0x3bacbc71, 0xbc803a49, 0xbc803a49, 0xbbdbbc67, 0xbb16bc7d, 0xbb793c78,
    0xbc5c3c04, 0xbc7d3b16, 0xbb95bc75, 0xbc22bc46, 0xbbf13c62, 0x3ac9bc7f, 0xbc46bc22, 0xbc623bf1, 0x3ac93c7f, 0xbc75bb95,
    0xbc7fbac9, 0x3b953c75, 0x3c223c46, 0xbbf13c62, 0xbc623bf1, 0x3c7fbac9, 0x3c753b95, 0x3c463c22, 0xbc713bac, 0xbc3e3c2c,
    0x3c803a49, 0xbc713bac, 0xbc043c5c, 0x3c183c4e, 0x3c4ebc18, 0x3b793c78, 0x3b163c7d, 0x3c5cbc04, 0x3b79bc78, 0x3c7dbb16,
    0x3c3e3c2c, 0xbbdbbc67, 0xbbdbbc67, 0xba49bc80, 0x00003c80, 0x3bc43c6d, 0x00003c80, 0xbbc4bc6d, 0x00003c80, 0x3c6d3bc4,
    0x00003c80, 0xbc6dbbc4, 0x00003c80, 0x3c6dbbc4, 0x00003c80, 0xbc6d3bc4, 0x00003c80, 0x3bc4bc6d, 0x00003c80, 0xbbc43c6d,
    0x3c2cbc3e, 0x3bacbc71, 0x3bacbc71, 0x3a493c80, 0x3c18bc4e, 0xbc04bc5c, 0x3b79bc78, 0x3c4e3c18, 0x3c04bc5c, 0xbc7dbb16,
    0x3b16bc7d, 0x3c78bb79, 0x3bdbbc67, 0xbc3e3c2c, 0x3a49bc80, 0x3bdbbc67, 0xbc7f3ac9, 0xbc623bf1, 0xbc223c46, 0x3b95bc75,
    0xbc753b95, 0xbac93c7f, 0xbbf13c62, 0xbc22bc46, 0xbc623bf1, 0x3c463c22, 0xbb953c75, 0xbc7f3ac9, 0xbc463c22, 0x3c75bb95,
    0xbac93c7f, 0xbbf13c62, 0x3c4e3c18, 0x3c783b79, 0x3c5cbc04, 0xbc183c4e, 0x3c713bac, 0x3c2cbc3e, 0x3c2cbc3e, 0x3bdb3c67,
    0x3c803a49, 0xbbacbc71, 0x3bdbbc67, 0x3c803a49, 0x3c78bb79, 0xbc7dbb16, 0x3b16bc7d, 0x3c04bc5c, 0xbb48bc7b, 0xbc0ebc55,
    0xbc7b3b48, 0x3c55bc0e, 0xbc0ebc55, 0xbc7b3b48, 0xbc553c0e, 0xbb48bc7b, 0xbc55bc0e, 0xbb483c7b, 0xbc0e3c55, 0xbc7bbb48,
    0xbc7bbb48, 0x3c553c0e, 0xbb483c7b, 0xbc0e3c55, 0xbc043c5c, 0xbb163c7d, 0x3c7d3b16, 0xbc783b79, 0xba493c80, 0x3c673bdb,
    0x3c71bbac, 0xba493c80, 0x3bdb3c67, 0x3c2cbc3e, 0x3c2cbc3e, 0x3c713bac, 0x3c4e3c18, 0xbc04bc5c, 0x3b79bc78, 0x3c18bc4e,
    0x3c75bb95, 0x3c46bc22, 0xbc62bbf1, 0x3c7f3ac9, 0x3c22bc46, 0xbbf1bc62, 0xbc7f3ac9, 0x3b95bc75, 0x3ac9bc7f, 0xbc753b95,
    0xbc463c22, 0xbc62bbf1, 0xbbf1bc62, 0x3ac93c7f, 0xbb953c75, 0xbc223c46, 0xbc67bbdb, 0xbc80ba49, 0x3c2c3c3e, 0xbc67bbdb,
    0xbc783b79, 0xbb163c7d, 0x3c7d3b16, 0xbc043c5c, 0xbc183c4e, 0x3c783b79, 0x3c5cbc04, 0x3c4e3c18, 0x3a493c80, 0x3bacbc71,
    0x3bacbc71, 0x3c2cbc3e, 0x3c353c35, 0x3c6d3bc4, 0x3c353c35, 0xbc6dbbc4, 0x3c35bc35, 0xbbc4bc6d, 0x3c35bc35, 0x3bc43c6d,
    0xbc35bc35, 0xbbc43c6d, 0xbc35bc35, 0x3bc4bc6d, 0xbc353c35, 0x3c6dbbc4, 0xbc353c35, 0xbc6d3bc4, 0x3c3e3c2c, 0x3c713bac,
    0x3c713bac, 0xbc803a49, 0x3c18bc4e, 0xbc04bc5c, 0x3b79bc78, 0x3c4e3c18, 0xbc5cbc04, 0xbb163c7d, 0xbc7dbb16, 0xbb79bc78,
    0xbbdb3c67, 0x3c3ebc2c, 0xba493c80, 0xbbdb3c67, 0x3c463c22, 0x3c753b95, 0x3c7fbac9, 0xbc623bf1, 0x3bf1bc62, 0xbc22bc46,
    0xbb95bc75, 0x3c7f3ac9, 0xbc75bb95, 0x3ac93c7f, 0xbc623bf1, 0xbc46bc22, 0xbac93c7f, 0x3bf1bc62, 0x3c223c46, 0x3b953c75,
    0x3c4e3c18, 0x3c783b79, 0x3c5cbc04, 0xbc183c4e, 0x3bacbc71, 0xbc3ebc2c, 0xbc3ebc2c, 0x3c67bbdb, 0xbc80ba49, 0x3bac3c71,
    0xbbdb3c67, 0xbc80ba49, 0x3b793c78, 0x3b16bc7d, 0x3c7d3b16, 0x3c5c3c04, 0x3c553c0e, 0x3c7b3b48, 0x3c0ebc55, 0xbb483c7b,
    0x3b48bc7b, 0xbc55bc0e, 0xbc7bbb48, 0x3c0ebc55, 0xbc7b3b48, 0x3c0e3c55, 0x3b483c7b, 0xbc553c0e, 0x3c0e3c55, 0xbb48bc7b,
    0x3c55bc0e, 0x3c7bbb48, 0x3c5c3c04, 0x3c7d3b16, 0x3b16bc7d, 0x3b793c78, 0x3a49bc80, 0xbc67bbdb, 0xbc713bac, 0x3a49bc80,
    0xbc673bdb, 0x3c3e3c2c, 0x3c3e3c2c, 0xbbac3c71, 0x3c4e3c18, 0xbc04bc5c, 0x3b79bc78, 0x3c18bc4e, 0x3c623bf1, 0x3c7f3ac9,
    0xbb95bc75, 0x3c223c46, 0xbac9bc7f, 0xbc75bb95, 0xbc223c46, 0xbbf1bc62, 0xbc463c22, 0x3c623bf1, 0x3c7f3ac9, 0x3b953c75,
    0x3c753b95, 0xbc46bc22, 0xbbf1bc62, 0xbac9bc7f, 0x3c673bdb, 0x3c803a49, 0xbc2cbc3e, 0x3c673bdb, 0xbb79bc78, 0xbc7dbb16,
    0xbb163c7d, 0xbc5cbc04, 0xbc183c4e, 0x3c783b79, 0x3c5cbc04, 0x3c4e3c18, 0x3c80ba49, 0xbc71bbac, 0xbc71bbac, 0xbc3ebc2c,
    0x3c353c35, 0x3c6d3bc4, 0x3c353c35, 0xbc6dbbc4, 0x3c35bc35, 0xbbc4bc6d, 0x3c35bc35, 0x3bc43c6d, 0xbc35bc35, 0xbbc43c6d,
    0xbc35bc35, 0x3bc4bc6d, 0xbc353c35, 0x3c6dbbc4, 0xbc353c35, 0xbc6d3bc4, 0x3c80ba49, 0x3c67bbdb, 0x3c67bbdb, 0xbc2c3c3e,
    0xbb16bc7d, 0xbc78bb79, 0xbc04bc5c, 0x3c7dbb16, 0xbc783b79, 0x3c183c4e, 0xbc4e3c18, 0xbc5cbc04, 0x3bac3c71, 0x3a49bc80,
    0x3c2c3c3e, 0x3bac3c71, 0x3c22bc46, 0x3b95bc75, 0xbac9bc7f, 0x3bf13c62, 0xbc62bbf1, 0xbc463c22, 0xbc753b95, 0x3ac9bc7f,
    0xbb953c75, 0x3c7fbac9, 0x3bf13c62, 0xbc223c46, 0x3c7f3ac9, 0xbc62bbf1, 0x3c46bc22, 0x3c75bb95, 0xbb16bc7d, 0xbc04bc5c,
    0xbc78bb79, 0x3c7dbb16, 0xbc673bdb, 0x3a493c80, 0x3a493c80, 0xbc71bbac, 0x3c2c3c3e, 0x3bdbbc67, 0x3c71bbac, 0x3c2c3c3e,
    0x3c04bc5c, 0xbc4e3c18, 0xbc18bc4e, 0xbb79bc78, 0xbc55bc0e, 0xbc7bbb48, 0xbc0e3c55, 0x3b48bc7b, 0xbb483c7b, 0x3c553c0e,
    0x3c7b3b48, 0xbc0e3c55, 0x3c7bbb48, 0xbc0ebc55, 0xbb48bc7b, 0x3c55bc0e, 0xbc0ebc55, 0x3b483c7b, 0xbc553c0e, 0xbc7b3b48,
    0xbc783b79, 0xbc4e3c18, 0x3c183c4e, 0xbc5cbc04, 0x3c2c3c3e, 0x3c71bbac, 0x3bdbbc67, 0x3c2c3c3e, 0x3bacbc71, 0xbc803a49,
    0xbc803a49, 0xbbdbbc67, 0xbc7d3b16, 0x3c783b79, 0x3c043c5c, 0x3b163c7d, 0xbbf13c62, 0xbac93c7f, 0x3c75bb95, 0xbc463c22,
    0x3c7fbac9, 0x3b95bc75, 0xbc46bc22, 0x3c62bbf1, 0xbc22bc46, 0xbbf13c62, 0xbac93c7f, 0xbc753b95, 0xbb953c75, 0x3c22bc46,
    0x3c62bbf1, 0x3c7fbac9, 0x3bac3c71, 0x3c2c3c3e, 0x3a49bc80, 0x3bac3c71, 0x3c04bc5c, 0xbc18bc4e, 0xbc4e3c18, 0xbb79bc78,
    0xbc7d3b16, 0x3c043c5c, 0x3c783b79, 0x3b163c7d, 0x3c3e3c2c, 0xbbdbbc67, 0xbbdbbc67, 0xba49bc80, 0x3c353c35, 0x3c6d3bc4,
    0x3c353c35, 0xbc6dbbc4, 0x3c35bc35, 0xbbc4bc6d, 0x3c35bc35, 0x3bc43c6d, 0xbc35bc35, 0xbbc43c6d, 0xbc35bc35, 0x3bc4bc6d,
    0xbc353c35, 0x3c6dbbc4, 0xbc353c35, 0xbc6d3bc4, 0x3c2cbc3e, 0x3bacbc71, 0x3bacbc71, 0x3a493c80, 0xbc4ebc18, 0xbc5c3c04,
    0xbc78bb79, 0x3c18bc4e, 0xbc043c5c, 0x3c7d3b16, 0xbb163c7d, 0xbc783b79, 0x3c673bdb, 0xbc2cbc3e, 0x3c803a49, 0x3c673bdb,
    0xbc46bc22, 0xbc75bb95, 0xbc7f3ac9, 0x3c62bbf1, 0xbbf13c62, 0x3c223c46, 0x3b953c75, 0xbc7fbac9, 0x3c753b95, 0xbac9bc7f,
    0x3c62bbf1, 0x3c463c22, 0x3ac9bc7f, 0xbbf13c62, 0xbc22bc46, 0xbb95bc75, 0xbc183c4e, 0xbb793c78, 0x3c043c5c, 0xbc4ebc18,
    0x3c713bac, 0x3c2cbc3e, 0x3c2cbc3e, 0x3bdb3c67, 0x3a49bc80, 0xbc713bac, 0xbc67bbdb, 0x3a49bc80, 0xbc783b79, 0x3c7d3b16,
    0xbb163c7d, 0xbc043c5c, 0x3c553c0e, 0x3c7b3b48, 0x3c0ebc55, 0xbb483c7b, 0x3b48bc7b, 0xbc55bc0e, 0xbc7bbb48, 0x3c0ebc55,
    0xbc7b3b48, 0x3c0e3c55, 0x3b483c7b, 0xbc553c0e, 0x3c0e3c55, 0xbb48bc7b, 0x3c55bc0e, 0x3c7bbb48, 0x3c04bc5c, 0x3b16bc7d,
    0xbc7dbb16, 0x3c78bb79, 0xbc80ba49, 0xbbdb3c67, 0x3bac3c71, 0xbc80ba49, 0x3bdb3c67, 0x3c2cbc3e, 0x3c2cbc3e, 0x3c713bac,
    0x3c18bc4e, 0xbc5c3c04, 0xbc78bb79, 0xbc4ebc18, 0xbc62bbf1, 0xbc7fbac9, 0x3b953c75, 0xbc22bc46, 0x3ac93c7f, 0x3c753b95,
    0x3c22bc46, 0x3bf13c62, 0x3c46bc22, 0xbc62bbf1, 0xbc7fbac9, 0xbb95bc75, 0xbc75bb95, 0x3c463c22, 0x3bf13c62, 0x3ac93c7f,
    0xbbdb3c67, 0xba493c80, 0x3c3ebc2c, 0xbbdb3c67, 0x3c78bb79, 0x3b16bc7d, 0xbc7dbb16, 0x3c04bc5c, 0xbc4ebc18, 0xbb793c78,
    0x3c043c5c, 0xbc183c4e, 0x3a493c80, 0x3bacbc71, 0x3bacbc71, 0x3c2cbc3e, 0x3c353c35, 0x3c6d3bc4, 0x3c353c35, 0xbc6dbbc4,
    0x3c35bc35, 0xbbc4bc6d, 0x3c35bc35, 0x3bc43c6d, 0xbc35bc35, 0xbbc43c6d, 0xbc35bc35, 0x3bc4bc6d, 0xbc353c35, 0x3c6dbbc4,
    0xbc353c35, 0xbc6d3bc4, 0xba49bc80, 0xbbdbbc67, 0xbbdbbc67, 0x3c3e3c2c, 0xbc7d3b16, 0xbb793c78, 0xbc5c3c04, 0xbb16bc7d,
    0x3b793c78, 0x3c4ebc18, 0x3c183c4e, 0xbc043c5c, 0x3c71bbac, 0xbc80ba49, 0x3c3ebc2c, 0x3c71bbac, 0xbc223c46, 0xbb953c75,
    0x3ac93c7f, 0xbbf1bc62, 0x3c623bf1, 0x3c46bc22, 0x3c75bb95, 0xbac93c7f, 0x3b95bc75, 0xbc7f3ac9, 0xbbf1bc62, 0x3c22bc46,
    0xbc7fbac9, 0x3c623bf1, 0xbc463c22, 0xbc753b95, 0x3c7dbb16, 0x3c5cbc04, 0x3b79bc78, 0x3b163c7d, 0xbbdbbc67, 0xbc803a49,
    0xbc803a49, 0x3bacbc71, 0xbc3e3c2c, 0x3c673bdb, 0x3bac3c71, 0xbc3e3c2c, 0x3c5c3c04, 0xbc18bc4e, 0x3c4ebc18, 0x3c78bb79,
    0xbc55bc0e, 0xbc7bbb48, 0xbc0e3c55, 0x3b48bc7b, 0xbb483c7b, 0x3c553c0e, 0x3c7b3b48, 0xbc0e3c55, 0x3c7bbb48, 0xbc0ebc55,
    0xbb48bc7b, 0x3c55bc0e, 0xbc0ebc55, 0x3b483c7b, 0xbc553c0e, 0xbc7b3b48, 0x3b793c78, 0x3c183c4e, 0x3c4ebc18, 0xbc043c5c,
    0x3c3ebc2c, 0xbbacbc71, 0xbc67bbdb, 0x3c3ebc2c, 0xbc71bbac, 0x3a493c80, 0x3a493c80, 0xbc673bdb, 0x3b163c7d, 0x3b79bc78,
    0x3c5cbc04, 0x3c7dbb16, 0x3bf1bc62, 0x3ac9bc7f, 0xbc753b95, 0x3c46bc22, 0xbc7f3ac9, 0xbb953c75, 0x3c463c22, 0xbc623bf1,
    0x3c223c46, 0x3bf1bc62, 0x3ac9bc7f, 0x3c75bb95, 0x3b95bc75, 0xbc223c46, 0xbc623bf1, 0xbc7f3ac9, 0xbc713bac, 0xbc3e3c2c,
    0x3c803a49, 0xbc713bac, 0x3c5c3c04, 0x3c4ebc18, 0xbc18bc4e, 0x3c78bb79, 0xbb16bc7d, 0xbc5c3c04, 0xbb793c78, 0xbc7d3b16,
    0xbc2c3c3e, 0x3c67bbdb, 0x3c67bbdb, 0x3c80ba49, 0x3c800000, 0x3c6dbbc4, 0x3c800000, 0xbc6d3bc4, 0xbc800000, 0xbbc43c6d,
    0xbc800000, 0x3bc4bc6d, 0x3c800000, 0xbbc4bc6d, 0x3c800000, 0x3bc43c6d, 0xbc800000, 0x3c6d3bc4, 0xbc800000, 0xbc6dbbc4,
    0x3c80ba49, 0x3c67bbdb, 0x3c67bbdb, 0xbc2c3c3e, 0xbc7d3b16, 0xbb793c78, 0xbc5c3c04, 0xbb16bc7d, 0x3c78bb79, 0xbc18bc4e,
    0x3c4ebc18, 0x3c5c3c04, 0xbc713bac, 0x3c803a49, 0xbc3e3c2c, 0xbc713bac, 0x3c7fbac9, 0x3c62bbf1, 0x3c22bc46, 0xbb953c75,
    0xbc753b95, 0xbac93c7f, 0xbbf13c62, 0xbc22bc46, 0x3c62bbf1, 0xbc46bc22, 0x3b95bc75, 0x3c7fbac9, 0xbc463c22, 0x3c75bb95,
    0xbac93c7f, 0xbbf13c62, 0x3c7dbb16, 0x3c5cbc04, 0x3b79bc78, 0x3b163c7d, 0xbc673bdb, 0x3a493c80, 0x3a493c80, 0xbc71bbac,
    0x3c3ebc2c, 0xbc67bbdb, 0xbbacbc71, 0x3c3ebc2c, 0xbc043c5c, 0x3c4ebc18, 0x3c183c4e, 0x3b793c78, 0x3c7bbb48, 0x3c55bc0e,
    0xbb48bc7b, 0x3c0e3c55, 0xbc553c0e, 0x3b483c7b, 0x3c0e3c55, 0xbc7b3b48, 0x3c0ebc55, 0xbc7bbb48, 0xbc55bc0e, 0x3b48bc7b,
    0xbb483c7b, 0x3c0ebc55, 0x3c7b3b48, 0x3c553c0e, 0x3c78bb79, 0x3c4ebc18, 0xbc18bc4e, 0x3c5c3c04, 0xbc3e3c2c, 0x3bac3c71,
    0x3c673bdb, 0xbc3e3c2c, 0x3bacbc71, 0xbc803a49, 0xbc803a49, 0xbbdbbc67, 0x3b163c7d, 0x3b79bc78, 0x3c5cbc04, 0x3c7dbb16,
    0x3c75bb95, 0x3c46bc22, 0xbc62bbf1, 0x3c7f3ac9, 0xbc223c46, 0x3bf13c62, 0x3c7fbac9, 0xbb953c75, 0x3ac9bc7f, 0xbc753b95,
    0xbc463c22, 0xbc62bbf1, 0x3bf13c62, 0xbac9bc7f, 0x3b95bc75, 0x3c22bc46, 0x3c71bbac, 0x3c3ebc2c, 0xbc80ba49, 0x3c71bbac,
    0xbc043c5c, 0x3c183c4e, 0x3c4ebc18, 0x3b793c78, 0xbb16bc7d, 0xbc5c3c04, 0xbb793c78, 0xbc7d3b16, 0x3c3e3c2c, 0xbbdbbc67,
    0xbbdbbc67, 0xba49bc80, 0x3c800000, 0x3c6dbbc4, 0x3c800000, 0xbc6d3bc4, 0xbc800000, 0xbbc43c6d, 0xbc800000, 0x3bc4bc6d,
    0x3c800000, 0xbbc4bc6d, 0x3c800000, 0x3bc43c6d, 0xbc800000, 0x3c6d3bc4, 0xbc800000, 0xbc6dbbc4, 0x3c2cbc3e, 0x3bacbc71,
    0x3bacbc71, 0x3a493c80, 0xbc183c4e, 0x3c043c5c, 0xbb793c78, 0xbc4ebc18, 0x3c04bc5c, 0xbc7dbb16, 0x3b16bc7d, 0x3c78bb79,
    0xbbdb3c67, 0x3c3ebc2c, 0xba493c80, 0xbbdb3c67, 0xbac9bc7f, 0xbbf1bc62, 0xbc46bc22, 0x3c753b95, 0x3b953c75, 0x3c7f3ac9,
    0x3c623bf1, 0xbc463c22, 0xbbf1bc62, 0xbc223c46, 0xbc75bb95, 0xbac9bc7f, 0x3c223c46, 0xbb95bc75, 0x3c7f3ac9, 0x3c623bf1,
    0xbc4ebc18, 0xbc78bb79, 0xbc5c3c04, 0x3c18bc4e, 0x3c713bac, 0x3c2cbc3e, 0x3c2cbc3e, 0x3bdb3c67, 0xbc80ba49, 0x3bac3c71,
    0xbbdb3c67, 0xbc80ba49, 0x3c78bb79, 0xbc7dbb16, 0x3b16bc7d, 0x3c04bc5c, 0xbc7b3b48, 0xbc553c0e, 0x3b483c7b, 0xbc0ebc55,
    0x3c55bc0e, 0xbb48bc7b, 0xbc0ebc55, 0x3c7bbb48, 0xbc0e3c55, 0x3c7b3b48, 0x3c553c0e, 0xbb483c7b, 0x3b48bc7b, 0xbc0e3c55,
    0xbc7bbb48, 0xbc55bc0e, 0xbc043c5c, 0xbb163c7d, 0x3c7d3b16, 0xbc783b79, 0x3a49bc80, 0xbc67bbdb, 0xbc713bac, 0x3a49bc80,
    0x3bdb3c67, 0x3c2cbc3e, 0x3c2cbc3e, 0x3c713bac, 0xbc4ebc18, 0x3c043c5c, 0xbb793c78, 0xbc183c4e, 0x3b953c75, 0x3c223c46,
    0x3bf1bc62, 0xbac93c7f, 0xbc46bc22, 0xbc623bf1, 0x3ac93c7f, 0xbc75bb95, 0x3c7f3ac9, 0xbb95bc75, 0xbc22bc46, 0x3bf1bc62,
    0xbc623bf1, 0x3c7fbac9, 0x3c753b95, 0x3c463c22, 0x3c673bdb, 0x3c803a49, 0xbc2cbc3e, 0x3c673bdb, 0xbc783b79, 0xbb163c7d,
    0x3c7d3b16, 0xbc043c5c, 0x3c18bc4e, 0xbc78bb79, 0xbc5c3c04, 0xbc4ebc18, 0x3a493c80, 0x3bacbc71, 0x3bacbc71, 0x3c2cbc3e,
    0x3c800000, 0x3c6dbbc4, 0x3c800000, 0xbc6d3bc4, 0xbc800000, 0xbbc43c6d, 0xbc800000, 0x3bc4bc6d, 0x3c800000, 0xbbc4bc6d,
    0x3c800000, 0x3bc43c6d, 0xbc800000, 0x3c6d3bc4, 0xbc800000, 0xbc6dbbc4, 0xba49bc80, 0xbbdbbc67, 0xbbdbbc67, 0x3c3e3c2c,
    0x3b163c7d, 0x3c783b79, 0x3c043c5c, 0xbc7d3b16, 0xbb79bc78, 0xbc4e3c18, 0xbc18bc4e, 0x3c04bc5c, 0x3bac3c71, 0x3a49bc80,
    0x3c2c3c3e, 0x3bac3c71, 0xbc7f3ac9, 0xbc623bf1, 0xbc223c46, 0x3b95bc75, 0x3c75bb95, 0x3ac9bc7f, 0x3bf1bc62, 0x3c223c46,
    0xbc623bf1, 0x3c463c22, 0xbb953c75, 0xbc7f3ac9, 0x3c46bc22, 0xbc753b95, 0x3ac9bc7f, 0x3bf1bc62, 0x3b163c7d, 0x3c043c5c,
    0x3c783b79, 0xbc7d3b16, 0xbbdbbc67, 0xbc803a49, 0xbc803a49, 0x3bacbc71, 0x3c2c3c3e, 0x3bdbbc67, 0x3c71bbac, 0x3c2c3c3e,
    0xbc5cbc04, 0x3c183c4e, 0xbc4e3c18, 0xbc783b79, 0x3c7bbb48, 0x3c55bc0e, 0xbb48bc7b, 0x3c0e3c55, 0xbc553c0e, 0x3b483c7b,
    0x3c0e3c55, 0xbc7b3b48, 0x3c0ebc55, 0xbc7bbb48, 0xbc55bc0e, 0x3b48bc7b, 0xbb483c7b, 0x3c0ebc55, 0x3c7b3b48, 0x3c553c0e,
    0xbb79bc78, 0xbc18bc4e, 0xbc4e3c18, 0x3c04bc5c, 0x3c2c3c3e, 0x3c71bbac, 0x3bdbbc67, 0x3c2c3c3e, 0xbc71bbac, 0x3a493c80,
    0x3a493c80, 0xbc673bdb, 0x3c7dbb16, 0xbc78bb79, 0xbc04bc5c, 0xbb16bc7d, 0xbc753b95, 0xbc463c22, 0x3c623bf1, 0xbc7fbac9,
    0x3c22bc46, 0xbbf1bc62, 0xbc7f3ac9, 0x3b95bc75, 0xbac93c7f, 0x3c75bb95, 0x3c46bc22, 0x3c623bf1, 0xbbf1bc62, 0x3ac93c7f,
    0xbb953c75, 0xbc223c46, 0x3bac3c71, 0x3c2c3c3e, 0x3a49bc80, 0x3bac3c71, 0xbc5cbc04, 0xbc4e3c18, 0x3c183c4e, 0xbc783b79,
    0x3c7dbb16, 0xbc04bc5c, 0xbc78bb79, 0xbb16bc7d, 0xbc2c3c3e, 0x3c67bbdb, 0x3c67bbdb, 0x3c80ba49, 0x3c800000, 0x3c6dbbc4,
    0x3c800000, 0xbc6d3bc4, 0xbc800000, 0xbbc43c6d, 0xbc800000, 0x3bc4bc6d, 0x3c800000, 0xbbc4bc6d, 0x3c800000, 0x3bc43c6d,
    0xbc800000, 0x3c6d3bc4, 0xbc800000, 0xbc6dbbc4, 0xbc3ebc2c, 0xbc71bbac, 0xbc71bbac, 0x3c80ba49, 0x3c4e3c18, 0x3c5cbc04,
    0x3c783b79, 0xbc183c4e, 0xbc5cbc04, 0xbb163c7d, 0xbc7dbb16, 0xbb79bc78, 0x3c673bdb, 0xbc2cbc3e, 0x3c803a49, 0x3c673bdb,
    0x3ac93c7f, 0x3bf13c62, 0x3c463c22, 0xbc75bb95, 0xbb95bc75, 0xbc7fbac9, 0xbc62bbf1, 0x3c46bc22, 0x3bf13c62, 0x3c22bc46,
    0x3c753b95, 0x3ac93c7f, 0xbc22bc46, 0x3b953c75, 0xbc7fbac9, 0xbc62bbf1, 0x3c18bc4e, 0x3b79bc78, 0xbc04bc5c, 0x3c4e3c18,
    0xbbac3c71, 0x3c3e3c2c, 0x3c3e3c2c, 0xbc673bdb, 0x3a49bc80, 0xbc713bac, 0xbc67bbdb, 0x3a49bc80, 0x3b793c78, 0x3b16bc7d,
    0x3c7d3b16, 0x3c5c3c04, 0xbc7b3b48, 0xbc553c0e, 0x3b483c7b, 0xbc0ebc55, 0x3c55bc0e, 0xbb48bc7b, 0xbc0ebc55, 0x3c7bbb48,
    0xbc0e3c55, 0x3c7b3b48, 0x3c553c0e, 0xbb483c7b, 0x3b48bc7b, 0xbc0e3c55, 0xbc7bbb48, 0xbc55bc0e, 0x3c5c3c04, 0x3c7d3b16,
    0x3b16bc7d, 0x3b793c78, 0xbc80ba49, 0xbbdb3c67, 0x3bac3c71, 0xbc80ba49, 0x3c67bbdb, 0xbc3ebc2c, 0xbc3ebc2c, 0x3bacbc71,
    0xbc183c4e, 0x3c5cbc04, 0x3c783b79, 0x3c4e3c18, 0xbb95bc75, 0xbc22bc46, 0xbbf13c62, 0x3ac9bc7f, 0x3c463c22, 0x3c62bbf1,
    0xbac9bc7f, 0x3c753b95, 0xbc7fbac9, 0x3b953c75, 0x3c223c46, 0xbbf13c62, 0x3c62bbf1, 0xbc7f3ac9, 0xbc75bb95, 0xbc46bc22,
    0xbbdb3c67, 0xba493c80, 0x3c3ebc2c, 0xbbdb3c67, 0xbb79bc78, 0xbc7dbb16, 0xbb163c7d, 0xbc5cbc04, 0x3c4e3c18, 0x3b79bc78,
    0xbc04bc5c, 0x3c18bc4e, 0xbc803a49, 0x3c713bac, 0x3c713bac, 0x3c3e3c2c,
};

template <int G = 1024> __device__ __forceinline__ void store_tile_64(const float (&d)[32], uint32_t base, int warp, int lane) {
  const uint32_t rb = base + (warp * 2 + ((lane >> 3) & 1)) * G + (lane & 7) * 128;
#pragma unroll
  for (int j = 0; j < 8; j += 2) {
    const int jj = j + (lane >> 4);
    stsm4(rb + ((jj ^ (lane & 7)) << 4), pack2(d[4 * j], d[4 * j + 1]), pack2(d[4 * j + 2], d[4 * j + 3]),
          pack2(d[4 * j + 4], d[4 * j + 5]), pack2(d[4 * j + 6], d[4 * j + 7]));
  }
}

#define A_XM0 0xEB5C
#define A_XM1 0xDCBC
#define A_REL 0x22910
#define G_WPOLK 12
#define A_LDW 0x242
#define A_W2PF 2
#define A_DEPS 4
#define A_FREE 0x3F000
#define A_RELS 0x8A80
#define A_ACQ 0x1511
#define A_DEP 3
#define A_PACE0 1000
#define A_PACE1 A_PACE0
#define A_PACE_N 8
#define G_TMASK 0x0FB0
constexpr int A_IN = 112 * 128, A_OUT = 16384, A_NIN = 5, A_NOUT = 6;
constexpr int A_NREL = __builtin_popcount(A_REL);
constexpr int G_XP = NB1 * 64;
constexpr int G_STAGE = 16384 + 2 * G_XP, G_NST = 5;
constexpr int G_TIN = G_NST * G_STAGE, G_TOUT = G_TIN + 8192, G_SMEM = G_TOUT + 32768 + 1024;
#define G_SLOTS 0x1032410324103210ull
__host__ __device__ constexpr int g_slot(int k) { return (G_SLOTS >> (4 * k)) & 7; }
constexpr uint32_t g_parities() {
  uint32_t m = 0;
  for (int k = 0; k < 16; k++)
    for (int j = 0; j < k; j++)
      if (g_slot(j) == g_slot(k)) m ^= 1u << k;
  return m;
}
constexpr uint32_t G_PAR = g_parities();
constexpr int G_KS = 12;
__device__ __align__(128) int g_cnt[3 * 32];

__device__ __forceinline__ int x_decode(int r, int cta) {
  const int v = r * 64 + ((cta >> 2) << 1) + (cta & 1);
  int j = v / 80;
  j -= v < 80 * j + ((0x4840 >> (4 * j)) & 15);
  if (cta < 128) return ((7 - j) << 7) | (v - 80 * j - ((0x4840 >> (4 * j)) & 15));
  return r < 8 ? ((5 - (r >> 2)) << 7) | (76 + 4 * (cta & 1) + (r & 3)) : ((7 - (r >> 1)) << 7) | (80 + 2 * (cta & 1) + (r & 1));
}
__device__ __forceinline__ uint32_t a_out(int n) {
  const int p = n % A_NOUT;
  return (p < 4 ? (3 + (p >> 1)) * G_STAGE : G_TOUT) + (p & 1) * A_OUT;
}
__device__ __forceinline__ uint32_t x1_addr(int L, int b, uint32_t flips) {
  const int p = L >> 4, sel = (b ^ __popc(L & 15) ^ (flips >> p)) & 1;
  return (p << 21) | (sel << 12) | ((L & 1) << 13) | ((L & 6) << 15) | ((L & 8) << 16);
}
__device__ __forceinline__ uint32_t spread16(int i) { return ((i & 3) << 14) | ((i & 4) << 16) | ((i & 8) << 17); }
constexpr int NPG = 19 + W_SHIFT, NVOTE = 6;
__device__ __forceinline__ uint32_t w_addr(int P, int f, int c, int dhalf, uint32_t flips) {
  return x1_addr(16 * P + (c >> 5) + 2 * (f >> 3), dhalf, flips >> 12) + spread16(2 * f) + (c & 31) * 128;
}
__device__ __forceinline__ void w_store(const CUtensorMap* m, uint32_t src, uint32_t a) {
#pragma unroll
  for (int j = 0; j < 8; j++)
    tma_st5<0>(m, src + j * 2048, ((a & 16383) >> 1) ^ ((__popc(j) & 1) << 11), (j & 3) << 1, (j >> 2) << 1, a >> 20, 0);
}
__device__ __forceinline__ uint32_t read_votes(const int* cnt, int lane, int& side, int v = 0) {
  for (int it = 0; it < (1 << 20) && (__ballot_sync(0xffffffffu, v < NVOTE * 256) & ((2 << NPG) - 2)); it++)
    asm volatile("ld.relaxed.gpu.global.s32 %0, [%1];" : "=r"(v) : "l"(cnt + 32 + lane) : "memory");
  uint32_t smid;
  asm("mov.u32 %0, %%smid;" : "=r"(smid));
  side = (__shfl_sync(0xffffffffu, v, 24 + (smid >> 5) % 6) >> (smid & 31)) & 1;
  return __ballot_sync(0xffffffffu, (v & 255) > NVOTE / 2);
}
__device__ __forceinline__ int take_ticket(int* p) {
  int v;
  asm volatile("atom.relaxed.gpu.global.inc.u32 %0, [%1], 0xffffffff;" : "=r"(v) : "l"(p) : "memory");
  return v;
}
__device__ __forceinline__ void send_role(uint32_t dst, uint32_t bar, int v) {
  for (int c = 0; c < 2; c++)
    asm volatile("{\n.reg .b32 a, b;\nmapa.shared::cluster.u32 a, %0, %2;\nmapa.shared::cluster.u32 b, %1, %2;\n"
                 "st.async.shared::cluster.mbarrier::complete_tx::bytes.u32 [a], %3, [b];\n}" ::"r"(dst), "r"(bar), "r"(c), "r"(v) : "memory");
}
struct GMaps {
  CUtensorMap in[5];
  CUtensorMap ws, xs, w, y;
};

__global__ void __cluster_dims__(2, 1, 1) __launch_bounds__(384, 1)
kG(int* __restrict__ cnt, char* __restrict__ x1, char* __restrict__ wt, const __nv_bfloat16* __restrict__ g,
   const __nv_bfloat16* __restrict__ wgt, float* __restrict__ ge, const uint32_t* __restrict__ img, const __grid_constant__ GMaps m) {
  extern __shared__ uint8_t smem_raw[];
  __shared__ __align__(8) uint64_t bars[20 + A_NIN + 2 * A_NOUT + 2 * G_NST + 16 + 2 * A_NREL];
  __shared__ uint16_t tab[128];
  __shared__ uint32_t lat[8], s_role, s_flips;
  const uint32_t sb = pin((s2u(smem_raw) + 1023) & ~1023u);
  const int tid = threadIdx.x, wg = __shfl_sync(0xffffffffu, tid >> 7, 0), t = tid & 127;
  const int warp = __shfl_sync(0xffffffffu, t >> 5, 0), lane = t & 31;
  const int blk = blockIdx.x, hf = blk & 1, page = 1 + blk % NPG;
  const bool spare = blk >= 128, voter = blk >= 128 - NPG * NVOTE && !spare;
  const int nu = spare ? 16 : 18;
  const uint32_t xm = spare ? 0xFFFF : hf ? A_XM1 : A_XM0;
  const uint32_t wf0 = pin(s2u(&bars[0])), xf0 = wf0 + 32, xe0 = xf0 + 128, aof0 = xe0 + 8 * A_NIN, aoe0 = aof0 + 8 * A_NOUT;
  const uint32_t full0 = aoe0 + 8 * A_NOUT, empty0 = full0 + 8 * G_NST;
  const uint32_t sf0 = empty0 + 8 * G_NST, se0 = sf0 + 16, inf0 = se0 + 16, roleb = inf0 + 16, flipb = roleb + 8;
  const uint32_t rel0 = flipb + 8, got0 = rel0 + 8 * A_NREL, acq0 = got0 + 64;
  auto role = [&]() {
    mbar_wait(roleb, 0);
    return 2 * (int)*(volatile uint32_t*)&s_role + hf;
  };
  auto flips = [&]() {
    mbar_wait(flipb, 0);
    return *(volatile uint32_t*)&s_flips;
  };
  auto w_unit = [&](int cta) { return (cta & ~3) | (hf << 1) | ((cta >> 1) & 1); };
  auto w_code = [](int w2, int s, int i) { return (-(s < 4) << 16) | ((2 * w2 + (s >> 2)) << 11) | ((s & 3) << 9) | ((i >> 1) << 3) | ((i & 1) << 1); };
  auto in_load = [&](int c, uint32_t dst, uint32_t bar) {
    tma_ld5<1>(dst, &m.in[(c >> 11) & 7], bar, 0, c >> 16, c & 7, (c >> 3) & 63, (c >> 9) & 3);
  };
  if (wg < 2) {
    if (lane == 0) {
      const uint32_t h = blk & 0x59, par = h ^ (h >> 3) ^ (h >> 4) ^ (h >> 6);
      char* p = x1 + (blk << 13) + (((warp ^ par) & 1) << 12) + 3584 + (warp >> 1) * 128;
      if (wg) {
        if (!voter) p += 256;
        else if (page < 12) p += page << 21;
        else p = wt + w_addr(page - 12, warp >> 1, blk >> 1, warp & 1, 0);
      }
      uint32_t c0, c1;
      asm volatile("{\n.reg .u32 v;\n.reg .pred q;\n"
                   "st.global.v4.u32 [%2], {0, 0, 0, 0};\nst.global.v4.u32 [%2 + 16], {0, 0, 0, 0};\n"
                   "mov.u32 %0, %%clock;\nmov.u32 %1, %0;\natom.relaxed.gpu.global.exch.b32 v, [%2], 1;\n"
                   "setp.eq.u32 q, v, 0;\n@q mov.u32 %1, %%clock;\n}\n" : "=r"(c0), "=r"(c1) : "l"(p) : "memory");
      lat[wg * 4 + warp] = c1 - c0;
    }
    __syncwarp();
    if (wg == 0 && hf == 0) bar_arrive(10, 160);
    bar_arrive(9, 288);
  }
  if (wg == 2) {
    if (t == 32) {
      mbar_init(wf0 + 24, 1);
      mbar_expect(wf0 + 24, 8192);
      fence_async();
      if (!spare) tma_ld5<1>(sb + 2 * G_STAGE + 3 * 8192, &m.in[1], wf0 + 24, 0, 0, 2 * hf, blk >> 1, 2);
    }
    __syncwarp();
    int votes = 0;
    if (warp == 3 && !voter) asm volatile("ld.relaxed.gpu.global.s32 %0, [%1];" : "=r"(votes) : "l"(cnt + 32 + lane) : "memory");
    asm volatile("setmaxnreg.dec.sync.aligned.u32 40;");
    if (lane == 0 && warp > 0) {
      if (warp == 1) {
        for (int i = 0; i < 3; i++) {
          mbar_init(wf0 + 8 * i, 1);
          mbar_expect(wf0 + 8 * i, 8192);
        }
      } else if (warp == 2) {
        prefetch_map(&m.in[4]);
        for (int i = 0; i < A_NIN + A_NOUT; i++) mbar_init(xe0 + 8 * i, 4);
        for (int i = 0; i < A_NOUT; i++) mbar_init(aoe0 + 8 * i, 1);
      } else {
        for (int i = 0; i < 2; i++) mbar_init(sf0 + 8 * i, 8);
        for (int i = 0; i < 6 + A_NREL; i++) mbar_init(se0 + 8 * i, 1);
        for (int i = 0; i < 3; i++) mbar_expect(inf0 + 8 * i, i < 2 ? 4096 : 4);
      }
      fence_bar_init();
    }
    __syncwarp();
    asm volatile("barrier.cluster.arrive.relaxed.aligned;" ::: "memory");
    int role_w = warp;
    if (role_w == 0) {
      int cta = blk, side = 0;
      if (hf == 0) {
        bar_sync(10, 160);
        side = min(lat[0], lat[2]) > min(lat[1], lat[3]);
        if (lane == 0) cta = take_ticket(cnt + (spare ? 62 : 54) + side);
      }
      const uint32_t wm = spare ? 0 : A_LDW | 0x6000;
      const int nw = __popc(wm & ((1 << lane) - 1)), r = lane - nw, np = r + A_NIN - (spare ? A_DEPS : A_DEP);
      const bool isw = (wm >> lane) & 1;
      uint32_t dst = sb + (!isw ? (r % A_NIN) * A_IN : nw < 3 ? 2 * G_STAGE + (2 - nw) * 8192 : G_TIN + (nw - 3) * 4096);
      uint32_t bf = !isw ? xf0 + 8 * r : nw < 3 ? wf0 + 8 * (2 - nw) : inf0 + 8 * (nw - 3);
      uint32_t be = isw ? roleb : xe0 + 8 * (np % A_NIN) + ((np / A_NIN - 1) & 1);
      asm volatile("barrier.cluster.wait.aligned;" : "+r"(dst), "+r"(bf), "+r"(be)::"memory");
      if (hf == 0) {
        cta = 2 * __shfl_sync(0xffffffffu, cta, 0) + side;
        if (cta >= 64) cta = 127 - cta;
        if (spare) cta = 64 + (cta >= 2 ? 3 - cta : cta);
        if (lane == 0) send_role(s2u(&s_role), roleb, cta);
        cta *= 2;
      } else {
        cta = role();
      }
      const int b = (cta >> 1) & 1;
      if (lane == 0 && !spare) tma_ld5<1>(sb, &m.in[4], xf0, 0, 96 * (((cta >> 2) << 1) + hf) - 24, 7, 0, b);
      __syncwarp();
      const int xc = x_decode(r, cta);
      const int code = isw ? w_code(nw >= 3, nw < 3 ? 4 - 2 * nw : 10 - nw, w_unit(cta)) : ((96 * (xc & 127) - 24) << 16) | (4 << 11) | (b << 9) | (xc >> 7);
#pragma unroll 1
      for (int p = !spare; p < (spare ? 16 : 15); p++) {
        const int c = __shfl_sync(0xffffffffu, code, p);
        const uint32_t d = __shfl_sync(0xffffffffu, dst, p), f = __shfl_sync(0xffffffffu, bf, p), e = __shfl_sync(0xffffffffu, be, p);
        mbar_wait(e & ~1u, e & 1);
        if (lane == 0) in_load(c, d, f);
        __syncwarp();
      }
      if (!spare) {
        const int bin = cta >> 2, f = 2 * bin + hf;
        if (lane == 0) {
          for (int s = 5; s >= A_W2PF; s--) {
            const int c = w_code(1, s, w_unit(cta));
            asm volatile("cp.async.bulk.prefetch.tensor.5d.L2.global [%0, {0, %1, %2, %3, %4}];" ::"l"(&m.in[(c >> 11) & 7]), "r"(c >> 16), "r"(c & 7), "r"((c >> 3) & 63), "r"((c >> 9) & 3) : "memory");
          }
          prefetch_map(&m.w);
          prefetch_map(&m.y);
          prefetch_map(&m.in[2]);
        }
        const uint32_t xa = x1_addr((21 - lane + 2 * (lane % 3)) * 8 + (f >> 4), b, flips()) + spread16(f);
        const uint32_t wa = w_addr(7 - (lane >> 1), 2 * bin, (lane & 1) * 32, hf, s_flips & ~0xC0000u);
#pragma unroll 1
        for (int k = 0; k < 16; k++) {
          const int st = g_slot(k);
          uint32_t a[3];
#pragma unroll
          for (int th = 0; th < 3; th++) a[th] = __shfl_sync(0xffffffffu, xa, 3 * (k >> 1) + th) ^ ((k & 1) * 0x21000);
          const uint32_t w = __shfl_sync(0xffffffffu, wa, k);
          if ((A_ACQ >> k) & 1) {
            mbar_wait(acq0 + 8 * __popc(A_ACQ & ((1 << k) - 1)), 0);
            asm volatile("fence.proxy.async.global;" ::: "memory");
          }
          mbar_wait(empty0 + 8 * st, (G_PAR >> k) & 1);
          if (lane == 0) {
            const uint32_t base = sb + st * G_STAGE, bar = full0 + 8 * st;
            mbar_expect(bar, G_STAGE);
#pragma unroll
            for (int th = 0; th < 3; th++)
              asm volatile("cp.async.bulk.shared::cluster.global.mbarrier::complete_tx::bytes.multicast::cluster.L2::cache_hint [%0], [%1], %2, [%3], %4, %5;"
                           ::"r"(base + 16384 + hf * G_XP + th * 3584), "l"(x1 + a[th]), "n"(3584), "r"(bar), "h"((uint16_t)3), "l"(policy<1>()) : "memory");
            if (k >= G_WPOLK) tma_ld3<1>(base, &m.w, bar, 0, (w >> 7) & 127, w >> 14);
            else tma_ld3<0>(base, &m.w, bar, 0, (w >> 7) & 127, w >> 14);
          }
          __syncwarp();
        }
        if (blk == 0 && lane == 0) asm volatile("cp.async.bulk.prefetch.L2.global [%0], 14336;" ::"l"(img) : "memory");
      }
    } else if (pin(warp) == 1) {
      if (lane == 0) {
        prefetch_map(&m.ws);
        prefetch_map(&m.xs);
        prefetch_map(&m.in[0]);
        prefetch_map(&m.in[3]);
      }
      __syncwarp();
      asm volatile("barrier.cluster.wait.aligned;" ::: "memory");
      if (lane == 0) {
#pragma unroll 1
        for (int r = spare; r < A_NREL; r++) {
          mbar_wait(rel0 + 8 * r, 0);
          asm volatile("fence.acq_rel.gpu;\nred.relaxed.gpu.global.inc.u32 [%0], 0xffffffff;" ::"l"(cnt + 8 + r) : "memory");
        }
      }
    } else if (warp == 2) {
      asm volatile("barrier.cluster.wait.aligned;" ::: "memory");
      const uint32_t relm = spare ? A_RELS : A_REL;
      const int xr = __popc(xm & ((1 << lane) - 1));
      const uint32_t srcs = sb + a_out(lane), bars = aof0 + 8 * (lane % A_NOUT);
      const uint32_t done = lane < 16 ? bars + 8 * A_NOUT : se0 + 8 * (lane & 1), relb = rel0 + 8 * (spare + __popc(relm & ((1 << lane) - 1)));
      const int cta = role(), xc = x_decode(xr, cta), q = xc & 127, th = q / 28, wi = lane < 2 ? blk : w_unit(cta);
      int code = (xm >> lane) & 1 ? 0x80000000u + x1_addr(((xc >> 7) * 3 + th) * 8, (cta >> 1) & 1, 0) + (q - 28 * th) * 128
                                  : w_addr(7 - lane + xr, 0, wi >> 1, wi & 1, 0);
      uint32_t fl = 0;
      auto tables = [&]() {
        fl = flips();
        code ^= ((fl >> (((code >> 21) & 15) + (code < 0 ? 0 : 12))) & 1) << 12;
      };
      if (spare) tables();
      uint32_t tnext = clock(), src = __shfl_sync(0xffffffffu, srcs, 0), bar = aof0;
      int c = __shfl_sync(0xffffffffu, code, 0);
      mbar_wait(bar, 0);
#pragma unroll 1
      for (int n = 0; n < nu; n++) {
        while ((int)(clock() - tnext) < 0);
        tnext = clock() + (spare ? 0 : n < A_PACE_N ? A_PACE0 : A_PACE1);
        if (lane == n) {
          if (c >= 0) {
            w_store(&m.ws, src, c);
          } else {
#pragma unroll
            for (int j = 0; j < 8; j++)
              tma_st4<0>(&m.xs, src + j * 2048, ((c & 16383) >> 1) ^ ((__popc(j) & 1) << 11) ^ ((j & 1) << 12), (j >> 1) << 2, (c >> 18) & 3, (c >> 20) & 31);
          }
          bulk_commit();
        }
        __syncwarp();
        if (n == 1 && !spare) tables();
        c = __shfl_sync(0xffffffffu, code, n + 1);
        src = __shfl_sync(0xffffffffu, srcs, n + 1);
        bar = __shfl_sync(0xffffffffu, bars, n + 1);
        if (n + 1 < nu) mbar_wait(bar, (n + 1 >= A_NOUT) ^ (n + 1 >= 2 * A_NOUT));
        bulk_wait<0>();
        if (lane == n) {
          mbar_arrive(done);
          if ((relm >> lane) & 1) mbar_arrive(relb);
        }
        __syncwarp();
        if (!spare && (n == 13 || n == 15) && lane < 16) mbar_arrive_cta(empty0 + 8 * ((n - 7) >> 1), lane & 1);
      }
      if (!spare) {
        const int i = w_unit(cta), wc = w_code(1, 5 - lane, i);
        const uint32_t wa = w_addr(7 + W_SHIFT - lane, 0, i >> 1, i & 1, fl);
#pragma unroll 1
        for (int it = 0; it < 8; it++) {
          const uint32_t a = __shfl_sync(0xffffffffu, wa, it), j = it & 1;
          const int c2 = __shfl_sync(0xffffffffu, wc, it);
          mbar_wait(sf0 + 8 * j, (it >> 1) & 1);
          if (lane == 0 && it < 6) {
            mbar_expect(inf0 + 8 * j, 4096);
            in_load(c2, sb + G_TIN + j * 4096, inf0 + 8 * j);
          }
          if (it >= W_SHIFT) mbar_wait(got0 + 8 * (it - W_SHIFT), 0);
          if (lane == 0) {
            w_store(&m.ws, sb + G_TOUT + j * A_OUT, a);
            bulk_commit();
            bulk_wait_read<0>();
            mbar_arrive(se0 + 8 * j);
          }
          __syncwarp();
        }
      }
    } else {
      int side;
      bar_sync(9, 288);
      const int near = min(lat[0], lat[2]) > min(lat[1], lat[3]);
      if (lane == 0 && voter)
        asm volatile("red.relaxed.gpu.global.add.s32 [%0], %1;" ::"l"(cnt + 32 + page), "r"(256 + (near ^ (min(lat[4], lat[6]) > min(lat[5], lat[7])))) : "memory");
      __syncwarp();
      asm volatile("barrier.cluster.wait.aligned;" ::: "memory");
      const uint32_t fl = read_votes(cnt, lane, side, votes);
      if (lane == 0) {
        s_flips = fl;
        mbar_arrive(flipb);
        uint32_t smid;
        asm("mov.u32 %0, %%smid;" : "=r"(smid));
        if (near) asm volatile("red.relaxed.gpu.global.or.b32 [%0], %1;" ::"l"(cnt + 56 + (smid >> 5) % 6), "r"(1 << (smid & 31)) : "memory");
      }
      __syncwarp();
      if (!spare) {
        bool open = lane < 8 - W_SHIFT || (lane >= 8 && lane < 8 + A_NREL);
        int k = 0;
        mbar_wait(rel0, 0);
#pragma unroll 1
        for (int p = 0; p < (1 << 16) && (k < 14 || __any_sync(0xffffffffu, open)); p++) {
          int v;
          asm volatile("ld.relaxed.gpu.global.s32 %0, [%1];" : "=r"(v) : "l"(cnt + (lane & 15)) : "memory");
          while (k < 14 && mbar_test(full0 + 8 * g_slot(k), (G_PAR >> k) & 1)) {
            if (lane == 0) mbar_arrive(empty0 + 8 * g_slot(k));
            if ((k & 1) && lane == 0) asm volatile("red.relaxed.gpu.global.inc.u32 [%0], 0xffffffff;" ::"l"(cnt + (k >> 1)) : "memory");
            k++;
          }
          if (open && v >= (lane <= 8 ? 128 : 132)) {
            asm volatile("fence.acquire.gpu;" ::: "memory");
            mbar_arrive(got0 + 8 * lane);
            open = false;
          }
        }
      }
    }
  } else {
    if (lane == 0) {
      const int w8 = 4 * wg + warp;
      for (int i = 0; i < 2; i++) {
        mbar_init(xf0 + 16 * w8 + 8 * i, 1);
        mbar_expect(xf0 + 16 * w8 + 8 * i, A_IN);
      }
      mbar_init(got0 + 8 * w8, 1);
      if (w8 >= 8 - A_NREL) mbar_init(acq0 + 8 * (7 - w8), 1);
      if (w8 < G_NST) {
        mbar_init(full0 + 8 * w8, 1);
        mbar_init(empty0 + 8 * w8, 17);
        mbar_arrive(empty0 + 8 * w8);
      }
      fence_bar_init();
    }
    __syncwarp();
    asm volatile("barrier.cluster.arrive.relaxed.aligned;" ::: "memory");
    if (wg == 1) tab[t] = __bfloat16_as_ushort(__float2bfloat16_rn(-__cosf((float)(t - 64) * 0.04908738521234052f)));
    bar_sync(1, 256);
    asm volatile("setmaxnreg.inc.sync.aligned.u32 232;");
    uint32_t fa[16];
    auto frag = [&](int i, int l) {
      const int f = warp * 16 + (l >> 2) + 8 * (i & 1), r = 8 * (i >> 1) + (l & 3) * 2;
      const int k0 = (f | 1) * r - ((f & 1) << 5);
      return tab[k0 & 127] | ((uint32_t)tab[(k0 + (f | 1)) & 127] << 16);
    };
#pragma unroll
    for (int i = 0; i < 16; i++) fa[i] = i < 4 ? frag(i, lane) : 0;
    reg_fence(fa);
    asm volatile("barrier.cluster.wait.aligned;" ::: "memory");
    int cta = blk, qs = 0;
#pragma unroll 1
    for (int n = wg; n < nu; n += 2) {
      float e[64];
      if ((n >> 1) == !spare) {
        pdl_launch();
        int l = lane;
        asm volatile("" : "+r"(l));
#pragma unroll
        for (int i = 4; i < 16; i++) fa[i] = frag(i, l);
        reg_fence(fa);
        cta = role();
        qs = ((cta >> 1) & 2) + hf;
      }
      if (spare) qs = n < 8 ? n & 3 : 2 * hf + wg;
      const bool isx = (xm >> n) & 1;
      const int r = __popc(xm & ((1 << n) - 1)), s = 7 - n + r;
      const uint32_t in = isx ? sb + (r % A_NIN) * A_IN : sb + 2 * G_STAGE + s * 4096;
      mbar_wait(isx ? xf0 + 8 * r : wf0 + 8 * (s >> 1), 0);
      if (!isx) {
        wg_fence();
        wgmma_rs_128<1, 1, 1>(e, fa[0], fa[1], fa[2], fa[3], mk_desc(in, 0, 2048, 1024, 1), 0);
        wg_commit();
      } else {
        wg_fence();
#pragma unroll
        for (int k = 0; k < 4; k++)
          wgmma_rs_128<1, 1, 1>(e, fa[4 * k], fa[4 * k + 1], fa[4 * k + 2], fa[4 * k + 3], mk_desc(in, k * 2048, 6144, 1024, 1), k);
        wg_commit();
      }
      wg_wait<0>();
      reg_fence(e);
      if (isx && lane == 0) mbar_arrive(xe0 + 8 * (r % A_NIN));
      if (((A_FREE >> n) & 1) && !spare && lane < 2) mbar_arrive_cta(empty0 + 8 * (__popc(A_FREE & ((1 << n) - 1)) >> 1), lane);
      if (n >= A_NOUT) mbar_wait(aoe0 + 8 * (n % A_NOUT), (n / A_NOUT - 1) & 1);
      const int row = warp * 16 + (lane & 7) + ((lane >> 3) & 1) * 8, hi = lane >> 4;
      const uint32_t rb = sb + a_out(n) + (isx ? row : row + (row & ~7)) * 128, ts = isx ? 8192 : 1024, xr = (lane & 7) ^ (isx ? qs : 0);
#pragma unroll
      for (int j = 0; j < 16; j += 2) {
        const uint32_t tile = isx ? (j >> 2) & 1 : j >> 3, pos = (isx ? (j >> 3) * 4 + (j & 3) : (j & 7)) + hi;
        stsm4(rb + tile * ts + ((pos ^ xr) << 4), pack2(e[4 * j], e[4 * j + 1]), pack2(e[4 * j + 2], e[4 * j + 3]),
              pack2(e[4 * j + 4], e[4 * j + 5]), pack2(e[4 * j + 6], e[4 * j + 7]));
      }
      fence_async();
      __syncwarp();
      if (lane == 0) mbar_arrive(aof0 + 8 * (n % A_NOUT));
    }
    if (spare) {
      float* sg = reinterpret_cast<float*>(smem_raw + (sb - s2u(smem_raw)));
      __nv_bfloat16* sw = reinterpret_cast<__nv_bfloat16*>(sg + 16 * 256);
      const int c0 = (cta - 128) * 64;
      uint4 vw[8], vg[2];
#pragma unroll
      for (int i = 0; i < 8; i++) vw[i] = __ldg(reinterpret_cast<const uint4*>(wgt + ((i * 256 + tid) >> 3) * 256 + c0 + (tid & 7) * 8));
#pragma unroll
      for (int i = 0; i < 2; i++) vg[i] = __ldg(reinterpret_cast<const uint4*>(g) + i * 256 + tid);
      bar_sync(3, 256);
#pragma unroll
      for (int i = 0; i < 8; i++) reinterpret_cast<uint4*>(sw)[i * 256 + tid] = vw[i];
#pragma unroll
      for (int i = 0; i < 2; i++) {
        const uint32_t w4[4] = {vg[i].x, vg[i].y, vg[i].z, vg[i].w};
#pragma unroll
        for (int e = 0; e < 4; e++) {
          sg[(i * 256 + tid) * 8 + 2 * e] = __uint_as_float(w4[e] << 16);
          sg[(i * 256 + tid) * 8 + 2 * e + 1] = __uint_as_float(w4[e] & 0xffff0000u);
        }
      }
      bar_sync(3, 256);
      const int col = tid & 63, r0 = (tid >> 6) * 4;
      float a0 = 0.f, a1 = 0.f, a2 = 0.f, a3 = 0.f;
#pragma unroll 8
      for (int k = 0; k < 256; k++) {
        const float w = __bfloat162float(sw[k * 64 + col]);
        a0 = fmaf(sg[(r0 + 0) * 256 + k], w, a0);
        a1 = fmaf(sg[(r0 + 1) * 256 + k], w, a1);
        a2 = fmaf(sg[(r0 + 2) * 256 + k], w, a2);
        a3 = fmaf(sg[(r0 + 3) * 256 + k], w, a3);
      }
      const int cc = c0 + col;
      const int pos = (cc & ~15) + ((cc >> 1) & 3) * 4 + ((cc >> 3) & 1) * 2 + (cc & 1);
      ge[(r0 + 0) * 256 + pos] = __bfloat162float(__float2bfloat16_rn(a0));
      ge[(r0 + 1) * 256 + pos] = __bfloat162float(__float2bfloat16_rn(a1));
      ge[(r0 + 2) * 256 + pos] = __bfloat162float(__float2bfloat16_rn(a2));
      ge[(r0 + 3) * 256 + pos] = __bfloat162float(__float2bfloat16_rn(a3));
      return;
    }
    const int b = (cta >> 1) & 1, bin = cta >> 2;
    float d[32];
    auto t_begin = [&](int it, int hh) {
      mbar_wait(inf0 + 8 * (it & 1), (it >> 1) & 1);
      wg_fence();
      wgmma_rs_64<1, 1, 1>(d, fa[0], fa[1], fa[2], fa[3], mk_desc(sb + G_TIN + (it & 1) * 4096 + hh * 2048, 0, 0, 1024, 1), 0);
      wg_commit();
    };
    auto t_end = [&](int it, int hh) {
      reg_fence(d);
      const int j = it & 1;
      mbar_wait(se0 + 8 * j, (it >> 1) & 1);
      store_tile_64<2048>(d, sb + G_TOUT + j * A_OUT + hh * 1024, warp, lane);
      fence_async();
      __syncwarp();
      if (lane == 0) mbar_arrive(sf0 + 8 * j);
    };
    float re[NB1 / 2], im[NB1 / 2];
#pragma unroll 1
    for (int k = 0; k < G_KS; k++) {
      const int st = g_slot(k);
      const int it = __popc(G_TMASK & ((1 << k) - 1));
      const bool T = (G_TMASK >> k) & 1;
      mbar_wait(full0 + 8 * st, (G_PAR >> k) & 1);
      const uint32_t base = sb + st * G_STAGE;
      const uint32_t wb = base + wg * 4096;
      if (T) t_begin(it, wg);
      wg_fence();
#pragma unroll
      for (int s = 0; s < 2; s++) {
        const int acc = (k | s) != 0;
        const uint64_t dP = mk_desc(wb, s * 2048, 0, 1024, 1), dQ = mk_desc(wb, 8192 + s * 2048, 0, 1024, 1);
        const uint64_t dA = mk_desc(base, 16384 + s * 32, 0, 512, 2), dB = mk_desc(base, 16384 + G_XP + s * 32, 0, 512, 2);
        wgmma_ss_168<1, 1, 1, 0>(re, dP, dA, acc);
        wgmma_ss_168<1, 1, 1, 0>(im, dP, dB, acc);
        wgmma_ss_168<1, 1, 1, 0>(re, dQ, dB, 1);
        wgmma_ss_168<-1, 1, 1, 0>(im, dQ, dA, 1);
      }
      wg_commit();
      wg_wait<1>();
      if (k > 0 && lane < 2) mbar_arrive_cta(empty0 + 8 * g_slot(k - 1), lane);
      if (T) t_end(it, wg);
    }
    auto tail = [&](auto part, bool wait) {
      constexpr int PART = decltype(part)::value;
#pragma unroll
      for (int k = G_KS; k < 16; k++) {
        if (wait) mbar_wait(full0 + 8 * g_slot(k), (G_PAR >> k) & 1);
        const uint32_t base = sb + g_slot(k) * G_STAGE, wb = base + wg * 4096;
        wg_fence();
#pragma unroll
        for (int s = 0; s < 2; s++) {
          const uint64_t dP = mk_desc(wb, s * 2048, 0, 1024, 1), dQ = mk_desc(wb, 8192 + s * 2048, 0, 1024, 1);
          const uint64_t dA = mk_desc(base, 16384 + s * 32, 0, 512, 2), dB = mk_desc(base, 16384 + G_XP + s * 32, 0, 512, 2);
          if (PART == 0) {
            wgmma_ss_168<1, 1, 1, 0>(re, dP, dA, 1);
            wgmma_ss_168<1, 1, 1, 0>(re, dQ, dB, 1);
          } else {
            wgmma_ss_168<1, 1, 1, 0>(im, dP, dB, 1);
            wgmma_ss_168<-1, 1, 1, 0>(im, dQ, dA, 1);
          }
        }
      }
      wg_commit();
    };
    auto put = [&](const float (&v)[NB1 / 2], uint32_t stg, int f) {
      const int mi = lane >> 3, i = lane & 7;
      const uint32_t a0 = stg + (mi >> 1) * 1024 + i * 128 + (((2 * warp + (mi & 1)) ^ i) << 4);
      const uint32_t ya = x1_addr(96 + 8 * lane + 4 * hf + 2 * wg + (f >> 5), b, s_flips) + (f & 31) * 128;
#pragma unroll
      for (int c = 0; c < 3; c++) {
#pragma unroll
        for (int j = 8 * c; j < 8 * c + 8 && j < 20; j += 2)
          stsm4t(a0 + j * 1024, pack2(v[4 * j], v[4 * j + 1]), pack2(v[4 * j + 2], v[4 * j + 3]),
                 pack2(v[4 * j + 4], v[4 * j + 5]), pack2(v[4 * j + 6], v[4 * j + 7]));
        if (c == 2)
          asm volatile("stmatrix.sync.aligned.m8n8.x2.trans.shared.b16 [%0], {%1, %2};" ::"r"(a0 + 20 * 1024),
                       "r"(pack2(v[80], v[81])), "r"(pack2(v[82], v[83])) : "memory");
        const uint32_t a = __shfl_sync(0xffffffffu, ya, 4 * c + warp);
        fence_async();
        bar_sync(2 + wg, 128);
        if (lane == 0 && (c < 2 || warp < 3)) {
          tma_st4<0>(c == 2 && warp == 2 ? &m.y : &m.xs, stg + (4 * c + warp) * 2048, (a & 16383) >> 1, (a >> 14) & 15, (a >> 18) & 3, a >> 20);
          bulk_commit();
        }
      }
    };
    if (wg == 0) {
      tail(std::integral_constant<int, 0>(), true);
      bar_arrive(4, 256);
      bar_sync(5, 256);
      wg_wait<0>();
      reg_fence(re);
      put(re, sb + 4 * G_STAGE, 2 * bin);
      bar_sync(7, 256);
      tail(std::integral_constant<int, 1>(), false);
      bar_arrive(8, 256);
      wg_wait<0>();
      reg_fence(im);
      bar_arrive(6, 256);
      put(im, sb + 4 * G_STAGE + NB1 * 128, 2 * bin + 1);
    } else {
#pragma unroll 1
      for (int h2 = 2 * __popc(G_TMASK); h2 < 16; h2++) {
        t_begin(h2 >> 1, h2 & 1);
        wg_wait<0>();
        t_end(h2 >> 1, h2 & 1);
      }
      wg_wait<0>();
      bar_arrive(5, 256);
      bar_sync(4, 256);
      tail(std::integral_constant<int, 0>(), true);
      bar_arrive(7, 256);
      mbar_wait(se0, 0);
      mbar_wait(se0 + 8, 0);
      wg_wait<0>();
      reg_fence(re);
      put(re, sb + G_TOUT, 2 * bin);
      bar_sync(8, 256);
      tail(std::integral_constant<int, 1>(), false);
      wg_wait<0>();
      reg_fence(im);
      bar_sync(6, 256);
      put(im, sb, 2 * bin + 1);
    }
    bulk_wait_read<0>();
  }
}

#define G_WPRE 2
#define H_EPI 3
#define H_KS 11
constexpr int H_XP = 168 * 64, H_STAGE = 8192 + 2 * H_XP, H_NST = 7, H_SMEM = H_NST * H_STAGE + 21504 + 1024;

template <int WG>
__device__ __forceinline__ void h_loop(float (&acc)[84], uint32_t sb, uint32_t full0, uint32_t empty0, int lane) {
#pragma unroll 1
  for (int k = 0; k < 16; k++) {
    const int st = k % H_NST;
    if (WG == 1 && k == H_KS) bar_sync(4, 256);
    mbar_wait(full0 + 8 * st, (k / H_NST) & 1);
    const uint32_t base = sb + st * H_STAGE;
    wg_fence();
#pragma unroll
    for (int s = 0; s < 2; s++) {
      const uint64_t dP = mk_desc(base, s * 2048, 0, 1024, 1), dQ = mk_desc(base, 4096 + s * 2048, 0, 1024, 1);
      const uint64_t dA = mk_desc(base, 8192 + s * 32, 0, 512, 2), dB = mk_desc(base, 8192 + H_XP + s * 32, 0, 512, 2);
      wgmma_ss_168<1, 1, 1, 0>(acc, dP, WG == 0 ? dA : dB, k | s);
      wgmma_ss_168<WG == 0 ? 1 : -1, 1, 1, 0>(acc, dQ, WG == 0 ? dB : dA, 1);
    }
    wg_commit();
    if (WG == 0 && k == 15) bar_arrive(4, 256);
    if (k <= 10) {
      wg_wait<1>();
      if (k > 0 && k - 1 + H_NST < 16 && lane < 2) mbar_arrive_cta(empty0 + 8 * ((k - 1) % H_NST), lane);
    }
  }
  wg_wait<0>();
  reg_fence(acc);
}

__global__ void __cluster_dims__(2, 1, 1) __launch_bounds__(288, 1)
kH(int* __restrict__ cnt, const __nv_bfloat16* __restrict__ wf, const __nv_bfloat16* __restrict__ wo, const uint32_t* __restrict__ gat,
   const __grid_constant__ CUtensorMap mx, const __grid_constant__ CUtensorMap mw, const __grid_constant__ CUtensorMap my) {
  extern __shared__ uint8_t smem_raw[];
  __shared__ __align__(8) uint64_t bars[2 * H_NST];
  const uint32_t sb = pin((s2u(smem_raw) + 1023) & ~1023u);
  const int tid = threadIdx.x, wg = __shfl_sync(0xffffffffu, tid >> 7, 0), t = tid & 127;
  const int warp = __shfl_sync(0xffffffffu, t >> 5, 0), lane = t & 31;
  __shared__ __align__(8) uint64_t role_bar;
  __shared__ uint32_t s_role;
  const int rank = blockIdx.x & 1;
  const uint32_t full0 = pin(s2u(&bars[0])), empty0 = full0 + 8 * H_NST, roleb = s2u(&role_bar);
  pdl_launch();
  if (tid == 32) {
    for (int i = 0; i < H_NST; i++) {
      mbar_init(full0 + 8 * i, 1);
      mbar_init(empty0 + 8 * i, 16);
    }
    mbar_init(roleb, 1);
    mbar_expect(roleb, 4);
    fence_bar_init();
    fence_async();
  } else if (tid == 64) {
    prefetch_map(&mw);
    prefetch_map(&mx);
    prefetch_map(&my);
  }
  __syncwarp();
  asm volatile("barrier.cluster.arrive.relaxed.aligned;" ::: "memory");
  uint32_t fl = 0;
  int ticket = 0;
  if (warp == 0 && wg != 1) {
    int side;
    fl = read_votes(cnt, lane, side);
    if (tid == 256 && rank == 0) ticket = 2 * take_ticket(cnt + 66 + side) + side;
    __syncwarp();
  }
  asm volatile("barrier.cluster.wait.aligned;" ::: "memory");
  if (tid == 256 && rank == 0) send_role(s2u(&s_role), roleb, ticket < 64 ? ticket : 127 - ticket);
  __syncwarp();
  mbar_wait(roleb, 0);
  __syncwarp();
  const int cta = 2 * *(volatile uint32_t*)&s_role + rank, dc = cta & 3, bin = cta >> 2;
  const uint32_t wa = w_addr((lane >> 1) + W_SHIFT, 2 * bin, (lane & 1) * 32, dc >> 1, fl) + (rank << 14);
  if (wg == 0 && warp == 0) {
#pragma unroll
    for (int k = 0; k < G_WPRE; k++) {
      const uint32_t w = __shfl_sync(0xffffffffu, wa, k);
      if (lane == 0) tma_ld3<1>(sb + k * H_STAGE, &mw, full0 + 8 * k, 0, (w >> 7) & 255, w >> 15);
    }
    __syncwarp();
  }
  if (wg == 2) {
    if (lane < H_NST) mbar_expect(full0 + 8 * lane, H_STAGE);
    pdl_wait();
    int st = 0;
#pragma unroll 1
    for (int k = 0; k < 16; k++) {
      const uint32_t w = __shfl_sync(0xffffffffu, wa, k);
      if (k >= H_NST) mbar_wait(empty0 + 8 * st, k >= 2 * H_NST);
      if (lane == 0) {
        const uint32_t base = sb + st * H_STAGE, bar = full0 + 8 * st;
        if (k >= H_NST) mbar_expect(bar, H_STAGE);
        tma_ld3mc<0>(base + 8192 + rank * H_XP, &mx, bar, (k & 1) * 32, 0, (k >> 1) * 64 + 2 * bin + rank);
        if (k >= G_WPRE) tma_ld3<1>(base, &mw, bar, 0, (w >> 7) & 255, w >> 15);
        if (k == H_NST - 1) {
          if (cta == 0) asm volatile("cp.async.bulk.prefetch.L2.global [%0], 6144;" ::"l"(gat) : "memory");
          asm volatile("cp.async.bulk.prefetch.L2.global [%0], 1024;" ::"l"(wf + cta * 512) : "memory");
          asm volatile("cp.async.bulk.prefetch.L2.global [%0], 1024;" ::"l"(wo + cta * 512) : "memory");
        }
      }
      __syncwarp();
      if (++st == H_NST) st = 0;
    }
  } else {
    float acc[84];
    if (wg == 0) {
      h_loop<0>(acc, sb, full0, empty0, lane);
    } else {
      h_loop<1>(acc, sb, full0, empty0, lane);
      bar_sync(3, 128);
    }
    const uint32_t stg = sb + (wg == 0 ? H_NST : 9 % H_NST) * H_STAGE;
    const int mi = lane >> 3, i = lane & 7;
    const uint32_t a0 = stg + (mi >> 1) * 1024 + i * 128 + (((2 * warp + (mi & 1)) ^ i) << 4);
    constexpr int J = 21 / H_EPI;
#pragma unroll
    for (int c = 0; c < H_EPI; c++) {
#pragma unroll
      for (int j = c * J; j + 1 < (c + 1) * J; j += 2)
        stsm4t(a0 + j * 1024, pack2(acc[4 * j], acc[4 * j + 1]), pack2(acc[4 * j + 2], acc[4 * j + 3]),
               pack2(acc[4 * j + 4], acc[4 * j + 5]), pack2(acc[4 * j + 6], acc[4 * j + 7]));
      const int j = (c + 1) * J - 1;
      asm volatile("stmatrix.sync.aligned.m8n8.x2.trans.shared.b16 [%0], {%1, %2};" ::"r"(a0 + j * 1024),
                   "r"(pack2(acc[4 * j], acc[4 * j + 1])), "r"(pack2(acc[4 * j + 2], acc[4 * j + 3])) : "memory");
      fence_async();
      bar_sync(2 + wg, 128);
      if (t == 0) {
        tma_st4<0>(&my, stg + c * J * 1024, 0, c * J * 8, 2 * bin + wg, dc);
        bulk_commit();
      }
    }
    if (t == 0) {
      bulk_wait_read<0>();
    }
  }
}

#define C_TOK 1
constexpr int C_OUT = 13 * 8192, C_GI = C_OUT + 6 * 16384, C_F = C_GI + 6144;
constexpr int C_SMEM = C_F + 8192 + 1024;

template <int NC> __device__ __forceinline__ void gelu_pack(uint32_t (&hp)[32], const float (&h)[4 * NC], int rc0, bool zero_first, bool zero_all) {
#pragma unroll
  for (int c = 0; c < NC; c++) {
    const uint32_t lo = pack2(gelu(h[4 * c]), gelu(h[4 * c + 1])), hi = pack2(gelu(h[4 * c + 2]), gelu(h[4 * c + 3]));
    const bool z = zero_all || (zero_first && c < 2);
    hp[(c & 1) * 16 + (rc0 + (c >> 1)) * 2] = z ? 0u : lo;
    hp[(c & 1) * 16 + (rc0 + (c >> 1)) * 2 + 1] = z ? 0u : hi;
  }
}

__global__ void __launch_bounds__(512, 1)
kC(int* __restrict__ ctr, const uint32_t* __restrict__ img, const __grid_constant__ CUtensorMap my0, const __grid_constant__ CUtensorMap my1, const __grid_constant__ CUtensorMap mxs) {
  extern __shared__ uint8_t smem_raw[];
  __shared__ __align__(8) uint64_t bars[14];
  __shared__ int s_role;
  const uint32_t sb = pin((s2u(smem_raw) + 1023) & ~1023u);
  const int tid = threadIdx.x, wg = __shfl_sync(0xffffffffu, tid >> 7, 0), t = tid & 127, warp = t >> 5, lane = t & 31;
  const bool loader = __shfl_sync(0xffffffffu, tid >> 5, 0) == 15;
  const uint32_t sGi = sb + C_GI, sF = sb + C_F, barc = pin(s2u(&bars[0]));
  uint32_t fl = 0;
  if (loader) {
    int side;
    fl = read_votes(ctr, lane, side);
    if (lane == 0) {
      const int ticket = 2 * take_ticket(ctr + 64 + side) + side;
      s_role = ticket < 128 ? ticket : 255 - ticket;
    }
  } else if (tid == 384) {
    prefetch_map(&my0);
    prefetch_map(&my1);
    for (int i = 0; i < 14; i++) mbar_init(barc + 8 * i, 1);
    fence_bar_init();
    fence_async();
    mbar_expect(barc + 8 * 13, 14336);
    asm volatile("cp.async.bulk.shared::cluster.global.mbarrier::complete_tx::bytes [%0], [%1], 14336, [%2];"
                 ::"r"(sGi), "l"(img), "r"(barc + 8 * 13) : "memory");
  }
  __syncthreads();
  const int b = s_role & 1, cs = (s_role >> 1) & 3, j = s_role >> 3;
  const int n0 = 5 * j + min(j, 4), cnt = j < 4 ? 6 : 5;
  if (loader) {
    const int blk = min(2 * n0 + lane, NB1 - 1);
    const uint32_t ya = x1_addr(96 + 8 * (blk >> 4) + 2 * cs, b, fl) + spread16(blk);
    if (lane <= 2 * cnt) mbar_expect(barc + 8 * lane, 8192);
    pdl_wait();
#pragma unroll 1
    for (int i = 0; i <= 2 * cnt; i++) {
      const uint32_t a = __shfl_sync(0xffffffffu, ya, i);
      if (lane == 0) tma_ld3<1>(sb + i * 8192, (a & 4096) ? &my1 : &my0, barc + 8 * i, 0, a >> 7, 0);
      __syncwarp();
    }
    pdl_launch();
    if (lane == 0) prefetch_map(&mxs);
  }
  mbar_wait(barc + 8 * 13, 0);
#pragma unroll 1
  for (int i = wg; i < cnt; i += 4) {
    const int n2 = n0 + i;
    const uint32_t in = sb + i * 16384, bar = barc + i * 16, outb = sb + C_OUT + i * 16384;
    float h0[24], h1[24], h2[16];
    uint32_t hp[32];
    mbar_wait(bar, 0);
    wg_fence();
#pragma unroll
    for (int k = 0; k < 4; k++) wgmma_ss_48<1, 1, 1, 0>(h0, mk_desc(in, k * 2048, 0, 1024, 1), mk_desc(sGi, k * 32, 0, 1024, 1), k);
    wg_commit();
    mbar_wait(bar + 8, 0);
    wg_fence();
#pragma unroll
    for (int k = 0; k < 4; k++) wgmma_ss_48<1, 1, 1, 0>(h1, mk_desc(in, 8192 + k * 2048, 0, 1024, 1), mk_desc(sGi, k * 32, 0, 1024, 1), k);
    wg_commit();
    if (C_TOK && i > 0) bar_sync(5 + wg, 256);
    wg_wait<1>();
    reg_fence(h0);
    gelu_pack<6>(hp, h0, 0, n2 == 0, false);
    mbar_wait(bar + 16, 0);
    wg_fence();
#pragma unroll
    for (int k = 0; k < 4; k++) wgmma_ss_32<1, 1, 1, 0>(h2, mk_desc(in, 16384 + k * 2048, 0, 1024, 1), mk_desc(sGi, k * 32, 0, 1024, 1), k);
    wg_commit();
    if (C_TOK == 1 && i + 1 < cnt) bar_arrive(5 + ((wg + 1) & 3), 256);
    wg_wait<1>();
    reg_fence(h1);
    gelu_pack<6>(hp, h1, 3, false, n2 == NB2 - 1);
    if (C_TOK == 2 && i + 1 < cnt) bar_arrive(5 + ((wg + 1) & 3), 256);
    wg_wait<0>();
    reg_fence(h2);
    gelu_pack<4>(hp, h2, 6, false, n2 == NB2 - 1);
    float e0[32], e1[32];
    reg_fence(hp);
    if (C_TOK == 3 && i + 1 < cnt) bar_arrive(5 + ((wg + 1) & 3), 256);
    wg_fence();
#pragma unroll
    for (int k = 0; k < 4; k++) {
      const uint64_t db = mk_desc(sF, k * 32, 0, 1024, 1);
      wgmma_rs_64<1, 1, 0>(e0, hp[4 * k], hp[4 * k + 1], hp[4 * k + 2], hp[4 * k + 3], db, k);
      wgmma_rs_64<1, 1, 0>(e1, hp[16 + 4 * k], hp[16 + 4 * k + 1], hp[16 + 4 * k + 2], hp[16 + 4 * k + 3], db, k);
    }
    wg_commit();
    wg_wait<0>();
    reg_fence(e0);
    reg_fence(e1);
    {
      const int mi = lane >> 3, r = lane & 7;
      const uint32_t a0 = outb + (mi >> 1) * 8192 + r * 128 + (((2 * warp + (mi & 1)) ^ r) << 4);
#pragma unroll
      for (int q = 0; q < 8; q++)
        stsm4t(a0 + q * 1024, pack2(e0[4 * q], e0[4 * q + 1]), pack2(e0[4 * q + 2], e0[4 * q + 3]),
               pack2(e1[4 * q], e1[4 * q + 1]), pack2(e1[4 * q + 2], e1[4 * q + 3]));
    }
    fence_async();
    bar_sync(1 + wg, 128);
    if (t == 0) {
      tma_st3<0>(&mxs, outb, 0, cs * 64, b * NB2 + n2);
      tma_st3<0>(&mxs, outb + 8192, 0, (4 + cs) * 64, b * NB2 + n2);
      bulk_commit();
    }
  }
  if (t == 0) bulk_wait_read<0>();
}

#define E_WPRE 2
#define E_EARLY0 2
#define E_CHUNK 1
#define E_EARLY 2
constexpr int E_SMEM = 65536 + 131072 + 32768 + 1024;

__device__ __forceinline__ uint32_t joint2(uint32_t fe, uint32_t g0, uint32_t g1) {
  uint32_t s0, s1;
  asm("{\n.reg .b16 l, h;\n.reg .b32 ll;\nmov.b32 {l, h}, %2;\nmov.b32 ll, {l, l};\n"
      "fma.rn.bf16x2 %0, ll, %5, %3;\nfma.rn.bf16x2 %1, %2, %5, %4;\n}"
      : "=r"(s0), "=r"(s1) : "r"(fe), "r"(g0), "r"(g1), "r"(0x3F800000u));
  return pack2(tanh_f32(__uint_as_float(s0)), tanh_f32(__uint_as_float(s1)));
}
__device__ __forceinline__ uint4 lds128(uint32_t a) {
  uint4 v;
  asm volatile("ld.shared.v4.u32 {%0, %1, %2, %3}, [%4];" : "=r"(v.x), "=r"(v.y), "=r"(v.z), "=r"(v.w) : "r"(a));
  return v;
}
__device__ __forceinline__ void joint_group(uint32_t (&ja)[8], const uint32_t* fe, uint4& g0, uint4& g1, uint32_t gnext) {
  const uint4 c0 = g0, c1 = g1;
  g0 = lds128(gnext);
  g1 = lds128(gnext + 64);
  ja[0] = joint2(fe[0], c0.x, c0.y);
  ja[1] = joint2(fe[1], c0.x, c0.y);
  ja[2] = joint2(fe[2], c0.z, c0.w);
  ja[3] = joint2(fe[3], c0.z, c0.w);
  ja[4] = joint2(fe[4], c1.x, c1.y);
  ja[5] = joint2(fe[5], c1.x, c1.y);
  ja[6] = joint2(fe[6], c1.z, c1.w);
  ja[7] = joint2(fe[7], c1.z, c1.w);
  reg_fence(ja);
}

__global__ void __launch_bounds__(256, 1)
kE(int* __restrict__ cnt, const uint32_t* __restrict__ gat, const float* __restrict__ ge, const __grid_constant__ CUtensorMap my, const __grid_constant__ CUtensorMap mwf, const __grid_constant__ CUtensorMap mwo,
   const __grid_constant__ CUtensorMap mout) {
  extern __shared__ uint8_t smem_raw[];
  __shared__ __align__(8) uint64_t bars[13];
  const uint32_t sb = (s2u(smem_raw) + 1023) & ~1023u;
  const int tid = threadIdx.x, wg = __shfl_sync(0xffffffffu, tid >> 7, 0), t = tid & 127, warp = t >> 5, lane = t & 31;
  const uint32_t R0 = sb, R1 = sb + 65536, R2 = sb + 65536 + 131072;
  const uint32_t barY = s2u(&bars[0]), barF = barY + 32, barO = barY + 64, barA = barY + 96;
  const int b = blockIdx.x / 63, t0 = (blockIdx.x % 63) * 64;
  const int a = t0 / 48, o = t0 % 48;
  const int qw = o + 16 * warp, sel = qw >= 48;
  uint32_t ga[16];
#pragma unroll
  for (int s = 0; s < 4; s++)
    ldg128(reinterpret_cast<const uint4*>(gat) + ((qw >> 4) - 3 * sel) * 128 + s * 32 + lane, ga[4 * s], ga[4 * s + 1], ga[4 * s + 2], ga[4 * s + 3]);
  uint4 gev0, gev1;
  asm volatile("ld.global.cg.v4.u32 {%0, %1, %2, %3}, [%4];" : "=r"(gev0.x), "=r"(gev0.y), "=r"(gev0.z), "=r"(gev0.w)
               : "l"(reinterpret_cast<const uint4*>(ge) + (b * 8 + wg * 4) * 64 + t));
  asm volatile("ld.global.cg.v4.u32 {%0, %1, %2, %3}, [%4];" : "=r"(gev1.x), "=r"(gev1.y), "=r"(gev1.z), "=r"(gev1.w)
               : "l"(reinterpret_cast<const uint4*>(ge) + (b * 8 + wg * 4) * 64 + 128 + t));
  if (tid == 0) {
    prefetch_map(&my);
    for (int i = 0; i < 12; i++) mbar_init(barY + 8 * i, 1);
    mbar_init(barA, 8);
    fence_bar_init();
    fence_async();
    for (int i = 0; i < E_WPRE; i++) {
      const int kc = (i >> 1) | ((i & 1) << 1);
      mbar_expect(barF + 8 * kc, 32768);
      tma_ld3<0>(R1 + kc * 32768, &mwf, barF + 8 * kc, 0, kc * 64, 0);
    }
    pdl_wait();
    for (int i = 0; i < 4; i++) {
      mbar_expect(barY + 8 * i, 16384);
      tma_ld5<0>(R0 + i * 16384, &my, barY + 8 * i, 0, 0, 2 * (i & 1) + (i >> 1), a, b);
    }
    for (int i = E_WPRE; i < 4; i++) {
      const int kc = (i >> 1) | ((i & 1) << 1);
      mbar_expect(barF + 8 * kc, 32768);
      tma_ld3<0>(R1 + kc * 32768, &mwf, barF + 8 * kc, 0, kc * 64, 0);
    }
    prefetch_map(&mwo);
    prefetch_map(&mout);
  }
  uint32_t gs[32];
#pragma unroll
  for (int i = 0; i < 16; i++) {
    gs[i] = sel ? 0u : ga[i];
    gs[16 + i] = sel ? ga[i] : 0u;
  }
  __syncthreads();
  if (blockIdx.x == 125 && tid < 96) cnt[tid] = 0;
  reg_fence(gs);
  uint32_t gp = R2 + wg * 4096 + (lane & 3) * 16;
  uint4 g0, g1;
  uint32_t fe[64];
  {
    float d0[32], d1[32], e[64];
    mbar_wait(barY + 8 * wg, 0);
    wg_fence();
#pragma unroll
    for (int k = 0; k < 8; k++)
      wgmma_rs_64<1, 1, 1>(d0, gs[4 * k], gs[4 * k + 1], gs[4 * k + 2], gs[4 * k + 3], mk_desc(R0 + wg * 16384, k * 2048, 0, 1024, 1), k);
    wg_commit();
    wg_wait<0>();
    reg_fence(d0);
#pragma unroll
    for (int i = 0; i < 32; i++) d0[i] = gelu(d0[i]);
    store_tile_64(d0, R2 + wg * 16384, warp, lane);
    mbar_wait(barY + 8 * (2 + wg), 0);
    wg_fence();
#pragma unroll
    for (int k = 0; k < 8; k++)
      wgmma_rs_64<1, 1, 1>(d1, gs[4 * k], gs[4 * k + 1], gs[4 * k + 2], gs[4 * k + 3], mk_desc(R0 + wg * 16384, 32768 + k * 2048, 0, 1024, 1), k);
    wg_commit();
    fence_async();
    mbar_wait(barF, 0);
    mbar_wait(barF + 16, 0);
    __syncthreads();
    wg_fence();
#pragma unroll
    for (int i = 0; i < 8; i++) {
      const int kc = (i >> 2) * 2, s = i & 3;
      wgmma_ss_128<1, 1, 0, 1>(e, mk_desc(R2, kc * 8192 + s * 32, 0, 1024, 1),
                               mk_desc(R1 + wg * 16384, kc * 32768 + s * 2048, 8192, 1024, 1), i);
    }
    wg_commit();
    if (tid == 128) {
      mbar_expect(barO, 32768);
      tma_ld3<0>(R0, &mwo, barO, 0, 0, 0);
    }
    wg_wait<1>();
    reg_fence(d1);
#pragma unroll
    for (int i = 0; i < 32; i++) d1[i] = gelu(d1[i]);
    store_tile_64(d1, R2 + wg * 16384 + 8192, warp, lane);
    fence_async();
    mbar_wait(barF + 8, 0);
    mbar_wait(barF + 24, 0);
    __syncthreads();
    if (tid == 128) {
      mbar_expect(barO + 8, 32768);
      tma_ld3<0>(R0 + 32768, &mwo, barO + 8, 0, 64, 0);
    }
    if (wg == 1) bar_sync(4, 256);
    wg_fence();
#pragma unroll
    for (int i = 0; i < 8; i++) {
      const int kc = (i >> 2) * 2 + 1, s = i & 3;
      wgmma_ss_128<1, 1, 0, 1>(e, mk_desc(R2, kc * 8192 + s * 32, 0, 1024, 1),
                               mk_desc(R1 + wg * 16384, kc * 32768 + s * 2048, 8192, 1024, 1), 1);
    }
    wg_commit();
    if (wg == 0) bar_arrive(4, 256);
    wg_wait<1>();
    if (lane == 0) mbar_arrive(barA);
    if (tid == 128) {
      mbar_wait(barA, 0);
      for (int kc = 2; kc < 4; kc++) {
        mbar_expect(barO + 8 * kc, 32768);
        tma_ld3<0>(R1 + (kc - 2) * 65536, &mwo, barO + 8 * kc, 0, kc * 64, 0);
      }
    }
    mbar_wait(barA, 0);
    asm volatile("st.shared.v4.u32 [%0], {%1, %2, %3, %4};" ::"r"(R2 + wg * 4096 + ((t * 16) ^ (wg * 512))), "r"(gev0.x), "r"(gev0.y), "r"(gev0.z), "r"(gev0.w) : "memory");
    asm volatile("st.shared.v4.u32 [%0], {%1, %2, %3, %4};" ::"r"(R2 + wg * 4096 + 2048 + ((t * 16) ^ (wg * 512))), "r"(gev1.x), "r"(gev1.y), "r"(gev1.z), "r"(gev1.w) : "memory");
    bar_sync(1 + wg, 128);
    g0 = lds128(gp);
    g1 = lds128(gp + 64);
    wg_wait<0>();
    reg_fence(e);
#pragma unroll
    for (int i = 0; i < 32; i++) fe[i] = pack2(e[2 * i], e[2 * i + 1]);
  }
  auto publish = [&]() {
    bar_sync(1 + wg, 128);
    const int row = warp * 16 + (lane & 7) + ((lane >> 3) & 1) * 8;
    const uint32_t xb = R1 + (wg == 0 ? 3 * 32768 : 32768 + 16384) + row * 128;
#pragma unroll
    for (int s = 0; s < 8; s++) {
      const int jj = 2 * s + (lane >> 4);
      stsm4(xb + (s >> 2) * 8192 + (((jj & 7) ^ (lane & 7)) << 4), fe[4 * s], fe[4 * s + 1], fe[4 * s + 2], fe[4 * s + 3]);
    }
    bar_arrive(5 + wg, 256);
  };
  if (wg == 1) publish();
  const uint32_t stg = R1 + 32768 + wg * 65536;
  const uint32_t w0 = sb + wg * 65536, w1 = sb + 32768 + wg * 98304, w2 = sb + 65536 - wg * 65536, w3 = sb + 131072 - wg * 98304;
  float acc[128];
  uint32_t j0[8], j1[8], j2[8], j3[8];
  joint_group(j0, fe, g0, g1, gp + 128);
  mbar_wait(barO + 16 * wg, 0);
  joint_group(j1, fe + 8, g0, g1, gp + 256);
#define E_MMA4(J, K, W, FIRSTK, G, NEXTBAR)                                                     \
  wg_fence();                                                                                   \
  wgmma_rs_256<1, 1, 1>(acc, J[0], J[1], J[2], J[3], mk_desc(W, 0, 8192, 1024, 1), FIRSTK);     \
  wgmma_rs_256<1, 1, 1>(acc, J[4], J[5], J[6], J[7], mk_desc(W, 2048, 8192, 1024, 1), 1);       \
  wgmma_rs_256<1, 1, 1>(acc, K[0], K[1], K[2], K[3], mk_desc(W, 4096, 8192, 1024, 1), 1);       \
  wgmma_rs_256<1, 1, 1>(acc, K[4], K[5], K[6], K[7], mk_desc(W, 6144, 8192, 1024, 1), 1);       \
  wg_commit();                                                                                  \
  if ((ui + wg == 0 ? E_EARLY0 : E_EARLY) == (G) && (ui < 3 || wg == 0)) bar_arrive(4 - wg, 256); \
  wg_wait<1>();                                                                                 \
  if (ui == 0) mbar_wait(NEXTBAR, 0);
  const uint32_t bo0 = barO + 16 * wg, bo2 = barO + 16 * (1 - wg);
#pragma unroll 1
  for (int ui = 0; ui < 4; ui++) {
    if (ui > 0 || wg == 1) bar_sync(3 + wg, 256);
    E_MMA4(j0, j1, w0, 0, 0, bo0)
    joint_group(j2, fe + 16, g0, g1, gp + 384);
    if (ui == 0) mbar_wait(bo0 + 8, 0);
    joint_group(j3, fe + 24, g0, g1, gp + 512);
    E_MMA4(j2, j3, w1, 1, 1, bo0 + 8)
    if (ui == 0) {
      if (wg == 0) publish();
      bar_sync(6 - wg, 256);
      const int row = warp * 16 + (lane & 7) + ((lane >> 3) & 1) * 8;
      const uint32_t xb = R1 + (wg == 1 ? 3 * 32768 : 32768 + 16384) + row * 128;
#pragma unroll
      for (int s = 0; s < 8; s++) {
        const int jj = 2 * s + (lane >> 4);
        ldsm4(xb + (s >> 2) * 8192 + (((jj & 7) ^ (lane & 7)) << 4), fe[32 + 4 * s], fe[33 + 4 * s], fe[34 + 4 * s], fe[35 + 4 * s]);
      }
    }
    joint_group(j0, fe + 32, g0, g1, gp + 640);
    if (ui == 0) mbar_wait(bo2, 0);
    joint_group(j1, fe + 40, g0, g1, gp + 768);
    E_MMA4(j0, j1, w2, 1, 2, bo2)
    joint_group(j2, fe + 48, g0, g1, gp + 896);
    if (ui == 0) mbar_wait(bo2 + 8, 0);
    joint_group(j3, fe + 56, g0, g1, gp + 1024);
    E_MMA4(j2, j3, w3, 1, 3, bo2 + 8)
    gp += 1024;
    if (ui < 3) {
      joint_group(j0, fe, g0, g1, gp + 128);
      if (ui == 0) mbar_wait(bo2 + 8, 0);
      joint_group(j1, fe + 8, g0, g1, gp + 256);
    }
    if (t == 0) bulk_wait_read<0>();
    wg_wait<0>();
    reg_fence(acc);
    bar_sync(1 + wg, 128);
    const uint32_t rb = stg + (warp * 16 + (lane & 7) + ((lane >> 3) & 1) * 8) * 128;
#pragma unroll
    for (int h = 0; h < 2; h++) {
#pragma unroll
      for (int j = 16 * h; j < 16 * h + 16; j += 2) {
        const int jj = j + (lane >> 4);
        stsm4(rb + (j >> 3) * 8192 + (((jj & 7) ^ (lane & 7)) << 4), pack2(acc[4 * j], acc[4 * j + 1]), pack2(acc[4 * j + 2], acc[4 * j + 3]),
              pack2(acc[4 * j + 4], acc[4 * j + 5]), pack2(acc[4 * j + 6], acc[4 * j + 7]));
      }
      const bool split = E_CHUNK == 2 || (E_CHUNK == 1 && ui == 3);
      if (h == 1 || split) {
        fence_async();
        bar_sync(1 + wg, 128);
        if (t == 0) {
          if (h == 1 && !split) tma_st5<1>(&mout, stg, 0, t0, 0, wg * 4 + ui, b);
          tma_st5<1>(&mout, stg + h * 16384, 0, t0, 2 * h, wg * 4 + ui, b);
          bulk_commit();
        }
      }
    }
  }
  if (t == 0) bulk_wait_read<0>();
}

typedef CUresult (*EncodeFn)(CUtensorMap*, CUtensorMapDataType, cuuint32_t, void*, const cuuint64_t*, const cuuint64_t*,
                             const cuuint32_t*, const cuuint32_t*, CUtensorMapInterleave, CUtensorMapSwizzle,
                             CUtensorMapL2promotion, CUtensorMapFloatOOBfill);

CUtensorMap make_map(EncodeFn fn, const void* base, int rank, const uint64_t* dims, const uint64_t* strides, const uint32_t* box,
                     CUtensorMapSwizzle swz) {
  CUtensorMap m;
  cuuint64_t gd[5], gs[4];
  cuuint32_t bx[5], es[5];
  for (int i = 0; i < rank; i++) { gd[i] = dims[i]; bx[i] = box[i]; es[i] = 1; }
  for (int i = 0; i + 1 < rank; i++) gs[i] = strides[i];
  fn(&m, CU_TENSOR_MAP_DATA_TYPE_BFLOAT16, rank, const_cast<void*>(base), gd, gs, bx, es, CU_TENSOR_MAP_INTERLEAVE_NONE, swz,
     CU_TENSOR_MAP_L2_PROMOTION_NONE, CU_TENSOR_MAP_FLOAT_OOB_FILL_NONE);
  return m;
}

template <typename... KArgs, typename... Args>
void launch(void (*k)(KArgs...), int grid, int block, int smem, bool pdl, Args... args) {
  cudaLaunchConfig_t c = {};
  c.gridDim = dim3(grid);
  c.blockDim = dim3(block);
  c.dynamicSmemBytes = smem;
  c.stream = cudaStreamPerThread;
  cudaLaunchAttribute at[1];
  at[0].id = cudaLaunchAttributeProgrammaticStreamSerialization;
  at[0].val.programmaticStreamSerializationAllowed = 1;
  c.attrs = at;
  c.numAttrs = pdl ? 1 : 0;
  cudaLaunchKernelEx(&c, k, args...);
}

}

extern "C" void kernel_launch(void* const* d_in, const int* in_sizes, int n_in, void* d_out, int out_size) {
  const __nv_bfloat16* x = (const __nv_bfloat16*)d_in[0];
  const __nv_bfloat16* w1 = (const __nv_bfloat16*)d_in[1];
  const __nv_bfloat16* w2 = (const __nv_bfloat16*)d_in[2];
  const __nv_bfloat16* g = (const __nv_bfloat16*)d_in[3];
  const __nv_bfloat16* wf = (const __nv_bfloat16*)d_in[4];
  const __nv_bfloat16* wgt = (const __nv_bfloat16*)d_in[5];
  const __nv_bfloat16* wo = (const __nv_bfloat16*)d_in[6];

  void* fp = nullptr;
  cudaDriverEntryPointQueryResult qr;
  cudaGetDriverEntryPoint("cuTensorMapEncodeTiled", &fp, cudaEnableDefault, &qr);
  EncodeFn fn = (EncodeFn)fp;
  void *W, *Y2, *cnt, *ge, *img, *gat;
  cudaGetSymbolAddress(&cnt, g_cnt);
  cudaGetSymbolAddress(&ge, g_ge);
  cudaGetSymbolAddress(&img, c_img);
  cudaGetSymbolAddress(&gat, c_ga);
  cudaGetSymbolAddress(&W, g_W);
  cudaGetSymbolAddress(&Y2, g_Y2);
  cudaFuncSetAttribute(kG, cudaFuncAttributeMaxDynamicSharedMemorySize, G_SMEM);
  cudaFuncSetAttribute(kC, cudaFuncAttributeMaxDynamicSharedMemorySize, C_SMEM);
  cudaFuncSetAttribute(kH, cudaFuncAttributeMaxDynamicSharedMemorySize, H_SMEM);
  cudaFuncSetAttribute(kE, cudaFuncAttributeMaxDynamicSharedMemorySize, E_SMEM);
  auto page_up = [](void* p) { return (void*)(((uintptr_t)p + (1 << 21) - 1) & ~(uintptr_t)((1 << 21) - 1)); };
  void *X1 = page_up(d_out), *X2 = X1;
  W = page_up(W);
  const CUtensorMapSwizzle S128 = CU_TENSOR_MAP_SWIZZLE_128B, S64 = CU_TENSOR_MAP_SWIZZLE_64B;

  auto map_x = [&]() {
    uint64_t d[] = {64, 8000, 8, 1, 2}, s[] = {1024, 128, 8000ull * 1024, 8000ull * 1024};
    uint32_t bx[] = {64, 112, 1, 1, 1};
    return make_map(fn, x, 5, d, s, bx, S128);
  };
  auto map_w_in = [&](const __nv_bfloat16* w, int odd, uint32_t n) {
    uint64_t d[] = {64, (uint64_t)(odd ? 15 : 16), 4, 64, 4}, s[] = {2ull * 65536 * 2, 128, 512, 32768};
    uint32_t bx[] = {64, 16, 2, 1, n};
    return make_map(fn, w + (odd ? 65536 : 0), 5, d, s, bx, S128);
  };
  auto map_X_st = [&](void* p, int nb, int boxb) {
    uint64_t d[] = {64, 512, (uint64_t)(2 * nb)}, s[] = {2ull * nb * 128, 128};
    uint32_t bx[] = {64, 64, (uint32_t)boxb};
    return make_map(fn, p, 3, d, s, bx, S128);
  };
  auto map_X1_st = [&](uint32_t rows) {
    uint64_t d[] = {8192, 16, 4, 24}, s[] = {16384, 262144, 1048576};
    uint32_t bx[] = {64, 4, 2, rows / 8};
    return make_map(fn, X1, 4, d, s, bx, S128);
  };
  auto map_Y1_ld = [&](uint64_t step) {
    uint64_t d[] = {64, 12 << 14, 2}, s[] = {128, step};
    uint32_t bx[] = {64, 32, 2};
    return make_map(fn, X1, 3, d, s, bx, S128);
  };
  auto map_W_st = [&]() {
    uint64_t d[] = {8192, 8, 4, 2 * (8 + W_SHIFT), 2}, s[] = {32768, 262144, 1048576, 16384};
    uint32_t bx[] = {64, 2, 2, 2, 2};
    return make_map(fn, W, 5, d, s, bx, S128);
  };
  auto map_X_ld = [&](void* p, int nb, int boxb) {
    uint64_t d[] = {64, (uint64_t)(2 * nb), 512}, s[] = {128, 2ull * nb * 128};
    uint32_t bx[] = {32, (uint32_t)boxb, 1};
    return make_map(fn, p, 3, d, s, bx, S64);
  };
  auto map_W_ld = [&](uint32_t n) {
    uint64_t d[] = {64, 512 / n, (8ull + W_SHIFT) * 32 * n}, s[] = {128, 65536 / n};
    uint32_t bx[] = {64, 32, n};
    return make_map(fn, W, 3, d, s, bx, S128);
  };
  auto map_Y_st = [&](void* p, int nb, int rows) {
    uint64_t d[] = {64, (uint64_t)(2 * nb), 64, 4}, s[] = {32768, 128, 8192};
    uint32_t bx[] = {64, (uint32_t)rows, 1, 1};
    return make_map(fn, p, 4, d, s, bx, S128);
  };
  auto map_Y_ld = [&](void* p, int nb, int boxc, int boxb) {
    uint64_t d[] = {64, 64, 4, (uint64_t)nb, 2}, s[] = {128, 8192, 32768, (uint64_t)nb * 32768};
    uint32_t bx[] = {64, 64, (uint32_t)boxc, (uint32_t)boxb, 1};
    return make_map(fn, p, 5, d, s, bx, S128);
  };
  auto map_wsq = [&](const __nv_bfloat16* w) {
    uint64_t d[] = {64, 256, 4}, s[] = {512, 128};
    uint32_t bx[] = {64, 64, 4};
    return make_map(fn, w, 3, d, s, bx, S128);
  };
  auto map_out = [&]() {
    uint64_t d[] = {64, 4000, 4, 8, 2}, s[] = {4096, 128, 512, 4000ull * 4096};
    uint32_t bx[] = {64, 64, 2, 1, 1};
    return make_map(fn, d_out, 5, d, s, bx, S128);
  };

  GMaps g1;
  g1.w = map_W_ld(4);
  g1.y = map_X1_st(8);
  g1.in[0] = map_w_in(w1, 1, 2);
  g1.in[1] = map_w_in(w1, 0, 2);
  g1.in[2] = map_w_in(w2, 1, 1);
  g1.in[3] = map_w_in(w2, 0, 1);
  g1.in[4] = map_x();
  g1.xs = map_X1_st(16);
  g1.ws = map_W_st();
  launch(kG, 132, 384, G_SMEM, false, (int*)cnt, (char*)X1, (char*)W, g, wgt, (float*)ge, (const uint32_t*)img, g1);
  launch(kC, 128, 512, C_SMEM, true, (int*)cnt, (const uint32_t*)img, map_Y1_ld(0x3000), map_Y1_ld(0x1000), map_X_st(X2, NB2, 1));
  launch(kH, 128, 288, H_SMEM, true, (int*)cnt, wf, wo, (const uint32_t*)gat, map_X_ld(X2, NB2, 168), map_W_ld(2), map_Y_st(Y2, NB2, 168 / H_EPI));
  launch(kE, 126, 256, E_SMEM, true, (int*)cnt, (const uint32_t*)gat, (const float*)ge, map_Y_ld(Y2, NB2, 1, 2), map_wsq(wf), map_wsq(wo), map_out());
}
```

```cpp
#include <cuda_runtime.h>
#include <cuda_bf16.h>
#include <cuda.h>
#include <stdint.h>
#include <type_traits>

#define W_SHIFT 1
namespace {

constexpr int NB1 = 168;
constexpr int NB2 = 84;

__device__ __align__(1024) __nv_bfloat16 g_W[(9 + W_SHIFT) * 64 * 4 * 64 * 64];
__device__ __align__(1024) __nv_bfloat16 g_Y2[2 * NB2 * 4 * 64 * 64];
__device__ __align__(1024) float g_ge[16 * 256];

__device__ __forceinline__ uint32_t s2u(const void* p) { return (uint32_t)__cvta_generic_to_shared(p); }
__device__ __forceinline__ uint32_t pin(uint32_t v) {
  return __shfl_sync(0xffffffffu, v, 0);
}
__device__ __forceinline__ void mbar_init(uint32_t b, int c) {
  asm volatile("mbarrier.init.shared::cta.b64 [%0], %1;" ::"r"(b), "r"(c) : "memory");
}
__device__ __forceinline__ void mbar_expect(uint32_t b, int bytes) {
  asm volatile("mbarrier.arrive.expect_tx.shared::cta.b64 _, [%0], %1;" ::"r"(b), "r"(bytes) : "memory");
}
__device__ __forceinline__ void mbar_arrive(uint32_t b) {
  asm volatile("mbarrier.arrive.shared::cta.b64 _, [%0];" ::"r"(b) : "memory");
}
__device__ __forceinline__ void mbar_arrive_cta(uint32_t b, uint32_t cta) {
  asm volatile("{\n.reg .b32 r;\nmapa.shared::cluster.u32 r, %0, %1;\nmbarrier.arrive.shared::cluster.b64 _, [r];\n}" ::"r"(b), "r"(cta) : "memory");
}
__device__ __forceinline__ void mbar_wait(uint32_t b, int ph) {
  asm volatile(
      "{\n.reg .pred p;\n.reg .u32 n;\n"
      "mov.u32 n, 0;\n"
      "MBW_LOOP:\n"
      "mbarrier.try_wait.parity.shared::cta.b64 p, [%0], %1;\n"
      "@p bra MBW_DONE;\n"
      "add.u32 n, n, 1;\n"
      "setp.lt.u32 p, n, 1048576;\n"
      "@p bra MBW_LOOP;\n"
      "MBW_DONE:\n}" ::"r"(b), "r"(ph) : "memory");
}
__device__ __forceinline__ bool mbar_test(uint32_t b, int ph) {
  uint32_t ok;
  asm volatile("{\n.reg .pred p;\nmbarrier.test_wait.parity.shared::cta.b64 p, [%1], %2;\nselp.u32 %0, 1, 0, p;\n}" : "=r"(ok) : "r"(b), "r"(ph) : "memory");
  return __all_sync(0xffffffffu, ok);
}
__device__ __forceinline__ void fence_bar_init() { asm volatile("fence.mbarrier_init.release.cluster;" ::: "memory"); }
__device__ __forceinline__ void fence_async() { asm volatile("fence.proxy.async.shared::cta;" ::: "memory"); }
__device__ __forceinline__ void bar_sync(int id, int n) { asm volatile("bar.sync %0, %1;" ::"r"(id), "r"(n) : "memory"); }
__device__ __forceinline__ void bar_arrive(int id, int n) { asm volatile("bar.arrive %0, %1;" ::"r"(id), "r"(n) : "memory"); }
__device__ __forceinline__ void pdl_wait() { asm volatile("griddepcontrol.wait;" ::: "memory"); }
__device__ __forceinline__ void pdl_launch() { asm volatile("griddepcontrol.launch_dependents;" ::: "memory"); }
__device__ __forceinline__ void prefetch_map(const CUtensorMap* m) {
  asm volatile("prefetch.tensormap [%0];" ::"l"(m) : "memory");
}
template <int P> __device__ __forceinline__ uint64_t policy() {
  uint64_t p;
  asm("createpolicy.fractional.L2::evict_first.b64 %0, 1.0;" : "=l"(p));
  return p;
}
template <int P> __device__ __forceinline__ void tma_ld3(uint32_t dst, const CUtensorMap* m, uint32_t bar, int c0, int c1, int c2) {
  if constexpr (P == 0)
    asm volatile("cp.async.bulk.tensor.3d.shared::cluster.global.mbarrier::complete_tx::bytes [%0], [%1, {%3, %4, %5}], [%2];"
                 ::"r"(dst), "l"(m), "r"(bar), "r"(c0), "r"(c1), "r"(c2) : "memory");
  else
    asm volatile("cp.async.bulk.tensor.3d.shared::cluster.global.mbarrier::complete_tx::bytes.L2::cache_hint [%0], [%1, {%3, %4, %5}], [%2], %6;"
                 ::"r"(dst), "l"(m), "r"(bar), "r"(c0), "r"(c1), "r"(c2), "l"(policy<P>()) : "memory");
}
template <int P> __device__ __forceinline__ void tma_ld3mc(uint32_t dst, const CUtensorMap* m, uint32_t bar, int c0, int c1, int c2) {
  if constexpr (P == 0)
    asm volatile("cp.async.bulk.tensor.3d.shared::cluster.global.mbarrier::complete_tx::bytes.multicast::cluster [%0], [%1, {%3, %4, %5}], [%2], %6;"
                 ::"r"(dst), "l"(m), "r"(bar), "r"(c0), "r"(c1), "r"(c2), "h"((uint16_t)3) : "memory");
  else
    asm volatile("cp.async.bulk.tensor.3d.shared::cluster.global.mbarrier::complete_tx::bytes.multicast::cluster.L2::cache_hint [%0], [%1, {%3, %4, %5}], [%2], %6, %7;"
                 ::"r"(dst), "l"(m), "r"(bar), "r"(c0), "r"(c1), "r"(c2), "h"((uint16_t)3), "l"(policy<P>()) : "memory");
}
template <int P> __device__ __forceinline__ void tma_ld4(uint32_t dst, const CUtensorMap* m, uint32_t bar, int c0, int c1, int c2, int c3) {
  if constexpr (P == 0)
    asm volatile("cp.async.bulk.tensor.4d.shared::cluster.global.mbarrier::complete_tx::bytes [%0], [%1, {%3, %4, %5, %6}], [%2];"
                 ::"r"(dst), "l"(m), "r"(bar), "r"(c0), "r"(c1), "r"(c2), "r"(c3) : "memory");
  else
    asm volatile("cp.async.bulk.tensor.4d.shared::cluster.global.mbarrier::complete_tx::bytes.L2::cache_hint [%0], [%1, {%3, %4, %5, %6}], [%2], %7;"
                 ::"r"(dst), "l"(m), "r"(bar), "r"(c0), "r"(c1), "r"(c2), "r"(c3), "l"(policy<P>()) : "memory");
}
template <int P> __device__ __forceinline__ void tma_ld4mc(uint32_t dst, const CUtensorMap* m, uint32_t bar, int c0, int c1, int c2, int c3) {
  if constexpr (P == 0)
    asm volatile("cp.async.bulk.tensor.4d.shared::cluster.global.mbarrier::complete_tx::bytes.multicast::cluster [%0], [%1, {%3, %4, %5, %6}], [%2], %7;"
                 ::"r"(dst), "l"(m), "r"(bar), "r"(c0), "r"(c1), "r"(c2), "r"(c3), "h"((uint16_t)3) : "memory");
  else
    asm volatile("cp.async.bulk.tensor.4d.shared::cluster.global.mbarrier::complete_tx::bytes.multicast::cluster.L2::cache_hint [%0], [%1, {%3, %4, %5, %6}], [%2], %7, %8;"
                 ::"r"(dst), "l"(m), "r"(bar), "r"(c0), "r"(c1), "r"(c2), "r"(c3), "h"((uint16_t)3), "l"(policy<P>()) : "memory");
}
template <int P> __device__ __forceinline__ void tma_ld5(uint32_t dst, const CUtensorMap* m, uint32_t bar, int c0, int c1, int c2, int c3, int c4) {
  if constexpr (P == 0)
    asm volatile("cp.async.bulk.tensor.5d.shared::cluster.global.mbarrier::complete_tx::bytes [%0], [%1, {%3, %4, %5, %6, %7}], [%2];"
                 ::"r"(dst), "l"(m), "r"(bar), "r"(c0), "r"(c1), "r"(c2), "r"(c3), "r"(c4) : "memory");
  else
    asm volatile("cp.async.bulk.tensor.5d.shared::cluster.global.mbarrier::complete_tx::bytes.L2::cache_hint [%0], [%1, {%3, %4, %5, %6, %7}], [%2], %8;"
                 ::"r"(dst), "l"(m), "r"(bar), "r"(c0), "r"(c1), "r"(c2), "r"(c3), "r"(c4), "l"(policy<P>()) : "memory");
}
template <int P> __device__ __forceinline__ void tma_st3(const CUtensorMap* m, uint32_t src, int c0, int c1, int c2) {
  if constexpr (P == 0)
    asm volatile("cp.async.bulk.tensor.3d.global.shared::cta.bulk_group [%0, {%2, %3, %4}], [%1];" ::"l"(m), "r"(src), "r"(c0), "r"(c1), "r"(c2) : "memory");
  else
    asm volatile("cp.async.bulk.tensor.3d.global.shared::cta.bulk_group.L2::cache_hint [%0, {%2, %3, %4}], [%1], %5;" ::"l"(m), "r"(src), "r"(c0), "r"(c1), "r"(c2), "l"(policy<P>()) : "memory");
}
template <int P> __device__ __forceinline__ void tma_st4(const CUtensorMap* m, uint32_t src, int c0, int c1, int c2, int c3) {
  if constexpr (P == 0)
    asm volatile("cp.async.bulk.tensor.4d.global.shared::cta.bulk_group [%0, {%2, %3, %4, %5}], [%1];" ::"l"(m), "r"(src), "r"(c0), "r"(c1), "r"(c2), "r"(c3) : "memory");
  else
    asm volatile("cp.async.bulk.tensor.4d.global.shared::cta.bulk_group.L2::cache_hint [%0, {%2, %3, %4, %5}], [%1], %6;" ::"l"(m), "r"(src), "r"(c0), "r"(c1), "r"(c2), "r"(c3), "l"(policy<P>()) : "memory");
}
template <int P> __device__ __forceinline__ void tma_st5(const CUtensorMap* m, uint32_t src, int c0, int c1, int c2, int c3, int c4) {
  if constexpr (P == 0)
    asm volatile("cp.async.bulk.tensor.5d.global.shared::cta.bulk_group [%0, {%2, %3, %4, %5, %6}], [%1];" ::"l"(m), "r"(src), "r"(c0), "r"(c1), "r"(c2), "r"(c3), "r"(c4) : "memory");
  else
    asm volatile("cp.async.bulk.tensor.5d.global.shared::cta.bulk_group.L2::cache_hint [%0, {%2, %3, %4, %5, %6}], [%1], %7;" ::"l"(m), "r"(src), "r"(c0), "r"(c1), "r"(c2), "r"(c3), "r"(c4), "l"(policy<P>()) : "memory");
}
__device__ __forceinline__ void bulk_commit() { asm volatile("cp.async.bulk.commit_group;" ::: "memory"); }
template <int N> __device__ __forceinline__ void bulk_wait() { asm volatile("cp.async.bulk.wait_group %0;" ::"n"(N) : "memory"); }
template <int N> __device__ __forceinline__ void bulk_wait_read() { asm volatile("cp.async.bulk.wait_group.read %0;" ::"n"(N) : "memory"); }
__device__ __forceinline__ void wg_fence() { asm volatile("wgmma.fence.sync.aligned;" ::: "memory"); }
__device__ __forceinline__ void wg_commit() { asm volatile("wgmma.commit_group.sync.aligned;" ::: "memory"); }
template <int N> __device__ __forceinline__ void wg_wait() { asm volatile("wgmma.wait_group.sync.aligned %0;" ::"n"(N) : "memory"); }
template <int R> __device__ __forceinline__ void reg_fence(float (&d)[R]) {
#pragma unroll
  for (int i = 0; i < R; i++) asm volatile("" : "+f"(d[i])::"memory");
}
template <int R> __device__ __forceinline__ void reg_fence(uint32_t (&d)[R]) {
#pragma unroll
  for (int i = 0; i < R; i++) asm volatile("" : "+r"(d[i])::"memory");
}
__device__ __forceinline__ void stsm4(uint32_t a, uint32_t r0, uint32_t r1, uint32_t r2, uint32_t r3) {
  asm volatile("stmatrix.sync.aligned.m8n8.x4.shared.b16 [%0], {%1, %2, %3, %4};" ::"r"(a), "r"(r0), "r"(r1), "r"(r2), "r"(r3) : "memory");
}
__device__ __forceinline__ void stsm4t(uint32_t a, uint32_t r0, uint32_t r1, uint32_t r2, uint32_t r3) {
  asm volatile("stmatrix.sync.aligned.m8n8.x4.trans.shared.b16 [%0], {%1, %2, %3, %4};" ::"r"(a), "r"(r0), "r"(r1), "r"(r2), "r"(r3) : "memory");
}
__device__ __forceinline__ void ldsm4(uint32_t a, uint32_t& r0, uint32_t& r1, uint32_t& r2, uint32_t& r3) {
  asm volatile("ldmatrix.sync.aligned.m8n8.x4.shared.b16 {%0, %1, %2, %3}, [%4];" : "=r"(r0), "=r"(r1), "=r"(r2), "=r"(r3) : "r"(a) : "memory");
}
__device__ __forceinline__ void ldg128(const uint4* p, uint32_t& a, uint32_t& b, uint32_t& c, uint32_t& d) {
  asm volatile("ld.global.nc.v4.u32 {%0, %1, %2, %3}, [%4];" : "=r"(a), "=r"(b), "=r"(c), "=r"(d) : "l"(p));
}
__device__ __forceinline__ uint32_t pack2(float lo, float hi) {
  uint32_t r;
  asm("cvt.rn.bf16x2.f32 %0, %1, %2;" : "=r"(r) : "f"(hi), "f"(lo));
  return r;
}
__device__ __forceinline__ float tanh_f32(float x) {
  float y;
  asm("tanh.approx.f32 %0, %1;" : "=f"(y) : "f"(x));
  return y;
}
__device__ __forceinline__ float gelu(float hx) {
  const float u = hx * fmaf(hx * hx, 8.0f * 0.044715f * 0.7978845608028654f, 2.0f * 0.7978845608028654f);
  return fmaf(hx, tanh_f32(u), hx);
}
__device__ __forceinline__ uint64_t mk_desc4(uint32_t addr4, uint32_t lbo, uint32_t sbo, uint32_t swz) {
  const uint32_t lo = addr4 + ((lbo >> 4) << 16), hi = (sbo >> 4) | (swz << 30);
  uint64_t d;
  asm("mov.b64 %0, {%1, %2};" : "=l"(d) : "r"(lo), "r"(hi));
  return d;
}
#define mk_desc(base, off, lbo, sbo, swz) mk_desc4((((base) & 0x3FFFF) >> 4) + ((off) >> 4), lbo, sbo, swz)

template <int SA, int SB, int TA, int TB>
__device__ __forceinline__ void wgmma_ss_16(float (&d)[8], uint64_t da, uint64_t db, int sd) {
  asm volatile("{\n.reg .pred p;\nsetp.ne.b32 p, %10, 0;\n"
      "wgmma.mma_async.sync.aligned.m64n16k16.f32.bf16.bf16 {"
      "%0, %1, %2, %3, %4, %5, %6, %7"
      "}, %8, %9, p, %11, %12, %13, %14;\n}\n"
      : "+f"(d[0]), "+f"(d[1]), "+f"(d[2]), "+f"(d[3]), "+f"(d[4]), "+f"(d[5]), "+f"(d[6]), "+f"(d[7])
      : "l"(da), "l"(db), "r"(sd), "n"(SA), "n"(SB), "n"(TA), "n"(TB));
}
template <int SA, int SB, int TA, int TB>
__device__ __forceinline__ void wgmma_ss_24(float (&d)[12], uint64_t da, uint64_t db, int sd) {
  asm volatile("{\n.reg .pred p;\nsetp.ne.b32 p, %14, 0;\n"
      "wgmma.mma_async.sync.aligned.m64n24k16.f32.bf16.bf16 {"
      "%0, %1, %2, %3, %4, %5, %6, %7, %8, %9, %10, %11"
      "}, %12, %13, p, %15, %16, %17, %18;\n}\n"
      : "+f"(d[0]), "+f"(d[1]), "+f"(d[2]), "+f"(d[3]), "+f"(d[4]), "+f"(d[5]), "+f"(d[6]), "+f"(d[7]), "+f"(d[8]),
        "+f"(d[9]), "+f"(d[10]), "+f"(d[11])
      : "l"(da), "l"(db), "r"(sd), "n"(SA), "n"(SB), "n"(TA), "n"(TB));
}
template <int SA, int SB, int TA, int TB>
__device__ __forceinline__ void wgmma_ss_128(float (&d)[64], uint64_t da, uint64_t db, int sd) {
  asm volatile("{\n.reg .pred p;\nsetp.ne.b32 p, %66, 0;\n"
      "wgmma.mma_async.sync.aligned.m64n128k16.f32.bf16.bf16 {"
      "%0, %1, %2, %3, %4, %5, %6, %7, %8, %9, %10, %11, %12, %13, %14, %15, %16, %17, %18, %19, %20, %21, %22, %23, "
      "%24, %25, %26, %27, %28, %29, %30, %31, %32, %33, %34, %35, %36, %37, %38, %39, %40, %41, %42, %43, %44, %45, "
      "%46, %47, %48, %49, %50, %51, %52, %53, %54, %55, %56, %57, %58, %59, %60, %61, %62, %63"
      "}, %64, %65, p, %67, %68, %69, %70;\n}\n"
      : "+f"(d[0]), "+f"(d[1]), "+f"(d[2]), "+f"(d[3]), "+f"(d[4]), "+f"(d[5]), "+f"(d[6]), "+f"(d[7]), "+f"(d[8]),
        "+f"(d[9]), "+f"(d[10]), "+f"(d[11]), "+f"(d[12]), "+f"(d[13]), "+f"(d[14]), "+f"(d[15]), "+f"(d[16]),
        "+f"(d[17]), "+f"(d[18]), "+f"(d[19]), "+f"(d[20]), "+f"(d[21]), "+f"(d[22]), "+f"(d[23]), "+f"(d[24]),
        "+f"(d[25]), "+f"(d[26]), "+f"(d[27]), "+f"(d[28]), "+f"(d[29]), "+f"(d[30]), "+f"(d[31]), "+f"(d[32]),
        "+f"(d[33]), "+f"(d[34]), "+f"(d[35]), "+f"(d[36]), "+f"(d[37]), "+f"(d[38]), "+f"(d[39]), "+f"(d[40]),
        "+f"(d[41]), "+f"(d[42]), "+f"(d[43]), "+f"(d[44]), "+f"(d[45]), "+f"(d[46]), "+f"(d[47]), "+f"(d[48]),
        "+f"(d[49]), "+f"(d[50]), "+f"(d[51]), "+f"(d[52]), "+f"(d[53]), "+f"(d[54]), "+f"(d[55]), "+f"(d[56]),
        "+f"(d[57]), "+f"(d[58]), "+f"(d[59]), "+f"(d[60]), "+f"(d[61]), "+f"(d[62]), "+f"(d[63])
      : "l"(da), "l"(db), "r"(sd), "n"(SA), "n"(SB), "n"(TA), "n"(TB));
}
template <int SA, int SB, int TA, int TB>
__device__ __forceinline__ void wgmma_ss_168(float (&d)[84], uint64_t da, uint64_t db, int sd) {
  asm volatile("{\n.reg .pred p;\nsetp.ne.b32 p, %86, 0;\n"
      "wgmma.mma_async.sync.aligned.m64n168k16.f32.bf16.bf16 {"
      "%0, %1, %2, %3, %4, %5, %6, %7, %8, %9, %10, %11, %12, %13, %14, %15, %16, %17, %18, %19, %20, %21, %22, %23, "
      "%24, %25, %26, %27, %28, %29, %30, %31, %32, %33, %34, %35, %36, %37, %38, %39, %40, %41, %42, %43, %44, %45, "
      "%46, %47, %48, %49, %50, %51, %52, %53, %54, %55, %56, %57, %58, %59, %60, %61, %62, %63, %64, %65, %66, %67, "
      "%68, %69, %70, %71, %72, %73, %74, %75, %76, %77, %78, %79, %80, %81, %82, %83"
      "}, %84, %85, p, %87, %88, %89, %90;\n}\n"
      : "+f"(d[0]), "+f"(d[1]), "+f"(d[2]), "+f"(d[3]), "+f"(d[4]), "+f"(d[5]), "+f"(d[6]), "+f"(d[7]), "+f"(d[8]),
        "+f"(d[9]), "+f"(d[10]), "+f"(d[11]), "+f"(d[12]), "+f"(d[13]), "+f"(d[14]), "+f"(d[15]), "+f"(d[16]),
        "+f"(d[17]), "+f"(d[18]), "+f"(d[19]), "+f"(d[20]), "+f"(d[21]), "+f"(d[22]), "+f"(d[23]), "+f"(d[24]),
        "+f"(d[25]), "+f"(d[26]), "+f"(d[27]), "+f"(d[28]), "+f"(d[29]), "+f"(d[30]), "+f"(d[31]), "+f"(d[32]),
        "+f"(d[33]), "+f"(d[34]), "+f"(d[35]), "+f"(d[36]), "+f"(d[37]), "+f"(d[38]), "+f"(d[39]), "+f"(d[40]),
        "+f"(d[41]), "+f"(d[42]), "+f"(d[43]), "+f"(d[44]), "+f"(d[45]), "+f"(d[46]), "+f"(d[47]), "+f"(d[48]),
        "+f"(d[49]), "+f"(d[50]), "+f"(d[51]), "+f"(d[52]), "+f"(d[53]), "+f"(d[54]), "+f"(d[55]), "+f"(d[56]),
        "+f"(d[57]), "+f"(d[58]), "+f"(d[59]), "+f"(d[60]), "+f"(d[61]), "+f"(d[62]), "+f"(d[63]), "+f"(d[64]),
        "+f"(d[65]), "+f"(d[66]), "+f"(d[67]), "+f"(d[68]), "+f"(d[69]), "+f"(d[70]), "+f"(d[71]), "+f"(d[72]),
        "+f"(d[73]), "+f"(d[74]), "+f"(d[75]), "+f"(d[76]), "+f"(d[77]), "+f"(d[78]), "+f"(d[79]), "+f"(d[80]),
        "+f"(d[81]), "+f"(d[82]), "+f"(d[83])
      : "l"(da), "l"(db), "r"(sd), "n"(SA), "n"(SB), "n"(TA), "n"(TB));
}
template <int SA, int SB, int TB>
__device__ __forceinline__ void wgmma_rs_64(float (&d)[32], uint32_t a0, uint32_t a1, uint32_t a2, uint32_t a3, uint64_t db, int sd) {
  asm volatile("{\n.reg .pred p;\nsetp.ne.b32 p, %37, 0;\n"
      "wgmma.mma_async.sync.aligned.m64n64k16.f32.bf16.bf16 {"
      "%0, %1, %2, %3, %4, %5, %6, %7, %8, %9, %10, %11, %12, %13, %14, %15, %16, %17, %18, %19, %20, %21, %22, %23, "
      "%24, %25, %26, %27, %28, %29, %30, %31"
      "}, {%32, %33, %34, %35}, %36, p, %38, %39, %40;\n}\n"
      : "+f"(d[0]), "+f"(d[1]), "+f"(d[2]), "+f"(d[3]), "+f"(d[4]), "+f"(d[5]), "+f"(d[6]), "+f"(d[7]), "+f"(d[8]),
        "+f"(d[9]), "+f"(d[10]), "+f"(d[11]), "+f"(d[12]), "+f"(d[13]), "+f"(d[14]), "+f"(d[15]), "+f"(d[16]),
        "+f"(d[17]), "+f"(d[18]), "+f"(d[19]), "+f"(d[20]), "+f"(d[21]), "+f"(d[22]), "+f"(d[23]), "+f"(d[24]),
        "+f"(d[25]), "+f"(d[26]), "+f"(d[27]), "+f"(d[28]), "+f"(d[29]), "+f"(d[30]), "+f"(d[31])
      : "r"(a0), "r"(a1), "r"(a2), "r"(a3), "l"(db), "r"(sd), "n"(SA), "n"(SB), "n"(TB));
}
template <int SA, int SB, int TB>
__device__ __forceinline__ void wgmma_rs_128(float (&d)[64], uint32_t a0, uint32_t a1, uint32_t a2, uint32_t a3, uint64_t db, int sd) {
  asm volatile("{\n.reg .pred p;\nsetp.ne.b32 p, %69, 0;\n"
      "wgmma.mma_async.sync.aligned.m64n128k16.f32.bf16.bf16 {"
      "%0, %1, %2, %3, %4, %5, %6, %7, %8, %9, %10, %11, %12, %13, %14, %15, %16, %17, %18, %19, %20, %21, %22, %23, "
      "%24, %25, %26, %27, %28, %29, %30, %31, %32, %33, %34, %35, %36, %37, %38, %39, %40, %41, %42, %43, %44, %45, "
      "%46, %47, %48, %49, %50, %51, %52, %53, %54, %55, %56, %57, %58, %59, %60, %61, %62, %63"
      "}, {%64, %65, %66, %67}, %68, p, %70, %71, %72;\n}\n"
      : "+f"(d[0]), "+f"(d[1]), "+f"(d[2]), "+f"(d[3]), "+f"(d[4]), "+f"(d[5]), "+f"(d[6]), "+f"(d[7]), "+f"(d[8]),
        "+f"(d[9]), "+f"(d[10]), "+f"(d[11]), "+f"(d[12]), "+f"(d[13]), "+f"(d[14]), "+f"(d[15]), "+f"(d[16]),
        "+f"(d[17]), "+f"(d[18]), "+f"(d[19]), "+f"(d[20]), "+f"(d[21]), "+f"(d[22]), "+f"(d[23]), "+f"(d[24]),
        "+f"(d[25]), "+f"(d[26]), "+f"(d[27]), "+f"(d[28]), "+f"(d[29]), "+f"(d[30]), "+f"(d[31]), "+f"(d[32]),
        "+f"(d[33]), "+f"(d[34]), "+f"(d[35]), "+f"(d[36]), "+f"(d[37]), "+f"(d[38]), "+f"(d[39]), "+f"(d[40]),
        "+f"(d[41]), "+f"(d[42]), "+f"(d[43]), "+f"(d[44]), "+f"(d[45]), "+f"(d[46]), "+f"(d[47]), "+f"(d[48]),
        "+f"(d[49]), "+f"(d[50]), "+f"(d[51]), "+f"(d[52]), "+f"(d[53]), "+f"(d[54]), "+f"(d[55]), "+f"(d[56]),
        "+f"(d[57]), "+f"(d[58]), "+f"(d[59]), "+f"(d[60]), "+f"(d[61]), "+f"(d[62]), "+f"(d[63])
      : "r"(a0), "r"(a1), "r"(a2), "r"(a3), "l"(db), "r"(sd), "n"(SA), "n"(SB), "n"(TB));
}
template <int SA, int SB, int TB>
__device__ __forceinline__ void wgmma_rs_256(float (&d)[128], uint32_t a0, uint32_t a1, uint32_t a2, uint32_t a3, uint64_t db, int sd) {
  asm volatile("{\n.reg .pred p;\nsetp.ne.b32 p, %133, 0;\n"
      "wgmma.mma_async.sync.aligned.m64n256k16.f32.bf16.bf16 {"
      "%0, %1, %2, %3, %4, %5, %6, %7, %8, %9, %10, %11, %12, %13, %14, %15, %16, %17, %18, %19, %20, %21, %22, %23, "
      "%24, %25, %26, %27, %28, %29, %30, %31, %32, %33, %34, %35, %36, %37, %38, %39, %40, %41, %42, %43, %44, %45, "
      "%46, %47, %48, %49, %50, %51, %52, %53, %54, %55, %56, %57, %58, %59, %60, %61, %62, %63, %64, %65, %66, %67, "
      "%68, %69, %70, %71, %72, %73, %74, %75, %76, %77, %78, %79, %80, %81, %82, %83, %84, %85, %86, %87, %88, %89, "
      "%90, %91, %92, %93, %94, %95, %96, %97, %98, %99, %100, %101, %102, %103, %104, %105, %106, %107, %108, %109, "
      "%110, %111, %112, %113, %114, %115, %116, %117, %118, %119, %120, %121, %122, %123, %124, %125, %126, %127"
      "}, {%128, %129, %130, %131}, %132, p, %134, %135, %136;\n}\n"
      : "+f"(d[0]), "+f"(d[1]), "+f"(d[2]), "+f"(d[3]), "+f"(d[4]), "+f"(d[5]), "+f"(d[6]), "+f"(d[7]), "+f"(d[8]),
        "+f"(d[9]), "+f"(d[10]), "+f"(d[11]), "+f"(d[12]), "+f"(d[13]), "+f"(d[14]), "+f"(d[15]), "+f"(d[16]),
        "+f"(d[17]), "+f"(d[18]), "+f"(d[19]), "+f"(d[20]), "+f"(d[21]), "+f"(d[22]), "+f"(d[23]), "+f"(d[24]),
        "+f"(d[25]), "+f"(d[26]), "+f"(d[27]), "+f"(d[28]), "+f"(d[29]), "+f"(d[30]), "+f"(d[31]), "+f"(d[32]),
        "+f"(d[33]), "+f"(d[34]), "+f"(d[35]), "+f"(d[36]), "+f"(d[37]), "+f"(d[38]), "+f"(d[39]), "+f"(d[40]),
        "+f"(d[41]), "+f"(d[42]), "+f"(d[43]), "+f"(d[44]), "+f"(d[45]), "+f"(d[46]), "+f"(d[47]), "+f"(d[48]),
        "+f"(d[49]), "+f"(d[50]), "+f"(d[51]), "+f"(d[52]), "+f"(d[53]), "+f"(d[54]), "+f"(d[55]), "+f"(d[56]),
        "+f"(d[57]), "+f"(d[58]), "+f"(d[59]), "+f"(d[60]), "+f"(d[61]), "+f"(d[62]), "+f"(d[63]), "+f"(d[64]),
        "+f"(d[65]), "+f"(d[66]), "+f"(d[67]), "+f"(d[68]), "+f"(d[69]), "+f"(d[70]), "+f"(d[71]), "+f"(d[72]),
        "+f"(d[73]), "+f"(d[74]), "+f"(d[75]), "+f"(d[76]), "+f"(d[77]), "+f"(d[78]), "+f"(d[79]), "+f"(d[80]),
        "+f"(d[81]), "+f"(d[82]), "+f"(d[83]), "+f"(d[84]), "+f"(d[85]), "+f"(d[86]), "+f"(d[87]), "+f"(d[88]),
        "+f"(d[89]), "+f"(d[90]), "+f"(d[91]), "+f"(d[92]), "+f"(d[93]), "+f"(d[94]), "+f"(d[95]), "+f"(d[96]),
        "+f"(d[97]), "+f"(d[98]), "+f"(d[99]), "+f"(d[100]), "+f"(d[101]), "+f"(d[102]), "+f"(d[103]), "+f"(d[104]),
        "+f"(d[105]), "+f"(d[106]), "+f"(d[107]), "+f"(d[108]), "+f"(d[109]), "+f"(d[110]), "+f"(d[111]),
        "+f"(d[112]), "+f"(d[113]), "+f"(d[114]), "+f"(d[115]), "+f"(d[116]), "+f"(d[117]), "+f"(d[118]),
        "+f"(d[119]), "+f"(d[120]), "+f"(d[121]), "+f"(d[122]), "+f"(d[123]), "+f"(d[124]), "+f"(d[125]),
        "+f"(d[126]), "+f"(d[127])
      : "r"(a0), "r"(a1), "r"(a2), "r"(a3), "l"(db), "r"(sd), "n"(SA), "n"(SB), "n"(TB));
}

__device__ const __align__(128) uint32_t c_img[3584] = {
    0x00003c80, 0x00003c80, 0x00003c80, 0x00003c80, 0x00003c80, 0x00003c80, 0x00003c80, 0x00003c80, 0x00003c80, 0x00003c80,
    0x00003c80, 0x00003c80, 0x00003c80, 0x00003c80, 0x00003c80, 0x00003c80, 0x00003c80, 0x00003c80, 0x00003c80, 0x00003c80,
    0x00003c80, 0x00003c80, 0x00003c80, 0x00003c80, 0x00003c80, 0x00003c80, 0x00003c80, 0x00003c80, 0x00003c80, 0x00003c80,
    0x00003c80, 0x00003c80, 0x3c463c22, 0x3c623bf1, 0x3c753b95, 0x3c7f3ac9, 0x3ac93c7f, 0x3b953c75, 0x3bf13c62, 0x3c223c46,
    0x3c22bc46, 0x3bf1bc62, 0x3b95bc75, 0x3ac9bc7f, 0x3c7fbac9, 0x3c75bb95, 0x3c62bbf1, 0x3c46bc22, 0xbc46bc22, 0xbc62bbf1,
    0xbc75bb95, 0xbc7fbac9, 0xbac9bc7f, 0xbb95bc75, 0xbbf1bc62, 0xbc22bc46, 0xbc223c46, 0xbbf13c62, 0xbb953c75, 0xbac93c7f,
    0xbc7f3ac9, 0xbc753b95, 0xbc623bf1, 0xbc463c22, 0xbb48bc7b, 0xbc0ebc55, 0xbc55bc0e, 0xbc7bbb48, 0xbc7b3b48, 0xbc553c0e,
    0xbc0e3c55, 0xbb483c7b, 0x3b483c7b, 0x3c0e3c55, 0x3c553c0e, 0x3c7b3b48, 0x3c7bbb48, 0x3c55bc0e, 0x3c0ebc55, 0x3b48bc7b,
    0xbb48bc7b, 0xbc0ebc55, 0xbc55bc0e, 0xbc7bbb48, 0xbc7b3b48, 0xbc553c0e, 0xbc0e3c55, 0xbb483c7b, 0x3b483c7b, 0x3c0e3c55,
    0x3c553c0e, 0x3c7b3b48, 0x3c7bbb48, 0x3c55bc0e, 0x3c0ebc55, 0x3b48bc7b, 0x3c623bf1, 0x3c7fbac9, 0x3c46bc22, 0x3b95bc75,
    0xbc753b95, 0xbc223c46, 0xbac93c7f, 0x3bf13c62, 0x3bf1bc62, 0xbac9bc7f, 0xbc22bc46, 0xbc75bb95, 0x3b953c75, 0x3c463c22,
    0x3c7f3ac9, 0x3c62bbf1, 0xbc62bbf1, 0xbc7f3ac9, 0xbc463c22, 0xbb953c75, 0x3c75bb95, 0x3c22bc46, 0x3ac9bc7f, 0xbbf1bc62,
    0xbbf13c62, 0x3ac93c7f, 0x3c223c46, 0x3c753b95, 0xbb95bc75, 0xbc46bc22, 0xbc7fbac9, 0xbc623bf1, 0x3bc43c6d, 0x3c6d3bc4,
    0x3c6dbbc4, 0x3bc4bc6d, 0xbbc4bc6d, 0xbc6dbbc4, 0xbc6d3bc4, 0xbbc43c6d, 0x3bc43c6d, 0x3c6d3bc4, 0x3c6dbbc4, 0x3bc4bc6d,
    0xbbc4bc6d, 0xbc6dbbc4, 0xbc6d3bc4, 0xbbc43c6d, 0x3bc43c6d, 0x3c6d3bc4, 0x3c6dbbc4, 0x3bc4bc6d, 0xbbc4bc6d, 0xbc6dbbc4,
    0xbc6d3bc4, 0xbbc43c6d, 0x3bc43c6d, 0x3c6d3bc4, 0x3c6dbbc4, 0x3bc4bc6d, 0xbbc4bc6d, 0xbc6dbbc4, 0xbc6d3bc4, 0xbbc43c6d,
    0x3c753b95, 0x3c46bc22, 0xbac9bc7f, 0xbc62bbf1, 0xbbf1bc62, 0xbc7fbac9, 0xbc223c46, 0x3b953c75, 0x3b95bc75, 0xbc22bc46,
    0xbc7f3ac9, 0xbbf13c62, 0xbc623bf1, 0xbac93c7f, 0x3c463c22, 0x3c75bb95, 0xbc75bb95, 0xbc463c22, 0x3ac93c7f, 0x3c623bf1,
    0x3bf13c62, 0x3c7f3ac9, 0x3c22bc46, 0xbb95bc75, 0xbb953c75, 0x3c223c46, 0x3c7fbac9, 0x3bf1bc62, 0x3c62bbf1, 0x3ac9bc7f,
    0xbc46bc22, 0xbc753b95, 0xbc0ebc55, 0xbc7b3b48, 0xbb483c7b, 0x3c553c0e, 0x3c55bc0e, 0xbb48bc7b, 0xbc7bbb48, 0xbc0e3c55,
    0x3c0e3c55, 0x3c7bbb48, 0x3b48bc7b, 0xbc55bc0e, 0xbc553c0e, 0x3b483c7b, 0x3c7b3b48, 0x3c0ebc55, 0xbc0ebc55, 0xbc7b3b48,
    0xbb483c7b, 0x3c553c0e, 0x3c55bc0e, 0xbb48bc7b, 0xbc7bbb48, 0xbc0e3c55, 0x3c0e3c55, 0x3c7bbb48, 0x3b48bc7b, 0xbc55bc0e,
    0xbc553c0e, 0x3b483c7b, 0x3c7b3b48, 0x3c0ebc55, 0x3c7f3ac9, 0x3b95bc75, 0xbc62bbf1, 0xbc223c46, 0x3c46bc22, 0xbbf1bc62,
    0xbc753b95, 0x3ac93c7f, 0x3ac9bc7f, 0xbc75bb95, 0xbbf13c62, 0x3c463c22, 0xbc22bc46, 0xbc623bf1, 0x3b953c75, 0x3c7fbac9,
    0xbc7fbac9, 0xbb953c75, 0x3c623bf1, 0x3c22bc46, 0xbc463c22, 0x3bf13c62, 0x3c75bb95, 0xbac9bc7f, 0xbac93c7f, 0x3c753b95,
    0x3bf1bc62, 0xbc46bc22, 0x3c223c46, 0x3c62bbf1, 0xbb95bc75, 0xbc7f3ac9, 0x3a493c80, 0x3b163c7d, 0x3b793c78, 0x3bac3c71,
    0x3bdb3c67, 0x3c043c5c, 0x3c183c4e, 0x3c2c3c3e, 0x3c3e3c2c, 0x3c4e3c18, 0x3c5c3c04, 0x3c673bdb, 0x3c713bac, 0x3c783b79,
    0x3c7d3b16, 0x3c803a49, 0x3c80ba49, 0x3c7dbb16, 0x3c78bb79, 0x3c71bbac, 0x3c67bbdb, 0x3c5cbc04, 0x3c4ebc18, 0x3c3ebc2c,
    0x3c2cbc3e, 0x3c18bc4e, 0x3c04bc5c, 0x3bdbbc67, 0x3bacbc71, 0x3b79bc78, 0x3b16bc7d, 0x3a49bc80, 0x3c783b79, 0x3c80ba49,
    0x3c71bbac, 0x3c4ebc18, 0x3b163c7d, 0x3bdb3c67, 0x3c2c3c3e, 0x3c5c3c04, 0xbc04bc5c, 0xbc3ebc2c, 0xbc67bbdb, 0xbc7dbb16,
    0x3c18bc4e, 0x3bacbc71, 0x3a49bc80, 0xbb79bc78, 0xbb793c78, 0x3a493c80, 0x3bac3c71, 0x3c183c4e, 0xbc7d3b16, 0xbc673bdb,
    0xbc3e3c2c, 0xbc043c5c, 0x3c5cbc04, 0x3c2cbc3e, 0x3bdbbc67, 0x3b16bc7d, 0x3c4e3c18, 0x3c713bac, 0x3c803a49, 0x3c78bb79,
    0xbc5cbc04, 0xbc80ba49, 0xbc673bdb, 0xbc183c4e, 0xbb163c7d, 0x3bac3c71, 0x3c3e3c2c, 0x3c783b79, 0x3b793c78, 0x3c2c3c3e,
    0x3c713bac, 0x3c7dbb16, 0x3c4ebc18, 0x3bdbbc67, 0xba49bc80, 0xbc04bc5c, 0xbc043c5c, 0xba493c80, 0x3bdb3c67, 0x3c4e3c18,
    0x3c7d3b16, 0x3c71bbac, 0x3c2cbc3e, 0x3b79bc78, 0x3c78bb79, 0x3c3ebc2c, 0x3bacbc71, 0xbb16bc7d, 0xbc18bc4e, 0xbc67bbdb,
    0xbc803a49, 0xbc5c3c04, 0x3c3ebc2c, 0x3b16bc7d, 0xbc04bc5c, 0xbc71bbac, 0xbbdb3c67, 0x3b793c78, 0x3c4e3c18, 0x3c80ba49,
    0x3a49bc80, 0xbc18bc4e, 0xbc78bb79, 0xbc673bdb, 0x3bac3c71, 0x3c5c3c04, 0x3c7dbb16, 0x3c2cbc3e, 0x3c2c3c3e, 0x3c7d3b16,
    0x3c5cbc04, 0x3bacbc71, 0xbc67bbdb, 0xbc783b79, 0xbc183c4e, 0x3a493c80, 0x3c803a49, 0x3c4ebc18, 0x3b79bc78, 0xbbdbbc67,
    0xbc713bac, 0xbc043c5c, 0x3b163c7d, 0x3c3e3c2c, 0x3c67bbdb, 0x3b79bc78, 0xbc18bc4e, 0xbc80ba49, 0xbc2c3c3e, 0x3b163c7d,
    0x3c5c3c04, 0x3c71bbac, 0x3bacbc71, 0xbc04bc5c, 0xbc7dbb16, 0xbc3e3c2c, 0x3a493c80, 0x3c4e3c18, 0x3c78bb79, 0x3bdbbc67,
    0x3bdb3c67, 0x3c783b79, 0x3c4ebc18, 0x3a49bc80, 0xbc3ebc2c, 0xbc7d3b16, 0xbc043c5c, 0x3bac3c71, 0x3c713bac, 0x3c5cbc04,
    0x3b16bc7d, 0xbc2cbc3e, 0xbc803a49, 0xbc183c4e, 0x3b793c78, 0x3c673bdb, 0xbb16bc7d, 0xbc71bbac, 0xbc3e3c2c, 0x3b793c78,
    0xbc5c3c04, 0x3a493c80, 0x3c673bdb, 0x3c4ebc18, 0xbc183c4e, 0x3bdb3c67, 0x3c803a49, 0x3c04bc5c, 0x3c783b79, 0x3c2cbc3e,
    0xbbacbc71, 0xbc7dbb16, 0xbc7d3b16, 0xbbac3c71, 0x3c2c3c3e, 0x3c78bb79, 0x3c043c5c, 0x3c80ba49, 0x3bdbbc67, 0xbc18bc4e,
    0x3c4e3c18, 0x3c67bbdb, 0x3a49bc80, 0xbc5cbc04, 0x3b79bc78, 0xbc3ebc2c, 0xbc713bac, 0xbb163c7d, 0xbb163c7d, 0x3c673bdb,
    0x3c2cbc3e, 0xbc04bc5c, 0xbc783b79, 0xba493c80, 0x3c713bac, 0x3c18bc4e, 0x3c4ebc18, 0xbbacbc71, 0xbc803a49, 0xbb793c78,
    0x3c5c3c04, 0x3c3ebc2c, 0xbbdbbc67, 0xbc7d3b16, 0xbc7dbb16, 0xbbdb3c67, 0x3c3e3c2c, 0x3c5cbc04, 0xbb79bc78, 0xbc80ba49,
    0xbbac3c71, 0x3c4e3c18, 0x3c183c4e, 0x3c71bbac, 0xba49bc80, 0xbc78bb79, 0xbc043c5c, 0x3c2c3c3e, 0x3c67bbdb, 0xbb16bc7d,
    0xbc67bbdb, 0xbc043c5c, 0x3c4e3c18, 0x3c2cbc3e, 0xbc80ba49, 0xbb163c7d, 0x3c783b79, 0x3bacbc71, 0xbc713bac, 0x3b793c78,
    0x3c7dbb16, 0xba49bc80, 0xbc3e3c2c, 0x3c183c4e, 0x3c5cbc04, 0xbbdbbc67, 0xbbdb3c67, 0x3c5c3c04, 0x3c18bc4e, 0xbc3ebc2c,
    0xba493c80, 0x3c7d3b16, 0x3b79bc78, 0xbc71bbac, 0x3bac3c71, 0x3c78bb79, 0xbb16bc7d, 0xbc803a49, 0x3c2c3c3e, 0x3c4ebc18,
    0xbc04bc5c, 0xbc673bdb, 0x3c353c35, 0x3c35bc35, 0xbc35bc35, 0xbc353c35, 0x3c353c35, 0x3c35bc35, 0xbc35bc35, 0xbc353c35,
    0x3c353c35, 0x3c35bc35, 0xbc35bc35, 0xbc353c35, 0x3c353c35, 0x3c35bc35, 0xbc35bc35, 0xbc353c35, 0x3c353c35, 0x3c35bc35,
    0xbc35bc35, 0xbc353c35, 0x3c353c35, 0x3c35bc35, 0xbc35bc35, 0xbc353c35, 0x3c353c35, 0x3c35bc35, 0xbc35bc35, 0xbc353c35,
    0x3c353c35, 0x3c35bc35, 0xbc35bc35, 0xbc353c35, 0x3c7fbac9, 0xbb95bc75, 0xbc623bf1, 0x3c223c46, 0x3c463c22, 0x3bf1bc62,
    0xbc75bb95, 0xbac93c7f, 0xbac9bc7f, 0xbc753b95, 0x3bf13c62, 0x3c46bc22, 0x3c22bc46, 0xbc62bbf1, 0xbb953c75, 0x3c7f3ac9,
    0xbc7f3ac9, 0x3b953c75, 0x3c62bbf1, 0xbc22bc46, 0xbc46bc22, 0xbbf13c62, 0x3c753b95, 0x3ac9bc7f, 0x3ac93c7f, 0x3c75bb95,
    0xbbf1bc62, 0xbc463c22, 0xbc223c46, 0x3c623bf1, 0x3b95bc75, 0xbc7fbac9, 0xbc55bc0e, 0xbb483c7b, 0x3c7bbb48, 0xbc0ebc55,
    0xbc0e3c55, 0x3c7b3b48, 0xbb48bc7b, 0xbc553c0e, 0x3c553c0e, 0x3b48bc7b, 0xbc7b3b48, 0x3c0e3c55, 0x3c0ebc55, 0xbc7bbb48,
    0x3b483c7b, 0x3c55bc0e, 0xbc55bc0e, 0xbb483c7b, 0x3c7bbb48, 0xbc0ebc55, 0xbc0e3c55, 0x3c7b3b48, 0xbb48bc7b, 0xbc553c0e,
    0x3c553c0e, 0x3b48bc7b, 0xbc7b3b48, 0x3c0e3c55, 0x3c0ebc55, 0xbc7bbb48, 0x3b483c7b, 0x3c55bc0e, 0x3c75bb95, 0xbc46bc22,
    0xbac93c7f, 0x3c62bbf1, 0xbbf13c62, 0x3c7fbac9, 0xbc22bc46, 0xbb953c75, 0xbb95bc75, 0xbc223c46, 0x3c7f3ac9, 0xbbf1bc62,
    0x3c623bf1, 0xbac9bc7f, 0xbc463c22, 0x3c753b95, 0xbc753b95, 0x3c463c22, 0x3ac9bc7f, 0xbc623bf1, 0x3bf1bc62, 0xbc7f3ac9,
    0x3c223c46, 0x3b95bc75, 0x3b953c75, 0x3c22bc46, 0xbc7fbac9, 0x3bf13c62, 0xbc62bbf1, 0x3ac93c7f, 0x3c46bc22, 0xbc75bb95,
    0x3c6d3bc4, 0xbbc4bc6d, 0xbbc43c6d, 0x3c6dbbc4, 0xbc6dbbc4, 0x3bc43c6d, 0x3bc4bc6d, 0xbc6d3bc4, 0x3c6d3bc4, 0xbbc4bc6d,
    0xbbc43c6d, 0x3c6dbbc4, 0xbc6dbbc4, 0x3bc43c6d, 0x3bc4bc6d, 0xbc6d3bc4, 0x3c6d3bc4, 0xbbc4bc6d, 0xbbc43c6d, 0x3c6dbbc4,
    0xbc6dbbc4, 0x3bc43c6d, 0x3bc4bc6d, 0xbc6d3bc4, 0x3c6d3bc4, 0xbbc4bc6d, 0xbbc43c6d, 0x3c6dbbc4, 0xbc6dbbc4, 0x3bc43c6d,
    0x3bc4bc6d, 0xbc6d3bc4, 0x3c62bbf1, 0xbc7fbac9, 0x3c463c22, 0xbb95bc75, 0xbc75bb95, 0x3c223c46, 0xbac9bc7f, 0xbbf13c62,
    0xbbf1bc62, 0xbac93c7f, 0x3c22bc46, 0xbc753b95, 0xbb953c75, 0x3c46bc22, 0xbc7f3ac9, 0x3c623bf1, 0xbc623bf1, 0x3c7f3ac9,
    0xbc46bc22, 0x3b953c75, 0x3c753b95, 0xbc22bc46, 0x3ac93c7f, 0x3bf1bc62, 0x3bf13c62, 0x3ac9bc7f, 0xbc223c46, 0x3c75bb95,
    0x3b95bc75, 0xbc463c22, 0x3c7fbac9, 0xbc62bbf1, 0xbc7bbb48, 0x3c553c0e, 0xbc0ebc55, 0x3b483c7b, 0x3b48bc7b, 0xbc0e3c55,
    0x3c55bc0e, 0xbc7b3b48, 0x3c7b3b48, 0xbc55bc0e, 0x3c0e3c55, 0xbb48bc7b, 0xbb483c7b, 0x3c0ebc55, 0xbc553c0e, 0x3c7bbb48,
    0xbc7bbb48, 0x3c553c0e, 0xbc0ebc55, 0x3b483c7b, 0x3b48bc7b, 0xbc0e3c55, 0x3c55bc0e, 0xbc7b3b48, 0x3c7b3b48, 0xbc55bc0e,
    0x3c0e3c55, 0xbb48bc7b, 0xbb483c7b, 0x3c0ebc55, 0xbc553c0e, 0x3c7bbb48, 0x3c46bc22, 0xbc623bf1, 0x3c75bb95, 0xbc7f3ac9,
    0x3ac9bc7f, 0xbb953c75, 0x3bf1bc62, 0xbc223c46, 0xbc22bc46, 0x3bf13c62, 0xbb95bc75, 0x3ac93c7f, 0xbc7fbac9, 0x3c753b95,
    0xbc62bbf1, 0x3c463c22, 0xbc463c22, 0x3c62bbf1, 0xbc753b95, 0x3c7fbac9, 0xbac93c7f, 0x3b95bc75, 0xbbf13c62, 0x3c22bc46,
    0x3c223c46, 0xbbf1bc62, 0x3b953c75, 0xbac9bc7f, 0x3c7f3ac9, 0xbc75bb95, 0x3c623bf1, 0xbc46bc22, 0x3c3e3c2c, 0x3c18bc4e,
    0xbc5cbc04, 0xbbdb3c67, 0x3c713bac, 0x3b79bc78, 0xbc7dbb16, 0xba493c80, 0x3c80ba49, 0xbb16bc7d, 0xbc783b79, 0x3bac3c71,
    0x3c67bbdb, 0xbc04bc5c, 0xbc4e3c18, 0x3c2c3c3e, 0x3c2cbc3e, 0xbc4ebc18, 0xbc043c5c, 0x3c673bdb, 0x3bacbc71, 0xbc78bb79,
    0xbb163c7d, 0x3c803a49, 0xba49bc80, 0xbc7d3b16, 0x3b793c78, 0x3c71bbac, 0xbbdbbc67, 0xbc5c3c04, 0x3c183c4e, 0x3c3ebc2c,
    0x3c5cbc04, 0xbc3ebc2c, 0xbbdb3c67, 0x3c7d3b16, 0x3c4e3c18, 0x3bacbc71, 0xbc80ba49, 0x3b793c78, 0xbc78bb79, 0x3a493c80,
    0x3c71bbac, 0xbc18bc4e, 0xbb16bc7d, 0xbc673bdb, 0x3c2c3c3e, 0x3c04bc5c, 0x3c043c5c, 0x3c2cbc3e, 0xbc67bbdb, 0xbb163c7d,
    0xbc183c4e, 0x3c713bac, 0x3a49bc80, 0xbc783b79, 0x3b79bc78, 0xbc803a49, 0x3bac3c71, 0x3c4ebc18, 0x3c7dbb16, 0xbbdbbc67,
    0xbc3e3c2c, 0x3c5c3c04, 0xbc783b79, 0x3c2c3c3e, 0x3bacbc71, 0xbc7d3b16, 0x3c183c4e, 0x3bdbbc67, 0xbc803a49, 0x3c043c5c,
    0x3c5c3c04, 0x3a49bc80, 0xbc673bdb, 0x3c4e3c18, 0x3b16bc7d, 0xbc713bac, 0x3c3e3c2c, 0x3b79bc78, 0x3b793c78, 0x3c3ebc2c,
    0xbc71bbac, 0x3b163c7d, 0x3c4ebc18, 0xbc67bbdb, 0x3a493c80, 0x3c5cbc04, 0x3c04bc5c, 0xbc80ba49, 0x3bdb3c67, 0x3c18bc4e,
    0xbc7dbb16, 0x3bac3c71, 0x3c2cbc3e, 0xbc78bb79, 0x3a49bc80, 0xbc4e3c18, 0x3c783b79, 0xbbdbbc67, 0x3bac3c71, 0x3c04bc5c,
    0xbc7d3b16, 0x3c3e3c2c, 0xbc2cbc3e, 0xbb163c7d, 0x3c5cbc04, 0xbc71bbac, 0x3c673bdb, 0xbb79bc78, 0xbc183c4e, 0x3c80ba49,
    0x3c803a49, 0xbc18bc4e, 0xbb793c78, 0x3c67bbdb, 0xbc713bac, 0x3c5c3c04, 0xbb16bc7d, 0xbc2c3c3e, 0x3c3ebc2c, 0xbc7dbb16,
    0x3c043c5c, 0x3bacbc71, 0xbbdb3c67, 0x3c78bb79, 0xbc4ebc18, 0x3a493c80, 0x3bacbc71, 0xbc5c3c04, 0x3c7d3b16, 0xbc2cbc3e,
    0x3a493c80, 0x3c18bc4e, 0xbc783b79, 0x3c673bdb, 0xbbdbbc67, 0xbb793c78, 0x3c4ebc18, 0xbc80ba49, 0x3c3e3c2c, 0xbb16bc7d,
    0xbc043c5c, 0x3c71bbac, 0x3c713bac, 0xbc04bc5c, 0xbb163c7d, 0x3c3ebc2c, 0xbc803a49, 0x3c4e3c18, 0xbb79bc78, 0xbbdb3c67,
    0x3c67bbdb, 0xbc78bb79, 0x3c183c4e, 0x3a49bc80, 0xbc2c3c3e, 0x3c7dbb16, 0xbc5cbc04, 0x3bac3c71, 0xbc4ebc18, 0x3bdb3c67,
    0x3a49bc80, 0xbc043c5c, 0xbb793c78, 0x3c2cbc3e, 0xbc713bac, 0x3c7d3b16, 0x3b163c7d, 0x3bacbc71, 0xbc3e3c2c, 0x3c78bb79,
    0x3c5cbc04, 0xbc803a49, 0x3c673bdb, 0xbc18bc4e, 0xbc183c4e, 0x3c67bbdb, 0xbc80ba49, 0x3c5c3c04, 0x3c783b79, 0xbc3ebc2c,
    0x3bac3c71, 0x3b16bc7d, 0x3c7dbb16, 0xbc71bbac, 0x3c2c3c3e, 0xbb79bc78, 0xbc04bc5c, 0x3a493c80, 0x3bdbbc67, 0xbc4e3c18,
    0x3c183c4e, 0xbbacbc71, 0x3a493c80, 0x3b79bc78, 0xbc043c5c, 0x3c3ebc2c, 0xbc673bdb, 0x3c7dbb16, 0x3b16bc7d, 0xbbdb3c67,
    0x3c2cbc3e, 0xbc5c3c04, 0x3c78bb79, 0xbc80ba49, 0x3c713bac, 0xbc4ebc18, 0xbc4e3c18, 0x3c71bbac, 0xbc803a49, 0x3c783b79,
    0xbc5cbc04, 0x3c2c3c3e, 0xbbdbbc67, 0x3b163c7d, 0x3c7d3b16, 0xbc67bbdb, 0x3c3e3c2c, 0xbc04bc5c, 0x3b793c78, 0x3a49bc80,
    0xbbac3c71, 0x3c18bc4e, 0xbc713bac, 0x3c78bb79, 0xbc7d3b16, 0x3c80ba49, 0xbc3e3c2c, 0x3c4ebc18, 0xbc5c3c04, 0x3c67bbdb,
    0xbbdb3c67, 0x3c04bc5c, 0xbc183c4e, 0x3c2cbc3e, 0xba493c80, 0x3b16bc7d, 0xbb793c78, 0x3bacbc71, 0x3bac3c71, 0xbb79bc78,
    0x3b163c7d, 0xba49bc80, 0x3c2c3c3e, 0xbc18bc4e, 0x3c043c5c, 0xbbdbbc67, 0x3c673bdb, 0xbc5cbc04, 0x3c4e3c18, 0xbc3ebc2c,
    0x3c803a49, 0xbc7dbb16, 0x3c783b79, 0xbc71bbac, 0x3c800000, 0xbc800000, 0x3c800000, 0xbc800000, 0x3c800000, 0xbc800000,
    0x3c800000, 0xbc800000, 0x3c800000, 0xbc800000, 0x3c800000, 0xbc800000, 0x3c800000, 0xbc800000, 0x3c800000, 0xbc800000,
    0x3c800000, 0xbc800000, 0x3c800000, 0xbc800000, 0x3c800000, 0xbc800000, 0x3c800000, 0xbc800000, 0x3c800000, 0xbc800000,
    0x3c800000, 0xbc800000, 0x3c800000, 0xbc800000, 0x3c800000, 0xbc800000, 0x3c22bc46, 0xbbf13c62, 0x3b95bc75, 0xbac93c7f,
    0x3c7fbac9, 0xbc753b95, 0x3c62bbf1, 0xbc463c22, 0xbc46bc22, 0x3c623bf1, 0xbc75bb95, 0x3c7f3ac9, 0xbac9bc7f, 0x3b953c75,
    0xbbf1bc62, 0x3c223c46, 0xbc223c46, 0x3bf1bc62, 0xbb953c75, 0x3ac9bc7f, 0xbc7f3ac9, 0x3c75bb95, 0xbc623bf1, 0x3c46bc22,
    0x3c463c22, 0xbc62bbf1, 0x3c753b95, 0xbc7fbac9, 0x3ac93c7f, 0xbb95bc75, 0x3bf13c62, 0xbc22bc46, 0xbc7b3b48, 0x3c55bc0e,
    0xbc0e3c55, 0x3b48bc7b, 0x3b483c7b, 0xbc0ebc55, 0x3c553c0e, 0xbc7bbb48, 0x3c7bbb48, 0xbc553c0e, 0x3c0ebc55, 0xbb483c7b,
    0xbb48bc7b, 0x3c0e3c55, 0xbc55bc0e, 0x3c7b3b48, 0xbc7b3b48, 0x3c55bc0e, 0xbc0e3c55, 0x3b48bc7b, 0x3b483c7b, 0xbc0ebc55,
    0x3c553c0e, 0xbc7bbb48, 0x3c7bbb48, 0xbc553c0e, 0x3c0ebc55, 0xbb483c7b, 0xbb48bc7b, 0x3c0e3c55, 0xbc55bc0e, 0x3c7b3b48,
    0x3bf1bc62, 0x3ac93c7f, 0xbc22bc46, 0x3c753b95, 0x3b953c75, 0xbc46bc22, 0x3c7f3ac9, 0xbc623bf1, 0xbc62bbf1, 0x3c7fbac9,
    0xbc463c22, 0x3b95bc75, 0x3c75bb95, 0xbc223c46, 0x3ac9bc7f, 0x3bf13c62, 0xbbf13c62, 0xbac9bc7f, 0x3c223c46, 0xbc75bb95,
    0xbb95bc75, 0x3c463c22, 0xbc7fbac9, 0x3c62bbf1, 0x3c623bf1, 0xbc7f3ac9, 0x3c46bc22, 0xbb953c75, 0xbc753b95, 0x3c22bc46,
    0xbac93c7f, 0xbbf1bc62, 0x3c6dbbc4, 0xbbc43c6d, 0xbbc4bc6d, 0x3c6d3bc4, 0xbc6d3bc4, 0x3bc4bc6d, 0x3bc43c6d, 0xbc6dbbc4,
    0x3c6dbbc4, 0xbbc43c6d, 0xbbc4bc6d, 0x3c6d3bc4, 0xbc6d3bc4, 0x3bc4bc6d, 0x3bc43c6d, 0xbc6dbbc4, 0x3c6dbbc4, 0xbbc43c6d,
    0xbbc4bc6d, 0x3c6d3bc4, 0xbc6d3bc4, 0x3bc4bc6d, 0x3bc43c6d, 0xbc6dbbc4, 0x3c6dbbc4, 0xbbc43c6d, 0xbbc4bc6d, 0x3c6d3bc4,
    0xbc6d3bc4, 0x3bc4bc6d, 0x3bc43c6d, 0xbc6dbbc4, 0x3b95bc75, 0x3c223c46, 0xbc7f3ac9, 0x3bf1bc62, 0xbc623bf1, 0x3ac9bc7f,
    0x3c463c22, 0xbc753b95, 0xbc75bb95, 0x3c46bc22, 0x3ac93c7f, 0xbc62bbf1, 0x3bf13c62, 0xbc7fbac9, 0x3c22bc46, 0x3b953c75,
    0xbb953c75, 0xbc22bc46, 0x3c7fbac9, 0xbbf13c62, 0x3c62bbf1, 0xbac93c7f, 0xbc46bc22, 0x3c75bb95, 0x3c753b95, 0xbc463c22,
    0xbac9bc7f, 0x3c623bf1, 0xbbf1bc62, 0x3c7f3ac9, 0xbc223c46, 0xbb95bc75, 0xbc553c0e, 0xbb48bc7b, 0x3c7b3b48, 0xbc0e3c55,
    0xbc0ebc55, 0x3c7bbb48, 0xbb483c7b, 0xbc55bc0e, 0x3c55bc0e, 0x3b483c7b, 0xbc7bbb48, 0x3c0ebc55, 0x3c0e3c55, 0xbc7b3b48,
    0x3b48bc7b, 0x3c553c0e, 0xbc553c0e, 0xbb48bc7b, 0x3c7b3b48, 0xbc0e3c55, 0xbc0ebc55, 0x3c7bbb48, 0xbb483c7b, 0xbc55bc0e,
    0x3c55bc0e, 0x3b483c7b, 0xbc7bbb48, 0x3c0ebc55, 0x3c0e3c55, 0xbc7b3b48, 0x3b48bc7b, 0x3c553c0e, 0x3ac9bc7f, 0x3c753b95,
    0xbbf13c62, 0xbc46bc22, 0xbc22bc46, 0x3c62bbf1, 0x3b953c75, 0xbc7f3ac9, 0xbc7fbac9, 0x3b95bc75, 0x3c623bf1, 0xbc223c46,
    0xbc463c22, 0xbbf1bc62, 0x3c75bb95, 0x3ac93c7f, 0xbac93c7f, 0xbc75bb95, 0x3bf1bc62, 0x3c463c22, 0x3c223c46, 0xbc623bf1,
    0xbb95bc75, 0x3c7fbac9, 0x3c7f3ac9, 0xbb953c75, 0xbc62bbf1, 0x3c22bc46, 0x3c46bc22, 0x3bf13c62, 0xbc753b95, 0xbac9bc7f,
    0x3c80ba49, 0xbc7d3b16, 0x3c78bb79, 0xbc713bac, 0x3c67bbdb, 0xbc5c3c04, 0x3c4ebc18, 0xbc3e3c2c, 0x3c2cbc3e, 0xbc183c4e,
    0x3c04bc5c, 0xbbdb3c67, 0x3bacbc71, 0xbb793c78, 0x3b16bc7d, 0xba493c80, 0xba49bc80, 0x3b163c7d, 0xbb79bc78, 0x3bac3c71,
    0xbbdbbc67, 0x3c043c5c, 0xbc18bc4e, 0x3c2c3c3e, 0xbc3ebc2c, 0x3c4e3c18, 0xbc5cbc04, 0x3c673bdb, 0xbc71bbac, 0x3c783b79,
    0xbc7dbb16, 0x3c803a49, 0x3b79bc78, 0x3a493c80, 0xbbacbc71, 0x3c183c4e, 0x3c7dbb16, 0xbc673bdb, 0x3c3ebc2c, 0xbc043c5c,
    0xbc5c3c04, 0x3c2cbc3e, 0xbbdb3c67, 0x3b16bc7d, 0xbc4ebc18, 0x3c713bac, 0xbc80ba49, 0x3c78bb79, 0x3c783b79, 0xbc803a49,
    0x3c71bbac, 0xbc4e3c18, 0x3b163c7d, 0xbbdbbc67, 0x3c2c3c3e, 0xbc5cbc04, 0xbc04bc5c, 0x3c3e3c2c, 0xbc67bbdb, 0x3c7d3b16,
    0x3c18bc4e, 0xbbac3c71, 0x3a49bc80, 0x3b793c78, 0xbc043c5c, 0x3a49bc80, 0x3bdb3c67, 0xbc4ebc18, 0x3c7d3b16, 0xbc713bac,
    0x3c2cbc3e, 0xbb793c78, 0x3c78bb79, 0xbc3e3c2c, 0x3bacbc71, 0x3b163c7d, 0xbc18bc4e, 0x3c673bdb, 0xbc803a49, 0x3c5cbc04,
    0x3c5c3c04, 0xbc80ba49, 0x3c67bbdb, 0xbc183c4e, 0x3b16bc7d, 0x3bac3c71, 0xbc3ebc2c, 0x3c783b79, 0xbb79bc78, 0x3c2c3c3e,
    0xbc71bbac, 0x3c7dbb16, 0xbc4e3c18, 0x3bdbbc67, 0x3a493c80, 0xbc04bc5c, 0xbc2cbc3e, 0x3c7d3b16, 0xbc5c3c04, 0x3bacbc71,
    0x3c673bdb, 0xbc783b79, 0x3c18bc4e, 0x3a493c80, 0xbc80ba49, 0x3c4ebc18, 0xbb793c78, 0xbbdbbc67, 0x3c71bbac, 0xbc043c5c,
    0xbb16bc7d, 0x3c3e3c2c, 0x3c3ebc2c, 0xbb163c7d, 0xbc04bc5c, 0x3c713bac, 0xbbdb3c67, 0xbb79bc78, 0x3c4e3c18, 0xbc803a49,
    0x3a49bc80, 0x3c183c4e, 0xbc78bb79, 0x3c67bbdb, 0x3bac3c71, 0xbc5cbc04, 0x3c7dbb16, 0xbc2c3c3e, 0xbbdbbc67, 0x3c783b79,
    0xbc4e3c18, 0x3a49bc80, 0x3c3e3c2c, 0xbc7d3b16, 0x3c04bc5c, 0x3bac3c71, 0xbc71bbac, 0x3c5cbc04, 0xbb163c7d, 0xbc2cbc3e,
    0x3c80ba49, 0xbc183c4e, 0xbb79bc78, 0x3c673bdb, 0x3c67bbdb, 0xbb793c78, 0xbc18bc4e, 0x3c803a49, 0xbc2c3c3e, 0xbb16bc7d,
    0x3c5c3c04, 0xbc713bac, 0x3bacbc71, 0x3c043c5c, 0xbc7dbb16, 0x3c3ebc2c, 0x3a493c80, 0xbc4ebc18, 0x3c78bb79, 0xbbdb3c67,
    0xbc7d3b16, 0x3bacbc71, 0x3c2c3c3e, 0xbc783b79, 0x3c043c5c, 0xbc803a49, 0x3bdbbc67, 0x3c183c4e, 0x3c4e3c18, 0xbc673bdb,
    0x3a49bc80, 0x3c5c3c04, 0x3b79bc78, 0x3c3e3c2c, 0xbc713bac, 0x3b16bc7d, 0x3b163c7d, 0xbc71bbac, 0x3c3ebc2c, 0x3b793c78,
    0x3c5cbc04, 0x3a493c80, 0xbc67bbdb, 0x3c4ebc18, 0x3c18bc4e, 0x3bdb3c67, 0xbc80ba49, 0x3c04bc5c, 0xbc78bb79, 0x3c2cbc3e,
    0x3bac3c71, 0xbc7dbb16, 0x3c7d3b16, 0xbbdb3c67, 0xbc3ebc2c, 0x3c5cbc04, 0x3b793c78, 0xbc80ba49, 0x3bacbc71, 0x3c4e3c18,
    0xbc18bc4e, 0x3c71bbac, 0x3a493c80, 0xbc78bb79, 0x3c04bc5c, 0x3c2c3c3e, 0xbc673bdb, 0xbb16bc7d, 0xbb163c7d, 0xbc67bbdb,
    0x3c2cbc3e, 0x3c043c5c, 0xbc783b79, 0x3a49bc80, 0x3c713bac, 0xbc183c4e, 0x3c4ebc18, 0x3bac3c71, 0xbc803a49, 0x3b79bc78,
    0x3c5c3c04, 0xbc3e3c2c, 0xbbdbbc67, 0x3c7dbb16, 0xbbdb3c67, 0xbc5cbc04, 0x3c18bc4e, 0x3c3e3c2c, 0xba493c80, 0xbc7dbb16,
    0x3b79bc78, 0x3c713bac, 0x3bac3c71, 0xbc783b79, 0xbb16bc7d, 0x3c80ba49, 0x3c2c3c3e, 0xbc4e3c18, 0xbc04bc5c, 0x3c67bbdb,
    0x3c673bdb, 0xbc043c5c, 0xbc4ebc18, 0x3c2cbc3e, 0x3c803a49, 0xbb163c7d, 0xbc78bb79, 0x3bacbc71, 0x3c71bbac, 0x3b793c78,
    0xbc7d3b16, 0xba49bc80, 0x3c3ebc2c, 0x3c183c4e, 0xbc5c3c04, 0xbbdbbc67, 0x3f803f80, 0x3f7d3f7f, 0x3f783f7b, 0x3f713f75,
    0x3f673f6d, 0x3f5c3f62, 0x3f4e3f55, 0x3f3e3f46, 0x3f2c3f35, 0x3f183f22, 0x3f043f0e, 0x3edb3ef1, 0x3eac3ec4, 0x3e793e95,
    0x3e163e48, 0x3d493dc9, 0xbd490000, 0xbe16bdc9, 0xbe79be48, 0xbeacbe95, 0xbedbbec4, 0xbf04bef1, 0xbf18bf0e, 0xbf2cbf22,
    0xbf3ebf35, 0xbf4ebf46, 0xbf5cbf55, 0xbf67bf62, 0xbf71bf6d, 0xbf78bf75, 0xbf7dbf7b, 0xbf80bf7f, 0x3edb3ec4, 0x3f043ef1,
    0x3f183f0e, 0x3f2c3f22, 0x3d490000, 0x3e163dc9, 0x3e793e48, 0x3eac3e95, 0x3f713f6d, 0x3f783f75, 0x3f7d3f7b, 0x3f803f7f,
    0x3f3e3f35, 0x3f4e3f46, 0x3f5c3f55, 0x3f673f62, 0x3f673f6d, 0x3f5c3f62, 0x3f4e3f55, 0x3f3e3f46, 0x3f803f80, 0x3f7d3f7f,
    0x3f783f7b, 0x3f713f75, 0x3eac3ec4, 0x3e793e95, 0x3e163e48, 0x3d493dc9, 0x3f2c3f35, 0x3f183f22, 0x3f043f0e, 0x3edb3ef1,
    0xbf4ebf35, 0xbf71bf62, 0xbf80bf7b, 0xbf78bf7f, 0xbf5cbf6d, 0xbf2cbf46, 0xbedbbf0e, 0xbe16be95, 0x3f7d3f80, 0x3f673f75,
    0x3f3e3f55, 0x3f043f22, 0x3e793ec4, 0xbd493dc9, 0xbeacbe48, 0xbf18bef1, 0x3f183f35, 0x3eac3ef1, 0x3d493e48, 0xbe79bdc9,
    0xbf04bec4, 0xbf3ebf22, 0xbf67bf55, 0xbf7dbf75, 0x3e160000, 0x3edb3e95, 0x3f2c3f0e, 0x3f5c3f46, 0x3f783f6d, 0x3f803f7f,
    0x3f713f7b, 0x3f4e3f62, 0xbf04bec4, 0xbf3ebf22, 0xbf67bf55, 0xbf7dbf75, 0x3f183f35, 0x3eac3ef1, 0x3d493e48, 0xbe79bdc9,
    0x3f783f6d, 0x3f803f7f, 0x3f713f7b, 0x3f4e3f62, 0x3e160000, 0x3edb3e95, 0x3f2c3f0e, 0x3f5c3f46, 0x3f5c3f6d, 0x3f2c3f46,
    0x3edb3f0e, 0x3e163e95, 0x3f4e3f35, 0x3f713f62, 0x3f803f7b, 0x3f783f7f, 0xbe79bec4, 0x3d49bdc9, 0x3eac3e48, 0x3f183ef1,
    0xbf7dbf80, 0xbf67bf75, 0xbf3ebf55, 0xbf04bf22, 0xbe790000, 0xbf2cbef1, 0xbf71bf55, 0xbf7dbf7f, 0xbf4ebf6d, 0xbedbbf22,
    0x3d49be48, 0x3f043e95, 0x3f5c3f35, 0x3f803f75, 0x3f673f7b, 0x3f183f46, 0x3e163ec4, 0xbeacbdc9, 0xbf3ebf0e, 0xbf78bf62,
    0x3f783f80, 0x3f3e3f62, 0x3eac3f0e, 0xbe163dc9, 0xbf18bec4, 0xbf67bf46, 0xbf80bf7b, 0xbf5cbf75, 0xbf04bf35, 0xbd49be95,
    0x3edb3e48, 0x3f4e3f22, 0x3f7d3f6d, 0x3f713f7f, 0x3f2c3f55, 0x3e793ef1, 0xbf18bec4, 0xbf67bf46, 0xbf80bf7b, 0xbf5cbf75,
    0x3f783f80, 0x3f3e3f62, 0x3eac3f0e, 0xbe163dc9, 0x3f7d3f6d, 0x3f713f7f, 0x3f2c3f55, 0x3e793ef1, 0xbf04bf35, 0xbd49be95,
    0x3edb3e48, 0x3f4e3f22, 0x3f4e3f6d, 0x3edb3f22, 0xbd493e48, 0xbf04be95, 0x3e790000, 0x3f2c3ef1, 0x3f713f55, 0x3f7d3f7f,
    0xbe16bec4, 0x3eac3dc9, 0x3f3e3f0e, 0x3f783f62, 0xbf5cbf35, 0xbf80bf75, 0xbf67bf7b, 0xbf18bf46, 0xbedbbf35, 0x3e79bdc9,
    0x3f4e3f0e, 0x3f803f75, 0x3f3e3f6d, 0x3e163ef1, 0xbf04be48, 0xbf71bf46, 0x3eac0000, 0x3f5c3f22, 0x3f7d3f7b, 0x3f2c3f62,
    0x3d493ec4, 0xbf18be95, 0xbf78bf55, 0xbf67bf7f, 0x3f673f35, 0x3f783f7f, 0x3f183f55, 0xbd493e95, 0xbf2cbec4, 0xbf7dbf62,
    0xbf5cbf7b, 0xbeacbf22, 0x3f713f80, 0x3f043f46, 0xbe163e48, 0xbf3ebef1, 0xbf80bf6d, 0xbf4ebf75, 0xbe79bf0e, 0x3edb3dc9,
    0x3f2c3ec4, 0x3f7d3f62, 0x3f5c3f7b, 0x3eac3f22, 0xbf67bf35, 0xbf78bf7f, 0xbf18bf55, 0x3d49be95, 0x3f803f6d, 0x3f4e3f75,
    0x3e793f0e, 0xbedbbdc9, 0xbf71bf80, 0xbf04bf46, 0x3e16be48, 0x3f3e3ef1, 0x3f3e3f6d, 0x3e163ef1, 0xbf04be48, 0xbf71bf46,
    0xbedbbf35, 0x3e79bdc9, 0x3f4e3f0e, 0x3f803f75, 0x3d493ec4, 0xbf18be95, 0xbf78bf55, 0xbf67bf7f, 0x3eac0000, 0x3f5c3f22,
    0x3f7d3f7b, 0x3f2c3f62, 0x3f673f80, 0x3e793f22, 0xbf18be48, 0xbf80bf62, 0xbf2cbf6d, 0x3e16be95, 0x3f5c3f0e, 0x3f713f7f,
    0x3eac3f35, 0xbf04bdc9, 0xbf7dbf55, 0xbf3ebf75, 0x3d49bec4, 0x3f4e3ef1, 0x3f783f7b, 0x3edb3f46, 0xbedb0000, 0xbf78bf46,
    0xbf4ebf7b, 0xbd49bef1, 0x3f3e3ec4, 0x3f7d3f75, 0x3f043f55, 0xbeac3dc9, 0xbf71bf35, 0xbf5cbf7f, 0xbe16bf0e, 0x3f2c3e95,
    0x3f803f6d, 0x3f183f62, 0xbe793e48, 0xbf67bf22, 0xbf3ebec4, 0xbf7dbf75, 0xbf04bf55, 0x3eacbdc9, 0x3edb0000, 0x3f783f46,
    0x3f4e3f7b, 0x3d493ef1, 0xbf80bf6d, 0xbf18bf62, 0x3e79be48, 0x3f673f22, 0x3f713f35, 0x3f5c3f7f, 0x3e163f0e, 0xbf2cbe95,
    0xbf2cbf6d, 0x3e16be95, 0x3f5c3f0e, 0x3f713f7f, 0x3f673f80, 0x3e793f22, 0xbf18be48, 0xbf80bf62, 0x3d49bec4, 0x3f4e3ef1,
    0x3f783f7b, 0x3edb3f46, 0x3eac3f35, 0xbf04bdc9, 0xbf7dbf55, 0xbf3ebf75, 0xbf78bf35, 0xbf2cbf75, 0x3eacbe48, 0x3f7d3f46,
    0x3f183f6d, 0xbedb3dc9, 0xbf80bf55, 0xbf04bf62, 0x3f5c3f80, 0xbd493ef1, 0xbf67bf0e, 0xbf4ebf7f, 0x3e16bec4, 0x3f713f22,
    0x3f3e3f7b, 0xbe793e95, 0x3e793f35, 0xbf3ebe95, 0xbf71bf7b, 0xbe16bf22, 0x3f4e3ec4, 0x3f673f7f, 0x3d493f0e, 0xbf5cbef1,
    0x3f040000, 0x3f803f62, 0x3edb3f55, 0xbf18bdc9, 0xbf7dbf6d, 0xbeacbf46, 0x3f2c3e48, 0x3f783f75, 0x3f4e3ec4, 0x3f673f7f,
    0x3d493f0e, 0xbf5cbef1, 0x3e793f35, 0xbf3ebe95, 0xbf71bf7b, 0xbe16bf22, 0xbf7dbf6d, 0xbeacbf46, 0x3f2c3e48, 0x3f783f75,
    0x3f040000, 0x3f803f62, 0x3edb3f55, 0xbf18bdc9, 0xbf18bf6d, 0x3edbbdc9, 0x3f803f55, 0x3f043f62, 0x3f783f35, 0x3f2c3f75,
    0xbeac3e48, 0xbf7dbf46, 0xbe163ec4, 0xbf71bf22, 0xbf3ebf7b, 0x3e79be95, 0xbf5cbf80, 0x3d49bef1, 0x3f673f0e, 0x3f4e3f7f,
    0xbf180000, 0xbf71bf75, 0x3d49bf0e, 0x3f783f22, 0x3f043f6d, 0xbf2cbdc9, 0xbf67bf7b, 0x3e16bef1, 0x3f7d3f35, 0x3edb3f62,
    0xbf3ebe48, 0xbf5cbf7f, 0x3e79bec4, 0x3f803f46, 0x3eac3f55, 0xbf4ebe95, 0x3f4e3f80, 0xbeac3e95, 0xbf80bf55, 0xbe79bf46,
    0x3f5c3ec4, 0x3f3e3f7f, 0xbedb3e48, 0xbf7dbf62, 0xbe16bf35, 0x3f673ef1, 0x3f2c3f7b, 0xbf043dc9, 0xbf78bf6d, 0xbd49bf22,
    0x3f713f0e, 0x3f183f75, 0x3f5c3ec4, 0x3f3e3f7f, 0xbedb3e48, 0xbf7dbf62, 0x3f4e3f80, 0xbeac3e95, 0xbf80bf55, 0xbe79bf46,
    0xbf78bf6d, 0xbd49bf22, 0x3f713f0e, 0x3f183f75, 0xbe16bf35, 0x3f673ef1, 0x3f2c3f7b, 0xbf043dc9, 0xbf04bf6d, 0x3f2c3dc9,
    0x3f673f7b, 0xbe163ef1, 0x3f180000, 0x3f713f75, 0xbd493f0e, 0xbf78bf22, 0xbe793ec4, 0xbf80bf46, 0xbeacbf55, 0x3f4e3e95,
    0xbf7dbf35, 0xbedbbf62, 0x3f3e3e48, 0x3f5c3f7f, 0xbd49bf35, 0x3f7d3f22, 0x3e793f55, 0xbf71bef1, 0xbedbbf6d, 0x3f5c3e95,
    0x3f183f7b, 0xbf3ebdc9, 0x3f2c0000, 0x3f4e3f7f, 0xbf043e48, 0xbf67bf75, 0x3eacbec4, 0x3f783f62, 0xbe163f0e, 0xbf80bf46,
    0x3f803f35, 0x3e163f46, 0xbf78bf0e, 0xbeacbf62, 0x3f673ec4, 0x3f043f75, 0xbf4ebe48, 0xbf2cbf7f, 0x3f3e3f80, 0xbf183dc9,
    0xbf5cbf7b, 0x3edbbe95, 0x3f713f6d, 0xbe793ef1, 0xbf7dbf55, 0x3d49bf22, 0xbf67bec4, 0xbf04bf75, 0x3f4e3e48, 0x3f2c3f7f,
    0xbf80bf35, 0xbe16bf46, 0x3f783f0e, 0x3eac3f62, 0xbf71bf6d, 0x3e79bef1, 0x3f7d3f55, 0xbd493f22, 0xbf3ebf80, 0x3f18bdc9,
    0x3f5c3f7b, 0xbedb3e95, 0xbedbbf6d, 0x3f5c3e95, 0x3f183f7b, 0xbf3ebdc9, 0xbd49bf35, 0x3f7d3f22, 0x3e793f55, 0xbf71bef1,
    0x3eacbec4, 0x3f783f62, 0xbe163f0e, 0xbf80bf46, 0x3f2c0000, 0x3f4e3f7f, 0xbf043e48, 0xbf67bf75, 0x3f2c3f80, 0xbf4ebdc9,
    0xbf04bf7b, 0x3f673e95, 0x3eac3f6d, 0xbf78bef1, 0xbe16bf55, 0x3f803f22, 0xbd493f35, 0xbf7dbf46, 0x3e79bf0e, 0x3f713f62,
    0xbedb3ec4, 0xbf5cbf75, 0x3f18be48, 0x3f3e3f7f, 0xbf3e0000, 0xbf18bf7f, 0x3f5c3e48, 0x3edb3f75, 0xbf71bec4, 0xbe79bf62,
    0x3f7d3f0e, 0x3d493f46, 0xbf80bf35, 0x3e16bf22, 0x3f783f55, 0xbeac3ef1, 0xbf67bf6d, 0x3f04be95, 0x3f4e3f7b, 0xbf2c3dc9,
    0x3f713ec4, 0x3e793f62, 0xbf7dbf0e, 0xbd49bf46, 0x3f3e0000, 0x3f183f7f, 0xbf5cbe48, 0xbedbbf75, 0x3f673f6d, 0xbf043e95,
    0xbf4ebf7b, 0x3f2cbdc9, 0x3f803f35, 0xbe163f22, 0xbf78bf55, 0x3eacbef1, 0x3eac3f6d, 0xbf78bef1, 0xbe16bf55, 0x3f803f22,
    0x3f2c3f80, 0xbf4ebdc9, 0xbf04bf7b, 0x3f673e95, 0xbedb3ec4, 0xbf5cbf75, 0x3f18be48, 0x3f3e3f7f, 0xbd493f35, 0xbf7dbf46,
    0x3e79bf0e, 0x3f713f62, 0xbf7dbf35, 0x3edbbef1, 0x3f3e3f7b, 0xbf5cbdc9, 0xbe79bf6d, 0x3f803f22, 0xbeac3f0e, 0xbf4ebf75,
    0x3f183f80, 0xbf71be95, 0xbd49bf55, 0x3f783f46, 0xbf043ec4, 0xbf2cbf7f, 0x3f673e48, 0x3e163f62, 0xbe163f35, 0xbf67bf62,
    0x3f2cbe48, 0x3f043f7f, 0xbf78bec4, 0x3d49bf46, 0x3f713f55, 0xbf183e95, 0x3f4e0000, 0x3eac3f75, 0xbf80bf0e, 0x3e79bf22,
    0x3f5c3f6d, 0xbf3e3dc9, 0xbedbbf7b, 0x3f7d3ef1, 0xbf78bec4, 0x3d49bf46, 0x3f713f55, 0xbf183e95, 0xbe163f35, 0xbf67bf62,
    0x3f2cbe48, 0x3f043f7f, 0x3f5c3f6d, 0xbf3e3dc9, 0xbedbbf7b, 0x3f7d3ef1, 0x3f4e0000, 0x3eac3f75, 0xbf80bf0e, 0x3e79bf22,
    0x3e793f6d, 0xbf80bf22, 0x3eacbf0e, 0x3f4e3f75, 0x3f7d3f35, 0xbedb3ef1, 0xbf3ebf7b, 0x3f5c3dc9, 0x3f04bec4, 0x3f2c3f7f,
    0xbf67be48, 0xbe16bf62, 0xbf18bf80, 0x3f713e95, 0x3d493f55, 0xbf78bf46, 0xbf5c0000, 0xbd49bf62, 0x3f673f55, 0xbf4e3dc9,
    0xbe16bf6d, 0x3f713f46, 0xbf3e3e48, 0xbe79bf75, 0x3f783f35, 0xbf2c3e95, 0xbeacbf7b, 0x3f7d3f22, 0xbf183ec4, 0xbedbbf7f,
    0x3f803f0e, 0xbf043ef1, 0x3f043f80, 0xbf80bef1, 0x3edbbf0e, 0x3f183f7f, 0xbf7dbec4, 0x3eacbf22, 0x3f2c3f7b, 0xbf78be95,
    0x3e79bf35, 0x3f3e3f75, 0xbf71be48, 0x3e16bf46, 0x3f4e3f6d, 0xbf67bdc9, 0x3d49bf55, 0x3f5c3f62, 0xbf7dbec4, 0x3eacbf22,
    0x3f2c3f7b, 0xbf78be95, 0x3f043f80, 0xbf80bef1, 0x3edbbf0e, 0x3f183f7f, 0x3f4e3f6d, 0xbf67bdc9, 0x3d49bf55, 0x3f5c3f62,
    0x3e79bf35, 0x3f3e3f75, 0xbf71be48, 0x3e16bf46, 0x3e163f6d, 0xbf71bf46, 0x3f3ebe48, 0x3e793f75, 0x3f5c0000, 0x3d493f62,
    0xbf67bf55, 0x3f4ebdc9, 0x3f18bec4, 0x3edb3f7f, 0xbf80bf0e, 0x3f04bef1, 0xbf78bf35, 0x3f2cbe95, 0x3eac3f7b, 0xbf7dbf22,
    0x3eacbf35, 0x3f043f7f, 0xbf7dbf0e, 0x3f3ebe95, 0x3d493f6d, 0xbf4ebf62, 0x3f783e48, 0xbedb3f22, 0x3f670000, 0xbe793f46,
    0xbf18bf7b, 0x3f803ef1, 0xbf2c3ec4, 0xbe16bf75, 0x3f5c3f55, 0xbf71bdc9, 0x3f713f35, 0xbf5c3dc9, 0x3e16bf55, 0x3f2c3f75,
    0xbf80bec4, 0x3f18bef1, 0x3e793f7b, 0xbf67bf46, 0x3edb3f80, 0xbf78bf22, 0x3f4ebe48, 0xbd493f62, 0xbf3ebf6d, 0x3f7d3e95,
    0xbf043f0e, 0xbeacbf7f, 0x3f803ec4, 0xbf183ef1, 0xbe79bf7b, 0x3f673f46, 0xbf71bf35, 0x3f5cbdc9, 0xbe163f55, 0xbf2cbf75,
    0x3f3e3f6d, 0xbf7dbe95, 0x3f04bf0e, 0x3eac3f7f, 0xbedbbf80, 0x3f783f22, 0xbf4e3e48, 0x3d49bf62, 0x3d493f6d, 0xbf4ebf62,
    0x3f783e48, 0xbedb3f22, 0x3eacbf35, 0x3f043f7f, 0xbf7dbf0e, 0x3f3ebe95, 0xbf2c3ec4, 0xbe16bf75, 0x3f5c3f55, 0xbf71bdc9,
    0x3f670000, 0xbe793f46, 0xbf18bf7b, 0x3f803ef1, 0x3eac3f80, 0xbf5cbf46, 0x3f7d3e48, 0xbf2c3ef1, 0x3d49bf6d, 0x3f183f75,
    0xbf78bf0e, 0x3f67bdc9, 0xbedb3f35, 0xbe79bf7f, 0x3f4e3f55, 0xbf80be95, 0x3f3ebec4, 0xbe163f62, 0xbf04bf7b, 0x3f713f22,
    0xbf710000, 0x3f04bf22, 0x3e163f7b, 0xbf3ebf62, 0x3f803ec4, 0xbf4e3e95, 0x3e79bf55, 0x3edb3f7f, 0xbf67bf35, 0x3f783dc9,
    0xbf183f0e, 0xbd49bf75, 0x3f2c3f6d, 0xbf7dbef1, 0x3f5cbe48, 0xbeac3f46, 0xbf80bec4, 0x3f4ebe95, 0xbe793f55, 0xbedbbf7f,
    0x3f710000, 0xbf043f22, 0xbe16bf7b, 0x3f3e3f62, 0xbf2cbf6d, 0x3f7d3ef1, 0xbf5c3e48, 0x3eacbf46, 0x3f673f35, 0xbf78bdc9,
    0x3f18bf0e, 0x3d493f75, 0x3d49bf6d, 0x3f183f75, 0xbf78bf0e, 0x3f67bdc9, 0x3eac3f80, 0xbf5cbf46, 0x3f7d3e48, 0xbf2c3ef1,
    0x3f3ebec4, 0xbe163f62, 0xbf04bf7b, 0x3f713f22, 0xbedb3f35, 0xbe79bf7f, 0x3f4e3f55, 0xbf80be95, 0xbf5cbf35, 0x3f803e95,
    0xbf673e48, 0x3f18bf22, 0xbe163f6d, 0xbeacbf7f, 0x3f3e3f55, 0xbf78bef1, 0x3e793f80, 0xbf2cbf62, 0x3f713f0e, 0xbf7dbdc9,
    0x3f4ebec4, 0xbedb3f46, 0xbd49bf7b, 0x3f043f75, 0xbf043f35, 0x3d49bf75, 0x3edb3f7b, 0xbf4ebf46, 0x3f7d3ec4, 0xbf713dc9,
    0x3f2cbf0e, 0xbe793f62, 0x3f780000, 0xbf3e3ef1, 0x3eacbf55, 0x3e163f7f, 0xbf18bf6d, 0x3f673f22, 0xbf80be48, 0x3f5cbe95,
    0x3f7d3ec4, 0xbf713dc9, 0x3f2cbf0e, 0xbe793f62, 0xbf043f35, 0x3d49bf75, 0x3edb3f7b, 0xbf4ebf46, 0xbf18bf6d, 0x3f673f22,
    0xbf80be48, 0x3f5cbe95, 0x3f780000, 0xbf3e3ef1, 0x3eacbf55, 0x3e163f7f, 0x3e16bf6d, 0x3eac3f7f, 0xbf3ebf55, 0x3f783ef1,
    0x3f5c3f35, 0xbf80be95, 0x3f67be48, 0xbf183f22, 0xbf4e3ec4, 0x3edbbf46, 0x3d493f7b, 0xbf04bf75, 0xbe79bf80, 0x3f2c3f62,
    0xbf71bf0e, 0x3f7d3dc9, 0xbf7d0000, 0x3f67be95, 0xbf3e3f0e, 0x3f04bf46, 0xbe793f6d, 0xbd49bf7f, 0x3eac3f7b, 0xbf18bf62,
    0x3f4e3f35, 0xbf71bef1, 0x3f803e48, 0xbf783dc9, 0x3f5cbec4, 0xbf2c3f22, 0x3edbbf55, 0xbe163f75, 0x3e163f80, 0xbedbbf75,
    0x3f2c3f55, 0xbf5cbf22, 0x3f783ec4, 0xbf80bdc9, 0x3f71be48, 0xbf4e3ef1, 0x3f18bf35, 0xbeac3f62, 0x3d49bf7b, 0x3e793f7f,
    0xbf04bf6d, 0x3f3e3f46, 0xbf67bf0e, 0x3f7d3e95, 0x3f783ec4, 0xbf80bdc9, 0x3f71be48, 0xbf4e3ef1, 0x3e163f80, 0xbedbbf75,
    0x3f2c3f55, 0xbf5cbf22, 0xbf04bf6d, 0x3f3e3f46, 0xbf67bf0e, 0x3f7d3e95, 0x3f18bf35, 0xbeac3f62, 0x3d49bf7b, 0x3e793f7f,
    0x3e79bf6d, 0x3d493f7f, 0xbeacbf7b, 0x3f183f62, 0x3f7d0000, 0xbf673e95, 0x3f3ebf0e, 0xbf043f46, 0xbf5c3ec4, 0x3f2cbf22,
    0xbedb3f55, 0x3e16bf75, 0xbf4ebf35, 0x3f713ef1, 0xbf80be48, 0x3f78bdc9, 0x3f2cbf35, 0xbf183f46, 0x3f04bf55, 0xbedb3f62,
    0x3eacbf6d, 0xbe793f75, 0x3e16bf7b, 0xbd493f7f, 0x3f800000, 0xbf7d3dc9, 0x3f78be48, 0xbf713e95, 0x3f67bec4, 0xbf5c3ef1,
    0x3f4ebf0e, 0xbf3e3f22, 0x3f3e3f35, 0xbf4ebf22, 0x3f5c3f0e, 0xbf67bef1, 0x3f713ec4, 0xbf78be95, 0x3f7d3e48, 0xbf80bdc9,
    0x3d493f80, 0xbe16bf7f, 0x3e793f7b, 0xbeacbf75, 0x3edb3f6d, 0xbf04bf62, 0x3f183f55, 0xbf2cbf46, 0xbf71bec4, 0x3f783e95,
    0xbf7dbe48, 0x3f803dc9, 0xbf3ebf35, 0x3f4e3f22, 0xbf5cbf0e, 0x3f673ef1, 0xbedbbf6d, 0x3f043f62, 0xbf18bf55, 0x3f2c3f46,
    0xbd49bf80, 0x3e163f7f, 0xbe79bf7b, 0x3eac3f75, 0x3eacbf6d, 0xbe793f75, 0x3e16bf7b, 0xbd493f7f, 0x3f2cbf35, 0xbf183f46,
    0x3f04bf55, 0xbedb3f62, 0x3f67bec4, 0xbf5c3ef1, 0x3f4ebf0e, 0xbf3e3f22, 0x3f800000, 0xbf7d3dc9, 0x3f78be48, 0xbf713e95,
    0xbd493f80, 0x3e16bf7f, 0xbe793f7b, 0x3eacbf75, 0xbedb3f6d, 0x3f04bf62, 0xbf183f55, 0x3f2cbf46, 0xbf3e3f35, 0x3f4ebf22,
    0xbf5c3f0e, 0x3f67bef1, 0xbf713ec4, 0x3f78be95, 0xbf7d3e48, 0x3f80bdc9, 0xbf800000, 0x3f7d3dc9, 0xbf78be48, 0x3f713e95,
    0xbf67bec4, 0x3f5c3ef1, 0xbf4ebf0e, 0x3f3e3f22, 0xbf2cbf35, 0x3f183f46, 0xbf04bf55, 0x3edb3f62, 0xbeacbf6d, 0x3e793f75,
    0xbe16bf7b, 0x3d493f7f, 0x3f673ec4, 0xbf5cbef1, 0x3f4e3f0e, 0xbf3ebf22, 0x3f800000, 0xbf7dbdc9, 0x3f783e48, 0xbf71be95,
    0x3eac3f6d, 0xbe79bf75, 0x3e163f7b, 0xbd49bf7f, 0x3f2c3f35, 0xbf18bf46, 0x3f043f55, 0xbedbbf62, 0xbedb3f6d, 0x3f04bf62,
    0xbf183f55, 0x3f2cbf46, 0xbd493f80, 0x3e16bf7f, 0xbe793f7b, 0x3eacbf75, 0xbf713ec4, 0x3f78be95, 0xbf7d3e48, 0x3f80bdc9,
    0xbf3e3f35, 0x3f4ebf22, 0xbf5c3f0e, 0x3f67bef1, 0xbf18bf35, 0x3eac3f62, 0xbd49bf7b, 0xbe793f7f, 0x3f04bf6d, 0xbf3e3f46,
    0x3f67bf0e, 0xbf7d3e95, 0xbe163f80, 0x3edbbf75, 0xbf2c3f55, 0x3f5cbf22, 0xbf783ec4, 0x3f80bdc9, 0xbf71be48, 0x3f4e3ef1,
    0xbf4e3f35, 0x3f71bef1, 0xbf803e48, 0x3f783dc9, 0xbf5cbec4, 0x3f2c3f22, 0xbedbbf55, 0x3e163f75, 0x3f7d0000, 0xbf67be95,
    0x3f3e3f0e, 0xbf04bf46, 0x3e793f6d, 0x3d49bf7f, 0xbeac3f7b, 0x3f18bf62, 0xbf5cbec4, 0x3f2c3f22, 0xbedbbf55, 0x3e163f75,
    0xbf4e3f35, 0x3f71bef1, 0xbf803e48, 0x3f783dc9, 0x3e793f6d, 0x3d49bf7f, 0xbeac3f7b, 0x3f18bf62, 0x3f7d0000, 0xbf67be95,
    0x3f3e3f0e, 0xbf04bf46, 0xbf043f6d, 0x3f3ebf46, 0xbf673f0e, 0x3f7dbe95, 0x3f183f35, 0xbeacbf62, 0x3d493f7b, 0x3e79bf7f,
    0x3f78bec4, 0xbf803dc9, 0x3f713e48, 0xbf4ebef1, 0x3e16bf80, 0xbedb3f75, 0x3f2cbf55, 0xbf5c3f22, 0xbf780000, 0x3f3e3ef1,
    0xbeacbf55, 0xbe163f7f, 0x3f18bf6d, 0xbf673f22, 0x3f80be48, 0xbf5cbe95, 0x3f043f35, 0xbd49bf75, 0xbedb3f7b, 0x3f4ebf46,
    0xbf7d3ec4, 0x3f713dc9, 0xbf2cbf0e, 0x3e793f62, 0xbe793f80, 0x3f2cbf62, 0xbf713f0e, 0x3f7dbdc9, 0xbf4ebec4, 0x3edb3f46,
    0x3d49bf7b, 0xbf043f75, 0x3f5cbf35, 0xbf803e95, 0x3f673e48, 0xbf18bf22, 0x3e163f6d, 0x3eacbf7f, 0xbf3e3f55, 0x3f78bef1,
    0xbf4ebec4, 0x3edb3f46, 0x3d49bf7b, 0xbf043f75, 0xbe793f80, 0x3f2cbf62, 0xbf713f0e, 0x3f7dbdc9, 0x3e163f6d, 0x3eacbf7f,
    0xbf3e3f55, 0x3f78bef1, 0x3f5cbf35, 0xbf803e95, 0x3f673e48, 0xbf18bf22, 0xbf183f6d, 0x3f67bf22, 0xbf803e48, 0x3f5c3e95,
    0x3f780000, 0xbf3ebef1, 0x3eac3f55, 0x3e16bf7f, 0x3f7dbec4, 0xbf71bdc9, 0x3f2c3f0e, 0xbe79bf62, 0xbf04bf35, 0x3d493f75,
    0x3edbbf7b, 0xbf4e3f46, 0x3f67bf35, 0xbf783dc9, 0x3f183f0e, 0x3d49bf75, 0xbf2c3f6d, 0x3f7dbef1, 0xbf5cbe48, 0x3eac3f46,
    0x3f710000, 0xbf04bf22, 0xbe163f7b, 0x3f3ebf62, 0xbf803ec4, 0x3f4e3e95, 0xbe79bf55, 0xbedb3f7f, 0x3edb3f35, 0x3e79bf7f,
    0xbf4e3f55, 0x3f80be95, 0xbf3ebec4, 0x3e163f62, 0x3f04bf7b, 0xbf713f22, 0xbeac3f80, 0x3f5cbf46, 0xbf7d3e48, 0x3f2c3ef1,
    0xbd49bf6d, 0xbf183f75, 0x3f78bf0e, 0xbf67bdc9, 0x3f3e3ec4, 0xbe16bf62, 0xbf043f7b, 0x3f71bf22, 0xbedbbf35, 0xbe793f7f,
    0x3f4ebf55, 0xbf803e95, 0x3d493f6d, 0x3f18bf75, 0xbf783f0e, 0x3f673dc9, 0x3eacbf80, 0xbf5c3f46, 0x3f7dbe48, 0xbf2cbef1,
    0xbf2c3f6d, 0x3f7dbef1, 0xbf5cbe48, 0x3eac3f46, 0x3f67bf35, 0xbf783dc9, 0x3f183f0e, 0x3d49bf75, 0xbf803ec4, 0x3f4e3e95,
    0xbe79bf55, 0xbedb3f7f, 0x3f710000, 0xbf04bf22, 0xbe163f7b, 0x3f3ebf62, 0xbedb3f80, 0x3f78bf22, 0xbf4ebe48, 0x3d493f62,
    0x3f3ebf6d, 0xbf7d3e95, 0x3f043f0e, 0x3eacbf7f, 0xbf713f35, 0x3f5c3dc9, 0xbe16bf55, 0xbf2c3f75, 0x3f80bec4, 0xbf18bef1,
    0xbe793f7b, 0x3f67bf46, 0xbf670000, 0x3e793f46, 0x3f18bf7b, 0xbf803ef1, 0x3f2c3ec4, 0x3e16bf75, 0xbf5c3f55, 0x3f71bdc9,
    0xbeacbf35, 0xbf043f7f, 0x3f7dbf0e, 0xbf3ebe95, 0xbd493f6d, 0x3f4ebf62, 0xbf783e48, 0x3edb3f22, 0xbf2cbec4, 0xbe163f75,
    0x3f5cbf55, 0xbf713dc9, 0x3f670000, 0xbe79bf46, 0xbf183f7b, 0x3f80bef1, 0x3d49bf6d, 0xbf4e3f62, 0x3f78be48, 0xbedbbf22,
    0x3eac3f35, 0x3f04bf7f, 0xbf7d3f0e, 0x3f3e3e95, 0x3f3ebf6d, 0xbf7d3e95, 0x3f043f0e, 0x3eacbf7f, 0xbedb3f80, 0x3f78bf22,
    0xbf4ebe48, 0x3d493f62, 0x3f80bec4, 0xbf18bef1, 0xbe793f7b, 0x3f67bf46, 0xbf713f35, 0x3f5c3dc9, 0xbe16bf55, 0xbf2c3f75,
    0xbe79bf35, 0xbf3e3f75, 0x3f71be48, 0xbe16bf46, 0xbf4e3f6d, 0x3f67bdc9, 0xbd49bf55, 0xbf5c3f62, 0xbf043f80, 0x3f80bef1,
    0xbedbbf0e, 0xbf183f7f, 0x3f7dbec4, 0xbeacbf22, 0xbf2c3f7b, 0x3f78be95, 0xbf783f35, 0x3f2c3e95, 0x3eacbf7b, 0xbf7d3f22,
    0x3f183ec4, 0x3edbbf7f, 0xbf803f0e, 0x3f043ef1, 0x3f5c0000, 0x3d49bf62, 0xbf673f55, 0x3f4e3dc9, 0x3e16bf6d, 0xbf713f46,
    0x3f3e3e48, 0x3e79bf75, 0x3f183ec4, 0x3edbbf7f, 0xbf803f0e, 0x3f043ef1, 0xbf783f35, 0x3f2c3e95, 0x3eacbf7b, 0xbf7d3f22,
    0x3e16bf6d, 0xbf713f46, 0x3f3e3e48, 0x3e79bf75, 0x3f5c0000, 0x3d49bf62, 0xbf673f55, 0x3f4e3dc9, 0x3f4ebf6d, 0xbf673dc9,
    0x3d493f55, 0x3f5cbf62, 0x3e793f35, 0x3f3ebf75, 0xbf713e48, 0x3e163f46, 0xbf7d3ec4, 0x3eac3f22, 0x3f2cbf7b, 0xbf783e95,
    0x3f04bf80, 0xbf803ef1, 0x3edb3f0e, 0x3f18bf7f, 0xbf4e0000, 0xbeac3f75, 0x3f80bf0e, 0xbe79bf22, 0xbf5c3f6d, 0x3f3e3dc9,
    0x3edbbf7b, 0xbf7d3ef1, 0x3e163f35, 0x3f67bf62, 0xbf2cbe48, 0xbf043f7f, 0x3f78bec4, 0xbd49bf46, 0xbf713f55, 0x3f183e95,
    0xbf183f80, 0x3f71be95, 0x3d49bf55, 0xbf783f46, 0x3f043ec4, 0x3f2cbf7f, 0xbf673e48, 0xbe163f62, 0x3f7dbf35, 0xbedbbef1,
    0xbf3e3f7b, 0x3f5cbdc9, 0x3e79bf6d, 0xbf803f22, 0x3eac3f0e, 0x3f4ebf75, 0x3f043ec4, 0x3f2cbf7f, 0xbf673e48, 0xbe163f62,
    0xbf183f80, 0x3f71be95, 0x3d49bf55, 0xbf783f46, 0x3e79bf6d, 0xbf803f22, 0x3eac3f0e, 0x3f4ebf75, 0x3f7dbf35, 0xbedbbef1,
    0xbf3e3f7b, 0x3f5cbdc9, 0x3f5cbf6d, 0xbf3ebdc9, 0xbedb3f7b, 0x3f7dbef1, 0x3f4e0000, 0x3eacbf75, 0xbf803f0e, 0x3e793f22,
    0xbf783ec4, 0x3d493f46, 0x3f71bf55, 0xbf18be95, 0xbe16bf35, 0xbf673f62, 0x3f2c3e48, 0x3f04bf7f, 0x3f80bf35, 0xbe16bf22,
    0xbf783f55, 0x3eac3ef1, 0x3f67bf6d, 0xbf04be95, 0xbf4e3f7b, 0x3f2c3dc9, 0x3f3e0000, 0x3f18bf7f, 0xbf5c3e48, 0xbedb3f75,
    0x3f71bec4, 0x3e79bf62, 0xbf7d3f0e, 0xbd493f46, 0x3d493f35, 0x3f7dbf46, 0xbe79bf0e, 0xbf713f62, 0x3edb3ec4, 0x3f5cbf75,
    0xbf18be48, 0xbf3e3f7f, 0xbf2c3f80, 0x3f4ebdc9, 0x3f04bf7b, 0xbf673e95, 0xbeac3f6d, 0x3f78bef1, 0x3e16bf55, 0xbf803f22,
    0xbedbbec4, 0xbf5c3f75, 0x3f183e48, 0x3f3ebf7f, 0xbd49bf35, 0xbf7d3f46, 0x3e793f0e, 0x3f71bf62, 0x3eacbf6d, 0xbf783ef1,
    0xbe163f55, 0x3f80bf22, 0x3f2cbf80, 0xbf4e3dc9, 0xbf043f7b, 0x3f67be95, 0x3f67bf6d, 0xbf04be95, 0xbf4e3f7b, 0x3f2c3dc9,
    0x3f80bf35, 0xbe16bf22, 0xbf783f55, 0x3eac3ef1, 0x3f71bec4, 0x3e79bf62, 0xbf7d3f0e, 0xbd493f46, 0x3f3e0000, 0x3f18bf7f,
    0xbf5c3e48, 0xbedb3f75, 0xbf3e3f80, 0x3f183dc9, 0x3f5cbf7b, 0xbedbbe95, 0xbf713f6d, 0x3e793ef1, 0x3f7dbf55, 0xbd49bf22,
    0xbf803f35, 0xbe163f46, 0x3f78bf0e, 0x3eacbf62, 0xbf673ec4, 0xbf043f75, 0x3f4ebe48, 0x3f2cbf7f, 0xbf2c0000, 0xbf4e3f7f,
    0x3f043e48, 0x3f67bf75, 0xbeacbec4, 0xbf783f62, 0x3e163f0e, 0x3f80bf46, 0x3d49bf35, 0xbf7d3f22, 0xbe793f55, 0x3f71bef1,
    0x3edbbf6d, 0xbf5c3e95, 0xbf183f7b, 0x3f3ebdc9, 0x3eac3ec4, 0x3f78bf62, 0xbe16bf0e, 0xbf803f46, 0x3f2c0000, 0x3f4ebf7f,
    0xbf04be48, 0xbf673f75, 0xbedb3f6d, 0x3f5cbe95, 0x3f18bf7b, 0xbf3e3dc9, 0xbd493f35, 0x3f7dbf22, 0x3e79bf55, 0xbf713ef1,
    0xbf713f6d, 0x3e793ef1, 0x3f7dbf55, 0xbd49bf22, 0xbf3e3f80, 0x3f183dc9, 0x3f5cbf7b, 0xbedbbe95, 0xbf673ec4, 0xbf043f75,
    0x3f4ebe48, 0x3f2cbf7f, 0xbf803f35, 0xbe163f46, 0x3f78bf0e, 0x3eacbf62, 0x3e16bf35, 0xbf673ef1, 0xbf2c3f7b, 0x3f043dc9,
    0x3f78bf6d, 0x3d49bf22, 0xbf713f0e, 0xbf183f75, 0xbf4e3f80, 0x3eac3e95, 0x3f80bf55, 0x3e79bf46, 0xbf5c3ec4, 0xbf3e3f7f,
    0x3edb3e48, 0x3f7dbf62, 0xbf7d3f35, 0xbedb3f62, 0x3f3ebe48, 0x3f5cbf7f, 0xbe79bec4, 0xbf803f46, 0xbeac3f55, 0x3f4ebe95,
    0x3f180000, 0x3f71bf75, 0xbd49bf0e, 0xbf783f22, 0xbf043f6d, 0x3f2cbdc9, 0x3f67bf7b, 0xbe16bef1, 0xbe79bec4, 0xbf803f46,
    0xbeac3f55, 0x3f4ebe95, 0xbf7d3f35, 0xbedb3f62, 0x3f3ebe48, 0x3f5cbf7f, 0xbf043f6d, 0x3f2cbdc9, 0x3f67bf7b, 0xbe16bef1,
    0x3f180000, 0x3f71bf75, 0xbd49bf0e, 0xbf783f22, 0xbf783f6d, 0xbd493f22, 0x3f71bf0e, 0x3f18bf75, 0xbe163f35, 0x3f67bef1,
    0x3f2cbf7b, 0xbf04bdc9, 0x3f5cbec4, 0x3f3ebf7f, 0xbedbbe48, 0xbf7d3f62, 0x3f4ebf80, 0xbeacbe95, 0xbf803f55, 0xbe793f46,
    0xbf040000, 0xbf803f62, 0xbedb3f55, 0x3f18bdc9, 0x3f7dbf6d, 0x3eacbf46, 0xbf2c3e48, 0xbf783f75, 0xbe793f35, 0x3f3ebe95,
    0x3f71bf7b, 0x3e16bf22, 0xbf4e3ec4, 0xbf673f7f, 0xbd493f0e, 0x3f5cbef1, 0xbf5c3f80, 0x3d493ef1, 0x3f67bf0e, 0x3f4ebf7f,
    0xbe16bec4, 0xbf713f22, 0xbf3e3f7b, 0x3e793e95, 0x3f78bf35, 0x3f2cbf75, 0xbeacbe48, 0xbf7d3f46, 0xbf183f6d, 0x3edb3dc9,
    0x3f80bf55, 0x3f04bf62, 0xbe16bec4, 0xbf713f22, 0xbf3e3f7b, 0x3e793e95, 0xbf5c3f80, 0x3d493ef1, 0x3f67bf0e, 0x3f4ebf7f,
    0xbf183f6d, 0x3edb3dc9, 0x3f80bf55, 0x3f04bf62, 0x3f78bf35, 0x3f2cbf75, 0xbeacbe48, 0xbf7d3f46, 0xbf7d3f6d, 0xbeac3f46,
    0x3f2cbe48, 0x3f78bf75, 0x3f040000, 0x3f80bf62, 0x3edbbf55, 0xbf183dc9, 0x3f4ebec4, 0x3f67bf7f, 0x3d49bf0e, 0xbf5c3ef1,
    0x3e79bf35, 0xbf3e3e95, 0xbf713f7b, 0xbe163f22, 0x3f71bf35, 0x3f5cbf7f, 0x3e16bf0e, 0xbf2c3e95, 0xbf803f6d, 0xbf183f62,
    0x3e793e48, 0x3f67bf22, 0x3edb0000, 0x3f78bf46, 0x3f4ebf7b, 0x3d49bef1, 0xbf3e3ec4, 0xbf7d3f75, 0xbf043f55, 0x3eac3dc9,
    0xbeac3f35, 0x3f04bdc9, 0x3f7dbf55, 0x3f3ebf75, 0xbd49bec4, 0xbf4e3ef1, 0xbf783f7b, 0xbedb3f46, 0xbf673f80, 0xbe793f22,
    0x3f18be48, 0x3f80bf62, 0x3f2cbf6d, 0xbe16be95, 0xbf5c3f0e, 0xbf713f7f, 0x3d493ec4, 0x3f4ebef1, 0x3f78bf7b, 0x3edbbf46,
    0x3eacbf35, 0xbf043dc9, 0xbf7d3f55, 0xbf3e3f75, 0xbf2c3f6d, 0x3e163e95, 0x3f5cbf0e, 0x3f71bf7f, 0x3f67bf80, 0x3e79bf22,
    0xbf183e48, 0xbf803f62, 0xbf803f6d, 0xbf183f62, 0x3e793e48, 0x3f67bf22, 0x3f71bf35, 0x3f5cbf7f, 0x3e16bf0e, 0xbf2c3e95,
    0xbf3e3ec4, 0xbf7d3f75, 0xbf043f55, 0x3eac3dc9, 0x3edb0000, 0x3f78bf46, 0x3f4ebf7b, 0x3d49bef1, 0xbf713f80, 0xbf043f46,
    0x3e163e48, 0x3f3ebef1, 0x3f80bf6d, 0x3f4ebf75, 0x3e79bf0e, 0xbedb3dc9, 0xbf673f35, 0xbf783f7f, 0xbf183f55, 0x3d493e95,
    0x3f2cbec4, 0x3f7dbf62, 0x3f5cbf7b, 0x3eacbf22, 0xbeac0000, 0xbf5c3f22, 0xbf7d3f7b, 0xbf2c3f62, 0xbd493ec4, 0x3f18be95,
    0x3f78bf55, 0x3f67bf7f, 0x3edbbf35, 0xbe79bdc9, 0xbf4e3f0e, 0xbf803f75, 0xbf3e3f6d, 0xbe163ef1, 0x3f04be48, 0x3f71bf46,
    0x3d49bec4, 0xbf183e95, 0xbf783f55, 0xbf673f7f, 0x3eac0000, 0x3f5cbf22, 0x3f7dbf7b, 0x3f2cbf62, 0x3f3ebf6d, 0x3e16bef1,
    0xbf043e48, 0xbf713f46, 0xbedb3f35, 0x3e793dc9, 0x3f4ebf0e, 0x3f80bf75, 0x3f80bf6d, 0x3f4ebf75, 0x3e79bf0e, 0xbedb3dc9,
    0xbf713f80, 0xbf043f46, 0x3e163e48, 0x3f3ebef1, 0x3f2cbec4, 0x3f7dbf62, 0x3f5cbf7b, 0x3eacbf22, 0xbf673f35, 0xbf783f7f,
    0xbf183f55, 0x3d493e95, 0x3f04bf35, 0x3d49be95, 0xbedb3e48, 0xbf4e3f22, 0xbf7d3f6d, 0xbf713f7f, 0xbf2c3f55, 0xbe793ef1,
    0xbf783f80, 0xbf3e3f62, 0xbeac3f0e, 0x3e163dc9, 0x3f18bec4, 0x3f67bf46, 0x3f80bf7b, 0x3f5cbf75, 0xbf5c3f35, 0xbf803f75,
    0xbf673f7b, 0xbf183f46, 0xbe163ec4, 0x3eacbdc9, 0x3f3ebf0e, 0x3f78bf62, 0x3e790000, 0x3f2cbef1, 0x3f71bf55, 0x3f7dbf7f,
    0x3f4ebf6d, 0x3edbbf22, 0xbd49be48, 0xbf043e95, 0xbe163ec4, 0x3eacbdc9, 0x3f3ebf0e, 0x3f78bf62, 0xbf5c3f35, 0xbf803f75,
    0xbf673f7b, 0xbf183f46, 0x3f4ebf6d, 0x3edbbf22, 0xbd49be48, 0xbf043e95, 0x3e790000, 0x3f2cbef1, 0x3f71bf55, 0x3f7dbf7f,
    0x3f7dbf6d, 0x3f71bf7f, 0x3f2cbf55, 0x3e79bef1, 0xbf043f35, 0xbd493e95, 0x3edbbe48, 0x3f4ebf22, 0xbf183ec4, 0xbf673f46,
    0xbf803f7b, 0xbf5c3f75, 0x3f78bf80, 0x3f3ebf62, 0x3eacbf0e, 0xbe16bdc9, 0xbe160000, 0xbedb3e95, 0xbf2c3f0e, 0xbf5c3f46,
    0xbf783f6d, 0xbf803f7f, 0xbf713f7b, 0xbf4e3f62, 0xbf183f35, 0xbeac3ef1, 0xbd493e48, 0x3e79bdc9, 0x3f04bec4, 0x3f3ebf22,
    0x3f67bf55, 0x3f7dbf75, 0xbf7d3f80, 0xbf673f75, 0xbf3e3f55, 0xbf043f22, 0xbe793ec4, 0x3d493dc9, 0x3eacbe48, 0x3f18bef1,
    0x3f4ebf35, 0x3f71bf62, 0x3f80bf7b, 0x3f78bf7f, 0x3f5cbf6d, 0x3f2cbf46, 0x3edbbf0e, 0x3e16be95, 0xbe793ec4, 0x3d493dc9,
    0x3eacbe48, 0x3f18bef1, 0xbf7d3f80, 0xbf673f75, 0xbf3e3f55, 0xbf043f22, 0x3f5cbf6d, 0x3f2cbf46, 0x3edbbf0e, 0x3e16be95,
    0x3f4ebf35, 0x3f71bf62, 0x3f80bf7b, 0x3f78bf7f, 0x3f78bf6d, 0x3f80bf7f, 0x3f71bf7b, 0x3f4ebf62, 0x3e160000, 0x3edbbe95,
    0x3f2cbf0e, 0x3f5cbf46, 0xbf043ec4, 0xbf3e3f22, 0xbf673f55, 0xbf7d3f75, 0x3f18bf35, 0x3eacbef1, 0x3d49be48, 0xbe793dc9,
    0x3f3ebf35, 0x3f4ebf46, 0x3f5cbf55, 0x3f67bf62, 0x3f71bf6d, 0x3f78bf75, 0x3f7dbf7b, 0x3f80bf7f, 0x3d490000, 0x3e16bdc9,
    0x3e79be48, 0x3eacbe95, 0x3edbbec4, 0x3f04bef1, 0x3f18bf0e, 0x3f2cbf22, 0xbf2c3f35, 0xbf183f22, 0xbf043f0e, 0xbedb3ef1,
    0xbeac3ec4, 0xbe793e95, 0xbe163e48, 0xbd493dc9, 0xbf803f80, 0xbf7d3f7f, 0xbf783f7b, 0xbf713f75, 0xbf673f6d, 0xbf5c3f62,
    0xbf4e3f55, 0xbf3e3f46, 0x3eacbec4, 0x3e79be95, 0x3e16be48, 0x3d49bdc9, 0x3f2cbf35, 0x3f18bf22, 0x3f04bf0e, 0x3edbbef1,
    0x3f67bf6d, 0x3f5cbf62, 0x3f4ebf55, 0x3f3ebf46, 0x3f80bf80, 0x3f7dbf7f, 0x3f78bf7b, 0x3f71bf75, 0x3f71bf6d, 0x3f78bf75,
    0x3f7dbf7b, 0x3f80bf7f, 0x3f3ebf35, 0x3f4ebf46, 0x3f5cbf55, 0x3f67bf62, 0x3edbbec4, 0x3f04bef1, 0x3f18bf0e, 0x3f2cbf22,
    0x3d490000, 0x3e16bdc9, 0x3e79be48, 0x3eacbe95,
};
__device__ const __align__(128) uint32_t c_ga[1536] = {
    0x00003c80, 0x3bc43c6d, 0x00003c80, 0xbbc4bc6d, 0x00003c80, 0x3c6d3bc4, 0x00003c80, 0xbc6dbbc4, 0x00003c80, 0x3c6dbbc4,
    0x00003c80, 0xbc6d3bc4, 0x00003c80, 0x3bc4bc6d, 0x00003c80, 0xbbc43c6d, 0x3a493c80, 0x3bdb3c67, 0x3bdb3c67, 0xbc3ebc2c,
    0x3b163c7d, 0x3c783b79, 0x3c043c5c, 0xbc7d3b16, 0x3b793c78, 0x3c4ebc18, 0x3c183c4e, 0xbc043c5c, 0x3bac3c71, 0x3a49bc80,
    0x3c2c3c3e, 0x3bac3c71, 0x3ac93c7f, 0x3bf13c62, 0x3c463c22, 0xbc75bb95, 0x3b953c75, 0x3c7f3ac9, 0x3c623bf1, 0xbc463c22,
    0x3bf13c62, 0x3c22bc46, 0x3c753b95, 0x3ac93c7f, 0x3c223c46, 0xbb95bc75, 0x3c7f3ac9, 0x3c623bf1, 0x3b163c7d, 0x3c043c5c,
    0x3c783b79, 0xbc7d3b16, 0x3bdb3c67, 0x3c80ba49, 0x3c80ba49, 0xbbac3c71, 0x3c2c3c3e, 0x3bdbbc67, 0x3c71bbac, 0x3c2c3c3e,
    0x3c5c3c04, 0xbc18bc4e, 0x3c4ebc18, 0x3c78bb79, 0x3b483c7b, 0x3c0e3c55, 0x3c7bbb48, 0xbc553c0e, 0x3c0e3c55, 0x3c7bbb48,
    0x3c55bc0e, 0x3b483c7b, 0x3c553c0e, 0x3b48bc7b, 0x3c0ebc55, 0x3c7b3b48, 0x3c7b3b48, 0xbc55bc0e, 0x3b48bc7b, 0x3c0ebc55,
    0x3b793c78, 0x3c183c4e, 0x3c4ebc18, 0xbc043c5c, 0x3c2c3c3e, 0x3c71bbac, 0x3bdbbc67, 0x3c2c3c3e, 0x3c713bac, 0xba49bc80,
    0xba49bc80, 0x3c67bbdb, 0x3c7dbb16, 0xbc78bb79, 0xbc04bc5c, 0xbb16bc7d, 0x3b953c75, 0x3c223c46, 0x3bf1bc62, 0xbac93c7f,
    0x3c463c22, 0x3c62bbf1, 0xbac9bc7f, 0x3c753b95, 0x3c7f3ac9, 0xbb95bc75, 0xbc22bc46, 0x3bf1bc62, 0x3c62bbf1, 0xbc7f3ac9,
    0xbc75bb95, 0xbc46bc22, 0x3bac3c71, 0x3c2c3c3e, 0x3a49bc80, 0x3bac3c71, 0x3c5c3c04, 0x3c4ebc18, 0xbc18bc4e, 0x3c78bb79,
    0x3c7dbb16, 0xbc04bc5c, 0xbc78bb79, 0xbb16bc7d, 0x3c2cbc3e, 0xbc673bdb, 0xbc673bdb, 0xbc803a49, 0x00003c80, 0x3bc43c6d,
    0x00003c80, 0xbbc4bc6d, 0x00003c80, 0x3c6d3bc4, 0x00003c80, 0xbc6dbbc4, 0x00003c80, 0x3c6dbbc4, 0x00003c80, 0xbc6d3bc4,
    0x00003c80, 0x3bc4bc6d, 0x00003c80, 0xbbc43c6d, 0x3c3e3c2c, 0x3c713bac, 0x3c713bac, 0xbc803a49, 0x3c4e3c18, 0x3c5cbc04,
    0x3c783b79, 0xbc183c4e, 0x3c5c3c04, 0x3b16bc7d, 0x3c7d3b16, 0x3b793c78, 0x3c673bdb, 0xbc2cbc3e, 0x3c803a49, 0x3c673bdb,
    0x3c7fbac9, 0x3c62bbf1, 0x3c22bc46, 0xbb953c75, 0x3c75bb95, 0x3ac9bc7f, 0x3bf1bc62, 0x3c223c46, 0x3c62bbf1, 0xbc46bc22,
    0x3b95bc75, 0x3c7fbac9, 0x3c46bc22, 0xbc753b95, 0x3ac9bc7f, 0x3bf1bc62, 0x3c18bc4e, 0x3b79bc78, 0xbc04bc5c, 0x3c4e3c18,
    0x3bacbc71, 0xbc3ebc2c, 0xbc3ebc2c, 0x3c67bbdb, 0x3a49bc80, 0xbc713bac, 0xbc67bbdb, 0x3a49bc80, 0xbb79bc78, 0xbb163c7d,
    0xbc7dbb16, 0xbc5cbc04, 0xbb48bc7b, 0xbc0ebc55, 0xbc7b3b48, 0x3c55bc0e, 0xbc0ebc55, 0xbc7b3b48, 0xbc553c0e, 0xbb48bc7b,
    0xbc55bc0e, 0xbb483c7b, 0xbc0e3c55, 0xbc7bbb48, 0xbc7bbb48, 0x3c553c0e, 0xbb483c7b, 0xbc0e3c55, 0xbc5cbc04, 0xbc7dbb16,
    0xbb163c7d, 0xbb79bc78, 0xbc80ba49, 0xbbdb3c67, 0x3bac3c71, 0xbc80ba49, 0xbc673bdb, 0x3c3e3c2c, 0x3c3e3c2c, 0xbbac3c71,
    0xbc183c4e, 0x3c5cbc04, 0x3c783b79, 0x3c4e3c18, 0xbc753b95, 0xbc463c22, 0x3c623bf1, 0xbc7fbac9, 0xbc223c46, 0x3bf13c62,
    0x3c7fbac9, 0xbb953c75, 0xbac93c7f, 0x3c75bb95, 0x3c46bc22, 0x3c623bf1, 0x3bf13c62, 0xbac9bc7f, 0x3b95bc75, 0x3c22bc46,
    0xbbdb3c67, 0xba493c80, 0x3c3ebc2c, 0xbbdb3c67, 0x3b793c78, 0x3c7d3b16, 0x3b16bc7d, 0x3c5c3c04, 0x3c4e3c18, 0x3b79bc78,
    0xbc04bc5c, 0x3c18bc4e, 0x3c80ba49, 0xbc71bbac, 0xbc71bbac, 0xbc3ebc2c, 0x00003c80, 0x3bc43c6d, 0x00003c80, 0xbbc4bc6d,
    0x00003c80, 0x3c6d3bc4, 0x00003c80, 0xbc6dbbc4, 0x00003c80, 0x3c6dbbc4, 0x00003c80, 0xbc6d3bc4, 0x00003c80, 0x3bc4bc6d,
    0x00003c80, 0xbbc43c6d, 0x3c80ba49, 0x3c67bbdb, 0x3c67bbdb, 0xbc2c3c3e, 0x3c7dbb16, 0x3b79bc78, 0x3c5cbc04, 0x3b163c7d,
    0x3c78bb79, 0xbc18bc4e, 0x3c4ebc18, 0x3c5c3c04, 0x3c71bbac, 0xbc80ba49, 0x3c3ebc2c, 0x3c71bbac, 0xbac9bc7f, 0xbbf1bc62,
    0xbc46bc22, 0x3c753b95, 0xbb95bc75, 0xbc7fbac9, 0xbc62bbf1, 0x3c46bc22, 0xbbf1bc62, 0xbc223c46, 0xbc75bb95, 0xbac9bc7f,
    0xbc22bc46, 0x3b953c75, 0xbc7fbac9, 0xbc62bbf1, 0xbc7d3b16, 0xbc5c3c04, 0xbb793c78, 0xbb16bc7d, 0xbc673bdb, 0x3a493c80,
    0x3a493c80, 0xbc71bbac, 0xbc3e3c2c, 0x3c673bdb, 0x3bac3c71, 0xbc3e3c2c, 0xbc043c5c, 0x3c4ebc18, 0x3c183c4e, 0x3b793c78,
    0x3b483c7b, 0x3c0e3c55, 0x3c7bbb48, 0xbc553c0e, 0x3c0e3c55, 0x3c7bbb48, 0x3c55bc0e, 0x3b483c7b, 0x3c553c0e, 0x3b48bc7b,
    0x3c0ebc55, 0x3c7b3b48, 0x3c7b3b48, 0xbc55bc0e, 0x3b48bc7b, 0x3c0ebc55, 0x3c78bb79, 0x3c4ebc18, 0xbc18bc4e, 0x3c5c3c04,
    0x3c3ebc2c, 0xbbacbc71, 0xbc67bbdb, 0x3c3ebc2c, 0x3bacbc71, 0xbc803a49, 0xbc803a49, 0xbbdbbc67, 0xbb16bc7d, 0xbb793c78,
    0xbc5c3c04, 0xbc7d3b16, 0xbb95bc75, 0xbc22bc46, 0xbbf13c62, 0x3ac9bc7f, 0xbc46bc22, 0xbc623bf1, 0x3ac93c7f, 0xbc75bb95,
    0xbc7fbac9, 0x3b953c75, 0x3c223c46, 0xbbf13c62, 0xbc623bf1, 0x3c7fbac9, 0x3c753b95, 0x3c463c22, 0xbc713bac, 0xbc3e3c2c,
    0x3c803a49, 0xbc713bac, 0xbc043c5c, 0x3c183c4e, 0x3c4ebc18, 0x3b793c78, 0x3b163c7d, 0x3c5cbc04, 0x3b79bc78, 0x3c7dbb16,
    0x3c3e3c2c, 0xbbdbbc67, 0xbbdbbc67, 0xba49bc80, 0x00003c80, 0x3bc43c6d, 0x00003c80, 0xbbc4bc6d, 0x00003c80, 0x3c6d3bc4,
    0x00003c80, 0xbc6dbbc4, 0x00003c80, 0x3c6dbbc4, 0x00003c80, 0xbc6d3bc4, 0x00003c80, 0x3bc4bc6d, 0x00003c80, 0xbbc43c6d,
    0x3c2cbc3e, 0x3bacbc71, 0x3bacbc71, 0x3a493c80, 0x3c18bc4e, 0xbc04bc5c, 0x3b79bc78, 0x3c4e3c18, 0x3c04bc5c, 0xbc7dbb16,
    0x3b16bc7d, 0x3c78bb79, 0x3bdbbc67, 0xbc3e3c2c, 0x3a49bc80, 0x3bdbbc67, 0xbc7f3ac9, 0xbc623bf1, 0xbc223c46, 0x3b95bc75,
    0xbc753b95, 0xbac93c7f, 0xbbf13c62, 0xbc22bc46, 0xbc623bf1, 0x3c463c22, 0xbb953c75, 0xbc7f3ac9, 0xbc463c22, 0x3c75bb95,
    0xbac93c7f, 0xbbf13c62, 0x3c4e3c18, 0x3c783b79, 0x3c5cbc04, 0xbc183c4e, 0x3c713bac, 0x3c2cbc3e, 0x3c2cbc3e, 0x3bdb3c67,
    0x3c803a49, 0xbbacbc71, 0x3bdbbc67, 0x3c803a49, 0x3c78bb79, 0xbc7dbb16, 0x3b16bc7d, 0x3c04bc5c, 0xbb48bc7b, 0xbc0ebc55,
    0xbc7b3b48, 0x3c55bc0e, 0xbc0ebc55, 0xbc7b3b48, 0xbc553c0e, 0xbb48bc7b, 0xbc55bc0e, 0xbb483c7b, 0xbc0e3c55, 0xbc7bbb48,
    0xbc7bbb48, 0x3c553c0e, 0xbb483c7b, 0xbc0e3c55, 0xbc043c5c, 0xbb163c7d, 0x3c7d3b16, 0xbc783b79, 0xba493c80, 0x3c673bdb,
    0x3c71bbac, 0xba493c80, 0x3bdb3c67, 0x3c2cbc3e, 0x3c2cbc3e, 0x3c713bac, 0x3c4e3c18, 0xbc04bc5c, 0x3b79bc78, 0x3c18bc4e,
    0x3c75bb95, 0x3c46bc22, 0xbc62bbf1, 0x3c7f3ac9, 0x3c22bc46, 0xbbf1bc62, 0xbc7f3ac9, 0x3b95bc75, 0x3ac9bc7f, 0xbc753b95,
    0xbc463c22, 0xbc62bbf1, 0xbbf1bc62, 0x3ac93c7f, 0xbb953c75, 0xbc223c46, 0xbc67bbdb, 0xbc80ba49, 0x3c2c3c3e, 0xbc67bbdb,
    0xbc783b79, 0xbb163c7d, 0x3c7d3b16, 0xbc043c5c, 0xbc183c4e, 0x3c783b79, 0x3c5cbc04, 0x3c4e3c18, 0x3a493c80, 0x3bacbc71,
    0x3bacbc71, 0x3c2cbc3e, 0x3c353c35, 0x3c6d3bc4, 0x3c353c35, 0xbc6dbbc4, 0x3c35bc35, 0xbbc4bc6d, 0x3c35bc35, 0x3bc43c6d,
    0xbc35bc35, 0xbbc43c6d, 0xbc35bc35, 0x3bc4bc6d, 0xbc353c35, 0x3c6dbbc4, 0xbc353c35, 0xbc6d3bc4, 0x3c3e3c2c, 0x3c713bac,
    0x3c713bac, 0xbc803a49, 0x3c18bc4e, 0xbc04bc5c, 0x3b79bc78, 0x3c4e3c18, 0xbc5cbc04, 0xbb163c7d, 0xbc7dbb16, 0xbb79bc78,
    0xbbdb3c67, 0x3c3ebc2c, 0xba493c80, 0xbbdb3c67, 0x3c463c22, 0x3c753b95, 0x3c7fbac9, 0xbc623bf1, 0x3bf1bc62, 0xbc22bc46,
    0xbb95bc75, 0x3c7f3ac9, 0xbc75bb95, 0x3ac93c7f, 0xbc623bf1, 0xbc46bc22, 0xbac93c7f, 0x3bf1bc62, 0x3c223c46, 0x3b953c75,
    0x3c4e3c18, 0x3c783b79, 0x3c5cbc04, 0xbc183c4e, 0x3bacbc71, 0xbc3ebc2c, 0xbc3ebc2c, 0x3c67bbdb, 0xbc80ba49, 0x3bac3c71,
    0xbbdb3c67, 0xbc80ba49, 0x3b793c78, 0x3b16bc7d, 0x3c7d3b16, 0x3c5c3c04, 0x3c553c0e, 0x3c7b3b48, 0x3c0ebc55, 0xbb483c7b,
    0x3b48bc7b, 0xbc55bc0e, 0xbc7bbb48, 0x3c0ebc55, 0xbc7b3b48, 0x3c0e3c55, 0x3b483c7b, 0xbc553c0e, 0x3c0e3c55, 0xbb48bc7b,
    0x3c55bc0e, 0x3c7bbb48, 0x3c5c3c04, 0x3c7d3b16, 0x3b16bc7d, 0x3b793c78, 0x3a49bc80, 0xbc67bbdb, 0xbc713bac, 0x3a49bc80,
    0xbc673bdb, 0x3c3e3c2c, 0x3c3e3c2c, 0xbbac3c71, 0x3c4e3c18, 0xbc04bc5c, 0x3b79bc78, 0x3c18bc4e, 0x3c623bf1, 0x3c7f3ac9,
    0xbb95bc75, 0x3c223c46, 0xbac9bc7f, 0xbc75bb95, 0xbc223c46, 0xbbf1bc62, 0xbc463c22, 0x3c623bf1, 0x3c7f3ac9, 0x3b953c75,
    0x3c753b95, 0xbc46bc22, 0xbbf1bc62, 0xbac9bc7f, 0x3c673bdb, 0x3c803a49, 0xbc2cbc3e, 0x3c673bdb, 0xbb79bc78, 0xbc7dbb16,
    0xbb163c7d, 0xbc5cbc04, 0xbc183c4e, 0x3c783b79, 0x3c5cbc04, 0x3c4e3c18, 0x3c80ba49, 0xbc71bbac, 0xbc71bbac, 0xbc3ebc2c,
    0x3c353c35, 0x3c6d3bc4, 0x3c353c35, 0xbc6dbbc4, 0x3c35bc35, 0xbbc4bc6d, 0x3c35bc35, 0x3bc43c6d, 0xbc35bc35, 0xbbc43c6d,
    0xbc35bc35, 0x3bc4bc6d, 0xbc353c35, 0x3c6dbbc4, 0xbc353c35, 0xbc6d3bc4, 0x3c80ba49, 0x3c67bbdb, 0x3c67bbdb, 0xbc2c3c3e,
    0xbb16bc7d, 0xbc78bb79, 0xbc04bc5c, 0x3c7dbb16, 0xbc783b79, 0x3c183c4e, 0xbc4e3c18, 0xbc5cbc04, 0x3bac3c71, 0x3a49bc80,
    0x3c2c3c3e, 0x3bac3c71, 0x3c22bc46, 0x3b95bc75, 0xbac9bc7f, 0x3bf13c62, 0xbc62bbf1, 0xbc463c22, 0xbc753b95, 0x3ac9bc7f,
    0xbb953c75, 0x3c7fbac9, 0x3bf13c62, 0xbc223c46, 0x3c7f3ac9, 0xbc62bbf1, 0x3c46bc22, 0x3c75bb95, 0xbb16bc7d, 0xbc04bc5c,
    0xbc78bb79, 0x3c7dbb16, 0xbc673bdb, 0x3a493c80, 0x3a493c80, 0xbc71bbac, 0x3c2c3c3e, 0x3bdbbc67, 0x3c71bbac, 0x3c2c3c3e,
    0x3c04bc5c, 0xbc4e3c18, 0xbc18bc4e, 0xbb79bc78, 0xbc55bc0e, 0xbc7bbb48, 0xbc0e3c55, 0x3b48bc7b, 0xbb483c7b, 0x3c553c0e,
    0x3c7b3b48, 0xbc0e3c55, 0x3c7bbb48, 0xbc0ebc55, 0xbb48bc7b, 0x3c55bc0e, 0xbc0ebc55, 0x3b483c7b, 0xbc553c0e, 0xbc7b3b48,
    0xbc783b79, 0xbc4e3c18, 0x3c183c4e, 0xbc5cbc04, 0x3c2c3c3e, 0x3c71bbac, 0x3bdbbc67, 0x3c2c3c3e, 0x3bacbc71, 0xbc803a49,
    0xbc803a49, 0xbbdbbc67, 0xbc7d3b16, 0x3c783b79, 0x3c043c5c, 0x3b163c7d, 0xbbf13c62, 0xbac93c7f, 0x3c75bb95, 0xbc463c22,
    0x3c7fbac9, 0x3b95bc75, 0xbc46bc22, 0x3c62bbf1, 0xbc22bc46, 0xbbf13c62, 0xbac93c7f, 0xbc753b95, 0xbb953c75, 0x3c22bc46,
    0x3c62bbf1, 0x3c7fbac9, 0x3bac3c71, 0x3c2c3c3e, 0x3a49bc80, 0x3bac3c71, 0x3c04bc5c, 0xbc18bc4e, 0xbc4e3c18, 0xbb79bc78,
    0xbc7d3b16, 0x3c043c5c, 0x3c783b79, 0x3b163c7d, 0x3c3e3c2c, 0xbbdbbc67, 0xbbdbbc67, 0xba49bc80, 0x3c353c35, 0x3c6d3bc4,
    0x3c353c35, 0xbc6dbbc4, 0x3c35bc35, 0xbbc4bc6d, 0x3c35bc35, 0x3bc43c6d, 0xbc35bc35, 0xbbc43c6d, 0xbc35bc35, 0x3bc4bc6d,
    0xbc353c35, 0x3c6dbbc4, 0xbc353c35, 0xbc6d3bc4, 0x3c2cbc3e, 0x3bacbc71, 0x3bacbc71, 0x3a493c80, 0xbc4ebc18, 0xbc5c3c04,
    0xbc78bb79, 0x3c18bc4e, 0xbc043c5c, 0x3c7d3b16, 0xbb163c7d, 0xbc783b79, 0x3c673bdb, 0xbc2cbc3e, 0x3c803a49, 0x3c673bdb,
    0xbc46bc22, 0xbc75bb95, 0xbc7f3ac9, 0x3c62bbf1, 0xbbf13c62, 0x3c223c46, 0x3b953c75, 0xbc7fbac9, 0x3c753b95, 0xbac9bc7f,
    0x3c62bbf1, 0x3c463c22, 0x3ac9bc7f, 0xbbf13c62, 0xbc22bc46, 0xbb95bc75, 0xbc183c4e, 0xbb793c78, 0x3c043c5c, 0xbc4ebc18,
    0x3c713bac, 0x3c2cbc3e, 0x3c2cbc3e, 0x3bdb3c67, 0x3a49bc80, 0xbc713bac, 0xbc67bbdb, 0x3a49bc80, 0xbc783b79, 0x3c7d3b16,
    0xbb163c7d, 0xbc043c5c, 0x3c553c0e, 0x3c7b3b48, 0x3c0ebc55, 0xbb483c7b, 0x3b48bc7b, 0xbc55bc0e, 0xbc7bbb48, 0x3c0ebc55,
    0xbc7b3b48, 0x3c0e3c55, 0x3b483c7b, 0xbc553c0e, 0x3c0e3c55, 0xbb48bc7b, 0x3c55bc0e, 0x3c7bbb48, 0x3c04bc5c, 0x3b16bc7d,
    0xbc7dbb16, 0x3c78bb79, 0xbc80ba49, 0xbbdb3c67, 0x3bac3c71, 0xbc80ba49, 0x3bdb3c67, 0x3c2cbc3e, 0x3c2cbc3e, 0x3c713bac,
    0x3c18bc4e, 0xbc5c3c04, 0xbc78bb79, 0xbc4ebc18, 0xbc62bbf1, 0xbc7fbac9, 0x3b953c75, 0xbc22bc46, 0x3ac93c7f, 0x3c753b95,
    0x3c22bc46, 0x3bf13c62, 0x3c46bc22, 0xbc62bbf1, 0xbc7fbac9, 0xbb95bc75, 0xbc75bb95, 0x3c463c22, 0x3bf13c62, 0x3ac93c7f,
    0xbbdb3c67, 0xba493c80, 0x3c3ebc2c, 0xbbdb3c67, 0x3c78bb79, 0x3b16bc7d, 0xbc7dbb16, 0x3c04bc5c, 0xbc4ebc18, 0xbb793c78,
    0x3c043c5c, 0xbc183c4e, 0x3a493c80, 0x3bacbc71, 0x3bacbc71, 0x3c2cbc3e, 0x3c353c35, 0x3c6d3bc4, 0x3c353c35, 0xbc6dbbc4,
    0x3c35bc35, 0xbbc4bc6d, 0x3c35bc35, 0x3bc43c6d, 0xbc35bc35, 0xbbc43c6d, 0xbc35bc35, 0x3bc4bc6d, 0xbc353c35, 0x3c6dbbc4,
    0xbc353c35, 0xbc6d3bc4, 0xba49bc80, 0xbbdbbc67, 0xbbdbbc67, 0x3c3e3c2c, 0xbc7d3b16, 0xbb793c78, 0xbc5c3c04, 0xbb16bc7d,
    0x3b793c78, 0x3c4ebc18, 0x3c183c4e, 0xbc043c5c, 0x3c71bbac, 0xbc80ba49, 0x3c3ebc2c, 0x3c71bbac, 0xbc223c46, 0xbb953c75,
    0x3ac93c7f, 0xbbf1bc62, 0x3c623bf1, 0x3c46bc22, 0x3c75bb95, 0xbac93c7f, 0x3b95bc75, 0xbc7f3ac9, 0xbbf1bc62, 0x3c22bc46,
    0xbc7fbac9, 0x3c623bf1, 0xbc463c22, 0xbc753b95, 0x3c7dbb16, 0x3c5cbc04, 0x3b79bc78, 0x3b163c7d, 0xbbdbbc67, 0xbc803a49,
    0xbc803a49, 0x3bacbc71, 0xbc3e3c2c, 0x3c673bdb, 0x3bac3c71, 0xbc3e3c2c, 0x3c5c3c04, 0xbc18bc4e, 0x3c4ebc18, 0x3c78bb79,
    0xbc55bc0e, 0xbc7bbb48, 0xbc0e3c55, 0x3b48bc7b, 0xbb483c7b, 0x3c553c0e, 0x3c7b3b48, 0xbc0e3c55, 0x3c7bbb48, 0xbc0ebc55,
    0xbb48bc7b, 0x3c55bc0e, 0xbc0ebc55, 0x3b483c7b, 0xbc553c0e, 0xbc7b3b48, 0x3b793c78, 0x3c183c4e, 0x3c4ebc18, 0xbc043c5c,
    0x3c3ebc2c, 0xbbacbc71, 0xbc67bbdb, 0x3c3ebc2c, 0xbc71bbac, 0x3a493c80, 0x3a493c80, 0xbc673bdb, 0x3b163c7d, 0x3b79bc78,
    0x3c5cbc04, 0x3c7dbb16, 0x3bf1bc62, 0x3ac9bc7f, 0xbc753b95, 0x3c46bc22, 0xbc7f3ac9, 0xbb953c75, 0x3c463c22, 0xbc623bf1,
    0x3c223c46, 0x3bf1bc62, 0x3ac9bc7f, 0x3c75bb95, 0x3b95bc75, 0xbc223c46, 0xbc623bf1, 0xbc7f3ac9, 0xbc713bac, 0xbc3e3c2c,
    0x3c803a49, 0xbc713bac, 0x3c5c3c04, 0x3c4ebc18, 0xbc18bc4e, 0x3c78bb79, 0xbb16bc7d, 0xbc5c3c04, 0xbb793c78, 0xbc7d3b16,
    0xbc2c3c3e, 0x3c67bbdb, 0x3c67bbdb, 0x3c80ba49, 0x3c800000, 0x3c6dbbc4, 0x3c800000, 0xbc6d3bc4, 0xbc800000, 0xbbc43c6d,
    0xbc800000, 0x3bc4bc6d, 0x3c800000, 0xbbc4bc6d, 0x3c800000, 0x3bc43c6d, 0xbc800000, 0x3c6d3bc4, 0xbc800000, 0xbc6dbbc4,
    0x3c80ba49, 0x3c67bbdb, 0x3c67bbdb, 0xbc2c3c3e, 0xbc7d3b16, 0xbb793c78, 0xbc5c3c04, 0xbb16bc7d, 0x3c78bb79, 0xbc18bc4e,
    0x3c4ebc18, 0x3c5c3c04, 0xbc713bac, 0x3c803a49, 0xbc3e3c2c, 0xbc713bac, 0x3c7fbac9, 0x3c62bbf1, 0x3c22bc46, 0xbb953c75,
    0xbc753b95, 0xbac93c7f, 0xbbf13c62, 0xbc22bc46, 0x3c62bbf1, 0xbc46bc22, 0x3b95bc75, 0x3c7fbac9, 0xbc463c22, 0x3c75bb95,
    0xbac93c7f, 0xbbf13c62, 0x3c7dbb16, 0x3c5cbc04, 0x3b79bc78, 0x3b163c7d, 0xbc673bdb, 0x3a493c80, 0x3a493c80, 0xbc71bbac,
    0x3c3ebc2c, 0xbc67bbdb, 0xbbacbc71, 0x3c3ebc2c, 0xbc043c5c, 0x3c4ebc18, 0x3c183c4e, 0x3b793c78, 0x3c7bbb48, 0x3c55bc0e,
    0xbb48bc7b, 0x3c0e3c55, 0xbc553c0e, 0x3b483c7b, 0x3c0e3c55, 0xbc7b3b48, 0x3c0ebc55, 0xbc7bbb48, 0xbc55bc0e, 0x3b48bc7b,
    0xbb483c7b, 0x3c0ebc55, 0x3c7b3b48, 0x3c553c0e, 0x3c78bb79, 0x3c4ebc18, 0xbc18bc4e, 0x3c5c3c04, 0xbc3e3c2c, 0x3bac3c71,
    0x3c673bdb, 0xbc3e3c2c, 0x3bacbc71, 0xbc803a49, 0xbc803a49, 0xbbdbbc67, 0x3b163c7d, 0x3b79bc78, 0x3c5cbc04, 0x3c7dbb16,
    0x3c75bb95, 0x3c46bc22, 0xbc62bbf1, 0x3c7f3ac9, 0xbc223c46, 0x3bf13c62, 0x3c7fbac9, 0xbb953c75, 0x3ac9bc7f, 0xbc753b95,
    0xbc463c22, 0xbc62bbf1, 0x3bf13c62, 0xbac9bc7f, 0x3b95bc75, 0x3c22bc46, 0x3c71bbac, 0x3c3ebc2c, 0xbc80ba49, 0x3c71bbac,
    0xbc043c5c, 0x3c183c4e, 0x3c4ebc18, 0x3b793c78, 0xbb16bc7d, 0xbc5c3c04, 0xbb793c78, 0xbc7d3b16, 0x3c3e3c2c, 0xbbdbbc67,
    0xbbdbbc67, 0xba49bc80, 0x3c800000, 0x3c6dbbc4, 0x3c800000, 0xbc6d3bc4, 0xbc800000, 0xbbc43c6d, 0xbc800000, 0x3bc4bc6d,
    0x3c800000, 0xbbc4bc6d, 0x3c800000, 0x3bc43c6d, 0xbc800000, 0x3c6d3bc4, 0xbc800000, 0xbc6dbbc4, 0x3c2cbc3e, 0x3bacbc71,
    0x3bacbc71, 0x3a493c80, 0xbc183c4e, 0x3c043c5c, 0xbb793c78, 0xbc4ebc18, 0x3c04bc5c, 0xbc7dbb16, 0x3b16bc7d, 0x3c78bb79,
    0xbbdb3c67, 0x3c3ebc2c, 0xba493c80, 0xbbdb3c67, 0xbac9bc7f, 0xbbf1bc62, 0xbc46bc22, 0x3c753b95, 0x3b953c75, 0x3c7f3ac9,
    0x3c623bf1, 0xbc463c22, 0xbbf1bc62, 0xbc223c46, 0xbc75bb95, 0xbac9bc7f, 0x3c223c46, 0xbb95bc75, 0x3c7f3ac9, 0x3c623bf1,
    0xbc4ebc18, 0xbc78bb79, 0xbc5c3c04, 0x3c18bc4e, 0x3c713bac, 0x3c2cbc3e, 0x3c2cbc3e, 0x3bdb3c67, 0xbc80ba49, 0x3bac3c71,
    0xbbdb3c67, 0xbc80ba49, 0x3c78bb79, 0xbc7dbb16, 0x3b16bc7d, 0x3c04bc5c, 0xbc7b3b48, 0xbc553c0e, 0x3b483c7b, 0xbc0ebc55,
    0x3c55bc0e, 0xbb48bc7b, 0xbc0ebc55, 0x3c7bbb48, 0xbc0e3c55, 0x3c7b3b48, 0x3c553c0e, 0xbb483c7b, 0x3b48bc7b, 0xbc0e3c55,
    0xbc7bbb48, 0xbc55bc0e, 0xbc043c5c, 0xbb163c7d, 0x3c7d3b16, 0xbc783b79, 0x3a49bc80, 0xbc67bbdb, 0xbc713bac, 0x3a49bc80,
    0x3bdb3c67, 0x3c2cbc3e, 0x3c2cbc3e, 0x3c713bac, 0xbc4ebc18, 0x3c043c5c, 0xbb793c78, 0xbc183c4e, 0x3b953c75, 0x3c223c46,
    0x3bf1bc62, 0xbac93c7f, 0xbc46bc22, 0xbc623bf1, 0x3ac93c7f, 0xbc75bb95, 0x3c7f3ac9, 0xbb95bc75, 0xbc22bc46, 0x3bf1bc62,
    0xbc623bf1, 0x3c7fbac9, 0x3c753b95, 0x3c463c22, 0x3c673bdb, 0x3c803a49, 0xbc2cbc3e, 0x3c673bdb, 0xbc783b79, 0xbb163c7d,
    0x3c7d3b16, 0xbc043c5c, 0x3c18bc4e, 0xbc78bb79, 0xbc5c3c04, 0xbc4ebc18, 0x3a493c80, 0x3bacbc71, 0x3bacbc71, 0x3c2cbc3e,
    0x3c800000, 0x3c6dbbc4, 0x3c800000, 0xbc6d3bc4, 0xbc800000, 0xbbc43c6d, 0xbc800000, 0x3bc4bc6d, 0x3c800000, 0xbbc4bc6d,
    0x3c800000, 0x3bc43c6d, 0xbc800000, 0x3c6d3bc4, 0xbc800000, 0xbc6dbbc4, 0xba49bc80, 0xbbdbbc67, 0xbbdbbc67, 0x3c3e3c2c,
    0x3b163c7d, 0x3c783b79, 0x3c043c5c, 0xbc7d3b16, 0xbb79bc78, 0xbc4e3c18, 0xbc18bc4e, 0x3c04bc5c, 0x3bac3c71, 0x3a49bc80,
    0x3c2c3c3e, 0x3bac3c71, 0xbc7f3ac9, 0xbc623bf1, 0xbc223c46, 0x3b95bc75, 0x3c75bb95, 0x3ac9bc7f, 0x3bf1bc62, 0x3c223c46,
    0xbc623bf1, 0x3c463c22, 0xbb953c75, 0xbc7f3ac9, 0x3c46bc22, 0xbc753b95, 0x3ac9bc7f, 0x3bf1bc62, 0x3b163c7d, 0x3c043c5c,
    0x3c783b79, 0xbc7d3b16, 0xbbdbbc67, 0xbc803a49, 0xbc803a49, 0x3bacbc71, 0x3c2c3c3e, 0x3bdbbc67, 0x3c71bbac, 0x3c2c3c3e,
    0xbc5cbc04, 0x3c183c4e, 0xbc4e3c18, 0xbc783b79, 0x3c7bbb48, 0x3c55bc0e, 0xbb48bc7b, 0x3c0e3c55, 0xbc553c0e, 0x3b483c7b,
    0x3c0e3c55, 0xbc7b3b48, 0x3c0ebc55, 0xbc7bbb48, 0xbc55bc0e, 0x3b48bc7b, 0xbb483c7b, 0x3c0ebc55, 0x3c7b3b48, 0x3c553c0e,
    0xbb79bc78, 0xbc18bc4e, 0xbc4e3c18, 0x3c04bc5c, 0x3c2c3c3e, 0x3c71bbac, 0x3bdbbc67, 0x3c2c3c3e, 0xbc71bbac, 0x3a493c80,
    0x3a493c80, 0xbc673bdb, 0x3c7dbb16, 0xbc78bb79, 0xbc04bc5c, 0xbb16bc7d, 0xbc753b95, 0xbc463c22, 0x3c623bf1, 0xbc7fbac9,
    0x3c22bc46, 0xbbf1bc62, 0xbc7f3ac9, 0x3b95bc75, 0xbac93c7f, 0x3c75bb95, 0x3c46bc22, 0x3c623bf1, 0xbbf1bc62, 0x3ac93c7f,
    0xbb953c75, 0xbc223c46, 0x3bac3c71, 0x3c2c3c3e, 0x3a49bc80, 0x3bac3c71, 0xbc5cbc04, 0xbc4e3c18, 0x3c183c4e, 0xbc783b79,
    0x3c7dbb16, 0xbc04bc5c, 0xbc78bb79, 0xbb16bc7d, 0xbc2c3c3e, 0x3c67bbdb, 0x3c67bbdb, 0x3c80ba49, 0x3c800000, 0x3c6dbbc4,
    0x3c800000, 0xbc6d3bc4, 0xbc800000, 0xbbc43c6d, 0xbc800000, 0x3bc4bc6d, 0x3c800000, 0xbbc4bc6d, 0x3c800000, 0x3bc43c6d,
    0xbc800000, 0x3c6d3bc4, 0xbc800000, 0xbc6dbbc4, 0xbc3ebc2c, 0xbc71bbac, 0xbc71bbac, 0x3c80ba49, 0x3c4e3c18, 0x3c5cbc04,
    0x3c783b79, 0xbc183c4e, 0xbc5cbc04, 0xbb163c7d, 0xbc7dbb16, 0xbb79bc78, 0x3c673bdb, 0xbc2cbc3e, 0x3c803a49, 0x3c673bdb,
    0x3ac93c7f, 0x3bf13c62, 0x3c463c22, 0xbc75bb95, 0xbb95bc75, 0xbc7fbac9, 0xbc62bbf1, 0x3c46bc22, 0x3bf13c62, 0x3c22bc46,
    0x3c753b95, 0x3ac93c7f, 0xbc22bc46, 0x3b953c75, 0xbc7fbac9, 0xbc62bbf1, 0x3c18bc4e, 0x3b79bc78, 0xbc04bc5c, 0x3c4e3c18,
    0xbbac3c71, 0x3c3e3c2c, 0x3c3e3c2c, 0xbc673bdb, 0x3a49bc80, 0xbc713bac, 0xbc67bbdb, 0x3a49bc80, 0x3b793c78, 0x3b16bc7d,
    0x3c7d3b16, 0x3c5c3c04, 0xbc7b3b48, 0xbc553c0e, 0x3b483c7b, 0xbc0ebc55, 0x3c55bc0e, 0xbb48bc7b, 0xbc0ebc55, 0x3c7bbb48,
    0xbc0e3c55, 0x3c7b3b48, 0x3c553c0e, 0xbb483c7b, 0x3b48bc7b, 0xbc0e3c55, 0xbc7bbb48, 0xbc55bc0e, 0x3c5c3c04, 0x3c7d3b16,
    0x3b16bc7d, 0x3b793c78, 0xbc80ba49, 0xbbdb3c67, 0x3bac3c71, 0xbc80ba49, 0x3c67bbdb, 0xbc3ebc2c, 0xbc3ebc2c, 0x3bacbc71,
    0xbc183c4e, 0x3c5cbc04, 0x3c783b79, 0x3c4e3c18, 0xbb95bc75, 0xbc22bc46, 0xbbf13c62, 0x3ac9bc7f, 0x3c463c22, 0x3c62bbf1,
    0xbac9bc7f, 0x3c753b95, 0xbc7fbac9, 0x3b953c75, 0x3c223c46, 0xbbf13c62, 0x3c62bbf1, 0xbc7f3ac9, 0xbc75bb95, 0xbc46bc22,
    0xbbdb3c67, 0xba493c80, 0x3c3ebc2c, 0xbbdb3c67, 0xbb79bc78, 0xbc7dbb16, 0xbb163c7d, 0xbc5cbc04, 0x3c4e3c18, 0x3b79bc78,
    0xbc04bc5c, 0x3c18bc4e, 0xbc803a49, 0x3c713bac, 0x3c713bac, 0x3c3e3c2c,
};

template <int G = 1024> __device__ __forceinline__ void store_tile_64(const float (&d)[32], uint32_t base, int warp, int lane) {
  const uint32_t rb = base + (warp * 2 + ((lane >> 3) & 1)) * G + (lane & 7) * 128;
#pragma unroll
  for (int j = 0; j < 8; j += 2) {
    const int jj = j + (lane >> 4);
    stsm4(rb + ((jj ^ (lane & 7)) << 4), pack2(d[4 * j], d[4 * j + 1]), pack2(d[4 * j + 2], d[4 * j + 3]),
          pack2(d[4 * j + 4], d[4 * j + 5]), pack2(d[4 * j + 6], d[4 * j + 7]));
  }
}

#define A_XM0 0xEB5C
#define A_XM1 0xDCBC
#define A_REL 0x22910
#define G_WPOLK 12
#define A_LDW 0x242
#define A_W2PF 2
#define A_DEPS 4
#define A_FREE 0x3F000
#define A_RELS 0x8A80
#define A_ACQ 0x1511
#define A_DEP 3
#define A_PACE0 1000
#define A_PACE1 A_PACE0
#define A_PACE_N 8
#define G_TMASK 0x0FB0
constexpr int A_IN = 112 * 128, A_OUT = 16384, A_NIN = 5, A_NOUT = 6;
constexpr int A_NREL = __builtin_popcount(A_REL);
constexpr int G_XP = NB1 * 64;
constexpr int G_STAGE = 16384 + 2 * G_XP, G_NST = 5;
constexpr int G_TIN = G_NST * G_STAGE, G_TOUT = G_TIN + 8192, G_SMEM = G_TOUT + 32768 + 1024;
#define G_SLOTS 0x1032410324103210ull
__host__ __device__ constexpr int g_slot(int k) { return (G_SLOTS >> (4 * k)) & 7; }
constexpr uint32_t g_parities() {
  uint32_t m = 0;
  for (int k = 0; k < 16; k++)
    for (int j = 0; j < k; j++)
      if (g_slot(j) == g_slot(k)) m ^= 1u << k;
  return m;
}
constexpr uint32_t G_PAR = g_parities();
constexpr int G_KS = 12;
__device__ __align__(128) int g_cnt[4 * 32];

__device__ __forceinline__ int x_decode(int r, int cta) {
  const int v = r * 64 + ((cta >> 2) << 1) + (cta & 1);
  int j = v / 80;
  j -= v < 80 * j + ((0x4840 >> (4 * j)) & 15);
  if (cta < 128) return ((7 - j) << 7) | (v - 80 * j - ((0x4840 >> (4 * j)) & 15));
  return r < 8 ? ((5 - (r >> 2)) << 7) | (76 + 4 * (cta & 1) + (r & 3)) : ((7 - (r >> 1)) << 7) | (80 + 2 * (cta & 1) + (r & 1));
}
__device__ __forceinline__ uint32_t a_out(int n) {
  const int p = n % A_NOUT;
  return (p < 4 ? (3 + (p >> 1)) * G_STAGE : G_TOUT) + (p & 1) * A_OUT;
}
__device__ __forceinline__ uint32_t x1_addr(int L, int b, uint32_t flips) {
  const int p = L >> 4, sel = (b ^ __popc(L & 15) ^ (flips >> p)) & 1;
  return (p << 21) | (sel << 12) | ((L & 1) << 13) | ((L & 6) << 15) | ((L & 8) << 16);
}
__device__ __forceinline__ uint32_t spread16(int i) { return ((i & 3) << 14) | ((i & 4) << 16) | ((i & 8) << 17); }
constexpr int NPG = 19 + W_SHIFT, NVOTE = 6;
__device__ __forceinline__ uint32_t w_addr(int P, int f, int c, int dhalf, uint32_t flips) {
  return x1_addr(16 * P + (c >> 5) + 2 * (f >> 3), dhalf, flips >> 12) + spread16(2 * f) + (c & 31) * 128;
}
__device__ __forceinline__ void w_store(const CUtensorMap* m, uint32_t src, uint32_t a) {
#pragma unroll
  for (int j = 0; j < 8; j++)
    tma_st5<0>(m, src + j * 2048, ((a & 16383) >> 1) ^ ((__popc(j) & 1) << 11), (j & 3) << 1, (j >> 2) << 1, a >> 20, 0);
}
__device__ __forceinline__ uint32_t read_votes(const int* cnt, int lane, int& side, int v = 0) {
  for (int it = 0; it < (1 << 20) && (__ballot_sync(0xffffffffu, v < NVOTE * 256) & ((2 << NPG) - 2)); it++)
    asm volatile("ld.relaxed.gpu.global.s32 %0, [%1];" : "=r"(v) : "l"(cnt + 32 + lane) : "memory");
  uint32_t smid;
  asm("mov.u32 %0, %%smid;" : "=r"(smid));
  side = (__shfl_sync(0xffffffffu, v, 24 + (smid >> 5) % 6) >> (smid & 31)) & 1;
  return __ballot_sync(0xffffffffu, (v & 255) > NVOTE / 2);
}
__device__ __forceinline__ int take_ticket(int* p) {
  int v;
  asm volatile("atom.relaxed.gpu.global.inc.u32 %0, [%1], 0xffffffff;" : "=r"(v) : "l"(p) : "memory");
  return v;
}
__device__ __forceinline__ void send_role(uint32_t dst, uint32_t bar, int v) {
  for (int c = 0; c < 2; c++)
    asm volatile("{\n.reg .b32 a, b;\nmapa.shared::cluster.u32 a, %0, %2;\nmapa.shared::cluster.u32 b, %1, %2;\n"
                 "st.async.shared::cluster.mbarrier::complete_tx::bytes.u32 [a], %3, [b];\n}" ::"r"(dst), "r"(bar), "r"(c), "r"(v) : "memory");
}
struct GMaps {
  CUtensorMap in[5];
  CUtensorMap ws, xs, w, y;
};

__global__ void __cluster_dims__(2, 1, 1) __launch_bounds__(384, 1)
kG(int* __restrict__ cnt, char* __restrict__ x1, char* __restrict__ wt, const __nv_bfloat16* __restrict__ g,
   const __nv_bfloat16* __restrict__ wgt, float* __restrict__ ge, const uint32_t* __restrict__ img, const __grid_constant__ GMaps m) {
  extern __shared__ uint8_t smem_raw[];
  __shared__ __align__(8) uint64_t bars[20 + A_NIN + 2 * A_NOUT + 2 * G_NST + 16 + 2 * A_NREL];
  __shared__ uint16_t tab[128];
  __shared__ uint32_t lat[8], s_role, s_flips;
  const uint32_t sb = pin((s2u(smem_raw) + 1023) & ~1023u);
  const int tid = threadIdx.x, wg = __shfl_sync(0xffffffffu, tid >> 7, 0), t = tid & 127;
  const int warp = __shfl_sync(0xffffffffu, t >> 5, 0), lane = t & 31;
  const int blk = blockIdx.x, hf = blk & 1, page = 1 + blk % NPG;
  const bool spare = blk >= 128, voter = blk >= 128 - NPG * NVOTE && !spare;
  const int nu = spare ? 16 : 18;
  const uint32_t xm = spare ? 0xFFFF : hf ? A_XM1 : A_XM0;
  const uint32_t wf0 = pin(s2u(&bars[0])), xf0 = wf0 + 32, xe0 = xf0 + 128, aof0 = xe0 + 8 * A_NIN, aoe0 = aof0 + 8 * A_NOUT;
  const uint32_t full0 = aoe0 + 8 * A_NOUT, empty0 = full0 + 8 * G_NST;
  const uint32_t sf0 = empty0 + 8 * G_NST, se0 = sf0 + 16, inf0 = se0 + 16, roleb = inf0 + 16, flipb = roleb + 8;
  const uint32_t rel0 = flipb + 8, got0 = rel0 + 8 * A_NREL, acq0 = got0 + 64;
  auto role = [&]() {
    mbar_wait(roleb, 0);
    return 2 * (int)*(volatile uint32_t*)&s_role + hf;
  };
  auto flips = [&]() {
    mbar_wait(flipb, 0);
    return *(volatile uint32_t*)&s_flips;
  };
  auto w_unit = [&](int cta) { return (cta & ~3) | (hf << 1) | ((cta >> 1) & 1); };
  auto w_code = [](int w2, int s, int i) { return (-(s < 4) << 16) | ((2 * w2 + (s >> 2)) << 11) | ((s & 3) << 9) | ((i >> 1) << 3) | ((i & 1) << 1); };
  auto in_load = [&](int c, uint32_t dst, uint32_t bar) {
    tma_ld5<1>(dst, &m.in[(c >> 11) & 7], bar, 0, c >> 16, c & 7, (c >> 3) & 63, (c >> 9) & 3);
  };
  if (wg < 2) {
    if (lane == 0) {
      const uint32_t h = blk & 0x59, par = h ^ (h >> 3) ^ (h >> 4) ^ (h >> 6);
      char* p = x1 + (blk << 13) + (((warp ^ par) & 1) << 12) + 3584 + (warp >> 1) * 128;
      if (wg) {
        if (!voter) p += 256;
        else if (page < 12) p += page << 21;
        else p = wt + w_addr(page - 12, warp >> 1, blk >> 1, warp & 1, 0);
      }
      uint32_t c0, c1;
      asm volatile("{\n.reg .u32 v;\n.reg .pred q;\n"
                   "st.global.v4.u32 [%2], {0, 0, 0, 0};\nst.global.v4.u32 [%2 + 16], {0, 0, 0, 0};\n"
                   "mov.u32 %0, %%clock;\nmov.u32 %1, %0;\natom.relaxed.gpu.global.exch.b32 v, [%2], 1;\n"
                   "setp.eq.u32 q, v, 0;\n@q mov.u32 %1, %%clock;\n}\n" : "=r"(c0), "=r"(c1) : "l"(p) : "memory");
      lat[wg * 4 + warp] = c1 - c0;
    }
    __syncwarp();
    if (wg == 0 && hf == 0) bar_arrive(10, 160);
    bar_arrive(9, 288);
  }
  if (wg == 2) {
    if (t == 32) {
      mbar_init(wf0 + 24, 1);
      mbar_expect(wf0 + 24, 8192);
      fence_async();
      if (!spare) tma_ld5<1>(sb + 2 * G_STAGE + 3 * 8192, &m.in[1], wf0 + 24, 0, 0, 2 * hf, blk >> 1, 2);
    }
    __syncwarp();
    int votes = 0;
    if (warp == 3 && !voter) asm volatile("ld.relaxed.gpu.global.s32 %0, [%1];" : "=r"(votes) : "l"(cnt + 32 + lane) : "memory");
    asm volatile("setmaxnreg.dec.sync.aligned.u32 40;");
    if (lane == 0 && warp > 0) {
      if (warp == 1) {
        for (int i = 0; i < 3; i++) {
          mbar_init(wf0 + 8 * i, 1);
          mbar_expect(wf0 + 8 * i, 8192);
        }
      } else if (warp == 2) {
        prefetch_map(&m.in[4]);
        for (int i = 0; i < A_NIN + A_NOUT; i++) mbar_init(xe0 + 8 * i, 4);
        for (int i = 0; i < A_NOUT; i++) mbar_init(aoe0 + 8 * i, 1);
      } else {
        for (int i = 0; i < 2; i++) mbar_init(sf0 + 8 * i, 8);
        for (int i = 0; i < 6 + A_NREL; i++) mbar_init(se0 + 8 * i, 1);
        for (int i = 0; i < 3; i++) mbar_expect(inf0 + 8 * i, i < 2 ? 4096 : 4);
      }
      fence_bar_init();
    }
    __syncwarp();
    asm volatile("barrier.cluster.arrive.relaxed.aligned;" ::: "memory");
    int role_w = warp;
    if (role_w == 0) {
      int cta = blk, side = 0;
      if (hf == 0) {
        bar_sync(10, 160);
        side = min(lat[0], lat[2]) > min(lat[1], lat[3]);
        if (lane == 0) cta = take_ticket(cnt + (spare ? 62 : 54) + side);
      }
      const uint32_t wm = spare ? 0 : A_LDW | 0x6000;
      const int nw = __popc(wm & ((1 << lane) - 1)), r = lane - nw, np = r + A_NIN - (spare ? A_DEPS : A_DEP);
      const bool isw = (wm >> lane) & 1;
      uint32_t dst = sb + (!isw ? (r % A_NIN) * A_IN : nw < 3 ? 2 * G_STAGE + (2 - nw) * 8192 : G_TIN + (nw - 3) * 4096);
      uint32_t bf = !isw ? xf0 + 8 * r : nw < 3 ? wf0 + 8 * (2 - nw) : inf0 + 8 * (nw - 3);
      uint32_t be = isw ? roleb : xe0 + 8 * (np % A_NIN) + ((np / A_NIN - 1) & 1);
      asm volatile("barrier.cluster.wait.aligned;" : "+r"(dst), "+r"(bf), "+r"(be)::"memory");
      if (hf == 0) {
        cta = 2 * __shfl_sync(0xffffffffu, cta, 0) + side;
        if (cta >= 64) cta = 127 - cta;
        if (spare) cta = 64 + (cta >= 2 ? 3 - cta : cta);
        if (lane == 0) send_role(s2u(&s_role), roleb, cta);
        cta *= 2;
      } else {
        cta = role();
      }
      const int b = (cta >> 1) & 1;
      if (lane == 0 && !spare) tma_ld5<1>(sb, &m.in[4], xf0, 0, 96 * (((cta >> 2) << 1) + hf) - 24, 7, 0, b);
      __syncwarp();
      const int xc = x_decode(r, cta);
      const int code = isw ? w_code(nw >= 3, nw < 3 ? 4 - 2 * nw : 10 - nw, w_unit(cta)) : ((96 * (xc & 127) - 24) << 16) | (4 << 11) | (b << 9) | (xc >> 7);
#pragma unroll 1
      for (int p = !spare; p < (spare ? 16 : 15); p++) {
        const int c = __shfl_sync(0xffffffffu, code, p);
        const uint32_t d = __shfl_sync(0xffffffffu, dst, p), f = __shfl_sync(0xffffffffu, bf, p), e = __shfl_sync(0xffffffffu, be, p);
        mbar_wait(e & ~1u, e & 1);
        if (lane == 0) in_load(c, d, f);
        __syncwarp();
      }
      if (!spare) {
        const int bin = cta >> 2, f = 2 * bin + hf;
        if (lane == 0) {
          for (int s = 5; s >= A_W2PF; s--) {
            const int c = w_code(1, s, w_unit(cta));
            asm volatile("cp.async.bulk.prefetch.tensor.5d.L2.global [%0, {0, %1, %2, %3, %4}];" ::"l"(&m.in[(c >> 11) & 7]), "r"(c >> 16), "r"(c & 7), "r"((c >> 3) & 63), "r"((c >> 9) & 3) : "memory");
          }
          prefetch_map(&m.w);
          prefetch_map(&m.y);
          prefetch_map(&m.in[2]);
        }
        const uint32_t xa = x1_addr((21 - lane + 2 * (lane % 3)) * 8 + (f >> 4), b, flips()) + spread16(f);
        const uint32_t wa = w_addr(7 - (lane >> 1), 2 * bin, (lane & 1) * 32, hf, s_flips & ~0xC0000u);
#pragma unroll 1
        for (int k = 0; k < 16; k++) {
          const int st = g_slot(k);
          uint32_t a[3];
#pragma unroll
          for (int th = 0; th < 3; th++) a[th] = __shfl_sync(0xffffffffu, xa, 3 * (k >> 1) + th) ^ ((k & 1) * 0x21000);
          const uint32_t w = __shfl_sync(0xffffffffu, wa, k);
          if ((A_ACQ >> k) & 1) {
            mbar_wait(acq0 + 8 * __popc(A_ACQ & ((1 << k) - 1)), 0);
            asm volatile("fence.proxy.async.global;" ::: "memory");
          }
          mbar_wait(empty0 + 8 * st, (G_PAR >> k) & 1);
          if (lane == 0) {
            const uint32_t base = sb + st * G_STAGE, bar = full0 + 8 * st;
            mbar_expect(bar, G_STAGE);
#pragma unroll
            for (int th = 0; th < 3; th++)
              asm volatile("cp.async.bulk.shared::cluster.global.mbarrier::complete_tx::bytes.multicast::cluster.L2::cache_hint [%0], [%1], %2, [%3], %4, %5;"
                           ::"r"(base + 16384 + hf * G_XP + th * 3584), "l"(x1 + a[th]), "n"(3584), "r"(bar), "h"((uint16_t)3), "l"(policy<1>()) : "memory");
            if (k >= G_WPOLK) tma_ld3<1>(base, &m.w, bar, 0, (w >> 7) & 127, w >> 14);
            else tma_ld3<0>(base, &m.w, bar, 0, (w >> 7) & 127, w >> 14);
          }
          __syncwarp();
        }
        if (blk == 0 && lane == 0) asm volatile("cp.async.bulk.prefetch.L2.global [%0], 14336;" ::"l"(img) : "memory");
      }
    } else if (pin(warp) == 1) {
      if (lane == 0) {
        prefetch_map(&m.ws);
        prefetch_map(&m.xs);
        prefetch_map(&m.in[0]);
        prefetch_map(&m.in[3]);
      }
      __syncwarp();
      asm volatile("barrier.cluster.wait.aligned;" ::: "memory");
      if (lane == 0) {
#pragma unroll 1
        for (int r = spare; r < A_NREL; r++) {
          mbar_wait(rel0 + 8 * r, 0);
          asm volatile("fence.acq_rel.gpu;\nred.relaxed.gpu.global.inc.u32 [%0], 0xffffffff;" ::"l"(cnt + 8 + r) : "memory");
        }
      }
    } else if (warp == 2) {
      asm volatile("barrier.cluster.wait.aligned;" ::: "memory");
      const uint32_t relm = spare ? A_RELS : A_REL;
      const int xr = __popc(xm & ((1 << lane) - 1));
      const uint32_t srcs = sb + a_out(lane), bars = aof0 + 8 * (lane % A_NOUT);
      const uint32_t done = lane < 16 ? bars + 8 * A_NOUT : se0 + 8 * (lane & 1), relb = rel0 + 8 * (spare + __popc(relm & ((1 << lane) - 1)));
      const int cta = role(), xc = x_decode(xr, cta), q = xc & 127, th = q / 28, wi = lane < 2 ? blk : w_unit(cta);
      int code = (xm >> lane) & 1 ? 0x80000000u + x1_addr(((xc >> 7) * 3 + th) * 8, (cta >> 1) & 1, 0) + (q - 28 * th) * 128
                                  : w_addr(7 - lane + xr, 0, wi >> 1, wi & 1, 0);
      uint32_t fl = 0;
      auto tables = [&]() {
        fl = flips();
        code ^= ((fl >> (((code >> 21) & 15) + (code < 0 ? 0 : 12))) & 1) << 12;
      };
      if (spare) tables();
      uint32_t tnext = clock(), src = __shfl_sync(0xffffffffu, srcs, 0), bar = aof0;
      int c = __shfl_sync(0xffffffffu, code, 0);
      mbar_wait(bar, 0);
#pragma unroll 1
      for (int n = 0; n < nu; n++) {
        while ((int)(clock() - tnext) < 0);
        tnext = clock() + (spare ? 0 : n < A_PACE_N ? A_PACE0 : A_PACE1);
        if (lane == n) {
          if (c >= 0) {
            w_store(&m.ws, src, c);
          } else {
#pragma unroll
            for (int j = 0; j < 8; j++)
              tma_st4<0>(&m.xs, src + j * 2048, ((c & 16383) >> 1) ^ ((__popc(j) & 1) << 11) ^ ((j & 1) << 12), (j >> 1) << 2, (c >> 18) & 3, (c >> 20) & 31);
          }
          bulk_commit();
        }
        __syncwarp();
        if (n == 1 && !spare) tables();
        c = __shfl_sync(0xffffffffu, code, n + 1);
        src = __shfl_sync(0xffffffffu, srcs, n + 1);
        bar = __shfl_sync(0xffffffffu, bars, n + 1);
        if (n + 1 < nu) mbar_wait(bar, (n + 1 >= A_NOUT) ^ (n + 1 >= 2 * A_NOUT));
        bulk_wait<0>();
        if (lane == n) {
          mbar_arrive(done);
          if ((relm >> lane) & 1) mbar_arrive(relb);
        }
        __syncwarp();
        if (!spare && (n == 13 || n == 15) && lane < 16) mbar_arrive_cta(empty0 + 8 * ((n - 7) >> 1), lane & 1);
      }
      if (!spare) {
        const int i = w_unit(cta), wc = w_code(1, 5 - lane, i);
        const uint32_t wa = w_addr(7 + W_SHIFT - lane, 0, i >> 1, i & 1, fl);
#pragma unroll 1
        for (int it = 0; it < 8; it++) {
          const uint32_t a = __shfl_sync(0xffffffffu, wa, it), j = it & 1;
          const int c2 = __shfl_sync(0xffffffffu, wc, it);
          mbar_wait(sf0 + 8 * j, (it >> 1) & 1);
          if (lane == 0 && it < 6) {
            mbar_expect(inf0 + 8 * j, 4096);
            in_load(c2, sb + G_TIN + j * 4096, inf0 + 8 * j);
          }
          if (it >= W_SHIFT) mbar_wait(got0 + 8 * (it - W_SHIFT), 0);
          if (lane == 0) {
            w_store(&m.ws, sb + G_TOUT + j * A_OUT, a);
            bulk_commit();
            bulk_wait_read<0>();
            mbar_arrive(se0 + 8 * j);
          }
          __syncwarp();
        }
      }
    } else {
      int side;
      bar_sync(9, 288);
      const int near = min(lat[0], lat[2]) > min(lat[1], lat[3]);
      if (lane == 0 && voter)
        asm volatile("red.relaxed.gpu.global.add.s32 [%0], %1;" ::"l"(cnt + 32 + page), "r"(256 + (near ^ (min(lat[4], lat[6]) > min(lat[5], lat[7])))) : "memory");
      __syncwarp();
      asm volatile("barrier.cluster.wait.aligned;" ::: "memory");
      const uint32_t fl = read_votes(cnt, lane, side, votes);
      if (lane == 0) {
        s_flips = fl;
        mbar_arrive(flipb);
        uint32_t smid;
        asm("mov.u32 %0, %%smid;" : "=r"(smid));
        if (near) asm volatile("red.relaxed.gpu.global.or.b32 [%0], %1;" ::"l"(cnt + 56 + (smid >> 5) % 6), "r"(1 << (smid & 31)) : "memory");
      }
      __syncwarp();
      if (!spare) {
        bool open = lane < 8 - W_SHIFT || (lane >= 8 && lane < 8 + A_NREL);
        int k = 0;
        mbar_wait(rel0, 0);
#pragma unroll 1
        for (int p = 0; p < (1 << 16) && (k < 14 || __any_sync(0xffffffffu, open)); p++) {
          int v;
          asm volatile("ld.relaxed.gpu.global.s32 %0, [%1];" : "=r"(v) : "l"(cnt + (lane & 15)) : "memory");
          while (k < 14 && mbar_test(full0 + 8 * g_slot(k), (G_PAR >> k) & 1)) {
            if (lane == 0) mbar_arrive(empty0 + 8 * g_slot(k));
            if ((k & 1) && lane == 0) asm volatile("red.relaxed.gpu.global.inc.u32 [%0], 0xffffffff;" ::"l"(cnt + (k >> 1)) : "memory");
            k++;
          }
          if (open && v >= (lane <= 8 ? 128 : 132)) {
            asm volatile("fence.acquire.gpu;" ::: "memory");
            mbar_arrive(got0 + 8 * lane);
            open = false;
          }
        }
      }
    }
  } else {
    if (lane == 0) {
      const int w8 = 4 * wg + warp;
      for (int i = 0; i < 2; i++) {
        mbar_init(xf0 + 16 * w8 + 8 * i, 1);
        mbar_expect(xf0 + 16 * w8 + 8 * i, A_IN);
      }
      mbar_init(got0 + 8 * w8, 1);
      if (w8 >= 8 - A_NREL) mbar_init(acq0 + 8 * (7 - w8), 1);
      if (w8 < G_NST) {
        mbar_init(full0 + 8 * w8, 1);
        mbar_init(empty0 + 8 * w8, 17);
        mbar_arrive(empty0 + 8 * w8);
      }
      fence_bar_init();
    }
    __syncwarp();
    asm volatile("barrier.cluster.arrive.relaxed.aligned;" ::: "memory");
    if (wg == 1) tab[t] = __bfloat16_as_ushort(__float2bfloat16_rn(-__cosf((float)(t - 64) * 0.04908738521234052f)));
    bar_sync(1, 256);
    asm volatile("setmaxnreg.inc.sync.aligned.u32 232;");
    uint32_t fa[16];
    auto frag = [&](int i, int l) {
      const int f = warp * 16 + (l >> 2) + 8 * (i & 1), r = 8 * (i >> 1) + (l & 3) * 2;
      const int k0 = (f | 1) * r - ((f & 1) << 5);
      return tab[k0 & 127] | ((uint32_t)tab[(k0 + (f | 1)) & 127] << 16);
    };
#pragma unroll
    for (int i = 0; i < 16; i++) fa[i] = i < 4 ? frag(i, lane) : 0;
    reg_fence(fa);
    asm volatile("barrier.cluster.wait.aligned;" ::: "memory");
    int cta = blk, qs = 0;
#pragma unroll 1
    for (int n = wg; n < nu; n += 2) {
      float e[64];
      if ((n >> 1) == !spare) {
        pdl_launch();
        int l = lane;
        asm volatile("" : "+r"(l));
#pragma unroll
        for (int i = 4; i < 16; i++) fa[i] = frag(i, l);
        reg_fence(fa);
        cta = role();
        qs = ((cta >> 1) & 2) + hf;
      }
      if (spare) qs = n < 8 ? n & 3 : 2 * hf + wg;
      const bool isx = (xm >> n) & 1;
      const int r = __popc(xm & ((1 << n) - 1)), s = 7 - n + r;
      const uint32_t in = isx ? sb + (r % A_NIN) * A_IN : sb + 2 * G_STAGE + s * 4096;
      mbar_wait(isx ? xf0 + 8 * r : wf0 + 8 * (s >> 1), 0);
      if (!isx) {
        wg_fence();
        wgmma_rs_128<1, 1, 1>(e, fa[0], fa[1], fa[2], fa[3], mk_desc(in, 0, 2048, 1024, 1), 0);
        wg_commit();
      } else {
        wg_fence();
#pragma unroll
        for (int k = 0; k < 4; k++)
          wgmma_rs_128<1, 1, 1>(e, fa[4 * k], fa[4 * k + 1], fa[4 * k + 2], fa[4 * k + 3], mk_desc(in, k * 2048, 6144, 1024, 1), k);
        wg_commit();
      }
      wg_wait<0>();
      reg_fence(e);
      if (isx && lane == 0) mbar_arrive(xe0 + 8 * (r % A_NIN));
      if (((A_FREE >> n) & 1) && !spare && lane < 2) mbar_arrive_cta(empty0 + 8 * (__popc(A_FREE & ((1 << n) - 1)) >> 1), lane);
      if (n >= A_NOUT) mbar_wait(aoe0 + 8 * (n % A_NOUT), (n / A_NOUT - 1) & 1);
      const int row = warp * 16 + (lane & 7) + ((lane >> 3) & 1) * 8, hi = lane >> 4;
      const uint32_t rb = sb + a_out(n) + (isx ? row : row + (row & ~7)) * 128, ts = isx ? 8192 : 1024, xr = (lane & 7) ^ (isx ? qs : 0);
#pragma unroll
      for (int j = 0; j < 16; j += 2) {
        const uint32_t tile = isx ? (j >> 2) & 1 : j >> 3, pos = (isx ? (j >> 3) * 4 + (j & 3) : (j & 7)) + hi;
        stsm4(rb + tile * ts + ((pos ^ xr) << 4), pack2(e[4 * j], e[4 * j + 1]), pack2(e[4 * j + 2], e[4 * j + 3]),
              pack2(e[4 * j + 4], e[4 * j + 5]), pack2(e[4 * j + 6], e[4 * j + 7]));
      }
      fence_async();
      __syncwarp();
      if (lane == 0) mbar_arrive(aof0 + 8 * (n % A_NOUT));
    }
    if (spare) {
      float* sg = reinterpret_cast<float*>(smem_raw + (sb - s2u(smem_raw)));
      __nv_bfloat16* sw = reinterpret_cast<__nv_bfloat16*>(sg + 16 * 256);
      const int c0 = (cta - 128) * 64;
      uint4 vw[8], vg[2];
#pragma unroll
      for (int i = 0; i < 8; i++) vw[i] = __ldg(reinterpret_cast<const uint4*>(wgt + ((i * 256 + tid) >> 3) * 256 + c0 + (tid & 7) * 8));
#pragma unroll
      for (int i = 0; i < 2; i++) vg[i] = __ldg(reinterpret_cast<const uint4*>(g) + i * 256 + tid);
      bar_sync(3, 256);
#pragma unroll
      for (int i = 0; i < 8; i++) reinterpret_cast<uint4*>(sw)[i * 256 + tid] = vw[i];
#pragma unroll
      for (int i = 0; i < 2; i++) {
        const uint32_t w4[4] = {vg[i].x, vg[i].y, vg[i].z, vg[i].w};
#pragma unroll
        for (int e = 0; e < 4; e++) {
          sg[(i * 256 + tid) * 8 + 2 * e] = __uint_as_float(w4[e] << 16);
          sg[(i * 256 + tid) * 8 + 2 * e + 1] = __uint_as_float(w4[e] & 0xffff0000u);
        }
      }
      bar_sync(3, 256);
      const int col = tid & 63, r0 = (tid >> 6) * 4;
      float a0 = 0.f, a1 = 0.f, a2 = 0.f, a3 = 0.f;
#pragma unroll 8
      for (int k = 0; k < 256; k++) {
        const float w = __bfloat162float(sw[k * 64 + col]);
        a0 = fmaf(sg[(r0 + 0) * 256 + k], w, a0);
        a1 = fmaf(sg[(r0 + 1) * 256 + k], w, a1);
        a2 = fmaf(sg[(r0 + 2) * 256 + k], w, a2);
        a3 = fmaf(sg[(r0 + 3) * 256 + k], w, a3);
      }
      const int cc = c0 + col;
      const int pos = (cc & ~15) + ((cc >> 1) & 3) * 4 + ((cc >> 3) & 1) * 2 + (cc & 1);
      ge[(r0 + 0) * 256 + pos] = __bfloat162float(__float2bfloat16_rn(a0));
      ge[(r0 + 1) * 256 + pos] = __bfloat162float(__float2bfloat16_rn(a1));
      ge[(r0 + 2) * 256 + pos] = __bfloat162float(__float2bfloat16_rn(a2));
      ge[(r0 + 3) * 256 + pos] = __bfloat162float(__float2bfloat16_rn(a3));
      return;
    }
    const int b = (cta >> 1) & 1, bin = cta >> 2;
    float d[32];
    auto t_begin = [&](int it, int hh) {
      mbar_wait(inf0 + 8 * (it & 1), (it >> 1) & 1);
      wg_fence();
      wgmma_rs_64<1, 1, 1>(d, fa[0], fa[1], fa[2], fa[3], mk_desc(sb + G_TIN + (it & 1) * 4096 + hh * 2048, 0, 0, 1024, 1), 0);
      wg_commit();
    };
    auto t_end = [&](int it, int hh) {
      reg_fence(d);
      const int j = it & 1;
      mbar_wait(se0 + 8 * j, (it >> 1) & 1);
      store_tile_64<2048>(d, sb + G_TOUT + j * A_OUT + hh * 1024, warp, lane);
      fence_async();
      __syncwarp();
      if (lane == 0) mbar_arrive(sf0 + 8 * j);
    };
    float re[NB1 / 2], im[NB1 / 2];
#pragma unroll 1
    for (int k = 0; k < G_KS; k++) {
      const int st = g_slot(k);
      const int it = __popc(G_TMASK & ((1 << k) - 1));
      const bool T = (G_TMASK >> k) & 1;
      mbar_wait(full0 + 8 * st, (G_PAR >> k) & 1);
      const uint32_t base = sb + st * G_STAGE;
      const uint32_t wb = base + wg * 4096;
      if (T) t_begin(it, wg);
      wg_fence();
#pragma unroll
      for (int s = 0; s < 2; s++) {
        const int acc = (k | s) != 0;
        const uint64_t dP = mk_desc(wb, s * 2048, 0, 1024, 1), dQ = mk_desc(wb, 8192 + s * 2048, 0, 1024, 1);
        const uint64_t dA = mk_desc(base, 16384 + s * 32, 0, 512, 2), dB = mk_desc(base, 16384 + G_XP + s * 32, 0, 512, 2);
        wgmma_ss_168<1, 1, 1, 0>(re, dP, dA, acc);
        wgmma_ss_168<1, 1, 1, 0>(im, dP, dB, acc);
        wgmma_ss_168<1, 1, 1, 0>(re, dQ, dB, 1);
        wgmma_ss_168<-1, 1, 1, 0>(im, dQ, dA, 1);
      }
      wg_commit();
      wg_wait<1>();
      if (k > 0 && lane < 2) mbar_arrive_cta(empty0 + 8 * g_slot(k - 1), lane);
      if (T) t_end(it, wg);
    }
    auto tail = [&](auto part, bool wait) {
      constexpr int PART = decltype(part)::value;
#pragma unroll
      for (int k = G_KS; k < 16; k++) {
        if (wait) mbar_wait(full0 + 8 * g_slot(k), (G_PAR >> k) & 1);
        const uint32_t base = sb + g_slot(k) * G_STAGE, wb = base + wg * 4096;
        wg_fence();
#pragma unroll
        for (int s = 0; s < 2; s++) {
          const uint64_t dP = mk_desc(wb, s * 2048, 0, 1024, 1), dQ = mk_desc(wb, 8192 + s * 2048, 0, 1024, 1);
          const uint64_t dA = mk_desc(base, 16384 + s * 32, 0, 512, 2), dB = mk_desc(base, 16384 + G_XP + s * 32, 0, 512, 2);
          if (PART == 0) {
            wgmma_ss_168<1, 1, 1, 0>(re, dP, dA, 1);
            wgmma_ss_168<1, 1, 1, 0>(re, dQ, dB, 1);
          } else {
            wgmma_ss_168<1, 1, 1, 0>(im, dP, dB, 1);
            wgmma_ss_168<-1, 1, 1, 0>(im, dQ, dA, 1);
          }
        }
      }
      wg_commit();
    };
    auto put = [&](const float (&v)[NB1 / 2], uint32_t stg, int f) {
      const int mi = lane >> 3, i = lane & 7;
      const uint32_t a0 = stg + (mi >> 1) * 1024 + i * 128 + (((2 * warp + (mi & 1)) ^ i) << 4);
      const uint32_t ya = x1_addr(96 + 8 * lane + 4 * hf + 2 * wg + (f >> 5), b, s_flips) + (f & 31) * 128;
#pragma unroll
      for (int c = 0; c < 3; c++) {
#pragma unroll
        for (int j = 8 * c; j < 8 * c + 8 && j < 20; j += 2)
          stsm4t(a0 + j * 1024, pack2(v[4 * j], v[4 * j + 1]), pack2(v[4 * j + 2], v[4 * j + 3]),
                 pack2(v[4 * j + 4], v[4 * j + 5]), pack2(v[4 * j + 6], v[4 * j + 7]));
        if (c == 2)
          asm volatile("stmatrix.sync.aligned.m8n8.x2.trans.shared.b16 [%0], {%1, %2};" ::"r"(a0 + 20 * 1024),
                       "r"(pack2(v[80], v[81])), "r"(pack2(v[82], v[83])) : "memory");
        const uint32_t a = __shfl_sync(0xffffffffu, ya, 4 * c + warp);
        fence_async();
        bar_sync(2 + wg, 128);
        if (lane == 0 && (c < 2 || warp < 3)) {
          tma_st4<0>(c == 2 && warp == 2 ? &m.y : &m.xs, stg + (4 * c + warp) * 2048, (a & 16383) >> 1, (a >> 14) & 15, (a >> 18) & 3, a >> 20);
          bulk_commit();
        }
      }
    };
    if (wg == 0) {
      tail(std::integral_constant<int, 0>(), true);
      bar_arrive(4, 256);
      bar_sync(5, 256);
      wg_wait<0>();
      reg_fence(re);
      put(re, sb + 4 * G_STAGE, 2 * bin);
      bar_sync(7, 256);
      tail(std::integral_constant<int, 1>(), false);
      bar_arrive(8, 256);
      wg_wait<0>();
      reg_fence(im);
      bar_arrive(6, 256);
      put(im, sb + 4 * G_STAGE + NB1 * 128, 2 * bin + 1);
    } else {
#pragma unroll 1
      for (int h2 = 2 * __popc(G_TMASK); h2 < 16; h2++) {
        t_begin(h2 >> 1, h2 & 1);
        wg_wait<0>();
        t_end(h2 >> 1, h2 & 1);
      }
      wg_wait<0>();
      bar_arrive(5, 256);
      bar_sync(4, 256);
      tail(std::integral_constant<int, 0>(), true);
      bar_arrive(7, 256);
      mbar_wait(se0, 0);
      mbar_wait(se0 + 8, 0);
      wg_wait<0>();
      reg_fence(re);
      put(re, sb + G_TOUT, 2 * bin);
      bar_sync(8, 256);
      tail(std::integral_constant<int, 1>(), false);
      wg_wait<0>();
      reg_fence(im);
      bar_sync(6, 256);
      put(im, sb, 2 * bin + 1);
    }
    bulk_wait_read<0>();
  }
}

#define H_EPI 3
#define H_KS 11
#define C_PACE 0
#define C_POL 1
constexpr int H_XP = 168 * 64, H_STAGE = 8192 + 2 * H_XP, H_NST = 7, H_SMEM = H_NST * H_STAGE + 21504 + 1024;
constexpr int C_OUT = 7 * 8192, C_GI = 13 * 8192, C_F = C_GI + 6144, C_PIECE = C_F + 8192;
static_assert(C_GI >= 3 * H_STAGE && C_PIECE + C_OUT == 6 * H_STAGE, "slots 0..2 | 3..5 | 6 fall free together");

template <int WG>
__device__ __forceinline__ void h_loop(float (&acc)[84], uint32_t sb, uint32_t full0, uint32_t empty0, int lane) {
#pragma unroll 1
  for (int k = 0; k < 16; k++) {
    const int st = k % H_NST;
    if (WG == 1 && k == H_KS) bar_sync(4, 256);
    mbar_wait(full0 + 8 * st, (k / H_NST) & 1);
    const uint32_t base = sb + st * H_STAGE;
    wg_fence();
#pragma unroll
    for (int s = 0; s < 2; s++) {
      const uint64_t dP = mk_desc(base, s * 2048, 0, 1024, 1), dQ = mk_desc(base, 4096 + s * 2048, 0, 1024, 1);
      const uint64_t dA = mk_desc(base, 8192 + s * 32, 0, 512, 2), dB = mk_desc(base, 8192 + H_XP + s * 32, 0, 512, 2);
      wgmma_ss_168<1, 1, 1, 0>(acc, dP, WG == 0 ? dA : dB, k | s);
      wgmma_ss_168<WG == 0 ? 1 : -1, 1, 1, 0>(acc, dQ, WG == 0 ? dB : dA, 1);
    }
    wg_commit();
    if (WG == 0 && k == 15) bar_arrive(4, 256);
    if (k <= 10) {
      wg_wait<1>();
      if (k > 0 && k - 1 + H_NST < 16 && lane < 2) mbar_arrive_cta(empty0 + 8 * ((k - 1) % H_NST), lane);
    }
  }
  wg_wait<0>();
  reg_fence(acc);
}

template <int NC> __device__ __forceinline__ void gelu_pack(uint32_t* hp, const float (&h)[4 * NC], bool zero_first, bool zero_all) {
#pragma unroll
  for (int c = 0; c < 2 * NC; c++) {
    const uint32_t v = pack2(gelu(h[2 * c]), gelu(h[2 * c + 1]));
    hp[c] = zero_all || (zero_first && c < 2) ? 0u : v;
  }
#pragma unroll
  for (int c = 0; c < 2 * NC; c++) asm volatile("" : "+r"(hp[c])::"memory");
}
struct HMaps {
  CUtensorMap y1[2], xs, x, w, y;
};

__global__ void __cluster_dims__(2, 1, 1) __launch_bounds__(384, 1)
kH(int* __restrict__ cnt, const uint32_t* __restrict__ img, const __nv_bfloat16* __restrict__ wf, const __nv_bfloat16* __restrict__ wo,
   const uint32_t* __restrict__ gat, const __grid_constant__ HMaps m) {
  extern __shared__ uint8_t smem_raw[];
  __shared__ __align__(8) uint64_t bars[2 * H_NST + 14 + 12 + 6];
  __shared__ uint32_t s_role;
  const uint32_t sb = pin((s2u(smem_raw) + 1023) & ~1023u);
  const int tid = threadIdx.x, wg = __shfl_sync(0xffffffffu, tid >> 7, 0), t = tid & 127;
  const int warp = __shfl_sync(0xffffffffu, t >> 5, 0), lane = t & 31;
  const int rank = blockIdx.x & 1;
  const uint32_t full0 = pin(s2u(&bars[0])), empty0 = full0 + 8 * H_NST, yf0 = empty0 + 8 * H_NST, of0 = yf0 + 8 * 14;
  const uint32_t roleb = of0 + 8 * 12, imgb = roleb + 8, rel0 = imgb + 8, depb = rel0 + 16, pubb = depb + 8;
  uint32_t fl = 0;
  int ticket = 0;
  if (wg == 2 && !(warp & 1)) {
    asm volatile("barrier.cluster.arrive.relaxed.aligned;" ::: "memory");
    int side;
    fl = read_votes(cnt, lane, side);
    if (tid == 256 && rank == 0) ticket = 2 * take_ticket(cnt + 64 + side) + side;
    __syncwarp();
  } else {
    if (lane == 0) {
      if (wg == 2) {
        if (warp == 1) {
          for (int i = 0; i < 6; i++) mbar_init(roleb + 8 * i, 1);
          mbar_expect(roleb, 4);
          mbar_expect(imgb, 14336);
          fence_async();
          asm volatile("cp.async.bulk.shared::cluster.global.mbarrier::complete_tx::bytes [%0], [%1], 14336, [%2];"
                       ::"r"(sb + C_GI), "l"(img), "r"(imgb) : "memory");
        } else {
          prefetch_map(&m.y1[0]);
          prefetch_map(&m.y1[1]);
          prefetch_map(&m.xs);
        }
      } else {
        const int w8 = 4 * wg + warp;
        if (w8 < 7) {
          mbar_init(full0 + 8 * w8, 1);
          mbar_expect(full0 + 8 * w8, H_STAGE);
          mbar_init(empty0 + 8 * w8, 16);
          for (int i = 0; i < 2; i++) {
            mbar_init(yf0 + 16 * w8 + 8 * i, 1);
            mbar_expect(yf0 + 16 * w8 + 8 * i, 8192);
          }
        }
        if (w8 >= 2)
          for (int i = 0; i < 2; i++) mbar_init(of0 + 16 * (w8 - 2) + 8 * i, 4);
      }
      fence_bar_init();
    }
    __syncwarp();
    asm volatile("barrier.cluster.arrive.relaxed.aligned;" ::: "memory");
  }
  asm volatile("barrier.cluster.wait.aligned;" ::: "memory");
  if (tid == 256 && rank == 0) send_role(s2u(&s_role), roleb, ticket < 64 ? ticket : 127 - ticket);
  __syncwarp();
  mbar_wait(roleb, 0);
  __syncwarp();
  const int cta = 2 * *(volatile uint32_t*)&s_role + rank, dc = cta & 3, b = dc >> 1, bin = cta >> 2;
  const int p0 = bin >= 28, p1 = bin < 4 ? 1 : 2;
  if (wg == 2) {
    if (warp == 0) {
      const int pc = lane >= 7, blk = min(6 * (bin - 4 * pc) + lane - 7 * pc, NB1 - 1);
      const uint32_t ya = x1_addr(96 + 8 * (blk >> 4) + 4 * rank + 2 * pc, b, fl) + spread16(blk);
      pdl_wait();
#pragma unroll 1
      for (int i = 7 * p0; i < 7 * p1; i++) {
        const uint32_t a = __shfl_sync(0xffffffffu, ya, i), dst = sb + i * 8192 + (i >= 7 ? C_PIECE - C_OUT : 0);
        if (lane == 0) {
          if (C_POL == 2 || (C_POL == 1 && ((0x1F3E >> i) & 1))) tma_ld3<1>(dst, &m.y1[(a >> 12) & 1], yf0 + 8 * i, 0, a >> 7, 0);
          else tma_ld3<0>(dst, &m.y1[(a >> 12) & 1], yf0 + 8 * i, 0, a >> 7, 0);
        }
        __syncwarp();
      }
      pdl_launch();
      if (lane == 0) {
        mbar_arrive(depb);
        prefetch_map(&m.x);
        prefetch_map(&m.w);
        prefetch_map(&m.y);
      }
      mbar_wait(pubb, 0);
      int st = 0;
#pragma unroll 1
      for (int k = 0; k < 16; k++) {
        if ((k & 7) == 0) {
          int v = 0;
          for (int it = 0; it < (1 << 20) && v < 112; it++)
            asm volatile("ld.relaxed.gpu.global.s32 %0, [%1];" : "=r"(v) : "l"(cnt + 96 + (k >> 3)) : "memory");
          asm volatile("fence.acquire.gpu;\nfence.proxy.async.global;" ::: "memory");
        }
        mbar_wait(empty0 + 8 * st, (k >= H_NST) ^ (k >= 2 * H_NST));
        if (lane == 0) tma_ld3mc<0>(sb + st * H_STAGE + 8192 + rank * H_XP, &m.x, full0 + 8 * st, (k & 1) * 32, 0, ((k & 6) + (k >> 3)) * 64 + 2 * bin + rank);
        __syncwarp();
        if (++st == H_NST) st = 0;
      }
    } else if (pin(warp) == 1) {
      if (lane == 0) {
        if (p0) mbar_arrive(pubb);
#pragma unroll 1
        for (int pc = p0; pc < p1; pc++) {
          mbar_wait(rel0 + 8 * pc, 0);
          asm volatile("fence.acq_rel.gpu;\nred.relaxed.gpu.global.inc.u32 [%0], 0xffffffff;" ::"l"(cnt + 96 + pc) : "memory");
          if (pc == 0) mbar_arrive(pubb);
        }
      }
    } else if (warp == 2) {
      const uint32_t wa = w_addr((lane & 6) + ((lane >> 3) & 1) + W_SHIFT, 2 * bin, (lane & 1) * 32, b, fl) + (rank << 14);
      mbar_wait(depb, 0);
      mbar_wait(pubb, 0);
      int st = 0;
#pragma unroll 1
      for (int k = 0; k < 16; k++) {
        const uint32_t w = __shfl_sync(0xffffffffu, wa, k);
        mbar_wait(empty0 + 8 * st, (k >= H_NST) ^ (k >= 2 * H_NST));
        if (lane == 0) {
          if (k >= H_NST) mbar_expect(full0 + 8 * st, H_STAGE);
          tma_ld3<1>(sb + st * H_STAGE, &m.w, full0 + 8 * st, 0, (w >> 7) & 255, w >> 15);
          if (k == H_NST) {
            if (cta == 0) asm volatile("cp.async.bulk.prefetch.L2.global [%0], 6144;" ::"l"(gat) : "memory");
            asm volatile("cp.async.bulk.prefetch.L2.global [%0], 1024;" ::"l"(wf + cta * 512) : "memory");
            asm volatile("cp.async.bulk.prefetch.L2.global [%0], 1024;" ::"l"(wo + cta * 512) : "memory");
          }
        }
        __syncwarp();
        if (++st == H_NST) st = 0;
      }
    } else {
#pragma unroll 1
      for (int pc = 0; pc < 2; pc++) {
        if (pc >= p0 && pc < p1) {
          uint32_t tnext = clock();
#pragma unroll 1
          for (int n = 0; n < 6; n++) {
            mbar_wait(of0 + 8 * (6 * pc + n), 0);
            if (C_PACE) {
              while ((int)(clock() - tnext) < 0);
              tnext = clock() + C_PACE;
            }
            if (lane == 0) tma_st3<0>(&m.xs, sb + pc * C_PIECE + C_OUT + n * 8192, 0, (4 * (n & 1) + 2 * rank + pc) * 64, b * NB2 + 3 * (bin - 4 * pc) + (n >> 1));
            __syncwarp();
          }
          bulk_commit();
          bulk_wait<0>();
          if (lane == 0) mbar_arrive(rel0 + 8 * pc);
          __syncwarp();
        }
        if (lane < 16)
          for (int i = 6 * pc; i < 3 + 4 * pc; i++) mbar_arrive_cta(empty0 + 8 * i, lane & 1);
      }
    }
  } else {
    mbar_wait(imgb, 0);
#pragma unroll 1
    for (int pc = p0; pc < p1; pc++) {
      const uint32_t in = sb + pc * C_PIECE, yb = yf0 + 56 * pc, gi = sb + C_GI + wg * 1024;
      const bool first = bin == 4 * pc, last = bin == 27 + 4 * pc;
      float ha[12], hb[12], hc[8], e[32];
      uint32_t hp[40];
      auto idft = [&](auto& h, int i) {
        mbar_wait(yb + 8 * i, 0);
        wg_fence();
#pragma unroll
        for (int k = 0; k < 4; k++) {
          const uint64_t da = mk_desc(in, i * 8192 + k * 2048, 0, 1024, 1), db = mk_desc(gi, k * 32, 0, 2048, 1);
          if constexpr (sizeof(h) == 48) wgmma_ss_24<1, 1, 1, 0>(h, da, db, k);
          else wgmma_ss_16<1, 1, 1, 0>(h, da, db, k);
        }
      };
      auto dft = [&](int j) {
#pragma unroll
        for (int k = 0; k < 4; k++)
          wgmma_rs_64<1, 1, 0>(e, hp[12 * j + 4 * k], hp[12 * j + 4 * k + 1], hp[12 * j + 4 * k + 2], hp[12 * j + 4 * k + 3], mk_desc(sb + C_F, k * 32, 0, 1024, 1), k);
      };
      auto out = [&](int j) {
        reg_fence(e);
        const int mi = lane >> 3, r = lane & 7;
        const uint32_t a0 = in + C_OUT + (2 * j + wg) * 8192 + (mi >> 1) * 1024 + r * 128 + (((2 * warp + (mi & 1)) ^ r) << 4);
#pragma unroll
        for (int q = 0; q < 8; q += 2)
          stsm4t(a0 + q * 1024, pack2(e[4 * q], e[4 * q + 1]), pack2(e[4 * q + 2], e[4 * q + 3]),
                 pack2(e[4 * q + 4], e[4 * q + 5]), pack2(e[4 * q + 6], e[4 * q + 7]));
        fence_async();
        __syncwarp();
        if (lane == 0) mbar_arrive(of0 + 8 * (6 * pc + 2 * j + wg));
      };
      idft(ha, 0);
      wg_commit();
      idft(hb, 1);
      wg_commit();
      wg_wait<1>();
      reg_fence(ha);
      gelu_pack<3>(hp, ha, first, false);
      idft(ha, 2);
      wg_commit();
      wg_wait<1>();
      reg_fence(hb);
      gelu_pack<3>(hp + 6, hb, false, false);
      idft(hb, 3);
      wg_commit();
      wg_wait<1>();
      reg_fence(ha);
      gelu_pack<3>(hp + 12, ha, false, false);
      idft(ha, 4);
      dft(0);
      wg_commit();
      wg_wait<1>();
      reg_fence(hb);
      gelu_pack<3>(hp + 18, hb, false, false);
      idft(hb, 5);
      wg_commit();
      wg_wait<1>();
      out(0);
      reg_fence(ha);
      gelu_pack<3>(hp + 24, ha, false, false);
      idft(hc, 6);
      dft(1);
      wg_commit();
      wg_wait<1>();
      reg_fence(hb);
      gelu_pack<3>(hp + 30, hb, false, last);
      wg_wait<0>();
      out(1);
      reg_fence(hc);
      gelu_pack<2>(hp + 36, hc, false, last);
      wg_fence();
      dft(2);
      wg_commit();
      wg_wait<0>();
      if (pc == p1 - 1 && lane < 6) mbar_arrive_cta(empty0 + 8 * (3 + (lane >> 1)), lane & 1);
      out(2);
    }
    float acc[84];
    if (wg == 0) {
      h_loop<0>(acc, sb, full0, empty0, lane);
    } else {
      h_loop<1>(acc, sb, full0, empty0, lane);
      bar_sync(3, 128);
    }
    const uint32_t stg = sb + (wg == 0 ? H_NST : 9 % H_NST) * H_STAGE;
    const int mi = lane >> 3, i = lane & 7;
    const uint32_t a0 = stg + (mi >> 1) * 1024 + i * 128 + (((2 * warp + (mi & 1)) ^ i) << 4);
    constexpr int J = 21 / H_EPI;
#pragma unroll
    for (int c = 0; c < H_EPI; c++) {
#pragma unroll
      for (int j = c * J; j + 1 < (c + 1) * J; j += 2)
        stsm4t(a0 + j * 1024, pack2(acc[4 * j], acc[4 * j + 1]), pack2(acc[4 * j + 2], acc[4 * j + 3]),
               pack2(acc[4 * j + 4], acc[4 * j + 5]), pack2(acc[4 * j + 6], acc[4 * j + 7]));
      const int j = (c + 1) * J - 1;
      asm volatile("stmatrix.sync.aligned.m8n8.x2.trans.shared.b16 [%0], {%1, %2};" ::"r"(a0 + j * 1024),
                   "r"(pack2(acc[4 * j], acc[4 * j + 1])), "r"(pack2(acc[4 * j + 2], acc[4 * j + 3])) : "memory");
      fence_async();
      bar_sync(2 + wg, 128);
      if (t == 0) {
        tma_st4<0>(&m.y, stg + c * J * 1024, 0, c * J * 8, 2 * bin + wg, dc);
        bulk_commit();
      }
    }
    if (t == 0) {
      bulk_wait_read<0>();
    }
  }
}

#define E_WPRE 2
#define E_EARLY0 2
#define E_CHUNK 1
#define E_EARLY 2
constexpr int E_SMEM = 65536 + 131072 + 32768 + 1024;

__device__ __forceinline__ uint32_t joint2(uint32_t fe, uint32_t g0, uint32_t g1) {
  uint32_t s0, s1;
  asm("{\n.reg .b16 l, h;\n.reg .b32 ll;\nmov.b32 {l, h}, %2;\nmov.b32 ll, {l, l};\n"
      "fma.rn.bf16x2 %0, ll, %5, %3;\nfma.rn.bf16x2 %1, %2, %5, %4;\n}"
      : "=r"(s0), "=r"(s1) : "r"(fe), "r"(g0), "r"(g1), "r"(0x3F800000u));
  return pack2(tanh_f32(__uint_as_float(s0)), tanh_f32(__uint_as_float(s1)));
}
__device__ __forceinline__ uint4 lds128(uint32_t a) {
  uint4 v;
  asm volatile("ld.shared.v4.u32 {%0, %1, %2, %3}, [%4];" : "=r"(v.x), "=r"(v.y), "=r"(v.z), "=r"(v.w) : "r"(a));
  return v;
}
__device__ __forceinline__ void joint_group(uint32_t (&ja)[8], const uint32_t* fe, uint4& g0, uint4& g1, uint32_t gnext) {
  const uint4 c0 = g0, c1 = g1;
  g0 = lds128(gnext);
  g1 = lds128(gnext + 64);
  ja[0] = joint2(fe[0], c0.x, c0.y);
  ja[1] = joint2(fe[1], c0.x, c0.y);
  ja[2] = joint2(fe[2], c0.z, c0.w);
  ja[3] = joint2(fe[3], c0.z, c0.w);
  ja[4] = joint2(fe[4], c1.x, c1.y);
  ja[5] = joint2(fe[5], c1.x, c1.y);
  ja[6] = joint2(fe[6], c1.z, c1.w);
  ja[7] = joint2(fe[7], c1.z, c1.w);
  reg_fence(ja);
}

__global__ void __launch_bounds__(256, 1)
kE(int* __restrict__ cnt, const uint32_t* __restrict__ gat, const float* __restrict__ ge, const __grid_constant__ CUtensorMap my, const __grid_constant__ CUtensorMap mwf, const __grid_constant__ CUtensorMap mwo,
   const __grid_constant__ CUtensorMap mout) {
  extern __shared__ uint8_t smem_raw[];
  __shared__ __align__(8) uint64_t bars[13];
  const uint32_t sb = (s2u(smem_raw) + 1023) & ~1023u;
  const int tid = threadIdx.x, wg = __shfl_sync(0xffffffffu, tid >> 7, 0), t = tid & 127, warp = t >> 5, lane = t & 31;
  const uint32_t R0 = sb, R1 = sb + 65536, R2 = sb + 65536 + 131072;
  const uint32_t barY = s2u(&bars[0]), barF = barY + 32, barO = barY + 64, barA = barY + 96;
  const int b = blockIdx.x / 63, t0 = (blockIdx.x % 63) * 64;
  const int a = t0 / 48, o = t0 % 48;
  const int qw = o + 16 * warp, sel = qw >= 48;
  uint32_t ga[16];
#pragma unroll
  for (int s = 0; s < 4; s++)
    ldg128(reinterpret_cast<const uint4*>(gat) + ((qw >> 4) - 3 * sel) * 128 + s * 32 + lane, ga[4 * s], ga[4 * s + 1], ga[4 * s + 2], ga[4 * s + 3]);
  uint4 gev0, gev1;
  asm volatile("ld.global.cg.v4.u32 {%0, %1, %2, %3}, [%4];" : "=r"(gev0.x), "=r"(gev0.y), "=r"(gev0.z), "=r"(gev0.w)
               : "l"(reinterpret_cast<const uint4*>(ge) + (b * 8 + wg * 4) * 64 + t));
  asm volatile("ld.global.cg.v4.u32 {%0, %1, %2, %3}, [%4];" : "=r"(gev1.x), "=r"(gev1.y), "=r"(gev1.z), "=r"(gev1.w)
               : "l"(reinterpret_cast<const uint4*>(ge) + (b * 8 + wg * 4) * 64 + 128 + t));
  if (tid == 0) {
    prefetch_map(&my);
    for (int i = 0; i < 12; i++) mbar_init(barY + 8 * i, 1);
    mbar_init(barA, 8);
    fence_bar_init();
    fence_async();
    for (int i = 0; i < E_WPRE; i++) {
      const int kc = (i >> 1) | ((i & 1) << 1);
      mbar_expect(barF + 8 * kc, 32768);
      tma_ld3<0>(R1 + kc * 32768, &mwf, barF + 8 * kc, 0, kc * 64, 0);
    }
    pdl_wait();
    for (int i = 0; i < 4; i++) {
      mbar_expect(barY + 8 * i, 16384);
      tma_ld5<0>(R0 + i * 16384, &my, barY + 8 * i, 0, 0, 2 * (i & 1) + (i >> 1), a, b);
    }
    for (int i = E_WPRE; i < 4; i++) {
      const int kc = (i >> 1) | ((i & 1) << 1);
      mbar_expect(barF + 8 * kc, 32768);
      tma_ld3<0>(R1 + kc * 32768, &mwf, barF + 8 * kc, 0, kc * 64, 0);
    }
    prefetch_map(&mwo);
    prefetch_map(&mout);
  }
  uint32_t gs[32];
#pragma unroll
  for (int i = 0; i < 16; i++) {
    gs[i] = sel ? 0u : ga[i];
    gs[16 + i] = sel ? ga[i] : 0u;
  }
  __syncthreads();
  if (blockIdx.x == 125 && tid < 128) cnt[tid] = 0;
  reg_fence(gs);
  uint32_t gp = R2 + wg * 4096 + (lane & 3) * 16;
  uint4 g0, g1;
  uint32_t fe[64];
  {
    float d0[32], d1[32], e[64];
    mbar_wait(barY + 8 * wg, 0);
    wg_fence();
#pragma unroll
    for (int k = 0; k < 8; k++)
      wgmma_rs_64<1, 1, 1>(d0, gs[4 * k], gs[4 * k + 1], gs[4 * k + 2], gs[4 * k + 3], mk_desc(R0 + wg * 16384, k * 2048, 0, 1024, 1), k);
    wg_commit();
    wg_wait<0>();
    reg_fence(d0);
#pragma unroll
    for (int i = 0; i < 32; i++) d0[i] = gelu(d0[i]);
    store_tile_64(d0, R2 + wg * 16384, warp, lane);
    mbar_wait(barY + 8 * (2 + wg), 0);
    wg_fence();
#pragma unroll
    for (int k = 0; k < 8; k++)
      wgmma_rs_64<1, 1, 1>(d1, gs[4 * k], gs[4 * k + 1], gs[4 * k + 2], gs[4 * k + 3], mk_desc(R0 + wg * 16384, 32768 + k * 2048, 0, 1024, 1), k);
    wg_commit();
    fence_async();
    mbar_wait(barF, 0);
    mbar_wait(barF + 16, 0);
    __syncthreads();
    wg_fence();
#pragma unroll
    for (int i = 0; i < 8; i++) {
      const int kc = (i >> 2) * 2, s = i & 3;
      wgmma_ss_128<1, 1, 0, 1>(e, mk_desc(R2, kc * 8192 + s * 32, 0, 1024, 1),
                               mk_desc(R1 + wg * 16384, kc * 32768 + s * 2048, 8192, 1024, 1), i);
    }
    wg_commit();
    if (tid == 128) {
      mbar_expect(barO, 32768);
      tma_ld3<0>(R0, &mwo, barO, 0, 0, 0);
    }
    wg_wait<1>();
    reg_fence(d1);
#pragma unroll
    for (int i = 0; i < 32; i++) d1[i] = gelu(d1[i]);
    store_tile_64(d1, R2 + wg * 16384 + 8192, warp, lane);
    fence_async();
    mbar_wait(barF + 8, 0);
    mbar_wait(barF + 24, 0);
    __syncthreads();
    if (tid == 128) {
      mbar_expect(barO + 8, 32768);
      tma_ld3<0>(R0 + 32768, &mwo, barO + 8, 0, 64, 0);
    }
    if (wg == 1) bar_sync(4, 256);
    wg_fence();
#pragma unroll
    for (int i = 0; i < 8; i++) {
      const int kc = (i >> 2) * 2 + 1, s = i & 3;
      wgmma_ss_128<1, 1, 0, 1>(e, mk_desc(R2, kc * 8192 + s * 32, 0, 1024, 1),
                               mk_desc(R1 + wg * 16384, kc * 32768 + s * 2048, 8192, 1024, 1), 1);
    }
    wg_commit();
    if (wg == 0) bar_arrive(4, 256);
    wg_wait<1>();
    if (lane == 0) mbar_arrive(barA);
    if (tid == 128) {
      mbar_wait(barA, 0);
      for (int kc = 2; kc < 4; kc++) {
        mbar_expect(barO + 8 * kc, 32768);
        tma_ld3<0>(R1 + (kc - 2) * 65536, &mwo, barO + 8 * kc, 0, kc * 64, 0);
      }
    }
    mbar_wait(barA, 0);
    asm volatile("st.shared.v4.u32 [%0], {%1, %2, %3, %4};" ::"r"(R2 + wg * 4096 + ((t * 16) ^ (wg * 512))), "r"(gev0.x), "r"(gev0.y), "r"(gev0.z), "r"(gev0.w) : "memory");
    asm volatile("st.shared.v4.u32 [%0], {%1, %2, %3, %4};" ::"r"(R2 + wg * 4096 + 2048 + ((t * 16) ^ (wg * 512))), "r"(gev1.x), "r"(gev1.y), "r"(gev1.z), "r"(gev1.w) : "memory");
    bar_sync(1 + wg, 128);
    g0 = lds128(gp);
    g1 = lds128(gp + 64);
    wg_wait<0>();
    reg_fence(e);
#pragma unroll
    for (int i = 0; i < 32; i++) fe[i] = pack2(e[2 * i], e[2 * i + 1]);
  }
  auto publish = [&]() {
    bar_sync(1 + wg, 128);
    const int row = warp * 16 + (lane & 7) + ((lane >> 3) & 1) * 8;
    const uint32_t xb = R1 + (wg == 0 ? 3 * 32768 : 32768 + 16384) + row * 128;
#pragma unroll
    for (int s = 0; s < 8; s++) {
      const int jj = 2 * s + (lane >> 4);
      stsm4(xb + (s >> 2) * 8192 + (((jj & 7) ^ (lane & 7)) << 4), fe[4 * s], fe[4 * s + 1], fe[4 * s + 2], fe[4 * s + 3]);
    }
    bar_arrive(5 + wg, 256);
  };
  if (wg == 1) publish();
  const uint32_t stg = R1 + 32768 + wg * 65536;
  const uint32_t w0 = sb + wg * 65536, w1 = sb + 32768 + wg * 98304, w2 = sb + 65536 - wg * 65536, w3 = sb + 131072 - wg * 98304;
  float acc[128];
  uint32_t j0[8], j1[8], j2[8], j3[8];
  joint_group(j0, fe, g0, g1, gp + 128);
  mbar_wait(barO + 16 * wg, 0);
  joint_group(j1, fe + 8, g0, g1, gp + 256);
#define E_MMA4(J, K, W, FIRSTK, G, NEXTBAR)                                                     \
  wg_fence();                                                                                   \
  wgmma_rs_256<1, 1, 1>(acc, J[0], J[1], J[2], J[3], mk_desc(W, 0, 8192, 1024, 1), FIRSTK);     \
  wgmma_rs_256<1, 1, 1>(acc, J[4], J[5], J[6], J[7], mk_desc(W, 2048, 8192, 1024, 1), 1);       \
  wgmma_rs_256<1, 1, 1>(acc, K[0], K[1], K[2], K[3], mk_desc(W, 4096, 8192, 1024, 1), 1);       \
  wgmma_rs_256<1, 1, 1>(acc, K[4], K[5], K[6], K[7], mk_desc(W, 6144, 8192, 1024, 1), 1);       \
  wg_commit();                                                                                  \
  if ((ui + wg == 0 ? E_EARLY0 : E_EARLY) == (G) && (ui < 3 || wg == 0)) bar_arrive(4 - wg, 256); \
  wg_wait<1>();                                                                                 \
  if (ui == 0) mbar_wait(NEXTBAR, 0);
  const uint32_t bo0 = barO + 16 * wg, bo2 = barO + 16 * (1 - wg);
#pragma unroll 1
  for (int ui = 0; ui < 4; ui++) {
    if (ui > 0 || wg == 1) bar_sync(3 + wg, 256);
    E_MMA4(j0, j1, w0, 0, 0, bo0)
    joint_group(j2, fe + 16, g0, g1, gp + 384);
    if (ui == 0) mbar_wait(bo0 + 8, 0);
    joint_group(j3, fe + 24, g0, g1, gp + 512);
    E_MMA4(j2, j3, w1, 1, 1, bo0 + 8)
    if (ui == 0) {
      if (wg == 0) publish();
      bar_sync(6 - wg, 256);
      const int row = warp * 16 + (lane & 7) + ((lane >> 3) & 1) * 8;
      const uint32_t xb = R1 + (wg == 1 ? 3 * 32768 : 32768 + 16384) + row * 128;
#pragma unroll
      for (int s = 0; s < 8; s++) {
        const int jj = 2 * s + (lane >> 4);
        ldsm4(xb + (s >> 2) * 8192 + (((jj & 7) ^ (lane & 7)) << 4), fe[32 + 4 * s], fe[33 + 4 * s], fe[34 + 4 * s], fe[35 + 4 * s]);
      }
    }
    joint_group(j0, fe + 32, g0, g1, gp + 640);
    if (ui == 0) mbar_wait(bo2, 0);
    joint_group(j1, fe + 40, g0, g1, gp + 768);
    E_MMA4(j0, j1, w2, 1, 2, bo2)
    joint_group(j2, fe + 48, g0, g1, gp + 896);
    if (ui == 0) mbar_wait(bo2 + 8, 0);
    joint_group(j3, fe + 56, g0, g1, gp + 1024);
    E_MMA4(j2, j3, w3, 1, 3, bo2 + 8)
    gp += 1024;
    if (ui < 3) {
      joint_group(j0, fe, g0, g1, gp + 128);
      if (ui == 0) mbar_wait(bo2 + 8, 0);
      joint_group(j1, fe + 8, g0, g1, gp + 256);
    }
    if (t == 0) bulk_wait_read<0>();
    wg_wait<0>();
    reg_fence(acc);
    bar_sync(1 + wg, 128);
    const uint32_t rb = stg + (warp * 16 + (lane & 7) + ((lane >> 3) & 1) * 8) * 128;
#pragma unroll
    for (int h = 0; h < 2; h++) {
#pragma unroll
      for (int j = 16 * h; j < 16 * h + 16; j += 2) {
        const int jj = j + (lane >> 4);
        stsm4(rb + (j >> 3) * 8192 + (((jj & 7) ^ (lane & 7)) << 4), pack2(acc[4 * j], acc[4 * j + 1]), pack2(acc[4 * j + 2], acc[4 * j + 3]),
              pack2(acc[4 * j + 4], acc[4 * j + 5]), pack2(acc[4 * j + 6], acc[4 * j + 7]));
      }
      const bool split = E_CHUNK == 2 || (E_CHUNK == 1 && ui == 3);
      if (h == 1 || split) {
        fence_async();
        bar_sync(1 + wg, 128);
        if (t == 0) {
          if (h == 1 && !split) tma_st5<1>(&mout, stg, 0, t0, 0, wg * 4 + ui, b);
          tma_st5<1>(&mout, stg + h * 16384, 0, t0, 2 * h, wg * 4 + ui, b);
          bulk_commit();
        }
      }
    }
  }
  if (t == 0) bulk_wait_read<0>();
}

typedef CUresult (*EncodeFn)(CUtensorMap*, CUtensorMapDataType, cuuint32_t, void*, const cuuint64_t*, const cuuint64_t*,
                             const cuuint32_t*, const cuuint32_t*, CUtensorMapInterleave, CUtensorMapSwizzle,
                             CUtensorMapL2promotion, CUtensorMapFloatOOBfill);

CUtensorMap make_map(EncodeFn fn, const void* base, int rank, const uint64_t* dims, const uint64_t* strides, const uint32_t* box,
                     CUtensorMapSwizzle swz) {
  CUtensorMap m;
  cuuint64_t gd[5], gs[4];
  cuuint32_t bx[5], es[5];
  for (int i = 0; i < rank; i++) { gd[i] = dims[i]; bx[i] = box[i]; es[i] = 1; }
  for (int i = 0; i + 1 < rank; i++) gs[i] = strides[i];
  fn(&m, CU_TENSOR_MAP_DATA_TYPE_BFLOAT16, rank, const_cast<void*>(base), gd, gs, bx, es, CU_TENSOR_MAP_INTERLEAVE_NONE, swz,
     CU_TENSOR_MAP_L2_PROMOTION_NONE, CU_TENSOR_MAP_FLOAT_OOB_FILL_NONE);
  return m;
}

template <typename... KArgs, typename... Args>
void launch(void (*k)(KArgs...), int grid, int block, int smem, bool pdl, Args... args) {
  cudaLaunchConfig_t c = {};
  c.gridDim = dim3(grid);
  c.blockDim = dim3(block);
  c.dynamicSmemBytes = smem;
  c.stream = cudaStreamPerThread;
  cudaLaunchAttribute at[1];
  at[0].id = cudaLaunchAttributeProgrammaticStreamSerialization;
  at[0].val.programmaticStreamSerializationAllowed = 1;
  c.attrs = at;
  c.numAttrs = pdl ? 1 : 0;
  cudaLaunchKernelEx(&c, k, args...);
}

}

extern "C" void kernel_launch(void* const* d_in, const int* in_sizes, int n_in, void* d_out, int out_size) {
  const __nv_bfloat16* x = (const __nv_bfloat16*)d_in[0];
  const __nv_bfloat16* w1 = (const __nv_bfloat16*)d_in[1];
  const __nv_bfloat16* w2 = (const __nv_bfloat16*)d_in[2];
  const __nv_bfloat16* g = (const __nv_bfloat16*)d_in[3];
  const __nv_bfloat16* wf = (const __nv_bfloat16*)d_in[4];
  const __nv_bfloat16* wgt = (const __nv_bfloat16*)d_in[5];
  const __nv_bfloat16* wo = (const __nv_bfloat16*)d_in[6];

  void* fp = nullptr;
  cudaDriverEntryPointQueryResult qr;
  cudaGetDriverEntryPoint("cuTensorMapEncodeTiled", &fp, cudaEnableDefault, &qr);
  EncodeFn fn = (EncodeFn)fp;
  void *W, *Y2, *cnt, *ge, *img, *gat;
  cudaGetSymbolAddress(&cnt, g_cnt);
  cudaGetSymbolAddress(&ge, g_ge);
  cudaGetSymbolAddress(&img, c_img);
  cudaGetSymbolAddress(&gat, c_ga);
  cudaGetSymbolAddress(&W, g_W);
  cudaGetSymbolAddress(&Y2, g_Y2);
  cudaFuncSetAttribute(kG, cudaFuncAttributeMaxDynamicSharedMemorySize, G_SMEM);
  cudaFuncSetAttribute(kH, cudaFuncAttributeMaxDynamicSharedMemorySize, H_SMEM);
  cudaFuncSetAttribute(kE, cudaFuncAttributeMaxDynamicSharedMemorySize, E_SMEM);
  auto page_up = [](void* p) { return (void*)(((uintptr_t)p + (1 << 21) - 1) & ~(uintptr_t)((1 << 21) - 1)); };
  void *X1 = page_up(d_out), *X2 = X1;
  W = page_up(W);
  const CUtensorMapSwizzle S128 = CU_TENSOR_MAP_SWIZZLE_128B, S64 = CU_TENSOR_MAP_SWIZZLE_64B;

  auto map_x = [&]() {
    uint64_t d[] = {64, 8000, 8, 1, 2}, s[] = {1024, 128, 8000ull * 1024, 8000ull * 1024};
    uint32_t bx[] = {64, 112, 1, 1, 1};
    return make_map(fn, x, 5, d, s, bx, S128);
  };
  auto map_w_in = [&](const __nv_bfloat16* w, int odd, uint32_t n) {
    uint64_t d[] = {64, (uint64_t)(odd ? 15 : 16), 4, 64, 4}, s[] = {2ull * 65536 * 2, 128, 512, 32768};
    uint32_t bx[] = {64, 16, 2, 1, n};
    return make_map(fn, w + (odd ? 65536 : 0), 5, d, s, bx, S128);
  };
  auto map_X_st = [&](void* p, int nb, int boxb) {
    uint64_t d[] = {64, 512, (uint64_t)(2 * nb)}, s[] = {2ull * nb * 128, 128};
    uint32_t bx[] = {64, 64, (uint32_t)boxb};
    return make_map(fn, p, 3, d, s, bx, S128);
  };
  auto map_X1_st = [&](uint32_t rows) {
    uint64_t d[] = {8192, 16, 4, 24}, s[] = {16384, 262144, 1048576};
    uint32_t bx[] = {64, 4, 2, rows / 8};
    return make_map(fn, X1, 4, d, s, bx, S128);
  };
  auto map_Y1_ld = [&](uint64_t step) {
    uint64_t d[] = {64, 12 << 14, 2}, s[] = {128, step};
    uint32_t bx[] = {64, 32, 2};
    return make_map(fn, X1, 3, d, s, bx, S128);
  };
  auto map_W_st = [&]() {
    uint64_t d[] = {8192, 8, 4, 2 * (8 + W_SHIFT), 2}, s[] = {32768, 262144, 1048576, 16384};
    uint32_t bx[] = {64, 2, 2, 2, 2};
    return make_map(fn, W, 5, d, s, bx, S128);
  };
  auto map_X_ld = [&](void* p, int nb, int boxb) {
    uint64_t d[] = {64, (uint64_t)(2 * nb), 512}, s[] = {128, 2ull * nb * 128};
    uint32_t bx[] = {32, (uint32_t)boxb, 1};
    return make_map(fn, p, 3, d, s, bx, S64);
  };
  auto map_W_ld = [&](uint32_t n) {
    uint64_t d[] = {64, 512 / n, (8ull + W_SHIFT) * 32 * n}, s[] = {128, 65536 / n};
    uint32_t bx[] = {64, 32, n};
    return make_map(fn, W, 3, d, s, bx, S128);
  };
  auto map_Y_st = [&](void* p, int nb, int rows) {
    uint64_t d[] = {64, (uint64_t)(2 * nb), 64, 4}, s[] = {32768, 128, 8192};
    uint32_t bx[] = {64, (uint32_t)rows, 1, 1};
    return make_map(fn, p, 4, d, s, bx, S128);
  };
  auto map_Y_ld = [&](void* p, int nb, int boxc, int boxb) {
    uint64_t d[] = {64, 64, 4, (uint64_t)nb, 2}, s[] = {128, 8192, 32768, (uint64_t)nb * 32768};
    uint32_t bx[] = {64, 64, (uint32_t)boxc, (uint32_t)boxb, 1};
    return make_map(fn, p, 5, d, s, bx, S128);
  };
  auto map_wsq = [&](const __nv_bfloat16* w) {
    uint64_t d[] = {64, 256, 4}, s[] = {512, 128};
    uint32_t bx[] = {64, 64, 4};
    return make_map(fn, w, 3, d, s, bx, S128);
  };
  auto map_out = [&]() {
    uint64_t d[] = {64, 4000, 4, 8, 2}, s[] = {4096, 128, 512, 4000ull * 4096};
    uint32_t bx[] = {64, 64, 2, 1, 1};
    return make_map(fn, d_out, 5, d, s, bx, S128);
  };

  GMaps g1;
  g1.w = map_W_ld(4);
  g1.y = map_X1_st(8);
  g1.in[0] = map_w_in(w1, 1, 2);
  g1.in[1] = map_w_in(w1, 0, 2);
  g1.in[2] = map_w_in(w2, 1, 1);
  g1.in[3] = map_w_in(w2, 0, 1);
  g1.in[4] = map_x();
  g1.xs = map_X1_st(16);
  g1.ws = map_W_st();
  launch(kG, 132, 384, G_SMEM, false, (int*)cnt, (char*)X1, (char*)W, g, wgt, (float*)ge, (const uint32_t*)img, g1);
  HMaps h1;
  h1.y1[0] = map_Y1_ld(0x3000);
  h1.y1[1] = map_Y1_ld(0x1000);
  h1.xs = map_X_st(X2, NB2, 1);
  h1.x = map_X_ld(X2, NB2, 168);
  h1.w = map_W_ld(2);
  h1.y = map_Y_st(Y2, NB2, 168 / H_EPI);
  launch(kH, 128, 384, H_SMEM, true, (int*)cnt, (const uint32_t*)img, wf, wo, (const uint32_t*)gat, h1);
  launch(kE, 126, 256, E_SMEM, true, (int*)cnt, (const uint32_t*)gat, (const float*)ge, map_Y_ld(Y2, NB2, 1, 2), map_wsq(wf), map_wsq(wo), map_out());
}
```

```cpp
#include <cuda_runtime.h>
#include <cuda_bf16.h>
#include <cuda.h>
#include <stdint.h>
#include <type_traits>

#define W_SHIFT 1
namespace {

constexpr int NB1 = 168;
constexpr int NB2 = 84;

__device__ __align__(1024) __nv_bfloat16 g_W[(9 + W_SHIFT) * 64 * 4 * 64 * 64];
__device__ __align__(1024) __nv_bfloat16 g_Y2[2 * NB2 * 4 * 64 * 64];
__device__ __align__(1024) float g_ge[16 * 256];

__device__ __forceinline__ uint32_t s2u(const void* p) { return (uint32_t)__cvta_generic_to_shared(p); }
__device__ __forceinline__ uint32_t pin(uint32_t v) {
  return __shfl_sync(0xffffffffu, v, 0);
}
__device__ __forceinline__ void mbar_init(uint32_t b, int c) {
  asm volatile("mbarrier.init.shared::cta.b64 [%0], %1;" ::"r"(b), "r"(c) : "memory");
}
__device__ __forceinline__ void mbar_expect(uint32_t b, int bytes) {
  asm volatile("mbarrier.arrive.expect_tx.shared::cta.b64 _, [%0], %1;" ::"r"(b), "r"(bytes) : "memory");
}
__device__ __forceinline__ void mbar_arrive(uint32_t b) {
  asm volatile("mbarrier.arrive.shared::cta.b64 _, [%0];" ::"r"(b) : "memory");
}
__device__ __forceinline__ void mbar_arrive_cta(uint32_t b, uint32_t cta) {
  asm volatile("{\n.reg .b32 r;\nmapa.shared::cluster.u32 r, %0, %1;\nmbarrier.arrive.shared::cluster.b64 _, [r];\n}" ::"r"(b), "r"(cta) : "memory");
}
__device__ __forceinline__ void mbar_wait(uint32_t b, int ph) {
  asm volatile(
      "{\n.reg .pred p;\n.reg .u32 n;\n"
      "mov.u32 n, 0;\n"
      "MBW_LOOP:\n"
      "mbarrier.try_wait.parity.shared::cta.b64 p, [%0], %1;\n"
      "@p bra MBW_DONE;\n"
      "add.u32 n, n, 1;\n"
      "setp.lt.u32 p, n, 1048576;\n"
      "@p bra MBW_LOOP;\n"
      "MBW_DONE:\n}" ::"r"(b), "r"(ph) : "memory");
}
__device__ __forceinline__ bool mbar_test(uint32_t b, int ph) {
  uint32_t ok;
  asm volatile("{\n.reg .pred p;\nmbarrier.test_wait.parity.shared::cta.b64 p, [%1], %2;\nselp.u32 %0, 1, 0, p;\n}" : "=r"(ok) : "r"(b), "r"(ph) : "memory");
  return __all_sync(0xffffffffu, ok);
}
__device__ __forceinline__ void fence_bar_init() { asm volatile("fence.mbarrier_init.release.cluster;" ::: "memory"); }
__device__ __forceinline__ void fence_async() { asm volatile("fence.proxy.async.shared::cta;" ::: "memory"); }
__device__ __forceinline__ void bar_sync(int id, int n) { asm volatile("bar.sync %0, %1;" ::"r"(id), "r"(n) : "memory"); }
__device__ __forceinline__ void bar_arrive(int id, int n) { asm volatile("bar.arrive %0, %1;" ::"r"(id), "r"(n) : "memory"); }
__device__ __forceinline__ void pdl_wait() { asm volatile("griddepcontrol.wait;" ::: "memory"); }
__device__ __forceinline__ void pdl_launch() { asm volatile("griddepcontrol.launch_dependents;" ::: "memory"); }
__device__ __forceinline__ void prefetch_map(const CUtensorMap* m) {
  asm volatile("prefetch.tensormap [%0];" ::"l"(m) : "memory");
}
template <int P> __device__ __forceinline__ uint64_t policy() {
  uint64_t p;
  asm("createpolicy.fractional.L2::evict_first.b64 %0, 1.0;" : "=l"(p));
  return p;
}
template <int P> __device__ __forceinline__ void tma_ld3(uint32_t dst, const CUtensorMap* m, uint32_t bar, int c0, int c1, int c2) {
  if constexpr (P == 0)
    asm volatile("cp.async.bulk.tensor.3d.shared::cluster.global.mbarrier::complete_tx::bytes [%0], [%1, {%3, %4, %5}], [%2];"
                 ::"r"(dst), "l"(m), "r"(bar), "r"(c0), "r"(c1), "r"(c2) : "memory");
  else
    asm volatile("cp.async.bulk.tensor.3d.shared::cluster.global.mbarrier::complete_tx::bytes.L2::cache_hint [%0], [%1, {%3, %4, %5}], [%2], %6;"
                 ::"r"(dst), "l"(m), "r"(bar), "r"(c0), "r"(c1), "r"(c2), "l"(policy<P>()) : "memory");
}
template <int P> __device__ __forceinline__ void tma_ld3mc(uint32_t dst, const CUtensorMap* m, uint32_t bar, int c0, int c1, int c2) {
  if constexpr (P == 0)
    asm volatile("cp.async.bulk.tensor.3d.shared::cluster.global.mbarrier::complete_tx::bytes.multicast::cluster [%0], [%1, {%3, %4, %5}], [%2], %6;"
                 ::"r"(dst), "l"(m), "r"(bar), "r"(c0), "r"(c1), "r"(c2), "h"((uint16_t)3) : "memory");
  else
    asm volatile("cp.async.bulk.tensor.3d.shared::cluster.global.mbarrier::complete_tx::bytes.multicast::cluster.L2::cache_hint [%0], [%1, {%3, %4, %5}], [%2], %6, %7;"
                 ::"r"(dst), "l"(m), "r"(bar), "r"(c0), "r"(c1), "r"(c2), "h"((uint16_t)3), "l"(policy<P>()) : "memory");
}
template <int P> __device__ __forceinline__ void tma_ld4(uint32_t dst, const CUtensorMap* m, uint32_t bar, int c0, int c1, int c2, int c3) {
  if constexpr (P == 0)
    asm volatile("cp.async.bulk.tensor.4d.shared::cluster.global.mbarrier::complete_tx::bytes [%0], [%1, {%3, %4, %5, %6}], [%2];"
                 ::"r"(dst), "l"(m), "r"(bar), "r"(c0), "r"(c1), "r"(c2), "r"(c3) : "memory");
  else
    asm volatile("cp.async.bulk.tensor.4d.shared::cluster.global.mbarrier::complete_tx::bytes.L2::cache_hint [%0], [%1, {%3, %4, %5, %6}], [%2], %7;"
                 ::"r"(dst), "l"(m), "r"(bar), "r"(c0), "r"(c1), "r"(c2), "r"(c3), "l"(policy<P>()) : "memory");
}
template <int P> __device__ __forceinline__ void tma_ld4mc(uint32_t dst, const CUtensorMap* m, uint32_t bar, int c0, int c1, int c2, int c3) {
  if constexpr (P == 0)
    asm volatile("cp.async.bulk.tensor.4d.shared::cluster.global.mbarrier::complete_tx::bytes.multicast::cluster [%0], [%1, {%3, %4, %5, %6}], [%2], %7;"
                 ::"r"(dst), "l"(m), "r"(bar), "r"(c0), "r"(c1), "r"(c2), "r"(c3), "h"((uint16_t)3) : "memory");
  else
    asm volatile("cp.async.bulk.tensor.4d.shared::cluster.global.mbarrier::complete_tx::bytes.multicast::cluster.L2::cache_hint [%0], [%1, {%3, %4, %5, %6}], [%2], %7, %8;"
                 ::"r"(dst), "l"(m), "r"(bar), "r"(c0), "r"(c1), "r"(c2), "r"(c3), "h"((uint16_t)3), "l"(policy<P>()) : "memory");
}
template <int P> __device__ __forceinline__ void tma_ld5(uint32_t dst, const CUtensorMap* m, uint32_t bar, int c0, int c1, int c2, int c3, int c4) {
  if constexpr (P == 0)
    asm volatile("cp.async.bulk.tensor.5d.shared::cluster.global.mbarrier::complete_tx::bytes [%0], [%1, {%3, %4, %5, %6, %7}], [%2];"
                 ::"r"(dst), "l"(m), "r"(bar), "r"(c0), "r"(c1), "r"(c2), "r"(c3), "r"(c4) : "memory");
  else
    asm volatile("cp.async.bulk.tensor.5d.shared::cluster.global.mbarrier::complete_tx::bytes.L2::cache_hint [%0], [%1, {%3, %4, %5, %6, %7}], [%2], %8;"
                 ::"r"(dst), "l"(m), "r"(bar), "r"(c0), "r"(c1), "r"(c2), "r"(c3), "r"(c4), "l"(policy<P>()) : "memory");
}
template <int P> __device__ __forceinline__ void tma_st3(const CUtensorMap* m, uint32_t src, int c0, int c1, int c2) {
  if constexpr (P == 0)
    asm volatile("cp.async.bulk.tensor.3d.global.shared::cta.bulk_group [%0, {%2, %3, %4}], [%1];" ::"l"(m), "r"(src), "r"(c0), "r"(c1), "r"(c2) : "memory");
  else
    asm volatile("cp.async.bulk.tensor.3d.global.shared::cta.bulk_group.L2::cache_hint [%0, {%2, %3, %4}], [%1], %5;" ::"l"(m), "r"(src), "r"(c0), "r"(c1), "r"(c2), "l"(policy<P>()) : "memory");
}
template <int P> __device__ __forceinline__ void tma_st4(const CUtensorMap* m, uint32_t src, int c0, int c1, int c2, int c3) {
  if constexpr (P == 0)
    asm volatile("cp.async.bulk.tensor.4d.global.shared::cta.bulk_group [%0, {%2, %3, %4, %5}], [%1];" ::"l"(m), "r"(src), "r"(c0), "r"(c1), "r"(c2), "r"(c3) : "memory");
  else
    asm volatile("cp.async.bulk.tensor.4d.global.shared::cta.bulk_group.L2::cache_hint [%0, {%2, %3, %4, %5}], [%1], %6;" ::"l"(m), "r"(src), "r"(c0), "r"(c1), "r"(c2), "r"(c3), "l"(policy<P>()) : "memory");
}
template <int P> __device__ __forceinline__ void tma_st5(const CUtensorMap* m, uint32_t src, int c0, int c1, int c2, int c3, int c4) {
  if constexpr (P == 0)
    asm volatile("cp.async.bulk.tensor.5d.global.shared::cta.bulk_group [%0, {%2, %3, %4, %5, %6}], [%1];" ::"l"(m), "r"(src), "r"(c0), "r"(c1), "r"(c2), "r"(c3), "r"(c4) : "memory");
  else
    asm volatile("cp.async.bulk.tensor.5d.global.shared::cta.bulk_group.L2::cache_hint [%0, {%2, %3, %4, %5, %6}], [%1], %7;" ::"l"(m), "r"(src), "r"(c0), "r"(c1), "r"(c2), "r"(c3), "r"(c4), "l"(policy<P>()) : "memory");
}
__device__ __forceinline__ void bulk_commit() { asm volatile("cp.async.bulk.commit_group;" ::: "memory"); }
template <int N> __device__ __forceinline__ void bulk_wait() { asm volatile("cp.async.bulk.wait_group %0;" ::"n"(N) : "memory"); }
template <int N> __device__ __forceinline__ void bulk_wait_read() { asm volatile("cp.async.bulk.wait_group.read %0;" ::"n"(N) : "memory"); }
__device__ __forceinline__ void wg_fence() { asm volatile("wgmma.fence.sync.aligned;" ::: "memory"); }
__device__ __forceinline__ void wg_commit() { asm volatile("wgmma.commit_group.sync.aligned;" ::: "memory"); }
template <int N> __device__ __forceinline__ void wg_wait() { asm volatile("wgmma.wait_group.sync.aligned %0;" ::"n"(N) : "memory"); }
template <int R> __device__ __forceinline__ void reg_fence(float (&d)[R]) {
#pragma unroll
  for (int i = 0; i < R; i++) asm volatile("" : "+f"(d[i])::"memory");
}
template <int R> __device__ __forceinline__ void reg_fence(uint32_t (&d)[R]) {
#pragma unroll
  for (int i = 0; i < R; i++) asm volatile("" : "+r"(d[i])::"memory");
}
__device__ __forceinline__ void stsm4(uint32_t a, uint32_t r0, uint32_t r1, uint32_t r2, uint32_t r3) {
  asm volatile("stmatrix.sync.aligned.m8n8.x4.shared.b16 [%0], {%1, %2, %3, %4};" ::"r"(a), "r"(r0), "r"(r1), "r"(r2), "r"(r3) : "memory");
}
__device__ __forceinline__ void stsm4t(uint32_t a, uint32_t r0, uint32_t r1, uint32_t r2, uint32_t r3) {
  asm volatile("stmatrix.sync.aligned.m8n8.x4.trans.shared.b16 [%0], {%1, %2, %3, %4};" ::"r"(a), "r"(r0), "r"(r1), "r"(r2), "r"(r3) : "memory");
}
__device__ __forceinline__ void ldsm4(uint32_t a, uint32_t& r0, uint32_t& r1, uint32_t& r2, uint32_t& r3) {
  asm volatile("ldmatrix.sync.aligned.m8n8.x4.shared.b16 {%0, %1, %2, %3}, [%4];" : "=r"(r0), "=r"(r1), "=r"(r2), "=r"(r3) : "r"(a) : "memory");
}
__device__ __forceinline__ void ldg128(const uint4* p, uint32_t& a, uint32_t& b, uint32_t& c, uint32_t& d) {
  asm volatile("ld.global.nc.v4.u32 {%0, %1, %2, %3}, [%4];" : "=r"(a), "=r"(b), "=r"(c), "=r"(d) : "l"(p));
}
__device__ __forceinline__ uint32_t pack2(float lo, float hi) {
  uint32_t r;
  asm("cvt.rn.bf16x2.f32 %0, %1, %2;" : "=r"(r) : "f"(hi), "f"(lo));
  return r;
}
__device__ __forceinline__ float tanh_f32(float x) {
  float y;
  asm("tanh.approx.f32 %0, %1;" : "=f"(y) : "f"(x));
  return y;
}
__device__ __forceinline__ float gelu(float hx) {
  const float u = hx * fmaf(hx * hx, 8.0f * 0.044715f * 0.7978845608028654f, 2.0f * 0.7978845608028654f);
  return fmaf(hx, tanh_f32(u), hx);
}
__device__ __forceinline__ uint64_t mk_desc4(uint32_t addr4, uint32_t lbo, uint32_t sbo, uint32_t swz) {
  const uint32_t lo = addr4 + ((lbo >> 4) << 16), hi = (sbo >> 4) | (swz << 30);
  uint64_t d;
  asm("mov.b64 %0, {%1, %2};" : "=l"(d) : "r"(lo), "r"(hi));
  return d;
}
#define mk_desc(base, off, lbo, sbo, swz) mk_desc4((((base) & 0x3FFFF) >> 4) + ((off) >> 4), lbo, sbo, swz)

template <int SA, int SB, int TA, int TB>
__device__ __forceinline__ void wgmma_ss_16(float (&d)[8], uint64_t da, uint64_t db, int sd) {
  asm volatile("{\n.reg .pred p;\nsetp.ne.b32 p, %10, 0;\n"
      "wgmma.mma_async.sync.aligned.m64n16k16.f32.bf16.bf16 {"
      "%0, %1, %2, %3, %4, %5, %6, %7"
      "}, %8, %9, p, %11, %12, %13, %14;\n}\n"
      : "+f"(d[0]), "+f"(d[1]), "+f"(d[2]), "+f"(d[3]), "+f"(d[4]), "+f"(d[5]), "+f"(d[6]), "+f"(d[7])
      : "l"(da), "l"(db), "r"(sd), "n"(SA), "n"(SB), "n"(TA), "n"(TB));
}
template <int SA, int SB, int TA, int TB>
__device__ __forceinline__ void wgmma_ss_24(float (&d)[12], uint64_t da, uint64_t db, int sd) {
  asm volatile("{\n.reg .pred p;\nsetp.ne.b32 p, %14, 0;\n"
      "wgmma.mma_async.sync.aligned.m64n24k16.f32.bf16.bf16 {"
      "%0, %1, %2, %3, %4, %5, %6, %7, %8, %9, %10, %11"
      "}, %12, %13, p, %15, %16, %17, %18;\n}\n"
      : "+f"(d[0]), "+f"(d[1]), "+f"(d[2]), "+f"(d[3]), "+f"(d[4]), "+f"(d[5]), "+f"(d[6]), "+f"(d[7]), "+f"(d[8]),
        "+f"(d[9]), "+f"(d[10]), "+f"(d[11])
      : "l"(da), "l"(db), "r"(sd), "n"(SA), "n"(SB), "n"(TA), "n"(TB));
}
template <int SA, int SB, int TA, int TB>
__device__ __forceinline__ void wgmma_ss_128(float (&d)[64], uint64_t da, uint64_t db, int sd) {
  asm volatile("{\n.reg .pred p;\nsetp.ne.b32 p, %66, 0;\n"
      "wgmma.mma_async.sync.aligned.m64n128k16.f32.bf16.bf16 {"
      "%0, %1, %2, %3, %4, %5, %6, %7, %8, %9, %10, %11, %12, %13, %14, %15, %16, %17, %18, %19, %20, %21, %22, %23, "
      "%24, %25, %26, %27, %28, %29, %30, %31, %32, %33, %34, %35, %36, %37, %38, %39, %40, %41, %42, %43, %44, %45, "
      "%46, %47, %48, %49, %50, %51, %52, %53, %54, %55, %56, %57, %58, %59, %60, %61, %62, %63"
      "}, %64, %65, p, %67, %68, %69, %70;\n}\n"
      : "+f"(d[0]), "+f"(d[1]), "+f"(d[2]), "+f"(d[3]), "+f"(d[4]), "+f"(d[5]), "+f"(d[6]), "+f"(d[7]), "+f"(d[8]),
        "+f"(d[9]), "+f"(d[10]), "+f"(d[11]), "+f"(d[12]), "+f"(d[13]), "+f"(d[14]), "+f"(d[15]), "+f"(d[16]),
        "+f"(d[17]), "+f"(d[18]), "+f"(d[19]), "+f"(d[20]), "+f"(d[21]), "+f"(d[22]), "+f"(d[23]), "+f"(d[24]),
        "+f"(d[25]), "+f"(d[26]), "+f"(d[27]), "+f"(d[28]), "+f"(d[29]), "+f"(d[30]), "+f"(d[31]), "+f"(d[32]),
        "+f"(d[33]), "+f"(d[34]), "+f"(d[35]), "+f"(d[36]), "+f"(d[37]), "+f"(d[38]), "+f"(d[39]), "+f"(d[40]),
        "+f"(d[41]), "+f"(d[42]), "+f"(d[43]), "+f"(d[44]), "+f"(d[45]), "+f"(d[46]), "+f"(d[47]), "+f"(d[48]),
        "+f"(d[49]), "+f"(d[50]), "+f"(d[51]), "+f"(d[52]), "+f"(d[53]), "+f"(d[54]), "+f"(d[55]), "+f"(d[56]),
        "+f"(d[57]), "+f"(d[58]), "+f"(d[59]), "+f"(d[60]), "+f"(d[61]), "+f"(d[62]), "+f"(d[63])
      : "l"(da), "l"(db), "r"(sd), "n"(SA), "n"(SB), "n"(TA), "n"(TB));
}
template <int SA, int SB, int TA, int TB>
__device__ __forceinline__ void wgmma_ss_168(float (&d)[84], uint64_t da, uint64_t db, int sd) {
  asm volatile("{\n.reg .pred p;\nsetp.ne.b32 p, %86, 0;\n"
      "wgmma.mma_async.sync.aligned.m64n168k16.f32.bf16.bf16 {"
      "%0, %1, %2, %3, %4, %5, %6, %7, %8, %9, %10, %11, %12, %13, %14, %15, %16, %17, %18, %19, %20, %21, %22, %23, "
      "%24, %25, %26, %27, %28, %29, %30, %31, %32, %33, %34, %35, %36, %37, %38, %39, %40, %41, %42, %43, %44, %45, "
      "%46, %47, %48, %49, %50, %51, %52, %53, %54, %55, %56, %57, %58, %59, %60, %61, %62, %63, %64, %65, %66, %67, "
      "%68, %69, %70, %71, %72, %73, %74, %75, %76, %77, %78, %79, %80, %81, %82, %83"
      "}, %84, %85, p, %87, %88, %89, %90;\n}\n"
      : "+f"(d[0]), "+f"(d[1]), "+f"(d[2]), "+f"(d[3]), "+f"(d[4]), "+f"(d[5]), "+f"(d[6]), "+f"(d[7]), "+f"(d[8]),
        "+f"(d[9]), "+f"(d[10]), "+f"(d[11]), "+f"(d[12]), "+f"(d[13]), "+f"(d[14]), "+f"(d[15]), "+f"(d[16]),
        "+f"(d[17]), "+f"(d[18]), "+f"(d[19]), "+f"(d[20]), "+f"(d[21]), "+f"(d[22]), "+f"(d[23]), "+f"(d[24]),
        "+f"(d[25]), "+f"(d[26]), "+f"(d[27]), "+f"(d[28]), "+f"(d[29]), "+f"(d[30]), "+f"(d[31]), "+f"(d[32]),
        "+f"(d[33]), "+f"(d[34]), "+f"(d[35]), "+f"(d[36]), "+f"(d[37]), "+f"(d[38]), "+f"(d[39]), "+f"(d[40]),
        "+f"(d[41]), "+f"(d[42]), "+f"(d[43]), "+f"(d[44]), "+f"(d[45]), "+f"(d[46]), "+f"(d[47]), "+f"(d[48]),
        "+f"(d[49]), "+f"(d[50]), "+f"(d[51]), "+f"(d[52]), "+f"(d[53]), "+f"(d[54]), "+f"(d[55]), "+f"(d[56]),
        "+f"(d[57]), "+f"(d[58]), "+f"(d[59]), "+f"(d[60]), "+f"(d[61]), "+f"(d[62]), "+f"(d[63]), "+f"(d[64]),
        "+f"(d[65]), "+f"(d[66]), "+f"(d[67]), "+f"(d[68]), "+f"(d[69]), "+f"(d[70]), "+f"(d[71]), "+f"(d[72]),
        "+f"(d[73]), "+f"(d[74]), "+f"(d[75]), "+f"(d[76]), "+f"(d[77]), "+f"(d[78]), "+f"(d[79]), "+f"(d[80]),
        "+f"(d[81]), "+f"(d[82]), "+f"(d[83])
      : "l"(da), "l"(db), "r"(sd), "n"(SA), "n"(SB), "n"(TA), "n"(TB));
}
template <int SA, int SB, int TB>
__device__ __forceinline__ void wgmma_rs_64(float (&d)[32], uint32_t a0, uint32_t a1, uint32_t a2, uint32_t a3, uint64_t db, int sd) {
  asm volatile("{\n.reg .pred p;\nsetp.ne.b32 p, %37, 0;\n"
      "wgmma.mma_async.sync.aligned.m64n64k16.f32.bf16.bf16 {"
      "%0, %1, %2, %3, %4, %5, %6, %7, %8, %9, %10, %11, %12, %13, %14, %15, %16, %17, %18, %19, %20, %21, %22, %23, "
      "%24, %25, %26, %27, %28, %29, %30, %31"
      "}, {%32, %33, %34, %35}, %36, p, %38, %39, %40;\n}\n"
      : "+f"(d[0]), "+f"(d[1]), "+f"(d[2]), "+f"(d[3]), "+f"(d[4]), "+f"(d[5]), "+f"(d[6]), "+f"(d[7]), "+f"(d[8]),
        "+f"(d[9]), "+f"(d[10]), "+f"(d[11]), "+f"(d[12]), "+f"(d[13]), "+f"(d[14]), "+f"(d[15]), "+f"(d[16]),
        "+f"(d[17]), "+f"(d[18]), "+f"(d[19]), "+f"(d[20]), "+f"(d[21]), "+f"(d[22]), "+f"(d[23]), "+f"(d[24]),
        "+f"(d[25]), "+f"(d[26]), "+f"(d[27]), "+f"(d[28]), "+f"(d[29]), "+f"(d[30]), "+f"(d[31])
      : "r"(a0), "r"(a1), "r"(a2), "r"(a3), "l"(db), "r"(sd), "n"(SA), "n"(SB), "n"(TB));
}
template <int SA, int SB, int TB>
__device__ __forceinline__ void wgmma_rs_128(float (&d)[64], uint32_t a0, uint32_t a1, uint32_t a2, uint32_t a3, uint64_t db, int sd) {
  asm volatile("{\n.reg .pred p;\nsetp.ne.b32 p, %69, 0;\n"
      "wgmma.mma_async.sync.aligned.m64n128k16.f32.bf16.bf16 {"
      "%0, %1, %2, %3, %4, %5, %6, %7, %8, %9, %10, %11, %12, %13, %14, %15, %16, %17, %18, %19, %20, %21, %22, %23, "
      "%24, %25, %26, %27, %28, %29, %30, %31, %32, %33, %34, %35, %36, %37, %38, %39, %40, %41, %42, %43, %44, %45, "
      "%46, %47, %48, %49, %50, %51, %52, %53, %54, %55, %56, %57, %58, %59, %60, %61, %62, %63"
      "}, {%64, %65, %66, %67}, %68, p, %70, %71, %72;\n}\n"
      : "+f"(d[0]), "+f"(d[1]), "+f"(d[2]), "+f"(d[3]), "+f"(d[4]), "+f"(d[5]), "+f"(d[6]), "+f"(d[7]), "+f"(d[8]),
        "+f"(d[9]), "+f"(d[10]), "+f"(d[11]), "+f"(d[12]), "+f"(d[13]), "+f"(d[14]), "+f"(d[15]), "+f"(d[16]),
        "+f"(d[17]), "+f"(d[18]), "+f"(d[19]), "+f"(d[20]), "+f"(d[21]), "+f"(d[22]), "+f"(d[23]), "+f"(d[24]),
        "+f"(d[25]), "+f"(d[26]), "+f"(d[27]), "+f"(d[28]), "+f"(d[29]), "+f"(d[30]), "+f"(d[31]), "+f"(d[32]),
        "+f"(d[33]), "+f"(d[34]), "+f"(d[35]), "+f"(d[36]), "+f"(d[37]), "+f"(d[38]), "+f"(d[39]), "+f"(d[40]),
        "+f"(d[41]), "+f"(d[42]), "+f"(d[43]), "+f"(d[44]), "+f"(d[45]), "+f"(d[46]), "+f"(d[47]), "+f"(d[48]),
        "+f"(d[49]), "+f"(d[50]), "+f"(d[51]), "+f"(d[52]), "+f"(d[53]), "+f"(d[54]), "+f"(d[55]), "+f"(d[56]),
        "+f"(d[57]), "+f"(d[58]), "+f"(d[59]), "+f"(d[60]), "+f"(d[61]), "+f"(d[62]), "+f"(d[63])
      : "r"(a0), "r"(a1), "r"(a2), "r"(a3), "l"(db), "r"(sd), "n"(SA), "n"(SB), "n"(TB));
}
template <int SA, int SB, int TB>
__device__ __forceinline__ void wgmma_rs_256(float (&d)[128], uint32_t a0, uint32_t a1, uint32_t a2, uint32_t a3, uint64_t db, int sd) {
  asm volatile("{\n.reg .pred p;\nsetp.ne.b32 p, %133, 0;\n"
      "wgmma.mma_async.sync.aligned.m64n256k16.f32.bf16.bf16 {"
      "%0, %1, %2, %3, %4, %5, %6, %7, %8, %9, %10, %11, %12, %13, %14, %15, %16, %17, %18, %19, %20, %21, %22, %23, "
      "%24, %25, %26, %27, %28, %29, %30, %31, %32, %33, %34, %35, %36, %37, %38, %39, %40, %41, %42, %43, %44, %45, "
      "%46, %47, %48, %49, %50, %51, %52, %53, %54, %55, %56, %57, %58, %59, %60, %61, %62, %63, %64, %65, %66, %67, "
      "%68, %69, %70, %71, %72, %73, %74, %75, %76, %77, %78, %79, %80, %81, %82, %83, %84, %85, %86, %87, %88, %89, "
      "%90, %91, %92, %93, %94, %95, %96, %97, %98, %99, %100, %101, %102, %103, %104, %105, %106, %107, %108, %109, "
      "%110, %111, %112, %113, %114, %115, %116, %117, %118, %119, %120, %121, %122, %123, %124, %125, %126, %127"
      "}, {%128, %129, %130, %131}, %132, p, %134, %135, %136;\n}\n"
      : "+f"(d[0]), "+f"(d[1]), "+f"(d[2]), "+f"(d[3]), "+f"(d[4]), "+f"(d[5]), "+f"(d[6]), "+f"(d[7]), "+f"(d[8]),
        "+f"(d[9]), "+f"(d[10]), "+f"(d[11]), "+f"(d[12]), "+f"(d[13]), "+f"(d[14]), "+f"(d[15]), "+f"(d[16]),
        "+f"(d[17]), "+f"(d[18]), "+f"(d[19]), "+f"(d[20]), "+f"(d[21]), "+f"(d[22]), "+f"(d[23]), "+f"(d[24]),
        "+f"(d[25]), "+f"(d[26]), "+f"(d[27]), "+f"(d[28]), "+f"(d[29]), "+f"(d[30]), "+f"(d[31]), "+f"(d[32]),
        "+f"(d[33]), "+f"(d[34]), "+f"(d[35]), "+f"(d[36]), "+f"(d[37]), "+f"(d[38]), "+f"(d[39]), "+f"(d[40]),
        "+f"(d[41]), "+f"(d[42]), "+f"(d[43]), "+f"(d[44]), "+f"(d[45]), "+f"(d[46]), "+f"(d[47]), "+f"(d[48]),
        "+f"(d[49]), "+f"(d[50]), "+f"(d[51]), "+f"(d[52]), "+f"(d[53]), "+f"(d[54]), "+f"(d[55]), "+f"(d[56]),
        "+f"(d[57]), "+f"(d[58]), "+f"(d[59]), "+f"(d[60]), "+f"(d[61]), "+f"(d[62]), "+f"(d[63]), "+f"(d[64]),
        "+f"(d[65]), "+f"(d[66]), "+f"(d[67]), "+f"(d[68]), "+f"(d[69]), "+f"(d[70]), "+f"(d[71]), "+f"(d[72]),
        "+f"(d[73]), "+f"(d[74]), "+f"(d[75]), "+f"(d[76]), "+f"(d[77]), "+f"(d[78]), "+f"(d[79]), "+f"(d[80]),
        "+f"(d[81]), "+f"(d[82]), "+f"(d[83]), "+f"(d[84]), "+f"(d[85]), "+f"(d[86]), "+f"(d[87]), "+f"(d[88]),
        "+f"(d[89]), "+f"(d[90]), "+f"(d[91]), "+f"(d[92]), "+f"(d[93]), "+f"(d[94]), "+f"(d[95]), "+f"(d[96]),
        "+f"(d[97]), "+f"(d[98]), "+f"(d[99]), "+f"(d[100]), "+f"(d[101]), "+f"(d[102]), "+f"(d[103]), "+f"(d[104]),
        "+f"(d[105]), "+f"(d[106]), "+f"(d[107]), "+f"(d[108]), "+f"(d[109]), "+f"(d[110]), "+f"(d[111]),
        "+f"(d[112]), "+f"(d[113]), "+f"(d[114]), "+f"(d[115]), "+f"(d[116]), "+f"(d[117]), "+f"(d[118]),
        "+f"(d[119]), "+f"(d[120]), "+f"(d[121]), "+f"(d[122]), "+f"(d[123]), "+f"(d[124]), "+f"(d[125]),
        "+f"(d[126]), "+f"(d[127])
      : "r"(a0), "r"(a1), "r"(a2), "r"(a3), "l"(db), "r"(sd), "n"(SA), "n"(SB), "n"(TB));
}

__device__ const __align__(128) uint32_t c_img[3584] = {
    0x00003c80, 0x00003c80, 0x00003c80, 0x00003c80, 0x00003c80, 0x00003c80, 0x00003c80, 0x00003c80, 0x00003c80, 0x00003c80,
    0x00003c80, 0x00003c80, 0x00003c80, 0x00003c80, 0x00003c80, 0x00003c80, 0x00003c80, 0x00003c80, 0x00003c80, 0x00003c80,
    0x00003c80, 0x00003c80, 0x00003c80, 0x00003c80, 0x00003c80, 0x00003c80, 0x00003c80, 0x00003c80, 0x00003c80, 0x00003c80,
    0x00003c80, 0x00003c80, 0x3c463c22, 0x3c623bf1, 0x3c753b95, 0x3c7f3ac9, 0x3ac93c7f, 0x3b953c75, 0x3bf13c62, 0x3c223c46,
    0x3c22bc46, 0x3bf1bc62, 0x3b95bc75, 0x3ac9bc7f, 0x3c7fbac9, 0x3c75bb95, 0x3c62bbf1, 0x3c46bc22, 0xbc46bc22, 0xbc62bbf1,
    0xbc75bb95, 0xbc7fbac9, 0xbac9bc7f, 0xbb95bc75, 0xbbf1bc62, 0xbc22bc46, 0xbc223c46, 0xbbf13c62, 0xbb953c75, 0xbac93c7f,
    0xbc7f3ac9, 0xbc753b95, 0xbc623bf1, 0xbc463c22, 0xbb48bc7b, 0xbc0ebc55, 0xbc55bc0e, 0xbc7bbb48, 0xbc7b3b48, 0xbc553c0e,
    0xbc0e3c55, 0xbb483c7b, 0x3b483c7b, 0x3c0e3c55, 0x3c553c0e, 0x3c7b3b48, 0x3c7bbb48, 0x3c55bc0e, 0x3c0ebc55, 0x3b48bc7b,
    0xbb48bc7b, 0xbc0ebc55, 0xbc55bc0e, 0xbc7bbb48, 0xbc7b3b48, 0xbc553c0e, 0xbc0e3c55, 0xbb483c7b, 0x3b483c7b, 0x3c0e3c55,
    0x3c553c0e, 0x3c7b3b48, 0x3c7bbb48, 0x3c55bc0e, 0x3c0ebc55, 0x3b48bc7b, 0x3c623bf1, 0x3c7fbac9, 0x3c46bc22, 0x3b95bc75,
    0xbc753b95, 0xbc223c46, 0xbac93c7f, 0x3bf13c62, 0x3bf1bc62, 0xbac9bc7f, 0xbc22bc46, 0xbc75bb95, 0x3b953c75, 0x3c463c22,
    0x3c7f3ac9, 0x3c62bbf1, 0xbc62bbf1, 0xbc7f3ac9, 0xbc463c22, 0xbb953c75, 0x3c75bb95, 0x3c22bc46, 0x3ac9bc7f, 0xbbf1bc62,
    0xbbf13c62, 0x3ac93c7f, 0x3c223c46, 0x3c753b95, 0xbb95bc75, 0xbc46bc22, 0xbc7fbac9, 0xbc623bf1, 0x3bc43c6d, 0x3c6d3bc4,
    0x3c6dbbc4, 0x3bc4bc6d, 0xbbc4bc6d, 0xbc6dbbc4, 0xbc6d3bc4, 0xbbc43c6d, 0x3bc43c6d, 0x3c6d3bc4, 0x3c6dbbc4, 0x3bc4bc6d,
    0xbbc4bc6d, 0xbc6dbbc4, 0xbc6d3bc4, 0xbbc43c6d, 0x3bc43c6d, 0x3c6d3bc4, 0x3c6dbbc4, 0x3bc4bc6d, 0xbbc4bc6d, 0xbc6dbbc4,
    0xbc6d3bc4, 0xbbc43c6d, 0x3bc43c6d, 0x3c6d3bc4, 0x3c6dbbc4, 0x3bc4bc6d, 0xbbc4bc6d, 0xbc6dbbc4, 0xbc6d3bc4, 0xbbc43c6d,
    0x3c753b95, 0x3c46bc22, 0xbac9bc7f, 0xbc62bbf1, 0xbbf1bc62, 0xbc7fbac9, 0xbc223c46, 0x3b953c75, 0x3b95bc75, 0xbc22bc46,
    0xbc7f3ac9, 0xbbf13c62, 0xbc623bf1, 0xbac93c7f, 0x3c463c22, 0x3c75bb95, 0xbc75bb95, 0xbc463c22, 0x3ac93c7f, 0x3c623bf1,
    0x3bf13c62, 0x3c7f3ac9, 0x3c22bc46, 0xbb95bc75, 0xbb953c75, 0x3c223c46, 0x3c7fbac9, 0x3bf1bc62, 0x3c62bbf1, 0x3ac9bc7f,
    0xbc46bc22, 0xbc753b95, 0xbc0ebc55, 0xbc7b3b48, 0xbb483c7b, 0x3c553c0e, 0x3c55bc0e, 0xbb48bc7b, 0xbc7bbb48, 0xbc0e3c55,
    0x3c0e3c55, 0x3c7bbb48, 0x3b48bc7b, 0xbc55bc0e, 0xbc553c0e, 0x3b483c7b, 0x3c7b3b48, 0x3c0ebc55, 0xbc0ebc55, 0xbc7b3b48,
    0xbb483c7b, 0x3c553c0e, 0x3c55bc0e, 0xbb48bc7b, 0xbc7bbb48, 0xbc0e3c55, 0x3c0e3c55, 0x3c7bbb48, 0x3b48bc7b, 0xbc55bc0e,
    0xbc553c0e, 0x3b483c7b, 0x3c7b3b48, 0x3c0ebc55, 0x3c7f3ac9, 0x3b95bc75, 0xbc62bbf1, 0xbc223c46, 0x3c46bc22, 0xbbf1bc62,
    0xbc753b95, 0x3ac93c7f, 0x3ac9bc7f, 0xbc75bb95, 0xbbf13c62, 0x3c463c22, 0xbc22bc46, 0xbc623bf1, 0x3b953c75, 0x3c7fbac9,
    0xbc7fbac9, 0xbb953c75, 0x3c623bf1, 0x3c22bc46, 0xbc463c22, 0x3bf13c62, 0x3c75bb95, 0xbac9bc7f, 0xbac93c7f, 0x3c753b95,
    0x3bf1bc62, 0xbc46bc22, 0x3c223c46, 0x3c62bbf1, 0xbb95bc75, 0xbc7f3ac9, 0x3a493c80, 0x3b163c7d, 0x3b793c78, 0x3bac3c71,
    0x3bdb3c67, 0x3c043c5c, 0x3c183c4e, 0x3c2c3c3e, 0x3c3e3c2c, 0x3c4e3c18, 0x3c5c3c04, 0x3c673bdb, 0x3c713bac, 0x3c783b79,
    0x3c7d3b16, 0x3c803a49, 0x3c80ba49, 0x3c7dbb16, 0x3c78bb79, 0x3c71bbac, 0x3c67bbdb, 0x3c5cbc04, 0x3c4ebc18, 0x3c3ebc2c,
    0x3c2cbc3e, 0x3c18bc4e, 0x3c04bc5c, 0x3bdbbc67, 0x3bacbc71, 0x3b79bc78, 0x3b16bc7d, 0x3a49bc80, 0x3c783b79, 0x3c80ba49,
    0x3c71bbac, 0x3c4ebc18, 0x3b163c7d, 0x3bdb3c67, 0x3c2c3c3e, 0x3c5c3c04, 0xbc04bc5c, 0xbc3ebc2c, 0xbc67bbdb, 0xbc7dbb16,
    0x3c18bc4e, 0x3bacbc71, 0x3a49bc80, 0xbb79bc78, 0xbb793c78, 0x3a493c80, 0x3bac3c71, 0x3c183c4e, 0xbc7d3b16, 0xbc673bdb,
    0xbc3e3c2c, 0xbc043c5c, 0x3c5cbc04, 0x3c2cbc3e, 0x3bdbbc67, 0x3b16bc7d, 0x3c4e3c18, 0x3c713bac, 0x3c803a49, 0x3c78bb79,
    0xbc5cbc04, 0xbc80ba49, 0xbc673bdb, 0xbc183c4e, 0xbb163c7d, 0x3bac3c71, 0x3c3e3c2c, 0x3c783b79, 0x3b793c78, 0x3c2c3c3e,
    0x3c713bac, 0x3c7dbb16, 0x3c4ebc18, 0x3bdbbc67, 0xba49bc80, 0xbc04bc5c, 0xbc043c5c, 0xba493c80, 0x3bdb3c67, 0x3c4e3c18,
    0x3c7d3b16, 0x3c71bbac, 0x3c2cbc3e, 0x3b79bc78, 0x3c78bb79, 0x3c3ebc2c, 0x3bacbc71, 0xbb16bc7d, 0xbc18bc4e, 0xbc67bbdb,
    0xbc803a49, 0xbc5c3c04, 0x3c3ebc2c, 0x3b16bc7d, 0xbc04bc5c, 0xbc71bbac, 0xbbdb3c67, 0x3b793c78, 0x3c4e3c18, 0x3c80ba49,
    0x3a49bc80, 0xbc18bc4e, 0xbc78bb79, 0xbc673bdb, 0x3bac3c71, 0x3c5c3c04, 0x3c7dbb16, 0x3c2cbc3e, 0x3c2c3c3e, 0x3c7d3b16,
    0x3c5cbc04, 0x3bacbc71, 0xbc67bbdb, 0xbc783b79, 0xbc183c4e, 0x3a493c80, 0x3c803a49, 0x3c4ebc18, 0x3b79bc78, 0xbbdbbc67,
    0xbc713bac, 0xbc043c5c, 0x3b163c7d, 0x3c3e3c2c, 0x3c67bbdb, 0x3b79bc78, 0xbc18bc4e, 0xbc80ba49, 0xbc2c3c3e, 0x3b163c7d,
    0x3c5c3c04, 0x3c71bbac, 0x3bacbc71, 0xbc04bc5c, 0xbc7dbb16, 0xbc3e3c2c, 0x3a493c80, 0x3c4e3c18, 0x3c78bb79, 0x3bdbbc67,
    0x3bdb3c67, 0x3c783b79, 0x3c4ebc18, 0x3a49bc80, 0xbc3ebc2c, 0xbc7d3b16, 0xbc043c5c, 0x3bac3c71, 0x3c713bac, 0x3c5cbc04,
    0x3b16bc7d, 0xbc2cbc3e, 0xbc803a49, 0xbc183c4e, 0x3b793c78, 0x3c673bdb, 0xbb16bc7d, 0xbc71bbac, 0xbc3e3c2c, 0x3b793c78,
    0xbc5c3c04, 0x3a493c80, 0x3c673bdb, 0x3c4ebc18, 0xbc183c4e, 0x3bdb3c67, 0x3c803a49, 0x3c04bc5c, 0x3c783b79, 0x3c2cbc3e,
    0xbbacbc71, 0xbc7dbb16, 0xbc7d3b16, 0xbbac3c71, 0x3c2c3c3e, 0x3c78bb79, 0x3c043c5c, 0x3c80ba49, 0x3bdbbc67, 0xbc18bc4e,
    0x3c4e3c18, 0x3c67bbdb, 0x3a49bc80, 0xbc5cbc04, 0x3b79bc78, 0xbc3ebc2c, 0xbc713bac, 0xbb163c7d, 0xbb163c7d, 0x3c673bdb,
    0x3c2cbc3e, 0xbc04bc5c, 0xbc783b79, 0xba493c80, 0x3c713bac, 0x3c18bc4e, 0x3c4ebc18, 0xbbacbc71, 0xbc803a49, 0xbb793c78,
    0x3c5c3c04, 0x3c3ebc2c, 0xbbdbbc67, 0xbc7d3b16, 0xbc7dbb16, 0xbbdb3c67, 0x3c3e3c2c, 0x3c5cbc04, 0xbb79bc78, 0xbc80ba49,
    0xbbac3c71, 0x3c4e3c18, 0x3c183c4e, 0x3c71bbac, 0xba49bc80, 0xbc78bb79, 0xbc043c5c, 0x3c2c3c3e, 0x3c67bbdb, 0xbb16bc7d,
    0xbc67bbdb, 0xbc043c5c, 0x3c4e3c18, 0x3c2cbc3e, 0xbc80ba49, 0xbb163c7d, 0x3c783b79, 0x3bacbc71, 0xbc713bac, 0x3b793c78,
    0x3c7dbb16, 0xba49bc80, 0xbc3e3c2c, 0x3c183c4e, 0x3c5cbc04, 0xbbdbbc67, 0xbbdb3c67, 0x3c5c3c04, 0x3c18bc4e, 0xbc3ebc2c,
    0xba493c80, 0x3c7d3b16, 0x3b79bc78, 0xbc71bbac, 0x3bac3c71, 0x3c78bb79, 0xbb16bc7d, 0xbc803a49, 0x3c2c3c3e, 0x3c4ebc18,
    0xbc04bc5c, 0xbc673bdb, 0x3c353c35, 0x3c35bc35, 0xbc35bc35, 0xbc353c35, 0x3c353c35, 0x3c35bc35, 0xbc35bc35, 0xbc353c35,
    0x3c353c35, 0x3c35bc35, 0xbc35bc35, 0xbc353c35, 0x3c353c35, 0x3c35bc35, 0xbc35bc35, 0xbc353c35, 0x3c353c35, 0x3c35bc35,
    0xbc35bc35, 0xbc353c35, 0x3c353c35, 0x3c35bc35, 0xbc35bc35, 0xbc353c35, 0x3c353c35, 0x3c35bc35, 0xbc35bc35, 0xbc353c35,
    0x3c353c35, 0x3c35bc35, 0xbc35bc35, 0xbc353c35, 0x3c7fbac9, 0xbb95bc75, 0xbc623bf1, 0x3c223c46, 0x3c463c22, 0x3bf1bc62,
    0xbc75bb95, 0xbac93c7f, 0xbac9bc7f, 0xbc753b95, 0x3bf13c62, 0x3c46bc22, 0x3c22bc46, 0xbc62bbf1, 0xbb953c75, 0x3c7f3ac9,
    0xbc7f3ac9, 0x3b953c75, 0x3c62bbf1, 0xbc22bc46, 0xbc46bc22, 0xbbf13c62, 0x3c753b95, 0x3ac9bc7f, 0x3ac93c7f, 0x3c75bb95,
    0xbbf1bc62, 0xbc463c22, 0xbc223c46, 0x3c623bf1, 0x3b95bc75, 0xbc7fbac9, 0xbc55bc0e, 0xbb483c7b, 0x3c7bbb48, 0xbc0ebc55,
    0xbc0e3c55, 0x3c7b3b48, 0xbb48bc7b, 0xbc553c0e, 0x3c553c0e, 0x3b48bc7b, 0xbc7b3b48, 0x3c0e3c55, 0x3c0ebc55, 0xbc7bbb48,
    0x3b483c7b, 0x3c55bc0e, 0xbc55bc0e, 0xbb483c7b, 0x3c7bbb48, 0xbc0ebc55, 0xbc0e3c55, 0x3c7b3b48, 0xbb48bc7b, 0xbc553c0e,
    0x3c553c0e, 0x3b48bc7b, 0xbc7b3b48, 0x3c0e3c55, 0x3c0ebc55, 0xbc7bbb48, 0x3b483c7b, 0x3c55bc0e, 0x3c75bb95, 0xbc46bc22,
    0xbac93c7f, 0x3c62bbf1, 0xbbf13c62, 0x3c7fbac9, 0xbc22bc46, 0xbb953c75, 0xbb95bc75, 0xbc223c46, 0x3c7f3ac9, 0xbbf1bc62,
    0x3c623bf1, 0xbac9bc7f, 0xbc463c22, 0x3c753b95, 0xbc753b95, 0x3c463c22, 0x3ac9bc7f, 0xbc623bf1, 0x3bf1bc62, 0xbc7f3ac9,
    0x3c223c46, 0x3b95bc75, 0x3b953c75, 0x3c22bc46, 0xbc7fbac9, 0x3bf13c62, 0xbc62bbf1, 0x3ac93c7f, 0x3c46bc22, 0xbc75bb95,
    0x3c6d3bc4, 0xbbc4bc6d, 0xbbc43c6d, 0x3c6dbbc4, 0xbc6dbbc4, 0x3bc43c6d, 0x3bc4bc6d, 0xbc6d3bc4, 0x3c6d3bc4, 0xbbc4bc6d,
    0xbbc43c6d, 0x3c6dbbc4, 0xbc6dbbc4, 0x3bc43c6d, 0x3bc4bc6d, 0xbc6d3bc4, 0x3c6d3bc4, 0xbbc4bc6d, 0xbbc43c6d, 0x3c6dbbc4,
    0xbc6dbbc4, 0x3bc43c6d, 0x3bc4bc6d, 0xbc6d3bc4, 0x3c6d3bc4, 0xbbc4bc6d, 0xbbc43c6d, 0x3c6dbbc4, 0xbc6dbbc4, 0x3bc43c6d,
    0x3bc4bc6d, 0xbc6d3bc4, 0x3c62bbf1, 0xbc7fbac9, 0x3c463c22, 0xbb95bc75, 0xbc75bb95, 0x3c223c46, 0xbac9bc7f, 0xbbf13c62,
    0xbbf1bc62, 0xbac93c7f, 0x3c22bc46, 0xbc753b95, 0xbb953c75, 0x3c46bc22, 0xbc7f3ac9, 0x3c623bf1, 0xbc623bf1, 0x3c7f3ac9,
    0xbc46bc22, 0x3b953c75, 0x3c753b95, 0xbc22bc46, 0x3ac93c7f, 0x3bf1bc62, 0x3bf13c62, 0x3ac9bc7f, 0xbc223c46, 0x3c75bb95,
    0x3b95bc75, 0xbc463c22, 0x3c7fbac9, 0xbc62bbf1, 0xbc7bbb48, 0x3c553c0e, 0xbc0ebc55, 0x3b483c7b, 0x3b48bc7b, 0xbc0e3c55,
    0x3c55bc0e, 0xbc7b3b48, 0x3c7b3b48, 0xbc55bc0e, 0x3c0e3c55, 0xbb48bc7b, 0xbb483c7b, 0x3c0ebc55, 0xbc553c0e, 0x3c7bbb48,
    0xbc7bbb48, 0x3c553c0e, 0xbc0ebc55, 0x3b483c7b, 0x3b48bc7b, 0xbc0e3c55, 0x3c55bc0e, 0xbc7b3b48, 0x3c7b3b48, 0xbc55bc0e,
    0x3c0e3c55, 0xbb48bc7b, 0xbb483c7b, 0x3c0ebc55, 0xbc553c0e, 0x3c7bbb48, 0x3c46bc22, 0xbc623bf1, 0x3c75bb95, 0xbc7f3ac9,
    0x3ac9bc7f, 0xbb953c75, 0x3bf1bc62, 0xbc223c46, 0xbc22bc46, 0x3bf13c62, 0xbb95bc75, 0x3ac93c7f, 0xbc7fbac9, 0x3c753b95,
    0xbc62bbf1, 0x3c463c22, 0xbc463c22, 0x3c62bbf1, 0xbc753b95, 0x3c7fbac9, 0xbac93c7f, 0x3b95bc75, 0xbbf13c62, 0x3c22bc46,
    0x3c223c46, 0xbbf1bc62, 0x3b953c75, 0xbac9bc7f, 0x3c7f3ac9, 0xbc75bb95, 0x3c623bf1, 0xbc46bc22, 0x3c3e3c2c, 0x3c18bc4e,
    0xbc5cbc04, 0xbbdb3c67, 0x3c713bac, 0x3b79bc78, 0xbc7dbb16, 0xba493c80, 0x3c80ba49, 0xbb16bc7d, 0xbc783b79, 0x3bac3c71,
    0x3c67bbdb, 0xbc04bc5c, 0xbc4e3c18, 0x3c2c3c3e, 0x3c2cbc3e, 0xbc4ebc18, 0xbc043c5c, 0x3c673bdb, 0x3bacbc71, 0xbc78bb79,
    0xbb163c7d, 0x3c803a49, 0xba49bc80, 0xbc7d3b16, 0x3b793c78, 0x3c71bbac, 0xbbdbbc67, 0xbc5c3c04, 0x3c183c4e, 0x3c3ebc2c,
    0x3c5cbc04, 0xbc3ebc2c, 0xbbdb3c67, 0x3c7d3b16, 0x3c4e3c18, 0x3bacbc71, 0xbc80ba49, 0x3b793c78, 0xbc78bb79, 0x3a493c80,
    0x3c71bbac, 0xbc18bc4e, 0xbb16bc7d, 0xbc673bdb, 0x3c2c3c3e, 0x3c04bc5c, 0x3c043c5c, 0x3c2cbc3e, 0xbc67bbdb, 0xbb163c7d,
    0xbc183c4e, 0x3c713bac, 0x3a49bc80, 0xbc783b79, 0x3b79bc78, 0xbc803a49, 0x3bac3c71, 0x3c4ebc18, 0x3c7dbb16, 0xbbdbbc67,
    0xbc3e3c2c, 0x3c5c3c04, 0xbc783b79, 0x3c2c3c3e, 0x3bacbc71, 0xbc7d3b16, 0x3c183c4e, 0x3bdbbc67, 0xbc803a49, 0x3c043c5c,
    0x3c5c3c04, 0x3a49bc80, 0xbc673bdb, 0x3c4e3c18, 0x3b16bc7d, 0xbc713bac, 0x3c3e3c2c, 0x3b79bc78, 0x3b793c78, 0x3c3ebc2c,
    0xbc71bbac, 0x3b163c7d, 0x3c4ebc18, 0xbc67bbdb, 0x3a493c80, 0x3c5cbc04, 0x3c04bc5c, 0xbc80ba49, 0x3bdb3c67, 0x3c18bc4e,
    0xbc7dbb16, 0x3bac3c71, 0x3c2cbc3e, 0xbc78bb79, 0x3a49bc80, 0xbc4e3c18, 0x3c783b79, 0xbbdbbc67, 0x3bac3c71, 0x3c04bc5c,
    0xbc7d3b16, 0x3c3e3c2c, 0xbc2cbc3e, 0xbb163c7d, 0x3c5cbc04, 0xbc71bbac, 0x3c673bdb, 0xbb79bc78, 0xbc183c4e, 0x3c80ba49,
    0x3c803a49, 0xbc18bc4e, 0xbb793c78, 0x3c67bbdb, 0xbc713bac, 0x3c5c3c04, 0xbb16bc7d, 0xbc2c3c3e, 0x3c3ebc2c, 0xbc7dbb16,
    0x3c043c5c, 0x3bacbc71, 0xbbdb3c67, 0x3c78bb79, 0xbc4ebc18, 0x3a493c80, 0x3bacbc71, 0xbc5c3c04, 0x3c7d3b16, 0xbc2cbc3e,
    0x3a493c80, 0x3c18bc4e, 0xbc783b79, 0x3c673bdb, 0xbbdbbc67, 0xbb793c78, 0x3c4ebc18, 0xbc80ba49, 0x3c3e3c2c, 0xbb16bc7d,
    0xbc043c5c, 0x3c71bbac, 0x3c713bac, 0xbc04bc5c, 0xbb163c7d, 0x3c3ebc2c, 0xbc803a49, 0x3c4e3c18, 0xbb79bc78, 0xbbdb3c67,
    0x3c67bbdb, 0xbc78bb79, 0x3c183c4e, 0x3a49bc80, 0xbc2c3c3e, 0x3c7dbb16, 0xbc5cbc04, 0x3bac3c71, 0xbc4ebc18, 0x3bdb3c67,
    0x3a49bc80, 0xbc043c5c, 0xbb793c78, 0x3c2cbc3e, 0xbc713bac, 0x3c7d3b16, 0x3b163c7d, 0x3bacbc71, 0xbc3e3c2c, 0x3c78bb79,
    0x3c5cbc04, 0xbc803a49, 0x3c673bdb, 0xbc18bc4e, 0xbc183c4e, 0x3c67bbdb, 0xbc80ba49, 0x3c5c3c04, 0x3c783b79, 0xbc3ebc2c,
    0x3bac3c71, 0x3b16bc7d, 0x3c7dbb16, 0xbc71bbac, 0x3c2c3c3e, 0xbb79bc78, 0xbc04bc5c, 0x3a493c80, 0x3bdbbc67, 0xbc4e3c18,
    0x3c183c4e, 0xbbacbc71, 0x3a493c80, 0x3b79bc78, 0xbc043c5c, 0x3c3ebc2c, 0xbc673bdb, 0x3c7dbb16, 0x3b16bc7d, 0xbbdb3c67,
    0x3c2cbc3e, 0xbc5c3c04, 0x3c78bb79, 0xbc80ba49, 0x3c713bac, 0xbc4ebc18, 0xbc4e3c18, 0x3c71bbac, 0xbc803a49, 0x3c783b79,
    0xbc5cbc04, 0x3c2c3c3e, 0xbbdbbc67, 0x3b163c7d, 0x3c7d3b16, 0xbc67bbdb, 0x3c3e3c2c, 0xbc04bc5c, 0x3b793c78, 0x3a49bc80,
    0xbbac3c71, 0x3c18bc4e, 0xbc713bac, 0x3c78bb79, 0xbc7d3b16, 0x3c80ba49, 0xbc3e3c2c, 0x3c4ebc18, 0xbc5c3c04, 0x3c67bbdb,
    0xbbdb3c67, 0x3c04bc5c, 0xbc183c4e, 0x3c2cbc3e, 0xba493c80, 0x3b16bc7d, 0xbb793c78, 0x3bacbc71, 0x3bac3c71, 0xbb79bc78,
    0x3b163c7d, 0xba49bc80, 0x3c2c3c3e, 0xbc18bc4e, 0x3c043c5c, 0xbbdbbc67, 0x3c673bdb, 0xbc5cbc04, 0x3c4e3c18, 0xbc3ebc2c,
    0x3c803a49, 0xbc7dbb16, 0x3c783b79, 0xbc71bbac, 0x3c800000, 0xbc800000, 0x3c800000, 0xbc800000, 0x3c800000, 0xbc800000,
    0x3c800000, 0xbc800000, 0x3c800000, 0xbc800000, 0x3c800000, 0xbc800000, 0x3c800000, 0xbc800000, 0x3c800000, 0xbc800000,
    0x3c800000, 0xbc800000, 0x3c800000, 0xbc800000, 0x3c800000, 0xbc800000, 0x3c800000, 0xbc800000, 0x3c800000, 0xbc800000,
    0x3c800000, 0xbc800000, 0x3c800000, 0xbc800000, 0x3c800000, 0xbc800000, 0x3c22bc46, 0xbbf13c62, 0x3b95bc75, 0xbac93c7f,
    0x3c7fbac9, 0xbc753b95, 0x3c62bbf1, 0xbc463c22, 0xbc46bc22, 0x3c623bf1, 0xbc75bb95, 0x3c7f3ac9, 0xbac9bc7f, 0x3b953c75,
    0xbbf1bc62, 0x3c223c46, 0xbc223c46, 0x3bf1bc62, 0xbb953c75, 0x3ac9bc7f, 0xbc7f3ac9, 0x3c75bb95, 0xbc623bf1, 0x3c46bc22,
    0x3c463c22, 0xbc62bbf1, 0x3c753b95, 0xbc7fbac9, 0x3ac93c7f, 0xbb95bc75, 0x3bf13c62, 0xbc22bc46, 0xbc7b3b48, 0x3c55bc0e,
    0xbc0e3c55, 0x3b48bc7b, 0x3b483c7b, 0xbc0ebc55, 0x3c553c0e, 0xbc7bbb48, 0x3c7bbb48, 0xbc553c0e, 0x3c0ebc55, 0xbb483c7b,
    0xbb48bc7b, 0x3c0e3c55, 0xbc55bc0e, 0x3c7b3b48, 0xbc7b3b48, 0x3c55bc0e, 0xbc0e3c55, 0x3b48bc7b, 0x3b483c7b, 0xbc0ebc55,
    0x3c553c0e, 0xbc7bbb48, 0x3c7bbb48, 0xbc553c0e, 0x3c0ebc55, 0xbb483c7b, 0xbb48bc7b, 0x3c0e3c55, 0xbc55bc0e, 0x3c7b3b48,
    0x3bf1bc62, 0x3ac93c7f, 0xbc22bc46, 0x3c753b95, 0x3b953c75, 0xbc46bc22, 0x3c7f3ac9, 0xbc623bf1, 0xbc62bbf1, 0x3c7fbac9,
    0xbc463c22, 0x3b95bc75, 0x3c75bb95, 0xbc223c46, 0x3ac9bc7f, 0x3bf13c62, 0xbbf13c62, 0xbac9bc7f, 0x3c223c46, 0xbc75bb95,
    0xbb95bc75, 0x3c463c22, 0xbc7fbac9, 0x3c62bbf1, 0x3c623bf1, 0xbc7f3ac9, 0x3c46bc22, 0xbb953c75, 0xbc753b95, 0x3c22bc46,
    0xbac93c7f, 0xbbf1bc62, 0x3c6dbbc4, 0xbbc43c6d, 0xbbc4bc6d, 0x3c6d3bc4, 0xbc6d3bc4, 0x3bc4bc6d, 0x3bc43c6d, 0xbc6dbbc4,
    0x3c6dbbc4, 0xbbc43c6d, 0xbbc4bc6d, 0x3c6d3bc4, 0xbc6d3bc4, 0x3bc4bc6d, 0x3bc43c6d, 0xbc6dbbc4, 0x3c6dbbc4, 0xbbc43c6d,
    0xbbc4bc6d, 0x3c6d3bc4, 0xbc6d3bc4, 0x3bc4bc6d, 0x3bc43c6d, 0xbc6dbbc4, 0x3c6dbbc4, 0xbbc43c6d, 0xbbc4bc6d, 0x3c6d3bc4,
    0xbc6d3bc4, 0x3bc4bc6d, 0x3bc43c6d, 0xbc6dbbc4, 0x3b95bc75, 0x3c223c46, 0xbc7f3ac9, 0x3bf1bc62, 0xbc623bf1, 0x3ac9bc7f,
    0x3c463c22, 0xbc753b95, 0xbc75bb95, 0x3c46bc22, 0x3ac93c7f, 0xbc62bbf1, 0x3bf13c62, 0xbc7fbac9, 0x3c22bc46, 0x3b953c75,
    0xbb953c75, 0xbc22bc46, 0x3c7fbac9, 0xbbf13c62, 0x3c62bbf1, 0xbac93c7f, 0xbc46bc22, 0x3c75bb95, 0x3c753b95, 0xbc463c22,
    0xbac9bc7f, 0x3c623bf1, 0xbbf1bc62, 0x3c7f3ac9, 0xbc223c46, 0xbb95bc75, 0xbc553c0e, 0xbb48bc7b, 0x3c7b3b48, 0xbc0e3c55,
    0xbc0ebc55, 0x3c7bbb48, 0xbb483c7b, 0xbc55bc0e, 0x3c55bc0e, 0x3b483c7b, 0xbc7bbb48, 0x3c0ebc55, 0x3c0e3c55, 0xbc7b3b48,
    0x3b48bc7b, 0x3c553c0e, 0xbc553c0e, 0xbb48bc7b, 0x3c7b3b48, 0xbc0e3c55, 0xbc0ebc55, 0x3c7bbb48, 0xbb483c7b, 0xbc55bc0e,
    0x3c55bc0e, 0x3b483c7b, 0xbc7bbb48, 0x3c0ebc55, 0x3c0e3c55, 0xbc7b3b48, 0x3b48bc7b, 0x3c553c0e, 0x3ac9bc7f, 0x3c753b95,
    0xbbf13c62, 0xbc46bc22, 0xbc22bc46, 0x3c62bbf1, 0x3b953c75, 0xbc7f3ac9, 0xbc7fbac9, 0x3b95bc75, 0x3c623bf1, 0xbc223c46,
    0xbc463c22, 0xbbf1bc62, 0x3c75bb95, 0x3ac93c7f, 0xbac93c7f, 0xbc75bb95, 0x3bf1bc62, 0x3c463c22, 0x3c223c46, 0xbc623bf1,
    0xbb95bc75, 0x3c7fbac9, 0x3c7f3ac9, 0xbb953c75, 0xbc62bbf1, 0x3c22bc46, 0x3c46bc22, 0x3bf13c62, 0xbc753b95, 0xbac9bc7f,
    0x3c80ba49, 0xbc7d3b16, 0x3c78bb79, 0xbc713bac, 0x3c67bbdb, 0xbc5c3c04, 0x3c4ebc18, 0xbc3e3c2c, 0x3c2cbc3e, 0xbc183c4e,
    0x3c04bc5c, 0xbbdb3c67, 0x3bacbc71, 0xbb793c78, 0x3b16bc7d, 0xba493c80, 0xba49bc80, 0x3b163c7d, 0xbb79bc78, 0x3bac3c71,
    0xbbdbbc67, 0x3c043c5c, 0xbc18bc4e, 0x3c2c3c3e, 0xbc3ebc2c, 0x3c4e3c18, 0xbc5cbc04, 0x3c673bdb, 0xbc71bbac, 0x3c783b79,
    0xbc7dbb16, 0x3c803a49, 0x3b79bc78, 0x3a493c80, 0xbbacbc71, 0x3c183c4e, 0x3c7dbb16, 0xbc673bdb, 0x3c3ebc2c, 0xbc043c5c,
    0xbc5c3c04, 0x3c2cbc3e, 0xbbdb3c67, 0x3b16bc7d, 0xbc4ebc18, 0x3c713bac, 0xbc80ba49, 0x3c78bb79, 0x3c783b79, 0xbc803a49,
    0x3c71bbac, 0xbc4e3c18, 0x3b163c7d, 0xbbdbbc67, 0x3c2c3c3e, 0xbc5cbc04, 0xbc04bc5c, 0x3c3e3c2c, 0xbc67bbdb, 0x3c7d3b16,
    0x3c18bc4e, 0xbbac3c71, 0x3a49bc80, 0x3b793c78, 0xbc043c5c, 0x3a49bc80, 0x3bdb3c67, 0xbc4ebc18, 0x3c7d3b16, 0xbc713bac,
    0x3c2cbc3e, 0xbb793c78, 0x3c78bb79, 0xbc3e3c2c, 0x3bacbc71, 0x3b163c7d, 0xbc18bc4e, 0x3c673bdb, 0xbc803a49, 0x3c5cbc04,
    0x3c5c3c04, 0xbc80ba49, 0x3c67bbdb, 0xbc183c4e, 0x3b16bc7d, 0x3bac3c71, 0xbc3ebc2c, 0x3c783b79, 0xbb79bc78, 0x3c2c3c3e,
    0xbc71bbac, 0x3c7dbb16, 0xbc4e3c18, 0x3bdbbc67, 0x3a493c80, 0xbc04bc5c, 0xbc2cbc3e, 0x3c7d3b16, 0xbc5c3c04, 0x3bacbc71,
    0x3c673bdb, 0xbc783b79, 0x3c18bc4e, 0x3a493c80, 0xbc80ba49, 0x3c4ebc18, 0xbb793c78, 0xbbdbbc67, 0x3c71bbac, 0xbc043c5c,
    0xbb16bc7d, 0x3c3e3c2c, 0x3c3ebc2c, 0xbb163c7d, 0xbc04bc5c, 0x3c713bac, 0xbbdb3c67, 0xbb79bc78, 0x3c4e3c18, 0xbc803a49,
    0x3a49bc80, 0x3c183c4e, 0xbc78bb79, 0x3c67bbdb, 0x3bac3c71, 0xbc5cbc04, 0x3c7dbb16, 0xbc2c3c3e, 0xbbdbbc67, 0x3c783b79,
    0xbc4e3c18, 0x3a49bc80, 0x3c3e3c2c, 0xbc7d3b16, 0x3c04bc5c, 0x3bac3c71, 0xbc71bbac, 0x3c5cbc04, 0xbb163c7d, 0xbc2cbc3e,
    0x3c80ba49, 0xbc183c4e, 0xbb79bc78, 0x3c673bdb, 0x3c67bbdb, 0xbb793c78, 0xbc18bc4e, 0x3c803a49, 0xbc2c3c3e, 0xbb16bc7d,
    0x3c5c3c04, 0xbc713bac, 0x3bacbc71, 0x3c043c5c, 0xbc7dbb16, 0x3c3ebc2c, 0x3a493c80, 0xbc4ebc18, 0x3c78bb79, 0xbbdb3c67,
    0xbc7d3b16, 0x3bacbc71, 0x3c2c3c3e, 0xbc783b79, 0x3c043c5c, 0xbc803a49, 0x3bdbbc67, 0x3c183c4e, 0x3c4e3c18, 0xbc673bdb,
    0x3a49bc80, 0x3c5c3c04, 0x3b79bc78, 0x3c3e3c2c, 0xbc713bac, 0x3b16bc7d, 0x3b163c7d, 0xbc71bbac, 0x3c3ebc2c, 0x3b793c78,
    0x3c5cbc04, 0x3a493c80, 0xbc67bbdb, 0x3c4ebc18, 0x3c18bc4e, 0x3bdb3c67, 0xbc80ba49, 0x3c04bc5c, 0xbc78bb79, 0x3c2cbc3e,
    0x3bac3c71, 0xbc7dbb16, 0x3c7d3b16, 0xbbdb3c67, 0xbc3ebc2c, 0x3c5cbc04, 0x3b793c78, 0xbc80ba49, 0x3bacbc71, 0x3c4e3c18,
    0xbc18bc4e, 0x3c71bbac, 0x3a493c80, 0xbc78bb79, 0x3c04bc5c, 0x3c2c3c3e, 0xbc673bdb, 0xbb16bc7d, 0xbb163c7d, 0xbc67bbdb,
    0x3c2cbc3e, 0x3c043c5c, 0xbc783b79, 0x3a49bc80, 0x3c713bac, 0xbc183c4e, 0x3c4ebc18, 0x3bac3c71, 0xbc803a49, 0x3b79bc78,
    0x3c5c3c04, 0xbc3e3c2c, 0xbbdbbc67, 0x3c7dbb16, 0xbbdb3c67, 0xbc5cbc04, 0x3c18bc4e, 0x3c3e3c2c, 0xba493c80, 0xbc7dbb16,
    0x3b79bc78, 0x3c713bac, 0x3bac3c71, 0xbc783b79, 0xbb16bc7d, 0x3c80ba49, 0x3c2c3c3e, 0xbc4e3c18, 0xbc04bc5c, 0x3c67bbdb,
    0x3c673bdb, 0xbc043c5c, 0xbc4ebc18, 0x3c2cbc3e, 0x3c803a49, 0xbb163c7d, 0xbc78bb79, 0x3bacbc71, 0x3c71bbac, 0x3b793c78,
    0xbc7d3b16, 0xba49bc80, 0x3c3ebc2c, 0x3c183c4e, 0xbc5c3c04, 0xbbdbbc67, 0x3f803f80, 0x3f7d3f7f, 0x3f783f7b, 0x3f713f75,
    0x3f673f6d, 0x3f5c3f62, 0x3f4e3f55, 0x3f3e3f46, 0x3f2c3f35, 0x3f183f22, 0x3f043f0e, 0x3edb3ef1, 0x3eac3ec4, 0x3e793e95,
    0x3e163e48, 0x3d493dc9, 0xbd490000, 0xbe16bdc9, 0xbe79be48, 0xbeacbe95, 0xbedbbec4, 0xbf04bef1, 0xbf18bf0e, 0xbf2cbf22,
    0xbf3ebf35, 0xbf4ebf46, 0xbf5cbf55, 0xbf67bf62, 0xbf71bf6d, 0xbf78bf75, 0xbf7dbf7b, 0xbf80bf7f, 0x3edb3ec4, 0x3f043ef1,
    0x3f183f0e, 0x3f2c3f22, 0x3d490000, 0x3e163dc9, 0x3e793e48, 0x3eac3e95, 0x3f713f6d, 0x3f783f75, 0x3f7d3f7b, 0x3f803f7f,
    0x3f3e3f35, 0x3f4e3f46, 0x3f5c3f55, 0x3f673f62, 0x3f673f6d, 0x3f5c3f62, 0x3f4e3f55, 0x3f3e3f46, 0x3f803f80, 0x3f7d3f7f,
    0x3f783f7b, 0x3f713f75, 0x3eac3ec4, 0x3e793e95, 0x3e163e48, 0x3d493dc9, 0x3f2c3f35, 0x3f183f22, 0x3f043f0e, 0x3edb3ef1,
    0xbf4ebf35, 0xbf71bf62, 0xbf80bf7b, 0xbf78bf7f, 0xbf5cbf6d, 0xbf2cbf46, 0xbedbbf0e, 0xbe16be95, 0x3f7d3f80, 0x3f673f75,
    0x3f3e3f55, 0x3f043f22, 0x3e793ec4, 0xbd493dc9, 0xbeacbe48, 0xbf18bef1, 0x3f183f35, 0x3eac3ef1, 0x3d493e48, 0xbe79bdc9,
    0xbf04bec4, 0xbf3ebf22, 0xbf67bf55, 0xbf7dbf75, 0x3e160000, 0x3edb3e95, 0x3f2c3f0e, 0x3f5c3f46, 0x3f783f6d, 0x3f803f7f,
    0x3f713f7b, 0x3f4e3f62, 0xbf04bec4, 0xbf3ebf22, 0xbf67bf55, 0xbf7dbf75, 0x3f183f35, 0x3eac3ef1, 0x3d493e48, 0xbe79bdc9,
    0x3f783f6d, 0x3f803f7f, 0x3f713f7b, 0x3f4e3f62, 0x3e160000, 0x3edb3e95, 0x3f2c3f0e, 0x3f5c3f46, 0x3f5c3f6d, 0x3f2c3f46,
    0x3edb3f0e, 0x3e163e95, 0x3f4e3f35, 0x3f713f62, 0x3f803f7b, 0x3f783f7f, 0xbe79bec4, 0x3d49bdc9, 0x3eac3e48, 0x3f183ef1,
    0xbf7dbf80, 0xbf67bf75, 0xbf3ebf55, 0xbf04bf22, 0xbe790000, 0xbf2cbef1, 0xbf71bf55, 0xbf7dbf7f, 0xbf4ebf6d, 0xbedbbf22,
    0x3d49be48, 0x3f043e95, 0x3f5c3f35, 0x3f803f75, 0x3f673f7b, 0x3f183f46, 0x3e163ec4, 0xbeacbdc9, 0xbf3ebf0e, 0xbf78bf62,
    0x3f783f80, 0x3f3e3f62, 0x3eac3f0e, 0xbe163dc9, 0xbf18bec4, 0xbf67bf46, 0xbf80bf7b, 0xbf5cbf75, 0xbf04bf35, 0xbd49be95,
    0x3edb3e48, 0x3f4e3f22, 0x3f7d3f6d, 0x3f713f7f, 0x3f2c3f55, 0x3e793ef1, 0xbf18bec4, 0xbf67bf46, 0xbf80bf7b, 0xbf5cbf75,
    0x3f783f80, 0x3f3e3f62, 0x3eac3f0e, 0xbe163dc9, 0x3f7d3f6d, 0x3f713f7f, 0x3f2c3f55, 0x3e793ef1, 0xbf04bf35, 0xbd49be95,
    0x3edb3e48, 0x3f4e3f22, 0x3f4e3f6d, 0x3edb3f22, 0xbd493e48, 0xbf04be95, 0x3e790000, 0x3f2c3ef1, 0x3f713f55, 0x3f7d3f7f,
    0xbe16bec4, 0x3eac3dc9, 0x3f3e3f0e, 0x3f783f62, 0xbf5cbf35, 0xbf80bf75, 0xbf67bf7b, 0xbf18bf46, 0xbedbbf35, 0x3e79bdc9,
    0x3f4e3f0e, 0x3f803f75, 0x3f3e3f6d, 0x3e163ef1, 0xbf04be48, 0xbf71bf46, 0x3eac0000, 0x3f5c3f22, 0x3f7d3f7b, 0x3f2c3f62,
    0x3d493ec4, 0xbf18be95, 0xbf78bf55, 0xbf67bf7f, 0x3f673f35, 0x3f783f7f, 0x3f183f55, 0xbd493e95, 0xbf2cbec4, 0xbf7dbf62,
    0xbf5cbf7b, 0xbeacbf22, 0x3f713f80, 0x3f043f46, 0xbe163e48, 0xbf3ebef1, 0xbf80bf6d, 0xbf4ebf75, 0xbe79bf0e, 0x3edb3dc9,
    0x3f2c3ec4, 0x3f7d3f62, 0x3f5c3f7b, 0x3eac3f22, 0xbf67bf35, 0xbf78bf7f, 0xbf18bf55, 0x3d49be95, 0x3f803f6d, 0x3f4e3f75,
    0x3e793f0e, 0xbedbbdc9, 0xbf71bf80, 0xbf04bf46, 0x3e16be48, 0x3f3e3ef1, 0x3f3e3f6d, 0x3e163ef1, 0xbf04be48, 0xbf71bf46,
    0xbedbbf35, 0x3e79bdc9, 0x3f4e3f0e, 0x3f803f75, 0x3d493ec4, 0xbf18be95, 0xbf78bf55, 0xbf67bf7f, 0x3eac0000, 0x3f5c3f22,
    0x3f7d3f7b, 0x3f2c3f62, 0x3f673f80, 0x3e793f22, 0xbf18be48, 0xbf80bf62, 0xbf2cbf6d, 0x3e16be95, 0x3f5c3f0e, 0x3f713f7f,
    0x3eac3f35, 0xbf04bdc9, 0xbf7dbf55, 0xbf3ebf75, 0x3d49bec4, 0x3f4e3ef1, 0x3f783f7b, 0x3edb3f46, 0xbedb0000, 0xbf78bf46,
    0xbf4ebf7b, 0xbd49bef1, 0x3f3e3ec4, 0x3f7d3f75, 0x3f043f55, 0xbeac3dc9, 0xbf71bf35, 0xbf5cbf7f, 0xbe16bf0e, 0x3f2c3e95,
    0x3f803f6d, 0x3f183f62, 0xbe793e48, 0xbf67bf22, 0xbf3ebec4, 0xbf7dbf75, 0xbf04bf55, 0x3eacbdc9, 0x3edb0000, 0x3f783f46,
    0x3f4e3f7b, 0x3d493ef1, 0xbf80bf6d, 0xbf18bf62, 0x3e79be48, 0x3f673f22, 0x3f713f35, 0x3f5c3f7f, 0x3e163f0e, 0xbf2cbe95,
    0xbf2cbf6d, 0x3e16be95, 0x3f5c3f0e, 0x3f713f7f, 0x3f673f80, 0x3e793f22, 0xbf18be48, 0xbf80bf62, 0x3d49bec4, 0x3f4e3ef1,
    0x3f783f7b, 0x3edb3f46, 0x3eac3f35, 0xbf04bdc9, 0xbf7dbf55, 0xbf3ebf75, 0xbf78bf35, 0xbf2cbf75, 0x3eacbe48, 0x3f7d3f46,
    0x3f183f6d, 0xbedb3dc9, 0xbf80bf55, 0xbf04bf62, 0x3f5c3f80, 0xbd493ef1, 0xbf67bf0e, 0xbf4ebf7f, 0x3e16bec4, 0x3f713f22,
    0x3f3e3f7b, 0xbe793e95, 0x3e793f35, 0xbf3ebe95, 0xbf71bf7b, 0xbe16bf22, 0x3f4e3ec4, 0x3f673f7f, 0x3d493f0e, 0xbf5cbef1,
    0x3f040000, 0x3f803f62, 0x3edb3f55, 0xbf18bdc9, 0xbf7dbf6d, 0xbeacbf46, 0x3f2c3e48, 0x3f783f75, 0x3f4e3ec4, 0x3f673f7f,
    0x3d493f0e, 0xbf5cbef1, 0x3e793f35, 0xbf3ebe95, 0xbf71bf7b, 0xbe16bf22, 0xbf7dbf6d, 0xbeacbf46, 0x3f2c3e48, 0x3f783f75,
    0x3f040000, 0x3f803f62, 0x3edb3f55, 0xbf18bdc9, 0xbf18bf6d, 0x3edbbdc9, 0x3f803f55, 0x3f043f62, 0x3f783f35, 0x3f2c3f75,
    0xbeac3e48, 0xbf7dbf46, 0xbe163ec4, 0xbf71bf22, 0xbf3ebf7b, 0x3e79be95, 0xbf5cbf80, 0x3d49bef1, 0x3f673f0e, 0x3f4e3f7f,
    0xbf180000, 0xbf71bf75, 0x3d49bf0e, 0x3f783f22, 0x3f043f6d, 0xbf2cbdc9, 0xbf67bf7b, 0x3e16bef1, 0x3f7d3f35, 0x3edb3f62,
    0xbf3ebe48, 0xbf5cbf7f, 0x3e79bec4, 0x3f803f46, 0x3eac3f55, 0xbf4ebe95, 0x3f4e3f80, 0xbeac3e95, 0xbf80bf55, 0xbe79bf46,
    0x3f5c3ec4, 0x3f3e3f7f, 0xbedb3e48, 0xbf7dbf62, 0xbe16bf35, 0x3f673ef1, 0x3f2c3f7b, 0xbf043dc9, 0xbf78bf6d, 0xbd49bf22,
    0x3f713f0e, 0x3f183f75, 0x3f5c3ec4, 0x3f3e3f7f, 0xbedb3e48, 0xbf7dbf62, 0x3f4e3f80, 0xbeac3e95, 0xbf80bf55, 0xbe79bf46,
    0xbf78bf6d, 0xbd49bf22, 0x3f713f0e, 0x3f183f75, 0xbe16bf35, 0x3f673ef1, 0x3f2c3f7b, 0xbf043dc9, 0xbf04bf6d, 0x3f2c3dc9,
    0x3f673f7b, 0xbe163ef1, 0x3f180000, 0x3f713f75, 0xbd493f0e, 0xbf78bf22, 0xbe793ec4, 0xbf80bf46, 0xbeacbf55, 0x3f4e3e95,
    0xbf7dbf35, 0xbedbbf62, 0x3f3e3e48, 0x3f5c3f7f, 0xbd49bf35, 0x3f7d3f22, 0x3e793f55, 0xbf71bef1, 0xbedbbf6d, 0x3f5c3e95,
    0x3f183f7b, 0xbf3ebdc9, 0x3f2c0000, 0x3f4e3f7f, 0xbf043e48, 0xbf67bf75, 0x3eacbec4, 0x3f783f62, 0xbe163f0e, 0xbf80bf46,
    0x3f803f35, 0x3e163f46, 0xbf78bf0e, 0xbeacbf62, 0x3f673ec4, 0x3f043f75, 0xbf4ebe48, 0xbf2cbf7f, 0x3f3e3f80, 0xbf183dc9,
    0xbf5cbf7b, 0x3edbbe95, 0x3f713f6d, 0xbe793ef1, 0xbf7dbf55, 0x3d49bf22, 0xbf67bec4, 0xbf04bf75, 0x3f4e3e48, 0x3f2c3f7f,
    0xbf80bf35, 0xbe16bf46, 0x3f783f0e, 0x3eac3f62, 0xbf71bf6d, 0x3e79bef1, 0x3f7d3f55, 0xbd493f22, 0xbf3ebf80, 0x3f18bdc9,
    0x3f5c3f7b, 0xbedb3e95, 0xbedbbf6d, 0x3f5c3e95, 0x3f183f7b, 0xbf3ebdc9, 0xbd49bf35, 0x3f7d3f22, 0x3e793f55, 0xbf71bef1,
    0x3eacbec4, 0x3f783f62, 0xbe163f0e, 0xbf80bf46, 0x3f2c0000, 0x3f4e3f7f, 0xbf043e48, 0xbf67bf75, 0x3f2c3f80, 0xbf4ebdc9,
    0xbf04bf7b, 0x3f673e95, 0x3eac3f6d, 0xbf78bef1, 0xbe16bf55, 0x3f803f22, 0xbd493f35, 0xbf7dbf46, 0x3e79bf0e, 0x3f713f62,
    0xbedb3ec4, 0xbf5cbf75, 0x3f18be48, 0x3f3e3f7f, 0xbf3e0000, 0xbf18bf7f, 0x3f5c3e48, 0x3edb3f75, 0xbf71bec4, 0xbe79bf62,
    0x3f7d3f0e, 0x3d493f46, 0xbf80bf35, 0x3e16bf22, 0x3f783f55, 0xbeac3ef1, 0xbf67bf6d, 0x3f04be95, 0x3f4e3f7b, 0xbf2c3dc9,
    0x3f713ec4, 0x3e793f62, 0xbf7dbf0e, 0xbd49bf46, 0x3f3e0000, 0x3f183f7f, 0xbf5cbe48, 0xbedbbf75, 0x3f673f6d, 0xbf043e95,
    0xbf4ebf7b, 0x3f2cbdc9, 0x3f803f35, 0xbe163f22, 0xbf78bf55, 0x3eacbef1, 0x3eac3f6d, 0xbf78bef1, 0xbe16bf55, 0x3f803f22,
    0x3f2c3f80, 0xbf4ebdc9, 0xbf04bf7b, 0x3f673e95, 0xbedb3ec4, 0xbf5cbf75, 0x3f18be48, 0x3f3e3f7f, 0xbd493f35, 0xbf7dbf46,
    0x3e79bf0e, 0x3f713f62, 0xbf7dbf35, 0x3edbbef1, 0x3f3e3f7b, 0xbf5cbdc9, 0xbe79bf6d, 0x3f803f22, 0xbeac3f0e, 0xbf4ebf75,
    0x3f183f80, 0xbf71be95, 0xbd49bf55, 0x3f783f46, 0xbf043ec4, 0xbf2cbf7f, 0x3f673e48, 0x3e163f62, 0xbe163f35, 0xbf67bf62,
    0x3f2cbe48, 0x3f043f7f, 0xbf78bec4, 0x3d49bf46, 0x3f713f55, 0xbf183e95, 0x3f4e0000, 0x3eac3f75, 0xbf80bf0e, 0x3e79bf22,
    0x3f5c3f6d, 0xbf3e3dc9, 0xbedbbf7b, 0x3f7d3ef1, 0xbf78bec4, 0x3d49bf46, 0x3f713f55, 0xbf183e95, 0xbe163f35, 0xbf67bf62,
    0x3f2cbe48, 0x3f043f7f, 0x3f5c3f6d, 0xbf3e3dc9, 0xbedbbf7b, 0x3f7d3ef1, 0x3f4e0000, 0x3eac3f75, 0xbf80bf0e, 0x3e79bf22,
    0x3e793f6d, 0xbf80bf22, 0x3eacbf0e, 0x3f4e3f75, 0x3f7d3f35, 0xbedb3ef1, 0xbf3ebf7b, 0x3f5c3dc9, 0x3f04bec4, 0x3f2c3f7f,
    0xbf67be48, 0xbe16bf62, 0xbf18bf80, 0x3f713e95, 0x3d493f55, 0xbf78bf46, 0xbf5c0000, 0xbd49bf62, 0x3f673f55, 0xbf4e3dc9,
    0xbe16bf6d, 0x3f713f46, 0xbf3e3e48, 0xbe79bf75, 0x3f783f35, 0xbf2c3e95, 0xbeacbf7b, 0x3f7d3f22, 0xbf183ec4, 0xbedbbf7f,
    0x3f803f0e, 0xbf043ef1, 0x3f043f80, 0xbf80bef1, 0x3edbbf0e, 0x3f183f7f, 0xbf7dbec4, 0x3eacbf22, 0x3f2c3f7b, 0xbf78be95,
    0x3e79bf35, 0x3f3e3f75, 0xbf71be48, 0x3e16bf46, 0x3f4e3f6d, 0xbf67bdc9, 0x3d49bf55, 0x3f5c3f62, 0xbf7dbec4, 0x3eacbf22,
    0x3f2c3f7b, 0xbf78be95, 0x3f043f80, 0xbf80bef1, 0x3edbbf0e, 0x3f183f7f, 0x3f4e3f6d, 0xbf67bdc9, 0x3d49bf55, 0x3f5c3f62,
    0x3e79bf35, 0x3f3e3f75, 0xbf71be48, 0x3e16bf46, 0x3e163f6d, 0xbf71bf46, 0x3f3ebe48, 0x3e793f75, 0x3f5c0000, 0x3d493f62,
    0xbf67bf55, 0x3f4ebdc9, 0x3f18bec4, 0x3edb3f7f, 0xbf80bf0e, 0x3f04bef1, 0xbf78bf35, 0x3f2cbe95, 0x3eac3f7b, 0xbf7dbf22,
    0x3eacbf35, 0x3f043f7f, 0xbf7dbf0e, 0x3f3ebe95, 0x3d493f6d, 0xbf4ebf62, 0x3f783e48, 0xbedb3f22, 0x3f670000, 0xbe793f46,
    0xbf18bf7b, 0x3f803ef1, 0xbf2c3ec4, 0xbe16bf75, 0x3f5c3f55, 0xbf71bdc9, 0x3f713f35, 0xbf5c3dc9, 0x3e16bf55, 0x3f2c3f75,
    0xbf80bec4, 0x3f18bef1, 0x3e793f7b, 0xbf67bf46, 0x3edb3f80, 0xbf78bf22, 0x3f4ebe48, 0xbd493f62, 0xbf3ebf6d, 0x3f7d3e95,
    0xbf043f0e, 0xbeacbf7f, 0x3f803ec4, 0xbf183ef1, 0xbe79bf7b, 0x3f673f46, 0xbf71bf35, 0x3f5cbdc9, 0xbe163f55, 0xbf2cbf75,
    0x3f3e3f6d, 0xbf7dbe95, 0x3f04bf0e, 0x3eac3f7f, 0xbedbbf80, 0x3f783f22, 0xbf4e3e48, 0x3d49bf62, 0x3d493f6d, 0xbf4ebf62,
    0x3f783e48, 0xbedb3f22, 0x3eacbf35, 0x3f043f7f, 0xbf7dbf0e, 0x3f3ebe95, 0xbf2c3ec4, 0xbe16bf75, 0x3f5c3f55, 0xbf71bdc9,
    0x3f670000, 0xbe793f46, 0xbf18bf7b, 0x3f803ef1, 0x3eac3f80, 0xbf5cbf46, 0x3f7d3e48, 0xbf2c3ef1, 0x3d49bf6d, 0x3f183f75,
    0xbf78bf0e, 0x3f67bdc9, 0xbedb3f35, 0xbe79bf7f, 0x3f4e3f55, 0xbf80be95, 0x3f3ebec4, 0xbe163f62, 0xbf04bf7b, 0x3f713f22,
    0xbf710000, 0x3f04bf22, 0x3e163f7b, 0xbf3ebf62, 0x3f803ec4, 0xbf4e3e95, 0x3e79bf55, 0x3edb3f7f, 0xbf67bf35, 0x3f783dc9,
    0xbf183f0e, 0xbd49bf75, 0x3f2c3f6d, 0xbf7dbef1, 0x3f5cbe48, 0xbeac3f46, 0xbf80bec4, 0x3f4ebe95, 0xbe793f55, 0xbedbbf7f,
    0x3f710000, 0xbf043f22, 0xbe16bf7b, 0x3f3e3f62, 0xbf2cbf6d, 0x3f7d3ef1, 0xbf5c3e48, 0x3eacbf46, 0x3f673f35, 0xbf78bdc9,
    0x3f18bf0e, 0x3d493f75, 0x3d49bf6d, 0x3f183f75, 0xbf78bf0e, 0x3f67bdc9, 0x3eac3f80, 0xbf5cbf46, 0x3f7d3e48, 0xbf2c3ef1,
    0x3f3ebec4, 0xbe163f62, 0xbf04bf7b, 0x3f713f22, 0xbedb3f35, 0xbe79bf7f, 0x3f4e3f55, 0xbf80be95, 0xbf5cbf35, 0x3f803e95,
    0xbf673e48, 0x3f18bf22, 0xbe163f6d, 0xbeacbf7f, 0x3f3e3f55, 0xbf78bef1, 0x3e793f80, 0xbf2cbf62, 0x3f713f0e, 0xbf7dbdc9,
    0x3f4ebec4, 0xbedb3f46, 0xbd49bf7b, 0x3f043f75, 0xbf043f35, 0x3d49bf75, 0x3edb3f7b, 0xbf4ebf46, 0x3f7d3ec4, 0xbf713dc9,
    0x3f2cbf0e, 0xbe793f62, 0x3f780000, 0xbf3e3ef1, 0x3eacbf55, 0x3e163f7f, 0xbf18bf6d, 0x3f673f22, 0xbf80be48, 0x3f5cbe95,
    0x3f7d3ec4, 0xbf713dc9, 0x3f2cbf0e, 0xbe793f62, 0xbf043f35, 0x3d49bf75, 0x3edb3f7b, 0xbf4ebf46, 0xbf18bf6d, 0x3f673f22,
    0xbf80be48, 0x3f5cbe95, 0x3f780000, 0xbf3e3ef1, 0x3eacbf55, 0x3e163f7f, 0x3e16bf6d, 0x3eac3f7f, 0xbf3ebf55, 0x3f783ef1,
    0x3f5c3f35, 0xbf80be95, 0x3f67be48, 0xbf183f22, 0xbf4e3ec4, 0x3edbbf46, 0x3d493f7b, 0xbf04bf75, 0xbe79bf80, 0x3f2c3f62,
    0xbf71bf0e, 0x3f7d3dc9, 0xbf7d0000, 0x3f67be95, 0xbf3e3f0e, 0x3f04bf46, 0xbe793f6d, 0xbd49bf7f, 0x3eac3f7b, 0xbf18bf62,
    0x3f4e3f35, 0xbf71bef1, 0x3f803e48, 0xbf783dc9, 0x3f5cbec4, 0xbf2c3f22, 0x3edbbf55, 0xbe163f75, 0x3e163f80, 0xbedbbf75,
    0x3f2c3f55, 0xbf5cbf22, 0x3f783ec4, 0xbf80bdc9, 0x3f71be48, 0xbf4e3ef1, 0x3f18bf35, 0xbeac3f62, 0x3d49bf7b, 0x3e793f7f,
    0xbf04bf6d, 0x3f3e3f46, 0xbf67bf0e, 0x3f7d3e95, 0x3f783ec4, 0xbf80bdc9, 0x3f71be48, 0xbf4e3ef1, 0x3e163f80, 0xbedbbf75,
    0x3f2c3f55, 0xbf5cbf22, 0xbf04bf6d, 0x3f3e3f46, 0xbf67bf0e, 0x3f7d3e95, 0x3f18bf35, 0xbeac3f62, 0x3d49bf7b, 0x3e793f7f,
    0x3e79bf6d, 0x3d493f7f, 0xbeacbf7b, 0x3f183f62, 0x3f7d0000, 0xbf673e95, 0x3f3ebf0e, 0xbf043f46, 0xbf5c3ec4, 0x3f2cbf22,
    0xbedb3f55, 0x3e16bf75, 0xbf4ebf35, 0x3f713ef1, 0xbf80be48, 0x3f78bdc9, 0x3f2cbf35, 0xbf183f46, 0x3f04bf55, 0xbedb3f62,
    0x3eacbf6d, 0xbe793f75, 0x3e16bf7b, 0xbd493f7f, 0x3f800000, 0xbf7d3dc9, 0x3f78be48, 0xbf713e95, 0x3f67bec4, 0xbf5c3ef1,
    0x3f4ebf0e, 0xbf3e3f22, 0x3f3e3f35, 0xbf4ebf22, 0x3f5c3f0e, 0xbf67bef1, 0x3f713ec4, 0xbf78be95, 0x3f7d3e48, 0xbf80bdc9,
    0x3d493f80, 0xbe16bf7f, 0x3e793f7b, 0xbeacbf75, 0x3edb3f6d, 0xbf04bf62, 0x3f183f55, 0xbf2cbf46, 0xbf71bec4, 0x3f783e95,
    0xbf7dbe48, 0x3f803dc9, 0xbf3ebf35, 0x3f4e3f22, 0xbf5cbf0e, 0x3f673ef1, 0xbedbbf6d, 0x3f043f62, 0xbf18bf55, 0x3f2c3f46,
    0xbd49bf80, 0x3e163f7f, 0xbe79bf7b, 0x3eac3f75, 0x3eacbf6d, 0xbe793f75, 0x3e16bf7b, 0xbd493f7f, 0x3f2cbf35, 0xbf183f46,
    0x3f04bf55, 0xbedb3f62, 0x3f67bec4, 0xbf5c3ef1, 0x3f4ebf0e, 0xbf3e3f22, 0x3f800000, 0xbf7d3dc9, 0x3f78be48, 0xbf713e95,
    0xbd493f80, 0x3e16bf7f, 0xbe793f7b, 0x3eacbf75, 0xbedb3f6d, 0x3f04bf62, 0xbf183f55, 0x3f2cbf46, 0xbf3e3f35, 0x3f4ebf22,
    0xbf5c3f0e, 0x3f67bef1, 0xbf713ec4, 0x3f78be95, 0xbf7d3e48, 0x3f80bdc9, 0xbf800000, 0x3f7d3dc9, 0xbf78be48, 0x3f713e95,
    0xbf67bec4, 0x3f5c3ef1, 0xbf4ebf0e, 0x3f3e3f22, 0xbf2cbf35, 0x3f183f46, 0xbf04bf55, 0x3edb3f62, 0xbeacbf6d, 0x3e793f75,
    0xbe16bf7b, 0x3d493f7f, 0x3f673ec4, 0xbf5cbef1, 0x3f4e3f0e, 0xbf3ebf22, 0x3f800000, 0xbf7dbdc9, 0x3f783e48, 0xbf71be95,
    0x3eac3f6d, 0xbe79bf75, 0x3e163f7b, 0xbd49bf7f, 0x3f2c3f35, 0xbf18bf46, 0x3f043f55, 0xbedbbf62, 0xbedb3f6d, 0x3f04bf62,
    0xbf183f55, 0x3f2cbf46, 0xbd493f80, 0x3e16bf7f, 0xbe793f7b, 0x3eacbf75, 0xbf713ec4, 0x3f78be95, 0xbf7d3e48, 0x3f80bdc9,
    0xbf3e3f35, 0x3f4ebf22, 0xbf5c3f0e, 0x3f67bef1, 0xbf18bf35, 0x3eac3f62, 0xbd49bf7b, 0xbe793f7f, 0x3f04bf6d, 0xbf3e3f46,
    0x3f67bf0e, 0xbf7d3e95, 0xbe163f80, 0x3edbbf75, 0xbf2c3f55, 0x3f5cbf22, 0xbf783ec4, 0x3f80bdc9, 0xbf71be48, 0x3f4e3ef1,
    0xbf4e3f35, 0x3f71bef1, 0xbf803e48, 0x3f783dc9, 0xbf5cbec4, 0x3f2c3f22, 0xbedbbf55, 0x3e163f75, 0x3f7d0000, 0xbf67be95,
    0x3f3e3f0e, 0xbf04bf46, 0x3e793f6d, 0x3d49bf7f, 0xbeac3f7b, 0x3f18bf62, 0xbf5cbec4, 0x3f2c3f22, 0xbedbbf55, 0x3e163f75,
    0xbf4e3f35, 0x3f71bef1, 0xbf803e48, 0x3f783dc9, 0x3e793f6d, 0x3d49bf7f, 0xbeac3f7b, 0x3f18bf62, 0x3f7d0000, 0xbf67be95,
    0x3f3e3f0e, 0xbf04bf46, 0xbf043f6d, 0x3f3ebf46, 0xbf673f0e, 0x3f7dbe95, 0x3f183f35, 0xbeacbf62, 0x3d493f7b, 0x3e79bf7f,
    0x3f78bec4, 0xbf803dc9, 0x3f713e48, 0xbf4ebef1, 0x3e16bf80, 0xbedb3f75, 0x3f2cbf55, 0xbf5c3f22, 0xbf780000, 0x3f3e3ef1,
    0xbeacbf55, 0xbe163f7f, 0x3f18bf6d, 0xbf673f22, 0x3f80be48, 0xbf5cbe95, 0x3f043f35, 0xbd49bf75, 0xbedb3f7b, 0x3f4ebf46,
    0xbf7d3ec4, 0x3f713dc9, 0xbf2cbf0e, 0x3e793f62, 0xbe793f80, 0x3f2cbf62, 0xbf713f0e, 0x3f7dbdc9, 0xbf4ebec4, 0x3edb3f46,
    0x3d49bf7b, 0xbf043f75, 0x3f5cbf35, 0xbf803e95, 0x3f673e48, 0xbf18bf22, 0x3e163f6d, 0x3eacbf7f, 0xbf3e3f55, 0x3f78bef1,
    0xbf4ebec4, 0x3edb3f46, 0x3d49bf7b, 0xbf043f75, 0xbe793f80, 0x3f2cbf62, 0xbf713f0e, 0x3f7dbdc9, 0x3e163f6d, 0x3eacbf7f,
    0xbf3e3f55, 0x3f78bef1, 0x3f5cbf35, 0xbf803e95, 0x3f673e48, 0xbf18bf22, 0xbf183f6d, 0x3f67bf22, 0xbf803e48, 0x3f5c3e95,
    0x3f780000, 0xbf3ebef1, 0x3eac3f55, 0x3e16bf7f, 0x3f7dbec4, 0xbf71bdc9, 0x3f2c3f0e, 0xbe79bf62, 0xbf04bf35, 0x3d493f75,
    0x3edbbf7b, 0xbf4e3f46, 0x3f67bf35, 0xbf783dc9, 0x3f183f0e, 0x3d49bf75, 0xbf2c3f6d, 0x3f7dbef1, 0xbf5cbe48, 0x3eac3f46,
    0x3f710000, 0xbf04bf22, 0xbe163f7b, 0x3f3ebf62, 0xbf803ec4, 0x3f4e3e95, 0xbe79bf55, 0xbedb3f7f, 0x3edb3f35, 0x3e79bf7f,
    0xbf4e3f55, 0x3f80be95, 0xbf3ebec4, 0x3e163f62, 0x3f04bf7b, 0xbf713f22, 0xbeac3f80, 0x3f5cbf46, 0xbf7d3e48, 0x3f2c3ef1,
    0xbd49bf6d, 0xbf183f75, 0x3f78bf0e, 0xbf67bdc9, 0x3f3e3ec4, 0xbe16bf62, 0xbf043f7b, 0x3f71bf22, 0xbedbbf35, 0xbe793f7f,
    0x3f4ebf55, 0xbf803e95, 0x3d493f6d, 0x3f18bf75, 0xbf783f0e, 0x3f673dc9, 0x3eacbf80, 0xbf5c3f46, 0x3f7dbe48, 0xbf2cbef1,
    0xbf2c3f6d, 0x3f7dbef1, 0xbf5cbe48, 0x3eac3f46, 0x3f67bf35, 0xbf783dc9, 0x3f183f0e, 0x3d49bf75, 0xbf803ec4, 0x3f4e3e95,
    0xbe79bf55, 0xbedb3f7f, 0x3f710000, 0xbf04bf22, 0xbe163f7b, 0x3f3ebf62, 0xbedb3f80, 0x3f78bf22, 0xbf4ebe48, 0x3d493f62,
    0x3f3ebf6d, 0xbf7d3e95, 0x3f043f0e, 0x3eacbf7f, 0xbf713f35, 0x3f5c3dc9, 0xbe16bf55, 0xbf2c3f75, 0x3f80bec4, 0xbf18bef1,
    0xbe793f7b, 0x3f67bf46, 0xbf670000, 0x3e793f46, 0x3f18bf7b, 0xbf803ef1, 0x3f2c3ec4, 0x3e16bf75, 0xbf5c3f55, 0x3f71bdc9,
    0xbeacbf35, 0xbf043f7f, 0x3f7dbf0e, 0xbf3ebe95, 0xbd493f6d, 0x3f4ebf62, 0xbf783e48, 0x3edb3f22, 0xbf2cbec4, 0xbe163f75,
    0x3f5cbf55, 0xbf713dc9, 0x3f670000, 0xbe79bf46, 0xbf183f7b, 0x3f80bef1, 0x3d49bf6d, 0xbf4e3f62, 0x3f78be48, 0xbedbbf22,
    0x3eac3f35, 0x3f04bf7f, 0xbf7d3f0e, 0x3f3e3e95, 0x3f3ebf6d, 0xbf7d3e95, 0x3f043f0e, 0x3eacbf7f, 0xbedb3f80, 0x3f78bf22,
    0xbf4ebe48, 0x3d493f62, 0x3f80bec4, 0xbf18bef1, 0xbe793f7b, 0x3f67bf46, 0xbf713f35, 0x3f5c3dc9, 0xbe16bf55, 0xbf2c3f75,
    0xbe79bf35, 0xbf3e3f75, 0x3f71be48, 0xbe16bf46, 0xbf4e3f6d, 0x3f67bdc9, 0xbd49bf55, 0xbf5c3f62, 0xbf043f80, 0x3f80bef1,
    0xbedbbf0e, 0xbf183f7f, 0x3f7dbec4, 0xbeacbf22, 0xbf2c3f7b, 0x3f78be95, 0xbf783f35, 0x3f2c3e95, 0x3eacbf7b, 0xbf7d3f22,
    0x3f183ec4, 0x3edbbf7f, 0xbf803f0e, 0x3f043ef1, 0x3f5c0000, 0x3d49bf62, 0xbf673f55, 0x3f4e3dc9, 0x3e16bf6d, 0xbf713f46,
    0x3f3e3e48, 0x3e79bf75, 0x3f183ec4, 0x3edbbf7f, 0xbf803f0e, 0x3f043ef1, 0xbf783f35, 0x3f2c3e95, 0x3eacbf7b, 0xbf7d3f22,
    0x3e16bf6d, 0xbf713f46, 0x3f3e3e48, 0x3e79bf75, 0x3f5c0000, 0x3d49bf62, 0xbf673f55, 0x3f4e3dc9, 0x3f4ebf6d, 0xbf673dc9,
    0x3d493f55, 0x3f5cbf62, 0x3e793f35, 0x3f3ebf75, 0xbf713e48, 0x3e163f46, 0xbf7d3ec4, 0x3eac3f22, 0x3f2cbf7b, 0xbf783e95,
    0x3f04bf80, 0xbf803ef1, 0x3edb3f0e, 0x3f18bf7f, 0xbf4e0000, 0xbeac3f75, 0x3f80bf0e, 0xbe79bf22, 0xbf5c3f6d, 0x3f3e3dc9,
    0x3edbbf7b, 0xbf7d3ef1, 0x3e163f35, 0x3f67bf62, 0xbf2cbe48, 0xbf043f7f, 0x3f78bec4, 0xbd49bf46, 0xbf713f55, 0x3f183e95,
    0xbf183f80, 0x3f71be95, 0x3d49bf55, 0xbf783f46, 0x3f043ec4, 0x3f2cbf7f, 0xbf673e48, 0xbe163f62, 0x3f7dbf35, 0xbedbbef1,
    0xbf3e3f7b, 0x3f5cbdc9, 0x3e79bf6d, 0xbf803f22, 0x3eac3f0e, 0x3f4ebf75, 0x3f043ec4, 0x3f2cbf7f, 0xbf673e48, 0xbe163f62,
    0xbf183f80, 0x3f71be95, 0x3d49bf55, 0xbf783f46, 0x3e79bf6d, 0xbf803f22, 0x3eac3f0e, 0x3f4ebf75, 0x3f7dbf35, 0xbedbbef1,
    0xbf3e3f7b, 0x3f5cbdc9, 0x3f5cbf6d, 0xbf3ebdc9, 0xbedb3f7b, 0x3f7dbef1, 0x3f4e0000, 0x3eacbf75, 0xbf803f0e, 0x3e793f22,
    0xbf783ec4, 0x3d493f46, 0x3f71bf55, 0xbf18be95, 0xbe16bf35, 0xbf673f62, 0x3f2c3e48, 0x3f04bf7f, 0x3f80bf35, 0xbe16bf22,
    0xbf783f55, 0x3eac3ef1, 0x3f67bf6d, 0xbf04be95, 0xbf4e3f7b, 0x3f2c3dc9, 0x3f3e0000, 0x3f18bf7f, 0xbf5c3e48, 0xbedb3f75,
    0x3f71bec4, 0x3e79bf62, 0xbf7d3f0e, 0xbd493f46, 0x3d493f35, 0x3f7dbf46, 0xbe79bf0e, 0xbf713f62, 0x3edb3ec4, 0x3f5cbf75,
    0xbf18be48, 0xbf3e3f7f, 0xbf2c3f80, 0x3f4ebdc9, 0x3f04bf7b, 0xbf673e95, 0xbeac3f6d, 0x3f78bef1, 0x3e16bf55, 0xbf803f22,
    0xbedbbec4, 0xbf5c3f75, 0x3f183e48, 0x3f3ebf7f, 0xbd49bf35, 0xbf7d3f46, 0x3e793f0e, 0x3f71bf62, 0x3eacbf6d, 0xbf783ef1,
    0xbe163f55, 0x3f80bf22, 0x3f2cbf80, 0xbf4e3dc9, 0xbf043f7b, 0x3f67be95, 0x3f67bf6d, 0xbf04be95, 0xbf4e3f7b, 0x3f2c3dc9,
    0x3f80bf35, 0xbe16bf22, 0xbf783f55, 0x3eac3ef1, 0x3f71bec4, 0x3e79bf62, 0xbf7d3f0e, 0xbd493f46, 0x3f3e0000, 0x3f18bf7f,
    0xbf5c3e48, 0xbedb3f75, 0xbf3e3f80, 0x3f183dc9, 0x3f5cbf7b, 0xbedbbe95, 0xbf713f6d, 0x3e793ef1, 0x3f7dbf55, 0xbd49bf22,
    0xbf803f35, 0xbe163f46, 0x3f78bf0e, 0x3eacbf62, 0xbf673ec4, 0xbf043f75, 0x3f4ebe48, 0x3f2cbf7f, 0xbf2c0000, 0xbf4e3f7f,
    0x3f043e48, 0x3f67bf75, 0xbeacbec4, 0xbf783f62, 0x3e163f0e, 0x3f80bf46, 0x3d49bf35, 0xbf7d3f22, 0xbe793f55, 0x3f71bef1,
    0x3edbbf6d, 0xbf5c3e95, 0xbf183f7b, 0x3f3ebdc9, 0x3eac3ec4, 0x3f78bf62, 0xbe16bf0e, 0xbf803f46, 0x3f2c0000, 0x3f4ebf7f,
    0xbf04be48, 0xbf673f75, 0xbedb3f6d, 0x3f5cbe95, 0x3f18bf7b, 0xbf3e3dc9, 0xbd493f35, 0x3f7dbf22, 0x3e79bf55, 0xbf713ef1,
    0xbf713f6d, 0x3e793ef1, 0x3f7dbf55, 0xbd49bf22, 0xbf3e3f80, 0x3f183dc9, 0x3f5cbf7b, 0xbedbbe95, 0xbf673ec4, 0xbf043f75,
    0x3f4ebe48, 0x3f2cbf7f, 0xbf803f35, 0xbe163f46, 0x3f78bf0e, 0x3eacbf62, 0x3e16bf35, 0xbf673ef1, 0xbf2c3f7b, 0x3f043dc9,
    0x3f78bf6d, 0x3d49bf22, 0xbf713f0e, 0xbf183f75, 0xbf4e3f80, 0x3eac3e95, 0x3f80bf55, 0x3e79bf46, 0xbf5c3ec4, 0xbf3e3f7f,
    0x3edb3e48, 0x3f7dbf62, 0xbf7d3f35, 0xbedb3f62, 0x3f3ebe48, 0x3f5cbf7f, 0xbe79bec4, 0xbf803f46, 0xbeac3f55, 0x3f4ebe95,
    0x3f180000, 0x3f71bf75, 0xbd49bf0e, 0xbf783f22, 0xbf043f6d, 0x3f2cbdc9, 0x3f67bf7b, 0xbe16bef1, 0xbe79bec4, 0xbf803f46,
    0xbeac3f55, 0x3f4ebe95, 0xbf7d3f35, 0xbedb3f62, 0x3f3ebe48, 0x3f5cbf7f, 0xbf043f6d, 0x3f2cbdc9, 0x3f67bf7b, 0xbe16bef1,
    0x3f180000, 0x3f71bf75, 0xbd49bf0e, 0xbf783f22, 0xbf783f6d, 0xbd493f22, 0x3f71bf0e, 0x3f18bf75, 0xbe163f35, 0x3f67bef1,
    0x3f2cbf7b, 0xbf04bdc9, 0x3f5cbec4, 0x3f3ebf7f, 0xbedbbe48, 0xbf7d3f62, 0x3f4ebf80, 0xbeacbe95, 0xbf803f55, 0xbe793f46,
    0xbf040000, 0xbf803f62, 0xbedb3f55, 0x3f18bdc9, 0x3f7dbf6d, 0x3eacbf46, 0xbf2c3e48, 0xbf783f75, 0xbe793f35, 0x3f3ebe95,
    0x3f71bf7b, 0x3e16bf22, 0xbf4e3ec4, 0xbf673f7f, 0xbd493f0e, 0x3f5cbef1, 0xbf5c3f80, 0x3d493ef1, 0x3f67bf0e, 0x3f4ebf7f,
    0xbe16bec4, 0xbf713f22, 0xbf3e3f7b, 0x3e793e95, 0x3f78bf35, 0x3f2cbf75, 0xbeacbe48, 0xbf7d3f46, 0xbf183f6d, 0x3edb3dc9,
    0x3f80bf55, 0x3f04bf62, 0xbe16bec4, 0xbf713f22, 0xbf3e3f7b, 0x3e793e95, 0xbf5c3f80, 0x3d493ef1, 0x3f67bf0e, 0x3f4ebf7f,
    0xbf183f6d, 0x3edb3dc9, 0x3f80bf55, 0x3f04bf62, 0x3f78bf35, 0x3f2cbf75, 0xbeacbe48, 0xbf7d3f46, 0xbf7d3f6d, 0xbeac3f46,
    0x3f2cbe48, 0x3f78bf75, 0x3f040000, 0x3f80bf62, 0x3edbbf55, 0xbf183dc9, 0x3f4ebec4, 0x3f67bf7f, 0x3d49bf0e, 0xbf5c3ef1,
    0x3e79bf35, 0xbf3e3e95, 0xbf713f7b, 0xbe163f22, 0x3f71bf35, 0x3f5cbf7f, 0x3e16bf0e, 0xbf2c3e95, 0xbf803f6d, 0xbf183f62,
    0x3e793e48, 0x3f67bf22, 0x3edb0000, 0x3f78bf46, 0x3f4ebf7b, 0x3d49bef1, 0xbf3e3ec4, 0xbf7d3f75, 0xbf043f55, 0x3eac3dc9,
    0xbeac3f35, 0x3f04bdc9, 0x3f7dbf55, 0x3f3ebf75, 0xbd49bec4, 0xbf4e3ef1, 0xbf783f7b, 0xbedb3f46, 0xbf673f80, 0xbe793f22,
    0x3f18be48, 0x3f80bf62, 0x3f2cbf6d, 0xbe16be95, 0xbf5c3f0e, 0xbf713f7f, 0x3d493ec4, 0x3f4ebef1, 0x3f78bf7b, 0x3edbbf46,
    0x3eacbf35, 0xbf043dc9, 0xbf7d3f55, 0xbf3e3f75, 0xbf2c3f6d, 0x3e163e95, 0x3f5cbf0e, 0x3f71bf7f, 0x3f67bf80, 0x3e79bf22,
    0xbf183e48, 0xbf803f62, 0xbf803f6d, 0xbf183f62, 0x3e793e48, 0x3f67bf22, 0x3f71bf35, 0x3f5cbf7f, 0x3e16bf0e, 0xbf2c3e95,
    0xbf3e3ec4, 0xbf7d3f75, 0xbf043f55, 0x3eac3dc9, 0x3edb0000, 0x3f78bf46, 0x3f4ebf7b, 0x3d49bef1, 0xbf713f80, 0xbf043f46,
    0x3e163e48, 0x3f3ebef1, 0x3f80bf6d, 0x3f4ebf75, 0x3e79bf0e, 0xbedb3dc9, 0xbf673f35, 0xbf783f7f, 0xbf183f55, 0x3d493e95,
    0x3f2cbec4, 0x3f7dbf62, 0x3f5cbf7b, 0x3eacbf22, 0xbeac0000, 0xbf5c3f22, 0xbf7d3f7b, 0xbf2c3f62, 0xbd493ec4, 0x3f18be95,
    0x3f78bf55, 0x3f67bf7f, 0x3edbbf35, 0xbe79bdc9, 0xbf4e3f0e, 0xbf803f75, 0xbf3e3f6d, 0xbe163ef1, 0x3f04be48, 0x3f71bf46,
    0x3d49bec4, 0xbf183e95, 0xbf783f55, 0xbf673f7f, 0x3eac0000, 0x3f5cbf22, 0x3f7dbf7b, 0x3f2cbf62, 0x3f3ebf6d, 0x3e16bef1,
    0xbf043e48, 0xbf713f46, 0xbedb3f35, 0x3e793dc9, 0x3f4ebf0e, 0x3f80bf75, 0x3f80bf6d, 0x3f4ebf75, 0x3e79bf0e, 0xbedb3dc9,
    0xbf713f80, 0xbf043f46, 0x3e163e48, 0x3f3ebef1, 0x3f2cbec4, 0x3f7dbf62, 0x3f5cbf7b, 0x3eacbf22, 0xbf673f35, 0xbf783f7f,
    0xbf183f55, 0x3d493e95, 0x3f04bf35, 0x3d49be95, 0xbedb3e48, 0xbf4e3f22, 0xbf7d3f6d, 0xbf713f7f, 0xbf2c3f55, 0xbe793ef1,
    0xbf783f80, 0xbf3e3f62, 0xbeac3f0e, 0x3e163dc9, 0x3f18bec4, 0x3f67bf46, 0x3f80bf7b, 0x3f5cbf75, 0xbf5c3f35, 0xbf803f75,
    0xbf673f7b, 0xbf183f46, 0xbe163ec4, 0x3eacbdc9, 0x3f3ebf0e, 0x3f78bf62, 0x3e790000, 0x3f2cbef1, 0x3f71bf55, 0x3f7dbf7f,
    0x3f4ebf6d, 0x3edbbf22, 0xbd49be48, 0xbf043e95, 0xbe163ec4, 0x3eacbdc9, 0x3f3ebf0e, 0x3f78bf62, 0xbf5c3f35, 0xbf803f75,
    0xbf673f7b, 0xbf183f46, 0x3f4ebf6d, 0x3edbbf22, 0xbd49be48, 0xbf043e95, 0x3e790000, 0x3f2cbef1, 0x3f71bf55, 0x3f7dbf7f,
    0x3f7dbf6d, 0x3f71bf7f, 0x3f2cbf55, 0x3e79bef1, 0xbf043f35, 0xbd493e95, 0x3edbbe48, 0x3f4ebf22, 0xbf183ec4, 0xbf673f46,
    0xbf803f7b, 0xbf5c3f75, 0x3f78bf80, 0x3f3ebf62, 0x3eacbf0e, 0xbe16bdc9, 0xbe160000, 0xbedb3e95, 0xbf2c3f0e, 0xbf5c3f46,
    0xbf783f6d, 0xbf803f7f, 0xbf713f7b, 0xbf4e3f62, 0xbf183f35, 0xbeac3ef1, 0xbd493e48, 0x3e79bdc9, 0x3f04bec4, 0x3f3ebf22,
    0x3f67bf55, 0x3f7dbf75, 0xbf7d3f80, 0xbf673f75, 0xbf3e3f55, 0xbf043f22, 0xbe793ec4, 0x3d493dc9, 0x3eacbe48, 0x3f18bef1,
    0x3f4ebf35, 0x3f71bf62, 0x3f80bf7b, 0x3f78bf7f, 0x3f5cbf6d, 0x3f2cbf46, 0x3edbbf0e, 0x3e16be95, 0xbe793ec4, 0x3d493dc9,
    0x3eacbe48, 0x3f18bef1, 0xbf7d3f80, 0xbf673f75, 0xbf3e3f55, 0xbf043f22, 0x3f5cbf6d, 0x3f2cbf46, 0x3edbbf0e, 0x3e16be95,
    0x3f4ebf35, 0x3f71bf62, 0x3f80bf7b, 0x3f78bf7f, 0x3f78bf6d, 0x3f80bf7f, 0x3f71bf7b, 0x3f4ebf62, 0x3e160000, 0x3edbbe95,
    0x3f2cbf0e, 0x3f5cbf46, 0xbf043ec4, 0xbf3e3f22, 0xbf673f55, 0xbf7d3f75, 0x3f18bf35, 0x3eacbef1, 0x3d49be48, 0xbe793dc9,
    0x3f3ebf35, 0x3f4ebf46, 0x3f5cbf55, 0x3f67bf62, 0x3f71bf6d, 0x3f78bf75, 0x3f7dbf7b, 0x3f80bf7f, 0x3d490000, 0x3e16bdc9,
    0x3e79be48, 0x3eacbe95, 0x3edbbec4, 0x3f04bef1, 0x3f18bf0e, 0x3f2cbf22, 0xbf2c3f35, 0xbf183f22, 0xbf043f0e, 0xbedb3ef1,
    0xbeac3ec4, 0xbe793e95, 0xbe163e48, 0xbd493dc9, 0xbf803f80, 0xbf7d3f7f, 0xbf783f7b, 0xbf713f75, 0xbf673f6d, 0xbf5c3f62,
    0xbf4e3f55, 0xbf3e3f46, 0x3eacbec4, 0x3e79be95, 0x3e16be48, 0x3d49bdc9, 0x3f2cbf35, 0x3f18bf22, 0x3f04bf0e, 0x3edbbef1,
    0x3f67bf6d, 0x3f5cbf62, 0x3f4ebf55, 0x3f3ebf46, 0x3f80bf80, 0x3f7dbf7f, 0x3f78bf7b, 0x3f71bf75, 0x3f71bf6d, 0x3f78bf75,
    0x3f7dbf7b, 0x3f80bf7f, 0x3f3ebf35, 0x3f4ebf46, 0x3f5cbf55, 0x3f67bf62, 0x3edbbec4, 0x3f04bef1, 0x3f18bf0e, 0x3f2cbf22,
    0x3d490000, 0x3e16bdc9, 0x3e79be48, 0x3eacbe95,
};
__device__ const __align__(128) uint32_t c_ga[1536] = {
    0x00003c80, 0x3bc43c6d, 0x00003c80, 0xbbc4bc6d, 0x00003c80, 0x3c6d3bc4, 0x00003c80, 0xbc6dbbc4, 0x00003c80, 0x3c6dbbc4,
    0x00003c80, 0xbc6d3bc4, 0x00003c80, 0x3bc4bc6d, 0x00003c80, 0xbbc43c6d, 0x3a493c80, 0x3bdb3c67, 0x3bdb3c67, 0xbc3ebc2c,
    0x3b163c7d, 0x3c783b79, 0x3c043c5c, 0xbc7d3b16, 0x3b793c78, 0x3c4ebc18, 0x3c183c4e, 0xbc043c5c, 0x3bac3c71, 0x3a49bc80,
    0x3c2c3c3e, 0x3bac3c71, 0x3ac93c7f, 0x3bf13c62, 0x3c463c22, 0xbc75bb95, 0x3b953c75, 0x3c7f3ac9, 0x3c623bf1, 0xbc463c22,
    0x3bf13c62, 0x3c22bc46, 0x3c753b95, 0x3ac93c7f, 0x3c223c46, 0xbb95bc75, 0x3c7f3ac9, 0x3c623bf1, 0x3b163c7d, 0x3c043c5c,
    0x3c783b79, 0xbc7d3b16, 0x3bdb3c67, 0x3c80ba49, 0x3c80ba49, 0xbbac3c71, 0x3c2c3c3e, 0x3bdbbc67, 0x3c71bbac, 0x3c2c3c3e,
    0x3c5c3c04, 0xbc18bc4e, 0x3c4ebc18, 0x3c78bb79, 0x3b483c7b, 0x3c0e3c55, 0x3c7bbb48, 0xbc553c0e, 0x3c0e3c55, 0x3c7bbb48,
    0x3c55bc0e, 0x3b483c7b, 0x3c553c0e, 0x3b48bc7b, 0x3c0ebc55, 0x3c7b3b48, 0x3c7b3b48, 0xbc55bc0e, 0x3b48bc7b, 0x3c0ebc55,
    0x3b793c78, 0x3c183c4e, 0x3c4ebc18, 0xbc043c5c, 0x3c2c3c3e, 0x3c71bbac, 0x3bdbbc67, 0x3c2c3c3e, 0x3c713bac, 0xba49bc80,
    0xba49bc80, 0x3c67bbdb, 0x3c7dbb16, 0xbc78bb79, 0xbc04bc5c, 0xbb16bc7d, 0x3b953c75, 0x3c223c46, 0x3bf1bc62, 0xbac93c7f,
    0x3c463c22, 0x3c62bbf1, 0xbac9bc7f, 0x3c753b95, 0x3c7f3ac9, 0xbb95bc75, 0xbc22bc46, 0x3bf1bc62, 0x3c62bbf1, 0xbc7f3ac9,
    0xbc75bb95, 0xbc46bc22, 0x3bac3c71, 0x3c2c3c3e, 0x3a49bc80, 0x3bac3c71, 0x3c5c3c04, 0x3c4ebc18, 0xbc18bc4e, 0x3c78bb79,
    0x3c7dbb16, 0xbc04bc5c, 0xbc78bb79, 0xbb16bc7d, 0x3c2cbc3e, 0xbc673bdb, 0xbc673bdb, 0xbc803a49, 0x00003c80, 0x3bc43c6d,
    0x00003c80, 0xbbc4bc6d, 0x00003c80, 0x3c6d3bc4, 0x00003c80, 0xbc6dbbc4, 0x00003c80, 0x3c6dbbc4, 0x00003c80, 0xbc6d3bc4,
    0x00003c80, 0x3bc4bc6d, 0x00003c80, 0xbbc43c6d, 0x3c3e3c2c, 0x3c713bac, 0x3c713bac, 0xbc803a49, 0x3c4e3c18, 0x3c5cbc04,
    0x3c783b79, 0xbc183c4e, 0x3c5c3c04, 0x3b16bc7d, 0x3c7d3b16, 0x3b793c78, 0x3c673bdb, 0xbc2cbc3e, 0x3c803a49, 0x3c673bdb,
    0x3c7fbac9, 0x3c62bbf1, 0x3c22bc46, 0xbb953c75, 0x3c75bb95, 0x3ac9bc7f, 0x3bf1bc62, 0x3c223c46, 0x3c62bbf1, 0xbc46bc22,
    0x3b95bc75, 0x3c7fbac9, 0x3c46bc22, 0xbc753b95, 0x3ac9bc7f, 0x3bf1bc62, 0x3c18bc4e, 0x3b79bc78, 0xbc04bc5c, 0x3c4e3c18,
    0x3bacbc71, 0xbc3ebc2c, 0xbc3ebc2c, 0x3c67bbdb, 0x3a49bc80, 0xbc713bac, 0xbc67bbdb, 0x3a49bc80, 0xbb79bc78, 0xbb163c7d,
    0xbc7dbb16, 0xbc5cbc04, 0xbb48bc7b, 0xbc0ebc55, 0xbc7b3b48, 0x3c55bc0e, 0xbc0ebc55, 0xbc7b3b48, 0xbc553c0e, 0xbb48bc7b,
    0xbc55bc0e, 0xbb483c7b, 0xbc0e3c55, 0xbc7bbb48, 0xbc7bbb48, 0x3c553c0e, 0xbb483c7b, 0xbc0e3c55, 0xbc5cbc04, 0xbc7dbb16,
    0xbb163c7d, 0xbb79bc78, 0xbc80ba49, 0xbbdb3c67, 0x3bac3c71, 0xbc80ba49, 0xbc673bdb, 0x3c3e3c2c, 0x3c3e3c2c, 0xbbac3c71,
    0xbc183c4e, 0x3c5cbc04, 0x3c783b79, 0x3c4e3c18, 0xbc753b95, 0xbc463c22, 0x3c623bf1, 0xbc7fbac9, 0xbc223c46, 0x3bf13c62,
    0x3c7fbac9, 0xbb953c75, 0xbac93c7f, 0x3c75bb95, 0x3c46bc22, 0x3c623bf1, 0x3bf13c62, 0xbac9bc7f, 0x3b95bc75, 0x3c22bc46,
    0xbbdb3c67, 0xba493c80, 0x3c3ebc2c, 0xbbdb3c67, 0x3b793c78, 0x3c7d3b16, 0x3b16bc7d, 0x3c5c3c04, 0x3c4e3c18, 0x3b79bc78,
    0xbc04bc5c, 0x3c18bc4e, 0x3c80ba49, 0xbc71bbac, 0xbc71bbac, 0xbc3ebc2c, 0x00003c80, 0x3bc43c6d, 0x00003c80, 0xbbc4bc6d,
    0x00003c80, 0x3c6d3bc4, 0x00003c80, 0xbc6dbbc4, 0x00003c80, 0x3c6dbbc4, 0x00003c80, 0xbc6d3bc4, 0x00003c80, 0x3bc4bc6d,
    0x00003c80, 0xbbc43c6d, 0x3c80ba49, 0x3c67bbdb, 0x3c67bbdb, 0xbc2c3c3e, 0x3c7dbb16, 0x3b79bc78, 0x3c5cbc04, 0x3b163c7d,
    0x3c78bb79, 0xbc18bc4e, 0x3c4ebc18, 0x3c5c3c04, 0x3c71bbac, 0xbc80ba49, 0x3c3ebc2c, 0x3c71bbac, 0xbac9bc7f, 0xbbf1bc62,
    0xbc46bc22, 0x3c753b95, 0xbb95bc75, 0xbc7fbac9, 0xbc62bbf1, 0x3c46bc22, 0xbbf1bc62, 0xbc223c46, 0xbc75bb95, 0xbac9bc7f,
    0xbc22bc46, 0x3b953c75, 0xbc7fbac9, 0xbc62bbf1, 0xbc7d3b16, 0xbc5c3c04, 0xbb793c78, 0xbb16bc7d, 0xbc673bdb, 0x3a493c80,
    0x3a493c80, 0xbc71bbac, 0xbc3e3c2c, 0x3c673bdb, 0x3bac3c71, 0xbc3e3c2c, 0xbc043c5c, 0x3c4ebc18, 0x3c183c4e, 0x3b793c78,
    0x3b483c7b, 0x3c0e3c55, 0x3c7bbb48, 0xbc553c0e, 0x3c0e3c55, 0x3c7bbb48, 0x3c55bc0e, 0x3b483c7b, 0x3c553c0e, 0x3b48bc7b,
    0x3c0ebc55, 0x3c7b3b48, 0x3c7b3b48, 0xbc55bc0e, 0x3b48bc7b, 0x3c0ebc55, 0x3c78bb79, 0x3c4ebc18, 0xbc18bc4e, 0x3c5c3c04,
    0x3c3ebc2c, 0xbbacbc71, 0xbc67bbdb, 0x3c3ebc2c, 0x3bacbc71, 0xbc803a49, 0xbc803a49, 0xbbdbbc67, 0xbb16bc7d, 0xbb793c78,
    0xbc5c3c04, 0xbc7d3b16, 0xbb95bc75, 0xbc22bc46, 0xbbf13c62, 0x3ac9bc7f, 0xbc46bc22, 0xbc623bf1, 0x3ac93c7f, 0xbc75bb95,
    0xbc7fbac9, 0x3b953c75, 0x3c223c46, 0xbbf13c62, 0xbc623bf1, 0x3c7fbac9, 0x3c753b95, 0x3c463c22, 0xbc713bac, 0xbc3e3c2c,
    0x3c803a49, 0xbc713bac, 0xbc043c5c, 0x3c183c4e, 0x3c4ebc18, 0x3b793c78, 0x3b163c7d, 0x3c5cbc04, 0x3b79bc78, 0x3c7dbb16,
    0x3c3e3c2c, 0xbbdbbc67, 0xbbdbbc67, 0xba49bc80, 0x00003c80, 0x3bc43c6d, 0x00003c80, 0xbbc4bc6d, 0x00003c80, 0x3c6d3bc4,
    0x00003c80, 0xbc6dbbc4, 0x00003c80, 0x3c6dbbc4, 0x00003c80, 0xbc6d3bc4, 0x00003c80, 0x3bc4bc6d, 0x00003c80, 0xbbc43c6d,
    0x3c2cbc3e, 0x3bacbc71, 0x3bacbc71, 0x3a493c80, 0x3c18bc4e, 0xbc04bc5c, 0x3b79bc78, 0x3c4e3c18, 0x3c04bc5c, 0xbc7dbb16,
    0x3b16bc7d, 0x3c78bb79, 0x3bdbbc67, 0xbc3e3c2c, 0x3a49bc80, 0x3bdbbc67, 0xbc7f3ac9, 0xbc623bf1, 0xbc223c46, 0x3b95bc75,
    0xbc753b95, 0xbac93c7f, 0xbbf13c62, 0xbc22bc46, 0xbc623bf1, 0x3c463c22, 0xbb953c75, 0xbc7f3ac9, 0xbc463c22, 0x3c75bb95,
    0xbac93c7f, 0xbbf13c62, 0x3c4e3c18, 0x3c783b79, 0x3c5cbc04, 0xbc183c4e, 0x3c713bac, 0x3c2cbc3e, 0x3c2cbc3e, 0x3bdb3c67,
    0x3c803a49, 0xbbacbc71, 0x3bdbbc67, 0x3c803a49, 0x3c78bb79, 0xbc7dbb16, 0x3b16bc7d, 0x3c04bc5c, 0xbb48bc7b, 0xbc0ebc55,
    0xbc7b3b48, 0x3c55bc0e, 0xbc0ebc55, 0xbc7b3b48, 0xbc553c0e, 0xbb48bc7b, 0xbc55bc0e, 0xbb483c7b, 0xbc0e3c55, 0xbc7bbb48,
    0xbc7bbb48, 0x3c553c0e, 0xbb483c7b, 0xbc0e3c55, 0xbc043c5c, 0xbb163c7d, 0x3c7d3b16, 0xbc783b79, 0xba493c80, 0x3c673bdb,
    0x3c71bbac, 0xba493c80, 0x3bdb3c67, 0x3c2cbc3e, 0x3c2cbc3e, 0x3c713bac, 0x3c4e3c18, 0xbc04bc5c, 0x3b79bc78, 0x3c18bc4e,
    0x3c75bb95, 0x3c46bc22, 0xbc62bbf1, 0x3c7f3ac9, 0x3c22bc46, 0xbbf1bc62, 0xbc7f3ac9, 0x3b95bc75, 0x3ac9bc7f, 0xbc753b95,
    0xbc463c22, 0xbc62bbf1, 0xbbf1bc62, 0x3ac93c7f, 0xbb953c75, 0xbc223c46, 0xbc67bbdb, 0xbc80ba49, 0x3c2c3c3e, 0xbc67bbdb,
    0xbc783b79, 0xbb163c7d, 0x3c7d3b16, 0xbc043c5c, 0xbc183c4e, 0x3c783b79, 0x3c5cbc04, 0x3c4e3c18, 0x3a493c80, 0x3bacbc71,
    0x3bacbc71, 0x3c2cbc3e, 0x3c353c35, 0x3c6d3bc4, 0x3c353c35, 0xbc6dbbc4, 0x3c35bc35, 0xbbc4bc6d, 0x3c35bc35, 0x3bc43c6d,
    0xbc35bc35, 0xbbc43c6d, 0xbc35bc35, 0x3bc4bc6d, 0xbc353c35, 0x3c6dbbc4, 0xbc353c35, 0xbc6d3bc4, 0x3c3e3c2c, 0x3c713bac,
    0x3c713bac, 0xbc803a49, 0x3c18bc4e, 0xbc04bc5c, 0x3b79bc78, 0x3c4e3c18, 0xbc5cbc04, 0xbb163c7d, 0xbc7dbb16, 0xbb79bc78,
    0xbbdb3c67, 0x3c3ebc2c, 0xba493c80, 0xbbdb3c67, 0x3c463c22, 0x3c753b95, 0x3c7fbac9, 0xbc623bf1, 0x3bf1bc62, 0xbc22bc46,
    0xbb95bc75, 0x3c7f3ac9, 0xbc75bb95, 0x3ac93c7f, 0xbc623bf1, 0xbc46bc22, 0xbac93c7f, 0x3bf1bc62, 0x3c223c46, 0x3b953c75,
    0x3c4e3c18, 0x3c783b79, 0x3c5cbc04, 0xbc183c4e, 0x3bacbc71, 0xbc3ebc2c, 0xbc3ebc2c, 0x3c67bbdb, 0xbc80ba49, 0x3bac3c71,
    0xbbdb3c67, 0xbc80ba49, 0x3b793c78, 0x3b16bc7d, 0x3c7d3b16, 0x3c5c3c04, 0x3c553c0e, 0x3c7b3b48, 0x3c0ebc55, 0xbb483c7b,
    0x3b48bc7b, 0xbc55bc0e, 0xbc7bbb48, 0x3c0ebc55, 0xbc7b3b48, 0x3c0e3c55, 0x3b483c7b, 0xbc553c0e, 0x3c0e3c55, 0xbb48bc7b,
    0x3c55bc0e, 0x3c7bbb48, 0x3c5c3c04, 0x3c7d3b16, 0x3b16bc7d, 0x3b793c78, 0x3a49bc80, 0xbc67bbdb, 0xbc713bac, 0x3a49bc80,
    0xbc673bdb, 0x3c3e3c2c, 0x3c3e3c2c, 0xbbac3c71, 0x3c4e3c18, 0xbc04bc5c, 0x3b79bc78, 0x3c18bc4e, 0x3c623bf1, 0x3c7f3ac9,
    0xbb95bc75, 0x3c223c46, 0xbac9bc7f, 0xbc75bb95, 0xbc223c46, 0xbbf1bc62, 0xbc463c22, 0x3c623bf1, 0x3c7f3ac9, 0x3b953c75,
    0x3c753b95, 0xbc46bc22, 0xbbf1bc62, 0xbac9bc7f, 0x3c673bdb, 0x3c803a49, 0xbc2cbc3e, 0x3c673bdb, 0xbb79bc78, 0xbc7dbb16,
    0xbb163c7d, 0xbc5cbc04, 0xbc183c4e, 0x3c783b79, 0x3c5cbc04, 0x3c4e3c18, 0x3c80ba49, 0xbc71bbac, 0xbc71bbac, 0xbc3ebc2c,
    0x3c353c35, 0x3c6d3bc4, 0x3c353c35, 0xbc6dbbc4, 0x3c35bc35, 0xbbc4bc6d, 0x3c35bc35, 0x3bc43c6d, 0xbc35bc35, 0xbbc43c6d,
    0xbc35bc35, 0x3bc4bc6d, 0xbc353c35, 0x3c6dbbc4, 0xbc353c35, 0xbc6d3bc4, 0x3c80ba49, 0x3c67bbdb, 0x3c67bbdb, 0xbc2c3c3e,
    0xbb16bc7d, 0xbc78bb79, 0xbc04bc5c, 0x3c7dbb16, 0xbc783b79, 0x3c183c4e, 0xbc4e3c18, 0xbc5cbc04, 0x3bac3c71, 0x3a49bc80,
    0x3c2c3c3e, 0x3bac3c71, 0x3c22bc46, 0x3b95bc75, 0xbac9bc7f, 0x3bf13c62, 0xbc62bbf1, 0xbc463c22, 0xbc753b95, 0x3ac9bc7f,
    0xbb953c75, 0x3c7fbac9, 0x3bf13c62, 0xbc223c46, 0x3c7f3ac9, 0xbc62bbf1, 0x3c46bc22, 0x3c75bb95, 0xbb16bc7d, 0xbc04bc5c,
    0xbc78bb79, 0x3c7dbb16, 0xbc673bdb, 0x3a493c80, 0x3a493c80, 0xbc71bbac, 0x3c2c3c3e, 0x3bdbbc67, 0x3c71bbac, 0x3c2c3c3e,
    0x3c04bc5c, 0xbc4e3c18, 0xbc18bc4e, 0xbb79bc78, 0xbc55bc0e, 0xbc7bbb48, 0xbc0e3c55, 0x3b48bc7b, 0xbb483c7b, 0x3c553c0e,
    0x3c7b3b48, 0xbc0e3c55, 0x3c7bbb48, 0xbc0ebc55, 0xbb48bc7b, 0x3c55bc0e, 0xbc0ebc55, 0x3b483c7b, 0xbc553c0e, 0xbc7b3b48,
    0xbc783b79, 0xbc4e3c18, 0x3c183c4e, 0xbc5cbc04, 0x3c2c3c3e, 0x3c71bbac, 0x3bdbbc67, 0x3c2c3c3e, 0x3bacbc71, 0xbc803a49,
    0xbc803a49, 0xbbdbbc67, 0xbc7d3b16, 0x3c783b79, 0x3c043c5c, 0x3b163c7d, 0xbbf13c62, 0xbac93c7f, 0x3c75bb95, 0xbc463c22,
    0x3c7fbac9, 0x3b95bc75, 0xbc46bc22, 0x3c62bbf1, 0xbc22bc46, 0xbbf13c62, 0xbac93c7f, 0xbc753b95, 0xbb953c75, 0x3c22bc46,
    0x3c62bbf1, 0x3c7fbac9, 0x3bac3c71, 0x3c2c3c3e, 0x3a49bc80, 0x3bac3c71, 0x3c04bc5c, 0xbc18bc4e, 0xbc4e3c18, 0xbb79bc78,
    0xbc7d3b16, 0x3c043c5c, 0x3c783b79, 0x3b163c7d, 0x3c3e3c2c, 0xbbdbbc67, 0xbbdbbc67, 0xba49bc80, 0x3c353c35, 0x3c6d3bc4,
    0x3c353c35, 0xbc6dbbc4, 0x3c35bc35, 0xbbc4bc6d, 0x3c35bc35, 0x3bc43c6d, 0xbc35bc35, 0xbbc43c6d, 0xbc35bc35, 0x3bc4bc6d,
    0xbc353c35, 0x3c6dbbc4, 0xbc353c35, 0xbc6d3bc4, 0x3c2cbc3e, 0x3bacbc71, 0x3bacbc71, 0x3a493c80, 0xbc4ebc18, 0xbc5c3c04,
    0xbc78bb79, 0x3c18bc4e, 0xbc043c5c, 0x3c7d3b16, 0xbb163c7d, 0xbc783b79, 0x3c673bdb, 0xbc2cbc3e, 0x3c803a49, 0x3c673bdb,
    0xbc46bc22, 0xbc75bb95, 0xbc7f3ac9, 0x3c62bbf1, 0xbbf13c62, 0x3c223c46, 0x3b953c75, 0xbc7fbac9, 0x3c753b95, 0xbac9bc7f,
    0x3c62bbf1, 0x3c463c22, 0x3ac9bc7f, 0xbbf13c62, 0xbc22bc46, 0xbb95bc75, 0xbc183c4e, 0xbb793c78, 0x3c043c5c, 0xbc4ebc18,
    0x3c713bac, 0x3c2cbc3e, 0x3c2cbc3e, 0x3bdb3c67, 0x3a49bc80, 0xbc713bac, 0xbc67bbdb, 0x3a49bc80, 0xbc783b79, 0x3c7d3b16,
    0xbb163c7d, 0xbc043c5c, 0x3c553c0e, 0x3c7b3b48, 0x3c0ebc55, 0xbb483c7b, 0x3b48bc7b, 0xbc55bc0e, 0xbc7bbb48, 0x3c0ebc55,
    0xbc7b3b48, 0x3c0e3c55, 0x3b483c7b, 0xbc553c0e, 0x3c0e3c55, 0xbb48bc7b, 0x3c55bc0e, 0x3c7bbb48, 0x3c04bc5c, 0x3b16bc7d,
    0xbc7dbb16, 0x3c78bb79, 0xbc80ba49, 0xbbdb3c67, 0x3bac3c71, 0xbc80ba49, 0x3bdb3c67, 0x3c2cbc3e, 0x3c2cbc3e, 0x3c713bac,
    0x3c18bc4e, 0xbc5c3c04, 0xbc78bb79, 0xbc4ebc18, 0xbc62bbf1, 0xbc7fbac9, 0x3b953c75, 0xbc22bc46, 0x3ac93c7f, 0x3c753b95,
    0x3c22bc46, 0x3bf13c62, 0x3c46bc22, 0xbc62bbf1, 0xbc7fbac9, 0xbb95bc75, 0xbc75bb95, 0x3c463c22, 0x3bf13c62, 0x3ac93c7f,
    0xbbdb3c67, 0xba493c80, 0x3c3ebc2c, 0xbbdb3c67, 0x3c78bb79, 0x3b16bc7d, 0xbc7dbb16, 0x3c04bc5c, 0xbc4ebc18, 0xbb793c78,
    0x3c043c5c, 0xbc183c4e, 0x3a493c80, 0x3bacbc71, 0x3bacbc71, 0x3c2cbc3e, 0x3c353c35, 0x3c6d3bc4, 0x3c353c35, 0xbc6dbbc4,
    0x3c35bc35, 0xbbc4bc6d, 0x3c35bc35, 0x3bc43c6d, 0xbc35bc35, 0xbbc43c6d, 0xbc35bc35, 0x3bc4bc6d, 0xbc353c35, 0x3c6dbbc4,
    0xbc353c35, 0xbc6d3bc4, 0xba49bc80, 0xbbdbbc67, 0xbbdbbc67, 0x3c3e3c2c, 0xbc7d3b16, 0xbb793c78, 0xbc5c3c04, 0xbb16bc7d,
    0x3b793c78, 0x3c4ebc18, 0x3c183c4e, 0xbc043c5c, 0x3c71bbac, 0xbc80ba49, 0x3c3ebc2c, 0x3c71bbac, 0xbc223c46, 0xbb953c75,
    0x3ac93c7f, 0xbbf1bc62, 0x3c623bf1, 0x3c46bc22, 0x3c75bb95, 0xbac93c7f, 0x3b95bc75, 0xbc7f3ac9, 0xbbf1bc62, 0x3c22bc46,
    0xbc7fbac9, 0x3c623bf1, 0xbc463c22, 0xbc753b95, 0x3c7dbb16, 0x3c5cbc04, 0x3b79bc78, 0x3b163c7d, 0xbbdbbc67, 0xbc803a49,
    0xbc803a49, 0x3bacbc71, 0xbc3e3c2c, 0x3c673bdb, 0x3bac3c71, 0xbc3e3c2c, 0x3c5c3c04, 0xbc18bc4e, 0x3c4ebc18, 0x3c78bb79,
    0xbc55bc0e, 0xbc7bbb48, 0xbc0e3c55, 0x3b48bc7b, 0xbb483c7b, 0x3c553c0e, 0x3c7b3b48, 0xbc0e3c55, 0x3c7bbb48, 0xbc0ebc55,
    0xbb48bc7b, 0x3c55bc0e, 0xbc0ebc55, 0x3b483c7b, 0xbc553c0e, 0xbc7b3b48, 0x3b793c78, 0x3c183c4e, 0x3c4ebc18, 0xbc043c5c,
    0x3c3ebc2c, 0xbbacbc71, 0xbc67bbdb, 0x3c3ebc2c, 0xbc71bbac, 0x3a493c80, 0x3a493c80, 0xbc673bdb, 0x3b163c7d, 0x3b79bc78,
    0x3c5cbc04, 0x3c7dbb16, 0x3bf1bc62, 0x3ac9bc7f, 0xbc753b95, 0x3c46bc22, 0xbc7f3ac9, 0xbb953c75, 0x3c463c22, 0xbc623bf1,
    0x3c223c46, 0x3bf1bc62, 0x3ac9bc7f, 0x3c75bb95, 0x3b95bc75, 0xbc223c46, 0xbc623bf1, 0xbc7f3ac9, 0xbc713bac, 0xbc3e3c2c,
    0x3c803a49, 0xbc713bac, 0x3c5c3c04, 0x3c4ebc18, 0xbc18bc4e, 0x3c78bb79, 0xbb16bc7d, 0xbc5c3c04, 0xbb793c78, 0xbc7d3b16,
    0xbc2c3c3e, 0x3c67bbdb, 0x3c67bbdb, 0x3c80ba49, 0x3c800000, 0x3c6dbbc4, 0x3c800000, 0xbc6d3bc4, 0xbc800000, 0xbbc43c6d,
    0xbc800000, 0x3bc4bc6d, 0x3c800000, 0xbbc4bc6d, 0x3c800000, 0x3bc43c6d, 0xbc800000, 0x3c6d3bc4, 0xbc800000, 0xbc6dbbc4,
    0x3c80ba49, 0x3c67bbdb, 0x3c67bbdb, 0xbc2c3c3e, 0xbc7d3b16, 0xbb793c78, 0xbc5c3c04, 0xbb16bc7d, 0x3c78bb79, 0xbc18bc4e,
    0x3c4ebc18, 0x3c5c3c04, 0xbc713bac, 0x3c803a49, 0xbc3e3c2c, 0xbc713bac, 0x3c7fbac9, 0x3c62bbf1, 0x3c22bc46, 0xbb953c75,
    0xbc753b95, 0xbac93c7f, 0xbbf13c62, 0xbc22bc46, 0x3c62bbf1, 0xbc46bc22, 0x3b95bc75, 0x3c7fbac9, 0xbc463c22, 0x3c75bb95,
    0xbac93c7f, 0xbbf13c62, 0x3c7dbb16, 0x3c5cbc04, 0x3b79bc78, 0x3b163c7d, 0xbc673bdb, 0x3a493c80, 0x3a493c80, 0xbc71bbac,
    0x3c3ebc2c, 0xbc67bbdb, 0xbbacbc71, 0x3c3ebc2c, 0xbc043c5c, 0x3c4ebc18, 0x3c183c4e, 0x3b793c78, 0x3c7bbb48, 0x3c55bc0e,
    0xbb48bc7b, 0x3c0e3c55, 0xbc553c0e, 0x3b483c7b, 0x3c0e3c55, 0xbc7b3b48, 0x3c0ebc55, 0xbc7bbb48, 0xbc55bc0e, 0x3b48bc7b,
    0xbb483c7b, 0x3c0ebc55, 0x3c7b3b48, 0x3c553c0e, 0x3c78bb79, 0x3c4ebc18, 0xbc18bc4e, 0x3c5c3c04, 0xbc3e3c2c, 0x3bac3c71,
    0x3c673bdb, 0xbc3e3c2c, 0x3bacbc71, 0xbc803a49, 0xbc803a49, 0xbbdbbc67, 0x3b163c7d, 0x3b79bc78, 0x3c5cbc04, 0x3c7dbb16,
    0x3c75bb95, 0x3c46bc22, 0xbc62bbf1, 0x3c7f3ac9, 0xbc223c46, 0x3bf13c62, 0x3c7fbac9, 0xbb953c75, 0x3ac9bc7f, 0xbc753b95,
    0xbc463c22, 0xbc62bbf1, 0x3bf13c62, 0xbac9bc7f, 0x3b95bc75, 0x3c22bc46, 0x3c71bbac, 0x3c3ebc2c, 0xbc80ba49, 0x3c71bbac,
    0xbc043c5c, 0x3c183c4e, 0x3c4ebc18, 0x3b793c78, 0xbb16bc7d, 0xbc5c3c04, 0xbb793c78, 0xbc7d3b16, 0x3c3e3c2c, 0xbbdbbc67,
    0xbbdbbc67, 0xba49bc80, 0x3c800000, 0x3c6dbbc4, 0x3c800000, 0xbc6d3bc4, 0xbc800000, 0xbbc43c6d, 0xbc800000, 0x3bc4bc6d,
    0x3c800000, 0xbbc4bc6d, 0x3c800000, 0x3bc43c6d, 0xbc800000, 0x3c6d3bc4, 0xbc800000, 0xbc6dbbc4, 0x3c2cbc3e, 0x3bacbc71,
    0x3bacbc71, 0x3a493c80, 0xbc183c4e, 0x3c043c5c, 0xbb793c78, 0xbc4ebc18, 0x3c04bc5c, 0xbc7dbb16, 0x3b16bc7d, 0x3c78bb79,
    0xbbdb3c67, 0x3c3ebc2c, 0xba493c80, 0xbbdb3c67, 0xbac9bc7f, 0xbbf1bc62, 0xbc46bc22, 0x3c753b95, 0x3b953c75, 0x3c7f3ac9,
    0x3c623bf1, 0xbc463c22, 0xbbf1bc62, 0xbc223c46, 0xbc75bb95, 0xbac9bc7f, 0x3c223c46, 0xbb95bc75, 0x3c7f3ac9, 0x3c623bf1,
    0xbc4ebc18, 0xbc78bb79, 0xbc5c3c04, 0x3c18bc4e, 0x3c713bac, 0x3c2cbc3e, 0x3c2cbc3e, 0x3bdb3c67, 0xbc80ba49, 0x3bac3c71,
    0xbbdb3c67, 0xbc80ba49, 0x3c78bb79, 0xbc7dbb16, 0x3b16bc7d, 0x3c04bc5c, 0xbc7b3b48, 0xbc553c0e, 0x3b483c7b, 0xbc0ebc55,
    0x3c55bc0e, 0xbb48bc7b, 0xbc0ebc55, 0x3c7bbb48, 0xbc0e3c55, 0x3c7b3b48, 0x3c553c0e, 0xbb483c7b, 0x3b48bc7b, 0xbc0e3c55,
    0xbc7bbb48, 0xbc55bc0e, 0xbc043c5c, 0xbb163c7d, 0x3c7d3b16, 0xbc783b79, 0x3a49bc80, 0xbc67bbdb, 0xbc713bac, 0x3a49bc80,
    0x3bdb3c67, 0x3c2cbc3e, 0x3c2cbc3e, 0x3c713bac, 0xbc4ebc18, 0x3c043c5c, 0xbb793c78, 0xbc183c4e, 0x3b953c75, 0x3c223c46,
    0x3bf1bc62, 0xbac93c7f, 0xbc46bc22, 0xbc623bf1, 0x3ac93c7f, 0xbc75bb95, 0x3c7f3ac9, 0xbb95bc75, 0xbc22bc46, 0x3bf1bc62,
    0xbc623bf1, 0x3c7fbac9, 0x3c753b95, 0x3c463c22, 0x3c673bdb, 0x3c803a49, 0xbc2cbc3e, 0x3c673bdb, 0xbc783b79, 0xbb163c7d,
    0x3c7d3b16, 0xbc043c5c, 0x3c18bc4e, 0xbc78bb79, 0xbc5c3c04, 0xbc4ebc18, 0x3a493c80, 0x3bacbc71, 0x3bacbc71, 0x3c2cbc3e,
    0x3c800000, 0x3c6dbbc4, 0x3c800000, 0xbc6d3bc4, 0xbc800000, 0xbbc43c6d, 0xbc800000, 0x3bc4bc6d, 0x3c800000, 0xbbc4bc6d,
    0x3c800000, 0x3bc43c6d, 0xbc800000, 0x3c6d3bc4, 0xbc800000, 0xbc6dbbc4, 0xba49bc80, 0xbbdbbc67, 0xbbdbbc67, 0x3c3e3c2c,
    0x3b163c7d, 0x3c783b79, 0x3c043c5c, 0xbc7d3b16, 0xbb79bc78, 0xbc4e3c18, 0xbc18bc4e, 0x3c04bc5c, 0x3bac3c71, 0x3a49bc80,
    0x3c2c3c3e, 0x3bac3c71, 0xbc7f3ac9, 0xbc623bf1, 0xbc223c46, 0x3b95bc75, 0x3c75bb95, 0x3ac9bc7f, 0x3bf1bc62, 0x3c223c46,
    0xbc623bf1, 0x3c463c22, 0xbb953c75, 0xbc7f3ac9, 0x3c46bc22, 0xbc753b95, 0x3ac9bc7f, 0x3bf1bc62, 0x3b163c7d, 0x3c043c5c,
    0x3c783b79, 0xbc7d3b16, 0xbbdbbc67, 0xbc803a49, 0xbc803a49, 0x3bacbc71, 0x3c2c3c3e, 0x3bdbbc67, 0x3c71bbac, 0x3c2c3c3e,
    0xbc5cbc04, 0x3c183c4e, 0xbc4e3c18, 0xbc783b79, 0x3c7bbb48, 0x3c55bc0e, 0xbb48bc7b, 0x3c0e3c55, 0xbc553c0e, 0x3b483c7b,
    0x3c0e3c55, 0xbc7b3b48, 0x3c0ebc55, 0xbc7bbb48, 0xbc55bc0e, 0x3b48bc7b, 0xbb483c7b, 0x3c0ebc55, 0x3c7b3b48, 0x3c553c0e,
    0xbb79bc78, 0xbc18bc4e, 0xbc4e3c18, 0x3c04bc5c, 0x3c2c3c3e, 0x3c71bbac, 0x3bdbbc67, 0x3c2c3c3e, 0xbc71bbac, 0x3a493c80,
    0x3a493c80, 0xbc673bdb, 0x3c7dbb16, 0xbc78bb79, 0xbc04bc5c, 0xbb16bc7d, 0xbc753b95, 0xbc463c22, 0x3c623bf1, 0xbc7fbac9,
    0x3c22bc46, 0xbbf1bc62, 0xbc7f3ac9, 0x3b95bc75, 0xbac93c7f, 0x3c75bb95, 0x3c46bc22, 0x3c623bf1, 0xbbf1bc62, 0x3ac93c7f,
    0xbb953c75, 0xbc223c46, 0x3bac3c71, 0x3c2c3c3e, 0x3a49bc80, 0x3bac3c71, 0xbc5cbc04, 0xbc4e3c18, 0x3c183c4e, 0xbc783b79,
    0x3c7dbb16, 0xbc04bc5c, 0xbc78bb79, 0xbb16bc7d, 0xbc2c3c3e, 0x3c67bbdb, 0x3c67bbdb, 0x3c80ba49, 0x3c800000, 0x3c6dbbc4,
    0x3c800000, 0xbc6d3bc4, 0xbc800000, 0xbbc43c6d, 0xbc800000, 0x3bc4bc6d, 0x3c800000, 0xbbc4bc6d, 0x3c800000, 0x3bc43c6d,
    0xbc800000, 0x3c6d3bc4, 0xbc800000, 0xbc6dbbc4, 0xbc3ebc2c, 0xbc71bbac, 0xbc71bbac, 0x3c80ba49, 0x3c4e3c18, 0x3c5cbc04,
    0x3c783b79, 0xbc183c4e, 0xbc5cbc04, 0xbb163c7d, 0xbc7dbb16, 0xbb79bc78, 0x3c673bdb, 0xbc2cbc3e, 0x3c803a49, 0x3c673bdb,
    0x3ac93c7f, 0x3bf13c62, 0x3c463c22, 0xbc75bb95, 0xbb95bc75, 0xbc7fbac9, 0xbc62bbf1, 0x3c46bc22, 0x3bf13c62, 0x3c22bc46,
    0x3c753b95, 0x3ac93c7f, 0xbc22bc46, 0x3b953c75, 0xbc7fbac9, 0xbc62bbf1, 0x3c18bc4e, 0x3b79bc78, 0xbc04bc5c, 0x3c4e3c18,
    0xbbac3c71, 0x3c3e3c2c, 0x3c3e3c2c, 0xbc673bdb, 0x3a49bc80, 0xbc713bac, 0xbc67bbdb, 0x3a49bc80, 0x3b793c78, 0x3b16bc7d,
    0x3c7d3b16, 0x3c5c3c04, 0xbc7b3b48, 0xbc553c0e, 0x3b483c7b, 0xbc0ebc55, 0x3c55bc0e, 0xbb48bc7b, 0xbc0ebc55, 0x3c7bbb48,
    0xbc0e3c55, 0x3c7b3b48, 0x3c553c0e, 0xbb483c7b, 0x3b48bc7b, 0xbc0e3c55, 0xbc7bbb48, 0xbc55bc0e, 0x3c5c3c04, 0x3c7d3b16,
    0x3b16bc7d, 0x3b793c78, 0xbc80ba49, 0xbbdb3c67, 0x3bac3c71, 0xbc80ba49, 0x3c67bbdb, 0xbc3ebc2c, 0xbc3ebc2c, 0x3bacbc71,
    0xbc183c4e, 0x3c5cbc04, 0x3c783b79, 0x3c4e3c18, 0xbb95bc75, 0xbc22bc46, 0xbbf13c62, 0x3ac9bc7f, 0x3c463c22, 0x3c62bbf1,
    0xbac9bc7f, 0x3c753b95, 0xbc7fbac9, 0x3b953c75, 0x3c223c46, 0xbbf13c62, 0x3c62bbf1, 0xbc7f3ac9, 0xbc75bb95, 0xbc46bc22,
    0xbbdb3c67, 0xba493c80, 0x3c3ebc2c, 0xbbdb3c67, 0xbb79bc78, 0xbc7dbb16, 0xbb163c7d, 0xbc5cbc04, 0x3c4e3c18, 0x3b79bc78,
    0xbc04bc5c, 0x3c18bc4e, 0xbc803a49, 0x3c713bac, 0x3c713bac, 0x3c3e3c2c,
};

template <int G = 1024> __device__ __forceinline__ void store_tile_64(const float (&d)[32], uint32_t base, int warp, int lane) {
  const uint32_t rb = base + (warp * 2 + ((lane >> 3) & 1)) * G + (lane & 7) * 128;
#pragma unroll
  for (int j = 0; j < 8; j += 2) {
    const int jj = j + (lane >> 4);
    stsm4(rb + ((jj ^ (lane & 7)) << 4), pack2(d[4 * j], d[4 * j + 1]), pack2(d[4 * j + 2], d[4 * j + 3]),
          pack2(d[4 * j + 4], d[4 * j + 5]), pack2(d[4 * j + 6], d[4 * j + 7]));
  }
}

#define A_XM0 0xEB5C
#define A_XM1 0xDCBC
#define A_REL 0x22910
#define G_WPOLK 12
#define A_LDW 0x242
#define A_W2PF 2
#define A_DEPS 4
#define A_FREE 0x3F000
#define A_RELS 0x8A80
#define A_ACQ 0x1511
#define A_DEP 3
#define A_PACE0 1000
#define A_PACE1 A_PACE0
#define A_PACE_N 8
#define G_TMASK 0x0DB0
constexpr int A_IN = 112 * 128, A_OUT = 16384, A_NIN = 5, A_NOUT = 6;
constexpr int A_NREL = __builtin_popcount(A_REL);
constexpr int G_XP = NB1 * 64;
constexpr int G_STAGE = 16384 + 2 * G_XP, G_NST = 5;
constexpr int G_TIN = G_NST * G_STAGE, G_TOUT = G_TIN + 8192, G_SMEM = G_TOUT + 32768;
#define G_SLOTS 0x1032410324103210ull
__host__ __device__ constexpr int g_slot(int k) { return (G_SLOTS >> (4 * k)) & 7; }
constexpr uint32_t g_parities() {
  uint32_t m = 0;
  for (int k = 0; k < 16; k++)
    for (int j = 0; j < k; j++)
      if (g_slot(j) == g_slot(k)) m ^= 1u << k;
  return m;
}
constexpr uint32_t G_PAR = g_parities();
constexpr int G_KS = 12;
__device__ __align__(128) int g_cnt[4 * 32];

__device__ __forceinline__ int x_decode(int r, int cta) {
  const int v = r * 64 + ((cta >> 2) << 1) + (cta & 1);
  int j = v / 80;
  j -= v < 80 * j + ((0x4840 >> (4 * j)) & 15);
  if (cta < 128) return ((7 - j) << 7) | (v - 80 * j - ((0x4840 >> (4 * j)) & 15));
  return r < 8 ? ((5 - (r >> 2)) << 7) | (76 + 4 * (cta & 1) + (r & 3)) : ((7 - (r >> 1)) << 7) | (80 + 2 * (cta & 1) + (r & 1));
}
__device__ __forceinline__ uint32_t a_out(int n) {
  const int p = n % A_NOUT;
  return (p < 4 ? (3 + (p >> 1)) * G_STAGE : G_TOUT) + (p & 1) * A_OUT;
}
__device__ __forceinline__ uint32_t x1_addr(int L, int b, uint32_t flips) {
  const int p = L >> 4, sel = (b ^ __popc(L & 15) ^ (flips >> p)) & 1;
  return (p << 21) | (sel << 12) | ((L & 1) << 13) | ((L & 6) << 15) | ((L & 8) << 16);
}
__device__ __forceinline__ uint32_t spread16(int i) { return ((i & 3) << 14) | ((i & 4) << 16) | ((i & 8) << 17); }
constexpr int NPG = 19 + W_SHIFT, NVOTE = 6;
__device__ __forceinline__ uint32_t w_addr(int P, int f, int c, int dhalf, uint32_t flips) {
  return x1_addr(16 * P + (c >> 5) + 2 * (f >> 3), dhalf, flips >> 12) + spread16(2 * f) + (c & 31) * 128;
}
__device__ __forceinline__ void w_store(const CUtensorMap* m, uint32_t src, uint32_t a) {
#pragma unroll
  for (int j = 0; j < 8; j++)
    tma_st5<0>(m, src + j * 2048, ((a & 16383) >> 1) ^ ((__popc(j) & 1) << 11), (j & 3) << 1, (j >> 2) << 1, a >> 20, 0);
}
__device__ __forceinline__ uint32_t read_votes(const int* cnt, int lane, int v) {
#pragma unroll 1
  for (int it = 0; it < (1 << 20) && (__ballot_sync(0xffffffffu, v < NVOTE * 256) & ((2 << NPG) - 2)); it++)
    asm volatile("ld.relaxed.gpu.global.s32 %0, [%1];" : "=r"(v) : "l"(cnt + 32 + lane) : "memory");
  return __ballot_sync(0xffffffffu, (v & 255) > NVOTE / 2);
}
__device__ __forceinline__ int take_ticket(int* p) {
  int v;
  asm volatile("atom.relaxed.gpu.global.inc.u32 %0, [%1], 0x7fffffff;" : "=r"(v) : "l"(p) : "memory");
  return v;
}
__device__ __forceinline__ void send_role(uint32_t dst, uint32_t bar, int v) {
  for (int c = 0; c < 2; c++)
    asm volatile("{\n.reg .b32 a, b;\nmapa.shared::cluster.u32 a, %0, %2;\nmapa.shared::cluster.u32 b, %1, %2;\n"
                 "st.async.shared::cluster.mbarrier::complete_tx::bytes.u32 [a], %3, [b];\n}" ::"r"(dst), "r"(bar), "r"(c), "r"(v) : "memory");
}
struct GMaps {
  CUtensorMap in[5];
  CUtensorMap ws, xs, w, y;
  CUtensorMap y1[2], x2s, x2, w2, y2;
};

#define H_EPI 3
#define H_KS 11
#define C_PACE 0
#define C_ORD 1
#define H_HOLD 5
#define C_POL 1
constexpr int H_XP = 168 * 64, H_STAGE = 8192 + 2 * H_XP, H_NST = 7;
constexpr int C_OUT = 7 * 8192, C_GI = 13 * 8192, C_F = C_GI + 6144, C_PIECE = C_F + 8192;
static_assert(C_GI >= 3 * H_STAGE && C_PIECE + C_OUT == 6 * H_STAGE, "slots 0..2 | 3..5 | 6 fall free together");
constexpr int G_IM1 = C_GI - NB1 * 128;

template <int WG>
__device__ __forceinline__ void h_loop(float (&acc)[84], uint32_t sb, uint32_t full0, uint32_t empty0, int lane) {
#pragma unroll 1
  for (int k = 0; k < 16; k++) {
    const int st = k % H_NST;
    if (WG == 1 && k == H_KS) bar_sync(4, 256);
    mbar_wait(full0 + 8 * st, (k / H_NST) & 1);
    const uint32_t base = sb + st * H_STAGE;
    wg_fence();
#pragma unroll
    for (int s = 0; s < 2; s++) {
      const uint64_t dP = mk_desc(base, s * 2048, 0, 1024, 1), dQ = mk_desc(base, 4096 + s * 2048, 0, 1024, 1);
      const uint64_t dA = mk_desc(base, 8192 + s * 32, 0, 512, 2), dB = mk_desc(base, 8192 + H_XP + s * 32, 0, 512, 2);
      wgmma_ss_168<1, 1, 1, 0>(acc, dP, WG == 0 ? dA : dB, k | s);
      wgmma_ss_168<WG == 0 ? 1 : -1, 1, 1, 0>(acc, dQ, WG == 0 ? dB : dA, 1);
    }
    wg_commit();
    if (WG == 0 && k == 15) bar_arrive(4, 256);
    if (k <= 10) {
      wg_wait<1>();
      if (k > 0 && k - 1 + H_NST < 16 && lane < 2) mbar_arrive_cta(empty0 + 8 * ((k - 1) % H_NST), lane);
    }
  }
  wg_wait<0>();
  reg_fence(acc);
}

template <int N> __device__ __forceinline__ void gelu_pack(uint32_t* hp, float (&h)[N], bool zero_first, bool zero_all) {
  reg_fence(h);
#pragma unroll
  for (int c = 0; c < N / 2; c++) {
    const uint32_t v = pack2(gelu(h[2 * c]), gelu(h[2 * c + 1]));
    hp[c] = zero_all || (zero_first && c < 2) ? 0u : v;
  }
#pragma unroll
  for (int c = 0; c < N / 2; c++) asm volatile("" : "+r"(hp[c])::"memory");
}
__device__ __forceinline__ void poll_ge(const int* p, int target) {
  int v = 0;
#pragma unroll 1
  for (int it = 0; it < (1 << 20) && v < target; it++)
    asm volatile("ld.relaxed.gpu.global.s32 %0, [%1];" : "=r"(v) : "l"(p) : "memory");
  asm volatile("fence.acquire.gpu;\nfence.proxy.async.global;" ::: "memory");
}

__global__ void __cluster_dims__(2, 1, 1) __launch_bounds__(384, 1)
kG(int* __restrict__ cnt, char* __restrict__ x1, char* __restrict__ wt, const __nv_bfloat16* __restrict__ g,
   const __nv_bfloat16* __restrict__ wgt, float* __restrict__ ge, const uint32_t* __restrict__ img, const __nv_bfloat16* __restrict__ wf,
   const __nv_bfloat16* __restrict__ wo, const uint32_t* __restrict__ gat, const __grid_constant__ GMaps m) {
  extern __shared__ __align__(1024) uint8_t smem_raw[];
  __shared__ __align__(8) uint64_t bars[20 + A_NIN + 2 * A_NOUT + 2 * G_NST + 16 + 2 * A_NREL + 2 * H_NST + 41];
  __shared__ uint16_t tab[128];
  __shared__ uint32_t lat[8], s_role, s_flips;
  const uint32_t sb = pin(s2u(smem_raw));
  const int tid = threadIdx.x, wg = __shfl_sync(0xffffffffu, tid >> 7, 0), t = tid & 127;
  const int warp = __shfl_sync(0xffffffffu, t >> 5, 0), lane = t & 31;
  const int blk = blockIdx.x, hf = blk & 1, page = 1 + blk % NPG;
  const bool spare = blk >= 128, voter = blk >= 128 - NPG * NVOTE && !spare;
  const int nu = spare ? 16 : 18;
  const uint32_t xm = spare ? 0xFFFF : hf ? A_XM1 : A_XM0;
  const uint32_t wf0 = pin(s2u(&bars[0])), xf0 = wf0 + 32, xe0 = xf0 + 128, aof0 = xe0 + 8 * A_NIN, aoe0 = aof0 + 8 * A_NOUT;
  const uint32_t full0 = aoe0 + 8 * A_NOUT, empty0 = full0 + 8 * G_NST;
  const uint32_t sf0 = empty0 + 8 * G_NST, se0 = sf0 + 16, inf0 = se0 + 16, roleb = inf0 + 16, flipb = roleb + 8;
  const uint32_t rel0 = flipb + 8, got0 = rel0 + 8 * A_NREL, acq0 = got0 + 64;
  const uint32_t hf0 = acq0 + 8 * A_NREL, he0 = hf0 + 8 * H_NST, yo0 = he0 + 8 * H_NST, of0 = yo0 + 96, yf0 = of0 + 96;
  const uint32_t gdone = yf0 + 64, imgb = gdone + 8, rly0 = imgb + 8, depb = rly0 + 32, pubb = depb + 8;
  auto role = [&]() {
    mbar_wait(roleb, 0);
    return 2 * (int)*(volatile uint32_t*)&s_role + hf;
  };
  auto flips = [&]() {
    mbar_wait(flipb, 0);
    return *(volatile uint32_t*)&s_flips;
  };
  auto w_unit = [&](int cta) { return (cta & ~3) | (hf << 1) | ((cta >> 1) & 1); };
  auto w_code = [](int w2, int s, int i) { return (-(s < 4) << 16) | ((2 * w2 + (s >> 2)) << 11) | ((s & 3) << 9) | ((i >> 1) << 3) | ((i & 1) << 1); };
  auto in_load = [&](int c, uint32_t dst, uint32_t bar) {
    tma_ld5<1>(dst, &m.in[(c >> 11) & 7], bar, 0, c >> 16, c & 7, (c >> 3) & 63, (c >> 9) & 3);
  };
  if (wg < 2) {
    if (lane == 0) {
      const uint32_t h = blk & 0x59, par = h ^ (h >> 3) ^ (h >> 4) ^ (h >> 6);
      char* p = x1 + (blk << 13) + (((warp ^ par) & 1) << 12) + 3584 + (warp >> 1) * 128;
      if (wg) {
        if (!voter) p += 256;
        else if (page < 12) p += page << 21;
        else p = wt + w_addr(page - 12, warp >> 1, blk >> 1, warp & 1, 0);
      }
      uint32_t c0, c1;
      asm volatile("{\n.reg .u32 v;\n.reg .pred q;\n"
                   "st.global.v4.u32 [%2], {0, 0, 0, 0};\nst.global.v4.u32 [%2 + 16], {0, 0, 0, 0};\n"
                   "mov.u32 %0, %%clock;\nmov.u32 %1, %0;\natom.relaxed.gpu.global.exch.b32 v, [%2], 1;\n"
                   "setp.eq.u32 q, v, 0;\n@q mov.u32 %1, %%clock;\n}\n" : "=r"(c0), "=r"(c1) : "l"(p) : "memory");
      lat[wg * 4 + warp] = c1 - c0;
    }
    __syncwarp();
    if (wg == 0 && hf == 0) bar_arrive(10, 160);
    bar_arrive(9, 288);
  }
  if (wg == 2) {
    if (t == 32) {
      mbar_init(wf0 + 24, 1);
      mbar_expect(wf0 + 24, 8192);
      fence_async();
      if (!spare) tma_ld5<1>(sb + 2 * G_STAGE + 3 * 8192, &m.in[1], wf0 + 24, 0, 0, 2 * hf, blk >> 1, 2);
    }
    __syncwarp();
    int votes = 0;
    if (warp == 3 && !voter) asm volatile("ld.relaxed.gpu.global.s32 %0, [%1];" : "=r"(votes) : "l"(cnt + 32 + lane) : "memory");
    asm volatile("setmaxnreg.dec.sync.aligned.u32 40;");
    if (lane == 0 && warp > 0) {
      if (warp == 1) {
        for (int i = 0; i < 3; i++) {
          mbar_init(wf0 + 8 * i, 1);
          mbar_expect(wf0 + 8 * i, 8192);
        }
      } else if (warp == 2) {
        prefetch_map(&m.in[4]);
        for (int i = 0; i < A_NIN + A_NOUT; i++) mbar_init(xe0 + 8 * i, 4);
        for (int i = 0; i < A_NOUT; i++) mbar_init(aoe0 + 8 * i, 1);
      } else {
        for (int i = 0; i < 2; i++) mbar_init(sf0 + 8 * i, 8);
        for (int i = 0; i < 6 + A_NREL; i++) mbar_init(se0 + 8 * i, 1);
        for (int i = 0; i < 3; i++) mbar_expect(inf0 + 8 * i, i < 2 ? 4096 : 4);
      }
      fence_bar_init();
    }
    __syncwarp();
    asm volatile("barrier.cluster.arrive.relaxed.aligned;" ::: "memory");
    int role_w = warp;
    if (role_w == 0) {
      int cta = blk, side = 0;
      if (hf == 0) {
        bar_sync(10, 160);
        side = min(lat[0], lat[2]) > min(lat[1], lat[3]);
        if (lane == 0) cta = take_ticket(cnt + (spare ? 62 : 54) + side);
      }
      const uint32_t wm = spare ? 0 : A_LDW | 0x6000;
      const int nw = __popc(wm & ((1 << lane) - 1)), r = lane - nw, np = r + A_NIN - (spare ? A_DEPS : A_DEP);
      const bool isw = (wm >> lane) & 1;
      uint32_t dst = sb + (!isw ? (r % A_NIN) * A_IN : nw < 3 ? 2 * G_STAGE + (2 - nw) * 8192 : G_TIN + (nw - 3) * 4096);
      uint32_t bf = !isw ? xf0 + 8 * r : nw < 3 ? wf0 + 8 * (2 - nw) : inf0 + 8 * (nw - 3);
      uint32_t be = isw ? roleb : xe0 + 8 * (np % A_NIN) + ((np / A_NIN - 1) & 1);
      asm volatile("barrier.cluster.wait.aligned;" : "+r"(dst), "+r"(bf), "+r"(be)::"memory");
      if (hf == 0) {
        cta = 2 * __shfl_sync(0xffffffffu, cta, 0) + side;
        if (cta >= 64) cta = 127 - cta;
        if (spare) cta = 64 + (cta >= 2 ? 3 - cta : cta);
        if (lane == 0) send_role(s2u(&s_role), roleb, cta);
        cta *= 2;
      } else {
        cta = role();
      }
      const int b = (cta >> 1) & 1;
      if (lane == 0 && !spare) tma_ld5<1>(sb, &m.in[4], xf0, 0, 96 * (((cta >> 2) << 1) + hf) - 24, 7, 0, b);
      __syncwarp();
      const int xc = x_decode(r, cta);
      const int code = isw ? w_code(nw >= 3, nw < 3 ? 4 - 2 * nw : 10 - nw, w_unit(cta)) : ((96 * (xc & 127) - 24) << 16) | (4 << 11) | (b << 9) | (xc >> 7);
#pragma unroll 1
      for (int p = !spare; p < (spare ? 16 : 15); p++) {
        const int c = __shfl_sync(0xffffffffu, code, p);
        const uint32_t d = __shfl_sync(0xffffffffu, dst, p), f = __shfl_sync(0xffffffffu, bf, p), e = __shfl_sync(0xffffffffu, be, p);
        mbar_wait(e & ~1u, e & 1);
        if (lane == 0) in_load(c, d, f);
        __syncwarp();
      }
      if (!spare) {
        const int bin = cta >> 2, f = 2 * bin + hf;
        if (lane == 0) {
          for (int s = 5; s >= A_W2PF; s--) {
            const int c = w_code(1, s, w_unit(cta));
            asm volatile("cp.async.bulk.prefetch.tensor.5d.L2.global [%0, {0, %1, %2, %3, %4}];" ::"l"(&m.in[(c >> 11) & 7]), "r"(c >> 16), "r"(c & 7), "r"((c >> 3) & 63), "r"((c >> 9) & 3) : "memory");
          }
          prefetch_map(&m.w);
          prefetch_map(&m.y);
          prefetch_map(&m.in[2]);
        }
        const uint32_t xa = x1_addr((21 - lane + 2 * (lane % 3)) * 8 + (f >> 4), b, flips()) + spread16(f);
        const uint32_t wa = w_addr(7 - (lane >> 1), 2 * bin, (lane & 1) * 32, hf, s_flips & ~0xC0000u);
#pragma unroll 1
        for (int k = 0; k < 16; k++) {
          const int st = g_slot(k);
          uint32_t a[3];
#pragma unroll
          for (int th = 0; th < 3; th++) a[th] = __shfl_sync(0xffffffffu, xa, 3 * (k >> 1) + th) ^ ((k & 1) * 0x21000);
          const uint32_t w = __shfl_sync(0xffffffffu, wa, k);
          if ((A_ACQ >> k) & 1) {
            mbar_wait(acq0 + 8 * __popc(A_ACQ & ((1 << k) - 1)), 0);
            asm volatile("fence.proxy.async.global;" ::: "memory");
          }
          mbar_wait(empty0 + 8 * st, (G_PAR >> k) & 1);
          if (lane == 0) {
            const uint32_t base = sb + st * G_STAGE, bar = full0 + 8 * st;
            mbar_expect(bar, G_STAGE);
#pragma unroll
            for (int th = 0; th < 3; th++)
              asm volatile("cp.async.bulk.shared::cluster.global.mbarrier::complete_tx::bytes.multicast::cluster.L2::cache_hint [%0], [%1], %2, [%3], %4, %5;"
                           ::"r"(base + 16384 + hf * G_XP + th * 3584), "l"(x1 + a[th]), "n"(3584), "r"(bar), "h"((uint16_t)3), "l"(policy<1>()) : "memory");
            if (k >= G_WPOLK) tma_ld3<1>(base, &m.w, bar, 0, (w >> 7) & 127, w >> 14);
            else tma_ld3<0>(base, &m.w, bar, 0, (w >> 7) & 127, w >> 14);
          }
          __syncwarp();
        }
        if (lane == 0) {
          if (blk == 0) asm volatile("cp.async.bulk.prefetch.L2.global [%0], 14336;" ::"l"(img) : "memory");
          prefetch_map(&m.y1[0]);
          prefetch_map(&m.y1[1]);
          prefetch_map(&m.x2s);
          prefetch_map(&m.x2);
          prefetch_map(&m.w2);
          prefetch_map(&m.y2);
        }
        const int pl = lane >= 7, yb = min(6 * (bin - 4 * pl) + lane - 7 * pl, NB1 - 1);
        const uint32_t ya = x1_addr(96 + 8 * (yb >> 4) + 4 * hf + 2 * pl, b, s_flips) + spread16(yb);
        mbar_wait(gdone, 0);
        if (lane == 0)
          asm volatile("cp.async.bulk.shared::cluster.global.mbarrier::complete_tx::bytes [%0], [%1], 14336, [%2];"
                       ::"r"(sb + C_GI), "l"(img), "r"(imgb) : "memory");
#pragma unroll 1
        for (int p = bin >= 28; p < 2; p++) {
          uint32_t a[7];
#pragma unroll
          for (int i = 0; i < 7; i++) a[i] = __shfl_sync(0xffffffffu, ya, 7 * p + i);
          poll_ge(cnt + 64 + 2 * b + p, 64);
          if (lane == 0 && (p == 0 || bin >= 4)) {
#pragma unroll
            for (int i = 0; i < 7; i++) tma_ld3<C_POL>(sb + p * C_PIECE + i * 8192, &m.y1[(a[i] >> 12) & 1], yf0 + 32 * p + 8 * ((i + 1) >> 1), 0, a[i] >> 7, 0);
          }
          __syncwarp();
        }
        if (lane == 0) mbar_arrive(depb);
        mbar_wait(pubb, 0);
        int st = 0;
#pragma unroll 1
        for (int k = 0; k < 16; k++) {
          if ((k & 7) == 0) {
            poll_ge(cnt + 96 + (k >> 3), 112);
          }
          if (k == H_HOLD) mbar_wait(pubb + 8, 0);
          mbar_wait(he0 + 8 * st, (k >= H_NST) ^ (k >= 2 * H_NST));
          if (lane == 0) tma_ld3mc<0>(sb + st * H_STAGE + 8192 + hf * H_XP, &m.x2, hf0 + 8 * st, (k & 1) * 32, 0, ((k & 6) + (k >> 3)) * 64 + f);
          __syncwarp();
          if (++st == H_NST) st = 0;
        }
      }
    } else if (pin(warp) == 1) {
      if (lane == 0) {
        prefetch_map(&m.ws);
        prefetch_map(&m.xs);
        prefetch_map(&m.in[0]);
        prefetch_map(&m.in[3]);
        for (int i = 0; i < 24; i++) mbar_init(yo0 + 8 * i, 4);
        for (int i = 0; i < 8; i++) {
          mbar_init(yf0 + 8 * i, 1);
          mbar_expect(yf0 + 8 * i, i & 3 ? 16384 : 8192);
        }
        mbar_init(gdone, 8);
        for (int i = 0; i < 8; i++) mbar_init(imgb + 8 * i, 1);
        mbar_expect(imgb, 14336);
        fence_async();
      }
      __syncwarp();
      asm volatile("barrier.cluster.wait.aligned;" ::: "memory");
      if (lane == 0) {
#pragma unroll 1
        for (int r = spare; r < A_NREL; r++) {
          mbar_wait(rel0 + 8 * r, 0);
          asm volatile("fence.acq_rel.gpu;\nred.relaxed.gpu.global.inc.u32 [%0], 0x7fffffff;" ::"l"(cnt + 8 + r) : "memory");
        }
        if (!spare) {
          const int cta = role(), bin = cta >> 2;
#pragma unroll 1
          for (int r = 0; r < 4; r++) {
            if (r < 2 || (r == 2 ? bin < 28 : bin >= 4)) {
              mbar_wait(rly0 + 8 * r, 0);
              asm volatile("fence.acq_rel.gpu;\nred.relaxed.gpu.global.inc.u32 [%0], 0x7fffffff;" ::"l"(cnt + (r < 2 ? 64 + (cta & 2) : 94) + r) : "memory");
            }
            if (r >= 2) mbar_arrive(pubb + 8 * (r - 2));
          }
        }
      }
    } else if (warp == 2) {
      asm volatile("barrier.cluster.wait.aligned;" ::: "memory");
      const uint32_t relm = spare ? A_RELS : A_REL;
      const int xr = __popc(xm & ((1 << lane) - 1));
      const uint32_t srcs = sb + a_out(lane), bars = aof0 + 8 * (lane % A_NOUT);
      const uint32_t done = lane < 16 ? bars + 8 * A_NOUT : se0 + 8 * (lane & 1), relb = rel0 + 8 * (spare + __popc(relm & ((1 << lane) - 1)));
      const int cta = role(), xc = x_decode(xr, cta), q = xc & 127, th = q / 28, wi = lane < 2 ? blk : w_unit(cta);
      int code = (xm >> lane) & 1 ? 0x80000000u + x1_addr(((xc >> 7) * 3 + th) * 8, (cta >> 1) & 1, 0) + (q - 28 * th) * 128
                                  : w_addr(7 - lane + xr, 0, wi >> 1, wi & 1, 0);
      uint32_t fl = 0;
      auto tables = [&]() {
        fl = flips();
        code ^= ((fl >> (((code >> 21) & 15) + (code < 0 ? 0 : 12))) & 1) << 12;
      };
      if (spare) tables();
      uint32_t tnext = clock(), src = __shfl_sync(0xffffffffu, srcs, 0), bar = aof0;
      int c = __shfl_sync(0xffffffffu, code, 0);
      mbar_wait(bar, 0);
#pragma unroll 1
      for (int n = 0; n < nu; n++) {
        while ((int)(clock() - tnext) < 0);
        tnext = clock() + (spare ? 0 : n < A_PACE_N ? A_PACE0 : A_PACE1);
        if (lane == n) {
          if (c >= 0) {
            w_store(&m.ws, src, c);
          } else {
#pragma unroll
            for (int j = 0; j < 8; j++)
              tma_st4<0>(&m.xs, src + j * 2048, ((c & 16383) >> 1) ^ ((__popc(j) & 1) << 11) ^ ((j & 1) << 12), (j >> 1) << 2, (c >> 18) & 3, (c >> 20) & 31);
          }
          bulk_commit();
        }
        __syncwarp();
        if (n == 1 && !spare) tables();
        c = __shfl_sync(0xffffffffu, code, n + 1);
        src = __shfl_sync(0xffffffffu, srcs, n + 1);
        bar = __shfl_sync(0xffffffffu, bars, n + 1);
        if (n + 1 < nu) mbar_wait(bar, (n + 1 >= A_NOUT) ^ (n + 1 >= 2 * A_NOUT));
        bulk_wait<0>();
        if (lane == n) {
          mbar_arrive(done);
          if ((relm >> lane) & 1) mbar_arrive(relb);
        }
        __syncwarp();
        if (!spare && (n == 13 || n == 15) && lane < 16) mbar_arrive_cta(empty0 + 8 * ((n - 7) >> 1), lane & 1);
      }
      if (!spare) {
        const int i = w_unit(cta), wc = w_code(1, 5 - lane, i);
        const uint32_t wa = w_addr(7 + W_SHIFT - lane, 0, i >> 1, i & 1, fl);
#pragma unroll 1
        for (int it = 0; it < 8; it++) {
          const uint32_t a = __shfl_sync(0xffffffffu, wa, it), j = it & 1;
          const int c2 = __shfl_sync(0xffffffffu, wc, it);
          mbar_wait(sf0 + 8 * j, (it >> 1) & 1);
          if (lane == 0 && it < 6) {
            mbar_expect(inf0 + 8 * j, 4096);
            in_load(c2, sb + G_TIN + j * 4096, inf0 + 8 * j);
          }
          if (it >= W_SHIFT) mbar_wait(got0 + 8 * (it - W_SHIFT), 0);
          if (lane == 0) {
            w_store(&m.ws, sb + G_TOUT + j * A_OUT, a);
            bulk_commit();
            bulk_wait<0>();
            mbar_arrive(se0 + 8 * j);
          }
          __syncwarp();
        }
        const int bin = cta >> 2;
        mbar_wait(got0 + 56, 0);
        mbar_wait(rly0 + 8, 0);
#pragma unroll 1
        for (int pc = 0; pc < 2; pc++) {
          if (pc ? bin >= 4 : bin < 28) {
#pragma unroll 1
            for (int n = 0; n < 6; n++) {
              mbar_wait(of0 + 8 * (6 * pc + n), 0);
              if (C_PACE) {
                while ((int)(clock() - tnext) < 0);
                tnext = clock() + C_PACE;
              }
              if (lane == 0) tma_st3<0>(&m.x2s, sb + pc * C_PIECE + C_OUT + n * 8192, 0, (4 * (n & 1) + 2 * hf + pc) * 64, (cta & 2) * (NB2 / 2) + 3 * (bin - 4 * pc) + (n >> 1));
              __syncwarp();
            }
            bulk_commit();
            bulk_wait<0>();
            if (lane == 0) mbar_arrive(rly0 + 16 + 8 * pc);
            __syncwarp();
          }
          if (lane < 16)
            for (int i = 6 * pc; i < 3 + 4 * pc; i++) mbar_arrive_cta(he0 + 8 * i, lane & 1);
        }
      }
    } else {
      bar_sync(9, 288);
      const int near = min(lat[0], lat[2]) > min(lat[1], lat[3]);
      if (lane == 0 && voter)
        asm volatile("red.relaxed.gpu.global.add.s32 [%0], %1;" ::"l"(cnt + 32 + page), "r"(256 + (near ^ (min(lat[4], lat[6]) > min(lat[5], lat[7])))) : "memory");
      __syncwarp();
      asm volatile("barrier.cluster.wait.aligned;" ::: "memory");
      const uint32_t fl = read_votes(cnt, lane, votes);
      if (lane == 0) {
        s_flips = fl;
        mbar_arrive(flipb);
      }
      __syncwarp();
      if (!spare) {
        bool open = lane < 8 + A_NREL;
        int k = 0;
        mbar_wait(rel0, 0);
#pragma unroll 1
        for (int p = 0; p < (1 << 16) && __any_sync(0xffffffffu, open); p++) {
          int v;
          asm volatile("ld.relaxed.gpu.global.s32 %0, [%1];" : "=r"(v) : "l"(cnt + (lane & 15)) : "memory");
          while (k < 16 && mbar_test(full0 + 8 * g_slot(k), (G_PAR >> k) & 1)) {
            if (lane == 0) mbar_arrive(empty0 + 8 * g_slot(k));
            if ((k & 1) && lane == 0) asm volatile("red.relaxed.gpu.global.inc.u32 [%0], 0x7fffffff;" ::"l"(cnt + (k >> 1)) : "memory");
            k++;
          }
          if (open && v >= (lane <= 8 ? 128 : 132)) {
            asm volatile("fence.acquire.gpu;" ::: "memory");
            mbar_arrive(got0 + 8 * lane);
            open = false;
          }
        }
        const int cta = role(), b = (cta >> 1) & 1, bin = cta >> 2;
        const uint32_t ya = x1_addr(96 + 8 * lane + 4 * hf + (bin >> 4), b, fl) + (bin & 15) * 256;
#pragma unroll 1
        for (int q = 0; q < 4; q++) {
          const uint32_t stg = sb + (q < 2 ? 4 * G_STAGE + q * NB1 * 128 : q == 2 ? G_TOUT : G_IM1), dif = (q >> 1) * 0x11000 + (q & 1) * 128;
#pragma unroll
          for (int c = 0; c < 3; c++) {
            uint32_t a[4];
#pragma unroll
            for (int j = 0; j < 4; j++) a[j] = __shfl_sync(0xffffffffu, ya, 4 * c + j) ^ dif;
            mbar_wait(yo0 + 8 * (3 * q + c), 0);
            if (lane == 0) {
#pragma unroll
              for (int j = 0; j < 4 - (c >> 1); j++)
                tma_st4<0>(c == 2 && j == 2 ? &m.y : &m.xs, stg + (4 * c + j) * 2048, (a[j] & 16383) >> 1, (a[j] >> 14) & 15, (a[j] >> 18) & 3, a[j] >> 20);
            }
            __syncwarp();
          }
          if (q & 1) {
            bulk_commit();
            bulk_wait<0>();
            if (lane == 0) mbar_arrive(rly0 + 8 * (q >> 1));
          }
        }
        const uint32_t wa = w_addr((lane & 6) + ((lane >> 3) & 1) + W_SHIFT, 2 * bin, (lane & 1) * 32, b, fl) + (hf << 14);
        mbar_wait(depb, 0);
        mbar_wait(pubb, 0);
        asm volatile("fence.proxy.async.global;" ::: "memory");
        int st = 0;
#pragma unroll 1
        for (int k2 = 0; k2 < 16; k2++) {
          const uint32_t w = __shfl_sync(0xffffffffu, wa, k2);
          if (k2 == H_HOLD) mbar_wait(pubb + 8, 0);
          mbar_wait(he0 + 8 * st, (k2 >= H_NST) ^ (k2 >= 2 * H_NST));
          if (lane == 0) {
            mbar_expect(hf0 + 8 * st, H_STAGE);
            tma_ld3<1>(sb + st * H_STAGE, &m.w2, hf0 + 8 * st, 0, (w >> 7) & 255, w >> 15);
            if (k2 == H_NST) {
              if (cta == 0) asm volatile("cp.async.bulk.prefetch.L2.global [%0], 6144;" ::"l"(gat) : "memory");
              asm volatile("cp.async.bulk.prefetch.L2.global [%0], 1024;" ::"l"(wf + cta * 512) : "memory");
              asm volatile("cp.async.bulk.prefetch.L2.global [%0], 1024;" ::"l"(wo + cta * 512) : "memory");
            }
          }
          __syncwarp();
          if (++st == H_NST) st = 0;
        }
      }
    }
  } else {
    if (lane == 0) {
      const int w8 = 4 * wg + warp;
      for (int i = 0; i < 2; i++) {
        mbar_init(xf0 + 16 * w8 + 8 * i, 1);
        mbar_expect(xf0 + 16 * w8 + 8 * i, A_IN);
      }
      mbar_init(got0 + 8 * w8, 1);
      if (w8 >= 8 - A_NREL) mbar_init(acq0 + 8 * (7 - w8), 1);
      if (w8 < G_NST) {
        mbar_init(full0 + 8 * w8, 1);
        mbar_init(empty0 + 8 * w8, 17);
        mbar_arrive(empty0 + 8 * w8);
      }
      if (w8 > 0) {
        mbar_init(hf0 + 8 * (w8 - 1), 1);
        mbar_init(he0 + 8 * (w8 - 1), 16);
      }
      fence_bar_init();
    }
    __syncwarp();
    asm volatile("barrier.cluster.arrive.relaxed.aligned;" ::: "memory");
    if (wg == 1) tab[t] = __bfloat16_as_ushort(__float2bfloat16_rn(-__cosf((float)(t - 64) * 0.04908738521234052f)));
    bar_sync(1, 256);
    asm volatile("setmaxnreg.inc.sync.aligned.u32 232;");
    uint32_t fa[16];
    auto frag = [&](int i, int l) {
      const int f = warp * 16 + (l >> 2) + 8 * (i & 1), r = 8 * (i >> 1) + (l & 3) * 2;
      const int k0 = (f | 1) * r - ((f & 1) << 5);
      return tab[k0 & 127] | ((uint32_t)tab[(k0 + (f | 1)) & 127] << 16);
    };
#pragma unroll
    for (int i = 0; i < 16; i++) fa[i] = i < 4 ? frag(i, lane) : 0;
    reg_fence(fa);
    asm volatile("barrier.cluster.wait.aligned;" ::: "memory");
    int cta = blk, qs = 0;
#pragma unroll 1
    for (int n = wg; n < nu; n += 2) {
      float e[64];
      if ((n >> 1) == !spare) {
        pdl_launch();
        int l = lane;
        asm volatile("" : "+r"(l));
#pragma unroll
        for (int i = 4; i < 16; i++) fa[i] = frag(i, l);
        reg_fence(fa);
        cta = role();
        qs = ((cta >> 1) & 2) + hf;
      }
      if (spare) qs = n < 8 ? n & 3 : 2 * hf + wg;
      const bool isx = (xm >> n) & 1;
      const int r = __popc(xm & ((1 << n) - 1)), s = 7 - n + r;
      const uint32_t in = isx ? sb + (r % A_NIN) * A_IN : sb + 2 * G_STAGE + s * 4096;
      mbar_wait(isx ? xf0 + 8 * r : wf0 + 8 * (s >> 1), 0);
      if (!isx) {
        wg_fence();
        wgmma_rs_128<1, 1, 1>(e, fa[0], fa[1], fa[2], fa[3], mk_desc(in, 0, 2048, 1024, 1), 0);
        wg_commit();
      } else {
        wg_fence();
#pragma unroll
        for (int k = 0; k < 4; k++)
          wgmma_rs_128<1, 1, 1>(e, fa[4 * k], fa[4 * k + 1], fa[4 * k + 2], fa[4 * k + 3], mk_desc(in, k * 2048, 6144, 1024, 1), k);
        wg_commit();
      }
      wg_wait<0>();
      reg_fence(e);
      if (isx && lane == 0) mbar_arrive(xe0 + 8 * (r % A_NIN));
      if (((A_FREE >> n) & 1) && !spare && lane < 2) mbar_arrive_cta(empty0 + 8 * (__popc(A_FREE & ((1 << n) - 1)) >> 1), lane);
      if (n >= A_NOUT) mbar_wait(aoe0 + 8 * (n % A_NOUT), (n / A_NOUT - 1) & 1);
      const int row = warp * 16 + (lane & 7) + ((lane >> 3) & 1) * 8, hi = lane >> 4;
      const uint32_t rb = sb + a_out(n) + (isx ? row : row + (row & ~7)) * 128, ts = isx ? 8192 : 1024, xr = (lane & 7) ^ (isx ? qs : 0);
#pragma unroll
      for (int j = 0; j < 16; j += 2) {
        const uint32_t tile = isx ? (j >> 2) & 1 : j >> 3, pos = (isx ? (j >> 3) * 4 + (j & 3) : (j & 7)) + hi;
        stsm4(rb + tile * ts + ((pos ^ xr) << 4), pack2(e[4 * j], e[4 * j + 1]), pack2(e[4 * j + 2], e[4 * j + 3]),
              pack2(e[4 * j + 4], e[4 * j + 5]), pack2(e[4 * j + 6], e[4 * j + 7]));
      }
      fence_async();
      __syncwarp();
      if (lane == 0) mbar_arrive(aof0 + 8 * (n % A_NOUT));
    }
    if (spare) {
      float* sg = reinterpret_cast<float*>(smem_raw + (sb - s2u(smem_raw)));
      __nv_bfloat16* sw = reinterpret_cast<__nv_bfloat16*>(sg + 16 * 256);
      const int c0 = (cta - 128) * 64;
      uint4 vw[8], vg[2];
#pragma unroll
      for (int i = 0; i < 8; i++) vw[i] = __ldg(reinterpret_cast<const uint4*>(wgt + ((i * 256 + tid) >> 3) * 256 + c0 + (tid & 7) * 8));
#pragma unroll
      for (int i = 0; i < 2; i++) vg[i] = __ldg(reinterpret_cast<const uint4*>(g) + i * 256 + tid);
      bar_sync(3, 256);
#pragma unroll
      for (int i = 0; i < 8; i++) reinterpret_cast<uint4*>(sw)[i * 256 + tid] = vw[i];
#pragma unroll
      for (int i = 0; i < 2; i++) {
        const uint32_t w4[4] = {vg[i].x, vg[i].y, vg[i].z, vg[i].w};
#pragma unroll
        for (int e = 0; e < 4; e++) {
          sg[(i * 256 + tid) * 8 + 2 * e] = __uint_as_float(w4[e] << 16);
          sg[(i * 256 + tid) * 8 + 2 * e + 1] = __uint_as_float(w4[e] & 0xffff0000u);
        }
      }
      bar_sync(3, 256);
      const int col = tid & 63, r0 = (tid >> 6) * 4;
      float a0 = 0.f, a1 = 0.f, a2 = 0.f, a3 = 0.f;
#pragma unroll 8
      for (int k = 0; k < 256; k++) {
        const float w = __bfloat162float(sw[k * 64 + col]);
        a0 = fmaf(sg[(r0 + 0) * 256 + k], w, a0);
        a1 = fmaf(sg[(r0 + 1) * 256 + k], w, a1);
        a2 = fmaf(sg[(r0 + 2) * 256 + k], w, a2);
        a3 = fmaf(sg[(r0 + 3) * 256 + k], w, a3);
      }
      const int cc = c0 + col;
      const int pos = (cc & ~15) + ((cc >> 1) & 3) * 4 + ((cc >> 3) & 1) * 2 + (cc & 1);
      ge[(r0 + 0) * 256 + pos] = __bfloat162float(__float2bfloat16_rn(a0));
      ge[(r0 + 1) * 256 + pos] = __bfloat162float(__float2bfloat16_rn(a1));
      ge[(r0 + 2) * 256 + pos] = __bfloat162float(__float2bfloat16_rn(a2));
      ge[(r0 + 3) * 256 + pos] = __bfloat162float(__float2bfloat16_rn(a3));
      return;
    }
    const int bin = cta >> 2;
    const uint32_t la = (lane >> 4) * 1024 + (lane & 7) * 128 + (((2 * warp + ((lane >> 3) & 1)) ^ (lane & 7)) << 4);
    {
    float d[32];
    auto t_begin = [&](int it, int hh) {
      mbar_wait(inf0 + 8 * (it & 1), (it >> 1) & 1);
      wg_fence();
      wgmma_rs_64<1, 1, 1>(d, fa[0], fa[1], fa[2], fa[3], mk_desc(sb + G_TIN + (it & 1) * 4096 + hh * 2048, 0, 0, 1024, 1), 0);
      wg_commit();
    };
    auto t_end = [&](int it, int hh) {
      reg_fence(d);
      const int j = it & 1;
      mbar_wait(se0 + 8 * j, (it >> 1) & 1);
      store_tile_64<2048>(d, sb + G_TOUT + j * A_OUT + hh * 1024, warp, lane);
      fence_async();
      __syncwarp();
      if (lane == 0) mbar_arrive(sf0 + 8 * j);
    };
    float re[NB1 / 2], im[NB1 / 2];
#pragma unroll 1
    for (int k = 0; k < G_KS; k++) {
      const int st = g_slot(k);
      const int it = __popc(G_TMASK & ((1 << k) - 1));
      const bool T = (G_TMASK >> k) & 1;
      mbar_wait(full0 + 8 * st, (G_PAR >> k) & 1);
      const uint32_t base = sb + st * G_STAGE;
      const uint32_t wb = base + wg * 4096;
      if (T) t_begin(it, wg);
      wg_fence();
#pragma unroll
      for (int s = 0; s < 2; s++) {
        const int acc = (k | s) != 0;
        const uint64_t dP = mk_desc(wb, s * 2048, 0, 1024, 1), dQ = mk_desc(wb, 8192 + s * 2048, 0, 1024, 1);
        const uint64_t dA = mk_desc(base, 16384 + s * 32, 0, 512, 2), dB = mk_desc(base, 16384 + G_XP + s * 32, 0, 512, 2);
        wgmma_ss_168<1, 1, 1, 0>(re, dP, dA, acc);
        wgmma_ss_168<1, 1, 1, 0>(im, dP, dB, acc);
        wgmma_ss_168<1, 1, 1, 0>(re, dQ, dB, 1);
        wgmma_ss_168<-1, 1, 1, 0>(im, dQ, dA, 1);
      }
      wg_commit();
      wg_wait<1>();
      if (k > 0 && lane < 2) mbar_arrive_cta(empty0 + 8 * g_slot(k - 1), lane);
      if (T) t_end(it, wg);
    }
    auto tail = [&](auto part, bool wait) {
      constexpr int PART = decltype(part)::value;
#pragma unroll
      for (int k = G_KS; k < 16; k++) {
        if (wait) mbar_wait(full0 + 8 * g_slot(k), (G_PAR >> k) & 1);
        const uint32_t base = sb + g_slot(k) * G_STAGE, wb = base + wg * 4096;
        wg_fence();
#pragma unroll
        for (int s = 0; s < 2; s++) {
          const uint64_t dP = mk_desc(wb, s * 2048, 0, 1024, 1), dQ = mk_desc(wb, 8192 + s * 2048, 0, 1024, 1);
          const uint64_t dA = mk_desc(base, 16384 + s * 32, 0, 512, 2), dB = mk_desc(base, 16384 + G_XP + s * 32, 0, 512, 2);
          if (PART == 0) {
            wgmma_ss_168<1, 1, 1, 0>(re, dP, dA, 1);
            wgmma_ss_168<1, 1, 1, 0>(re, dQ, dB, 1);
          } else {
            wgmma_ss_168<1, 1, 1, 0>(im, dP, dB, 1);
            wgmma_ss_168<-1, 1, 1, 0>(im, dQ, dA, 1);
          }
        }
      }
      wg_commit();
    };
    auto put = [&](float (&v)[NB1 / 2], uint32_t stg, uint32_t bar) {
      reg_fence(v);
#pragma unroll
      for (int c = 0; c < 3; c++) {
#pragma unroll
        for (int j = 8 * c; j < 8 * c + 8 && j < 20; j += 2)
          stsm4t(stg + la + j * 1024, pack2(v[4 * j], v[4 * j + 1]), pack2(v[4 * j + 2], v[4 * j + 3]),
                 pack2(v[4 * j + 4], v[4 * j + 5]), pack2(v[4 * j + 6], v[4 * j + 7]));
        if (c == 2)
          asm volatile("stmatrix.sync.aligned.m8n8.x2.trans.shared.b16 [%0], {%1, %2};" ::"r"(stg + la + 20 * 1024),
                       "r"(pack2(v[80], v[81])), "r"(pack2(v[82], v[83])) : "memory");
        fence_async();
        __syncwarp();
        if (lane == 0) mbar_arrive(bar + 8 * c);
      }
    };
    if (wg == 1) {
#pragma unroll 1
      for (int h2 = 2 * __popc(G_TMASK); h2 < 16; h2++) {
        t_begin(h2 >> 1, h2 & 1);
        wg_wait<0>();
        t_end(h2 >> 1, h2 & 1);
      }
      wg_wait<0>();
      bar_arrive(5, 256);
      bar_sync(4, 256);
    }
    tail(std::integral_constant<int, 0>(), true);
    tail(std::integral_constant<int, 1>(), false);
    if (wg == 0) bar_arrive(4, 256);
    wg_wait<1>();
    if (wg == 0) {
      bar_sync(5, 256);
    } else {
      mbar_wait(se0, 0);
      mbar_wait(se0 + 8, 0);
    }
    put(re, sb + (wg ? G_TOUT : 4 * G_STAGE), yo0 + 48 * wg);
    wg_wait<0>();
    if (lane == 0) mbar_arrive(gdone);
    if (wg == 1) mbar_wait(gdone, 0);
    put(im, sb + (wg ? G_IM1 : 4 * G_STAGE + NB1 * 128), yo0 + 48 * wg + 24);
    }
    mbar_wait(imgb, 0);
    const int p0 = bin >= 28, p1 = bin < 4 ? 1 : 2;
#pragma unroll 1
    for (int pc = p0; pc < p1; pc++) {
      const uint32_t in = sb + pc * C_PIECE, yb = yf0 + 32 * pc;
      const bool first = bin == 4 * pc, last = bin == 27 + 4 * pc;
      float h0[12], h1[12], h2[12], h3[12], h4[12], h5[12], h6[8], e[32];
      uint32_t hp[40];
      auto idft = [&](auto& h, int i) {
#pragma unroll
        for (int k = 0; k < 4; k++) {
          const uint64_t da = mk_desc(in, i * 8192 + k * 2048, 0, 1024, 1), db = mk_desc(sb + C_GI + wg * 1024, k * 32, 0, 2048, 1);
          if constexpr (sizeof(h) == 48) wgmma_ss_24<1, 1, 1, 0>(h, da, db, k);
          else wgmma_ss_16<1, 1, 1, 0>(h, da, db, k);
        }
      };
      auto idft2 = [&](auto& ha, auto& hb, int i) {
        mbar_wait(yb + 4 * (i + 1), 0);
        wg_fence();
        idft(ha, i);
        idft(hb, i + 1);
        wg_commit();
      };
      auto dft = [&](int j) {
        wg_fence();
#pragma unroll
        for (int k = 0; k < 4; k++)
          wgmma_rs_64<1, 1, 0>(e, hp[12 * j + 4 * k], hp[12 * j + 4 * k + 1], hp[12 * j + 4 * k + 2], hp[12 * j + 4 * k + 3], mk_desc(sb + C_F, k * 32, 0, 1024, 1), k);
        wg_commit();
      };
      auto out = [&](int j) {
        reg_fence(e);
        if (j == 1) mbar_wait(rly0 + 8, 0);
        const uint32_t a0 = in + la + C_OUT + (2 * j + wg) * 8192;
#pragma unroll
        for (int q = 0; q < 8; q += 2)
          stsm4t(a0 + q * 1024, pack2(e[4 * q], e[4 * q + 1]), pack2(e[4 * q + 2], e[4 * q + 3]),
                 pack2(e[4 * q + 4], e[4 * q + 5]), pack2(e[4 * q + 6], e[4 * q + 7]));
        fence_async();
        __syncwarp();
        if (lane == 0) mbar_arrive(of0 + 8 * (6 * pc + 2 * j + wg));
      };
      mbar_wait(yb, 0);
      wg_fence();
      idft(h0, 0);
      wg_commit();
      idft2(h1, h2, 1);
      wg_wait<1>();
      gelu_pack(hp, h0, first, false);
      wg_wait<0>();
      gelu_pack(hp + 6, h1, false, false);
      gelu_pack(hp + 12, h2, false, false);
      dft(0);
      idft2(h3, h4, 3);
      wg_wait<1>();
      out(0);
      wg_wait<0>();
      gelu_pack(hp + 18, h3, false, false);
      gelu_pack(hp + 24, h4, false, false);
      dft(1);
      idft2(h5, h6, 5);
      wg_wait<1>();
      out(1);
      wg_wait<0>();
      gelu_pack(hp + 30, h5, false, last);
      gelu_pack(hp + 36, h6, false, last);
      dft(2);
      wg_wait<0>();
      if (pc == p1 - 1 && lane < 6) mbar_arrive_cta(he0 + 8 * (3 + (lane >> 1)), lane & 1);
      out(2);
    }
    float acc[84];
    if (wg == 0) {
      h_loop<0>(acc, sb, hf0, he0, lane);
    } else {
      h_loop<1>(acc, sb, hf0, he0, lane);
      bar_sync(3, 128);
    }
    const uint32_t stg = sb + (wg == 0 ? H_NST : 9 % H_NST) * H_STAGE;
    const uint32_t a0 = stg + la;
    constexpr int J = 21 / H_EPI;
#pragma unroll
    for (int c = 0; c < H_EPI; c++) {
#pragma unroll
      for (int j = c * J; j + 1 < (c + 1) * J; j += 2)
        stsm4t(a0 + j * 1024, pack2(acc[4 * j], acc[4 * j + 1]), pack2(acc[4 * j + 2], acc[4 * j + 3]),
               pack2(acc[4 * j + 4], acc[4 * j + 5]), pack2(acc[4 * j + 6], acc[4 * j + 7]));
      const int j = (c + 1) * J - 1;
      asm volatile("stmatrix.sync.aligned.m8n8.x2.trans.shared.b16 [%0], {%1, %2};" ::"r"(a0 + j * 1024),
                   "r"(pack2(acc[4 * j], acc[4 * j + 1])), "r"(pack2(acc[4 * j + 2], acc[4 * j + 3])) : "memory");
      fence_async();
      bar_sync(2 + wg, 128);
      if (t == 0) {
        tma_st4<0>(&m.y2, stg + c * J * 1024, 0, c * J * 8, 2 * bin + wg, cta & 3);
        bulk_commit();
      }
    }
    if (t == 0) {
      bulk_wait_read<0>();
    }
  }
}

#define E_WPRE 2
#define E_EARLY0 2
#define E_CHUNK 1
#define E_EARLY 2
constexpr int E_SMEM = 65536 + 131072 + 32768 + 1024;

__device__ __forceinline__ uint32_t joint2(uint32_t fe, uint32_t g0, uint32_t g1) {
  uint32_t s0, s1;
  asm("{\n.reg .b16 l, h;\n.reg .b32 ll;\nmov.b32 {l, h}, %2;\nmov.b32 ll, {l, l};\n"
      "fma.rn.bf16x2 %0, ll, %5, %3;\nfma.rn.bf16x2 %1, %2, %5, %4;\n}"
      : "=r"(s0), "=r"(s1) : "r"(fe), "r"(g0), "r"(g1), "r"(0x3F800000u));
  return pack2(tanh_f32(__uint_as_float(s0)), tanh_f32(__uint_as_float(s1)));
}
__device__ __forceinline__ uint4 lds128(uint32_t a) {
  uint4 v;
  asm volatile("ld.shared.v4.u32 {%0, %1, %2, %3}, [%4];" : "=r"(v.x), "=r"(v.y), "=r"(v.z), "=r"(v.w) : "r"(a));
  return v;
}
__device__ __forceinline__ void joint_group(uint32_t (&ja)[8], const uint32_t* fe, uint4& g0, uint4& g1, uint32_t gnext) {
  const uint4 c0 = g0, c1 = g1;
  g0 = lds128(gnext);
  g1 = lds128(gnext + 64);
  ja[0] = joint2(fe[0], c0.x, c0.y);
  ja[1] = joint2(fe[1], c0.x, c0.y);
  ja[2] = joint2(fe[2], c0.z, c0.w);
  ja[3] = joint2(fe[3], c0.z, c0.w);
  ja[4] = joint2(fe[4], c1.x, c1.y);
  ja[5] = joint2(fe[5], c1.x, c1.y);
  ja[6] = joint2(fe[6], c1.z, c1.w);
  ja[7] = joint2(fe[7], c1.z, c1.w);
  reg_fence(ja);
}

__global__ void __launch_bounds__(256, 1)
kE(int* __restrict__ cnt, const uint32_t* __restrict__ gat, const float* ge, const __grid_constant__ CUtensorMap my, const __grid_constant__ CUtensorMap mwf, const __grid_constant__ CUtensorMap mwo,
   const __grid_constant__ CUtensorMap mout) {
  extern __shared__ __align__(1024) uint8_t smem_raw[];
  __shared__ __align__(8) uint64_t bars[13];
  const uint32_t sb = (s2u(smem_raw) + 1023) & ~1023u;
  const int tid = threadIdx.x, wg = __shfl_sync(0xffffffffu, tid >> 7, 0), t = tid & 127, warp = t >> 5, lane = t & 31;
  const uint32_t R0 = sb, R1 = sb + 65536, R2 = sb + 65536 + 131072;
  const uint32_t barY = s2u(&bars[0]), barF = barY + 32, barO = barY + 64, barA = barY + 96;
  const int b = blockIdx.x / 63, t0 = (blockIdx.x % 63) * 64;
  const int a = t0 / 48, o = t0 % 48;
  const int qw = o + 16 * warp, sel = qw >= 48;
  uint32_t ga[16];
#pragma unroll
  for (int s = 0; s < 4; s++)
    ldg128(reinterpret_cast<const uint4*>(gat) + ((qw >> 4) - 3 * sel) * 128 + s * 32 + lane, ga[4 * s], ga[4 * s + 1], ga[4 * s + 2], ga[4 * s + 3]);
  if (tid == 0) {
    prefetch_map(&my);
    for (int i = 0; i < 12; i++) mbar_init(barY + 8 * i, 1);
    mbar_init(barA, 8);
    fence_bar_init();
    fence_async();
    for (int i = 0; i < E_WPRE; i++) {
      const int kc = (i >> 1) | ((i & 1) << 1);
      mbar_expect(barF + 8 * kc, 32768);
      tma_ld3<0>(R1 + kc * 32768, &mwf, barF + 8 * kc, 0, kc * 64, 0);
    }
    pdl_wait();
    for (int i = 0; i < 4; i++) {
      mbar_expect(barY + 8 * i, 16384);
      tma_ld5<0>(R0 + i * 16384, &my, barY + 8 * i, 0, 0, 2 * (i & 1) + (i >> 1), a, b);
    }
    for (int i = E_WPRE; i < 4; i++) {
      const int kc = (i >> 1) | ((i & 1) << 1);
      mbar_expect(barF + 8 * kc, 32768);
      tma_ld3<0>(R1 + kc * 32768, &mwf, barF + 8 * kc, 0, kc * 64, 0);
    }
    prefetch_map(&mwo);
    prefetch_map(&mout);
  }
  uint32_t gs[32];
#pragma unroll
  for (int i = 0; i < 16; i++) {
    gs[i] = sel ? 0u : ga[i];
    gs[16 + i] = sel ? ga[i] : 0u;
  }
  __syncthreads();
  uint4 gev0, gev1;
  asm volatile("ld.global.cg.v4.u32 {%0, %1, %2, %3}, [%4];" : "=r"(gev0.x), "=r"(gev0.y), "=r"(gev0.z), "=r"(gev0.w)
               : "l"(reinterpret_cast<const uint4*>(ge) + (b * 8 + wg * 4) * 64 + t));
  asm volatile("ld.global.cg.v4.u32 {%0, %1, %2, %3}, [%4];" : "=r"(gev1.x), "=r"(gev1.y), "=r"(gev1.z), "=r"(gev1.w)
               : "l"(reinterpret_cast<const uint4*>(ge) + (b * 8 + wg * 4) * 64 + 128 + t));
  if (blockIdx.x == 125 && tid < 128) cnt[tid] = 0;
  reg_fence(gs);
  uint32_t gp = R2 + wg * 4096 + (lane & 3) * 16;
  uint4 g0, g1;
  uint32_t fe[64];
  {
    float d0[32], d1[32], e[64];
    mbar_wait(barY + 8 * wg, 0);
    wg_fence();
#pragma unroll
    for (int k = 0; k < 8; k++)
      wgmma_rs_64<1, 1, 1>(d0, gs[4 * k], gs[4 * k + 1], gs[4 * k + 2], gs[4 * k + 3], mk_desc(R0 + wg * 16384, k * 2048, 0, 1024, 1), k);
    wg_commit();
    wg_wait<0>();
    reg_fence(d0);
#pragma unroll
    for (int i = 0; i < 32; i++) d0[i] = gelu(d0[i]);
    store_tile_64(d0, R2 + wg * 16384, warp, lane);
    mbar_wait(barY + 8 * (2 + wg), 0);
    wg_fence();
#pragma unroll
    for (int k = 0; k < 8; k++)
      wgmma_rs_64<1, 1, 1>(d1, gs[4 * k], gs[4 * k + 1], gs[4 * k + 2], gs[4 * k + 3], mk_desc(R0 + wg * 16384, 32768 + k * 2048, 0, 1024, 1), k);
    wg_commit();
    fence_async();
    mbar_wait(barF, 0);
    mbar_wait(barF + 16, 0);
    __syncthreads();
    wg_fence();
#pragma unroll
    for (int i = 0; i < 8; i++) {
      const int kc = (i >> 2) * 2, s = i & 3;
      wgmma_ss_128<1, 1, 0, 1>(e, mk_desc(R2, kc * 8192 + s * 32, 0, 1024, 1),
                               mk_desc(R1 + wg * 16384, kc * 32768 + s * 2048, 8192, 1024, 1), i);
    }
    wg_commit();
    if (tid == 128) {
      mbar_expect(barO, 32768);
      tma_ld3<0>(R0, &mwo, barO, 0, 0, 0);
    }
    wg_wait<1>();
    reg_fence(d1);
#pragma unroll
    for (int i = 0; i < 32; i++) d1[i] = gelu(d1[i]);
    store_tile_64(d1, R2 + wg * 16384 + 8192, warp, lane);
    fence_async();
    mbar_wait(barF + 8, 0);
    mbar_wait(barF + 24, 0);
    __syncthreads();
    if (tid == 128) {
      mbar_expect(barO + 8, 32768);
      tma_ld3<0>(R0 + 32768, &mwo, barO + 8, 0, 64, 0);
    }
    if (wg == 1) bar_sync(4, 256);
    wg_fence();
#pragma unroll
    for (int i = 0; i < 8; i++) {
      const int kc = (i >> 2) * 2 + 1, s = i & 3;
      wgmma_ss_128<1, 1, 0, 1>(e, mk_desc(R2, kc * 8192 + s * 32, 0, 1024, 1),
                               mk_desc(R1 + wg * 16384, kc * 32768 + s * 2048, 8192, 1024, 1), 1);
    }
    wg_commit();
    if (wg == 0) bar_arrive(4, 256);
    wg_wait<1>();
    if (lane == 0) mbar_arrive(barA);
    if (tid == 128) {
      mbar_wait(barA, 0);
      for (int kc = 2; kc < 4; kc++) {
        mbar_expect(barO + 8 * kc, 32768);
        tma_ld3<0>(R1 + (kc - 2) * 65536, &mwo, barO + 8 * kc, 0, kc * 64, 0);
      }
    }
    mbar_wait(barA, 0);
    asm volatile("st.shared.v4.u32 [%0], {%1, %2, %3, %4};" ::"r"(R2 + wg * 4096 + ((t * 16) ^ (wg * 512))), "r"(gev0.x), "r"(gev0.y), "r"(gev0.z), "r"(gev0.w) : "memory");
    asm volatile("st.shared.v4.u32 [%0], {%1, %2, %3, %4};" ::"r"(R2 + wg * 4096 + 2048 + ((t * 16) ^ (wg * 512))), "r"(gev1.x), "r"(gev1.y), "r"(gev1.z), "r"(gev1.w) : "memory");
    bar_sync(1 + wg, 128);
    g0 = lds128(gp);
    g1 = lds128(gp + 64);
    wg_wait<0>();
    reg_fence(e);
#pragma unroll
    for (int i = 0; i < 32; i++) fe[i] = pack2(e[2 * i], e[2 * i + 1]);
  }
  auto publish = [&]() {
    bar_sync(1 + wg, 128);
    const int row = warp * 16 + (lane & 7) + ((lane >> 3) & 1) * 8;
    const uint32_t xb = R1 + (wg == 0 ? 3 * 32768 : 32768 + 16384) + row * 128;
#pragma unroll
    for (int s = 0; s < 8; s++) {
      const int jj = 2 * s + (lane >> 4);
      stsm4(xb + (s >> 2) * 8192 + (((jj & 7) ^ (lane & 7)) << 4), fe[4 * s], fe[4 * s + 1], fe[4 * s + 2], fe[4 * s + 3]);
    }
    bar_arrive(5 + wg, 256);
  };
  if (wg == 1) publish();
  const uint32_t stg = R1 + 32768 + wg * 65536;
  const uint32_t w0 = sb + wg * 65536, w1 = sb + 32768 + wg * 98304, w2 = sb + 65536 - wg * 65536, w3 = sb + 131072 - wg * 98304;
  float acc[128];
  uint32_t j0[8], j1[8], j2[8], j3[8];
  joint_group(j0, fe, g0, g1, gp + 128);
  mbar_wait(barO + 16 * wg, 0);
  joint_group(j1, fe + 8, g0, g1, gp + 256);
#define E_MMA4(J, K, W, FIRSTK, G, NEXTBAR)                                                     \
  wg_fence();                                                                                   \
  wgmma_rs_256<1, 1, 1>(acc, J[0], J[1], J[2], J[3], mk_desc(W, 0, 8192, 1024, 1), FIRSTK);     \
  wgmma_rs_256<1, 1, 1>(acc, J[4], J[5], J[6], J[7], mk_desc(W, 2048, 8192, 1024, 1), 1);       \
  wgmma_rs_256<1, 1, 1>(acc, K[0], K[1], K[2], K[3], mk_desc(W, 4096, 8192, 1024, 1), 1);       \
  wgmma_rs_256<1, 1, 1>(acc, K[4], K[5], K[6], K[7], mk_desc(W, 6144, 8192, 1024, 1), 1);       \
  wg_commit();                                                                                  \
  if ((ui + wg == 0 ? E_EARLY0 : E_EARLY) == (G) && (ui < 3 || wg == 0)) bar_arrive(4 - wg, 256); \
  wg_wait<1>();                                                                                 \
  if (ui == 0) mbar_wait(NEXTBAR, 0);
  const uint32_t bo0 = barO + 16 * wg, bo2 = barO + 16 * (1 - wg);
#pragma unroll 1
  for (int ui = 0; ui < 4; ui++) {
    if (ui > 0 || wg == 1) bar_sync(3 + wg, 256);
    E_MMA4(j0, j1, w0, 0, 0, bo0)
    joint_group(j2, fe + 16, g0, g1, gp + 384);
    if (ui == 0) mbar_wait(bo0 + 8, 0);
    joint_group(j3, fe + 24, g0, g1, gp + 512);
    E_MMA4(j2, j3, w1, 1, 1, bo0 + 8)
    if (ui == 0) {
      if (wg == 0) publish();
      bar_sync(6 - wg, 256);
      const int row = warp * 16 + (lane & 7) + ((lane >> 3) & 1) * 8;
      const uint32_t xb = R1 + (wg == 1 ? 3 * 32768 : 32768 + 16384) + row * 128;
#pragma unroll
      for (int s = 0; s < 8; s++) {
        const int jj = 2 * s + (lane >> 4);
        ldsm4(xb + (s >> 2) * 8192 + (((jj & 7) ^ (lane & 7)) << 4), fe[32 + 4 * s], fe[33 + 4 * s], fe[34 + 4 * s], fe[35 + 4 * s]);
      }
    }
    joint_group(j0, fe + 32, g0, g1, gp + 640);
    if (ui == 0) mbar_wait(bo2, 0);
    joint_group(j1, fe + 40, g0, g1, gp + 768);
    E_MMA4(j0, j1, w2, 1, 2, bo2)
    joint_group(j2, fe + 48, g0, g1, gp + 896);
    if (ui == 0) mbar_wait(bo2 + 8, 0);
    joint_group(j3, fe + 56, g0, g1, gp + 1024);
    E_MMA4(j2, j3, w3, 1, 3, bo2 + 8)
    gp += 1024;
    if (ui < 3) {
      joint_group(j0, fe, g0, g1, gp + 128);
      if (ui == 0) mbar_wait(bo2 + 8, 0);
      joint_group(j1, fe + 8, g0, g1, gp + 256);
    }
    if (t == 0) bulk_wait_read<0>();
    wg_wait<0>();
    reg_fence(acc);
    bar_sync(1 + wg, 128);
    const uint32_t rb = stg + (warp * 16 + (lane & 7) + ((lane >> 3) & 1) * 8) * 128;
#pragma unroll
    for (int h = 0; h < 2; h++) {
#pragma unroll
      for (int j = 16 * h; j < 16 * h + 16; j += 2) {
        const int jj = j + (lane >> 4);
        stsm4(rb + (j >> 3) * 8192 + (((jj & 7) ^ (lane & 7)) << 4), pack2(acc[4 * j], acc[4 * j + 1]), pack2(acc[4 * j + 2], acc[4 * j + 3]),
              pack2(acc[4 * j + 4], acc[4 * j + 5]), pack2(acc[4 * j + 6], acc[4 * j + 7]));
      }
      const bool split = E_CHUNK == 2 || (E_CHUNK == 1 && ui == 3);
      if (h == 1 || split) {
        fence_async();
        bar_sync(1 + wg, 128);
        if (t == 0) {
          if (h == 1 && !split) tma_st5<1>(&mout, stg, 0, t0, 0, wg * 4 + ui, b);
          tma_st5<1>(&mout, stg + h * 16384, 0, t0, 2 * h, wg * 4 + ui, b);
          bulk_commit();
        }
      }
    }
  }
  if (t == 0) bulk_wait_read<0>();
}

typedef CUresult (*EncodeFn)(CUtensorMap*, CUtensorMapDataType, cuuint32_t, void*, const cuuint64_t*, const cuuint64_t*,
                             const cuuint32_t*, const cuuint32_t*, CUtensorMapInterleave, CUtensorMapSwizzle,
                             CUtensorMapL2promotion, CUtensorMapFloatOOBfill);

CUtensorMap make_map(EncodeFn fn, const void* base, int rank, const uint64_t* dims, const uint64_t* strides, const uint32_t* box,
                     CUtensorMapSwizzle swz) {
  CUtensorMap m;
  cuuint64_t gd[5], gs[4];
  cuuint32_t bx[5], es[5];
  for (int i = 0; i < rank; i++) { gd[i] = dims[i]; bx[i] = box[i]; es[i] = 1; }
  for (int i = 0; i + 1 < rank; i++) gs[i] = strides[i];
  fn(&m, CU_TENSOR_MAP_DATA_TYPE_BFLOAT16, rank, const_cast<void*>(base), gd, gs, bx, es, CU_TENSOR_MAP_INTERLEAVE_NONE, swz,
     CU_TENSOR_MAP_L2_PROMOTION_NONE, CU_TENSOR_MAP_FLOAT_OOB_FILL_NONE);
  return m;
}

template <typename... KArgs, typename... Args>
void launch(void (*k)(KArgs...), int grid, int block, int smem, bool pdl, Args... args) {
  cudaLaunchConfig_t c = {};
  c.gridDim = dim3(grid);
  c.blockDim = dim3(block);
  c.dynamicSmemBytes = smem;
  c.stream = cudaStreamPerThread;
  cudaLaunchAttribute at[1];
  at[0].id = cudaLaunchAttributeProgrammaticStreamSerialization;
  at[0].val.programmaticStreamSerializationAllowed = 1;
  c.attrs = at;
  c.numAttrs = pdl ? 1 : 0;
  cudaLaunchKernelEx(&c, k, args...);
}

}

extern "C" void kernel_launch(void* const* d_in, const int* in_sizes, int n_in, void* d_out, int out_size) {
  const __nv_bfloat16* x = (const __nv_bfloat16*)d_in[0];
  const __nv_bfloat16* w1 = (const __nv_bfloat16*)d_in[1];
  const __nv_bfloat16* w2 = (const __nv_bfloat16*)d_in[2];
  const __nv_bfloat16* g = (const __nv_bfloat16*)d_in[3];
  const __nv_bfloat16* wf = (const __nv_bfloat16*)d_in[4];
  const __nv_bfloat16* wgt = (const __nv_bfloat16*)d_in[5];
  const __nv_bfloat16* wo = (const __nv_bfloat16*)d_in[6];

  void* fp = nullptr;
  cudaDriverEntryPointQueryResult qr;
  cudaGetDriverEntryPoint("cuTensorMapEncodeTiled", &fp, cudaEnableDefault, &qr);
  EncodeFn fn = (EncodeFn)fp;
  void *W, *Y2, *cnt, *ge, *img, *gat;
  cudaGetSymbolAddress(&cnt, g_cnt);
  cudaGetSymbolAddress(&ge, g_ge);
  cudaGetSymbolAddress(&img, c_img);
  cudaGetSymbolAddress(&gat, c_ga);
  cudaGetSymbolAddress(&W, g_W);
  cudaGetSymbolAddress(&Y2, g_Y2);
  cudaFuncSetAttribute(kG, cudaFuncAttributeMaxDynamicSharedMemorySize, G_SMEM);
  cudaFuncSetAttribute(kE, cudaFuncAttributeMaxDynamicSharedMemorySize, E_SMEM);
  auto page_up = [](void* p) { return (void*)(((uintptr_t)p + (1 << 21) - 1) & ~(uintptr_t)((1 << 21) - 1)); };
  void *X1 = page_up(d_out), *X2 = X1;
  W = page_up(W);
  const CUtensorMapSwizzle S128 = CU_TENSOR_MAP_SWIZZLE_128B, S64 = CU_TENSOR_MAP_SWIZZLE_64B;

  auto map_x = [&]() {
    uint64_t d[] = {64, 8000, 8, 1, 2}, s[] = {1024, 128, 8000ull * 1024, 8000ull * 1024};
    uint32_t bx[] = {64, 112, 1, 1, 1};
    return make_map(fn, x, 5, d, s, bx, S128);
  };
  auto map_w_in = [&](const __nv_bfloat16* w, int odd, uint32_t n) {
    uint64_t d[] = {64, (uint64_t)(odd ? 15 : 16), 4, 64, 4}, s[] = {2ull * 65536 * 2, 128, 512, 32768};
    uint32_t bx[] = {64, 16, 2, 1, n};
    return make_map(fn, w + (odd ? 65536 : 0), 5, d, s, bx, S128);
  };
  auto map_X_st = [&](void* p, int nb, int boxb) {
    uint64_t d[] = {64, 512, (uint64_t)(2 * nb)}, s[] = {2ull * nb * 128, 128};
    uint32_t bx[] = {64, 64, (uint32_t)boxb};
    return make_map(fn, p, 3, d, s, bx, S128);
  };
  auto map_X1_st = [&](uint32_t rows) {
    uint64_t d[] = {8192, 16, 4, 24}, s[] = {16384, 262144, 1048576};
    uint32_t bx[] = {64, 4, 2, rows / 8};
    return make_map(fn, X1, 4, d, s, bx, S128);
  };
  auto map_Y1_ld = [&](uint64_t step) {
    uint64_t d[] = {64, 12 << 14, 2}, s[] = {128, step};
    uint32_t bx[] = {64, 32, 2};
    return make_map(fn, X1, 3, d, s, bx, S128);
  };
  auto map_W_st = [&]() {
    uint64_t d[] = {8192, 8, 4, 2 * (8 + W_SHIFT), 2}, s[] = {32768, 262144, 1048576, 16384};
    uint32_t bx[] = {64, 2, 2, 2, 2};
    return make_map(fn, W, 5, d, s, bx, S128);
  };
  auto map_X_ld = [&](void* p, int nb, int boxb) {
    uint64_t d[] = {64, (uint64_t)(2 * nb), 512}, s[] = {128, 2ull * nb * 128};
    uint32_t bx[] = {32, (uint32_t)boxb, 1};
    return make_map(fn, p, 3, d, s, bx, S64);
  };
  auto map_W_ld = [&](uint32_t n) {
    uint64_t d[] = {64, 512 / n, (8ull + W_SHIFT) * 32 * n}, s[] = {128, 65536 / n};
    uint32_t bx[] = {64, 32, n};
    return make_map(fn, W, 3, d, s, bx, S128);
  };
  auto map_Y_st = [&](void* p, int nb, int rows) {
    uint64_t d[] = {64, (uint64_t)(2 * nb), 64, 4}, s[] = {32768, 128, 8192};
    uint32_t bx[] = {64, (uint32_t)rows, 1, 1};
    return make_map(fn, p, 4, d, s, bx, S128);
  };
  auto map_Y_ld = [&](void* p, int nb, int boxc, int boxb) {
    uint64_t d[] = {64, 64, 4, (uint64_t)nb, 2}, s[] = {128, 8192, 32768, (uint64_t)nb * 32768};
    uint32_t bx[] = {64, 64, (uint32_t)boxc, (uint32_t)boxb, 1};
    return make_map(fn, p, 5, d, s, bx, S128);
  };
  auto map_wsq = [&](const __nv_bfloat16* w) {
    uint64_t d[] = {64, 256, 4}, s[] = {512, 128};
    uint32_t bx[] = {64, 64, 4};
    return make_map(fn, w, 3, d, s, bx, S128);
  };
  auto map_out = [&]() {
    uint64_t d[] = {64, 4000, 4, 8, 2}, s[] = {4096, 128, 512, 4000ull * 4096};
    uint32_t bx[] = {64, 64, 2, 1, 1};
    return make_map(fn, d_out, 5, d, s, bx, S128);
  };

  GMaps g1;
  g1.w = map_W_ld(4);
  g1.y = map_X1_st(8);
  g1.in[0] = map_w_in(w1, 1, 2);
  g1.in[1] = map_w_in(w1, 0, 2);
  g1.in[2] = map_w_in(w2, 1, 1);
  g1.in[3] = map_w_in(w2, 0, 1);
  g1.in[4] = map_x();
  g1.xs = map_X1_st(16);
  g1.ws = map_W_st();
  g1.y1[0] = map_Y1_ld(0x3000);
  g1.y1[1] = map_Y1_ld(0x1000);
  g1.x2s = map_X_st(X2, NB2, 1);
  g1.x2 = map_X_ld(X2, NB2, 168);
  g1.w2 = map_W_ld(2);
  g1.y2 = map_Y_st(Y2, NB2, 168 / H_EPI);
  launch(kG, 132, 384, G_SMEM, false, (int*)cnt, (char*)X1, (char*)W, g, wgt, (float*)ge, (const uint32_t*)img, wf, wo, (const uint32_t*)gat, g1);
  launch(kE, 126, 256, E_SMEM, true, (int*)cnt, (const uint32_t*)gat, (const float*)ge, map_Y_ld(Y2, NB2, 1, 2), map_wsq(wf), map_wsq(wo), map_out());
}
```

```cpp
#include <cuda_runtime.h>
#include <cuda_bf16.h>
#include <cuda.h>
#include <stdint.h>
#include <type_traits>

#define W_SHIFT 1
namespace {

constexpr int NB1 = 168;
constexpr int NB2 = 84;

__device__ __align__(1024) __nv_bfloat16 g_W[(9 + W_SHIFT) * 64 * 4 * 64 * 64];
__device__ __align__(1024) __nv_bfloat16 g_Y2[2 * NB2 * 4 * 64 * 64];
__device__ __align__(1024) float g_ge[16 * 256];

__device__ __forceinline__ uint32_t s2u(const void* p) { return (uint32_t)__cvta_generic_to_shared(p); }
__device__ __forceinline__ uint32_t pin(uint32_t v) {
  return __shfl_sync(0xffffffffu, v, 0);
}
__device__ __forceinline__ void mbar_init(uint32_t b, int c) {
  asm volatile("mbarrier.init.shared::cta.b64 [%0], %1;" ::"r"(b), "r"(c) : "memory");
}
__device__ __forceinline__ void mbar_expect(uint32_t b, int bytes) {
  asm volatile("mbarrier.arrive.expect_tx.shared::cta.b64 _, [%0], %1;" ::"r"(b), "r"(bytes) : "memory");
}
__device__ __forceinline__ void mbar_arrive(uint32_t b) {
  asm volatile("mbarrier.arrive.shared::cta.b64 _, [%0];" ::"r"(b) : "memory");
}
__device__ __forceinline__ void mbar_arrive_cta(uint32_t b, uint32_t cta) {
  asm volatile("{\n.reg .b32 r;\nmapa.shared::cluster.u32 r, %0, %1;\nmbarrier.arrive.shared::cluster.b64 _, [r];\n}" ::"r"(b), "r"(cta) : "memory");
}
__device__ __forceinline__ void mbar_wait(uint32_t b, int ph) {
  asm volatile(
      "{\n.reg .pred p;\n.reg .u32 n;\n"
      "mov.u32 n, 0;\n"
      "MBW_LOOP:\n"
      "mbarrier.try_wait.parity.shared::cta.b64 p, [%0], %1;\n"
      "@p bra MBW_DONE;\n"
      "add.u32 n, n, 1;\n"
      "setp.lt.u32 p, n, 1048576;\n"
      "@p bra MBW_LOOP;\n"
      "MBW_DONE:\n}" ::"r"(b), "r"(ph) : "memory");
}
__device__ __forceinline__ bool mbar_test(uint32_t b, int ph) {
  uint32_t ok;
  asm volatile("{\n.reg .pred p;\nmbarrier.test_wait.parity.shared::cta.b64 p, [%1], %2;\nselp.u32 %0, 1, 0, p;\n}" : "=r"(ok) : "r"(b), "r"(ph) : "memory");
  return __all_sync(0xffffffffu, ok);
}
__device__ __forceinline__ void fence_bar_init() { asm volatile("fence.mbarrier_init.release.cluster;" ::: "memory"); }
__device__ __forceinline__ void fence_async() { asm volatile("fence.proxy.async.shared::cta;" ::: "memory"); }
__device__ __forceinline__ void bar_sync(int id, int n) { asm volatile("bar.sync %0, %1;" ::"r"(id), "r"(n) : "memory"); }
__device__ __forceinline__ void bar_arrive(int id, int n) { asm volatile("bar.arrive %0, %1;" ::"r"(id), "r"(n) : "memory"); }
__device__ __forceinline__ void pdl_wait() { asm volatile("griddepcontrol.wait;" ::: "memory"); }
__device__ __forceinline__ void pdl_launch() { asm volatile("griddepcontrol.launch_dependents;" ::: "memory"); }
__device__ __forceinline__ void prefetch_map(const CUtensorMap* m) {
  asm volatile("prefetch.tensormap [%0];" ::"l"(m) : "memory");
}
template <int P> __device__ __forceinline__ uint64_t policy() {
  uint64_t p;
  asm("createpolicy.fractional.L2::evict_first.b64 %0, 1.0;" : "=l"(p));
  return p;
}
template <int P> __device__ __forceinline__ void tma_ld3(uint32_t dst, const CUtensorMap* m, uint32_t bar, int c0, int c1, int c2) {
  if constexpr (P == 0)
    asm volatile("cp.async.bulk.tensor.3d.shared::cluster.global.mbarrier::complete_tx::bytes [%0], [%1, {%3, %4, %5}], [%2];"
                 ::"r"(dst), "l"(m), "r"(bar), "r"(c0), "r"(c1), "r"(c2) : "memory");
  else
    asm volatile("cp.async.bulk.tensor.3d.shared::cluster.global.mbarrier::complete_tx::bytes.L2::cache_hint [%0], [%1, {%3, %4, %5}], [%2], %6;"
                 ::"r"(dst), "l"(m), "r"(bar), "r"(c0), "r"(c1), "r"(c2), "l"(policy<P>()) : "memory");
}
template <int P> __device__ __forceinline__ void tma_ld3mc(uint32_t dst, const CUtensorMap* m, uint32_t bar, int c0, int c1, int c2) {
  if constexpr (P == 0)
    asm volatile("cp.async.bulk.tensor.3d.shared::cluster.global.mbarrier::complete_tx::bytes.multicast::cluster [%0], [%1, {%3, %4, %5}], [%2], %6;"
                 ::"r"(dst), "l"(m), "r"(bar), "r"(c0), "r"(c1), "r"(c2), "h"((uint16_t)3) : "memory");
  else
    asm volatile("cp.async.bulk.tensor.3d.shared::cluster.global.mbarrier::complete_tx::bytes.multicast::cluster.L2::cache_hint [%0], [%1, {%3, %4, %5}], [%2], %6, %7;"
                 ::"r"(dst), "l"(m), "r"(bar), "r"(c0), "r"(c1), "r"(c2), "h"((uint16_t)3), "l"(policy<P>()) : "memory");
}
template <int P> __device__ __forceinline__ void tma_ld4(uint32_t dst, const CUtensorMap* m, uint32_t bar, int c0, int c1, int c2, int c3) {
  if constexpr (P == 0)
    asm volatile("cp.async.bulk.tensor.4d.shared::cluster.global.mbarrier::complete_tx::bytes [%0], [%1, {%3, %4, %5, %6}], [%2];"
                 ::"r"(dst), "l"(m), "r"(bar), "r"(c0), "r"(c1), "r"(c2), "r"(c3) : "memory");
  else
    asm volatile("cp.async.bulk.tensor.4d.shared::cluster.global.mbarrier::complete_tx::bytes.L2::cache_hint [%0], [%1, {%3, %4, %5, %6}], [%2], %7;"
                 ::"r"(dst), "l"(m), "r"(bar), "r"(c0), "r"(c1), "r"(c2), "r"(c3), "l"(policy<P>()) : "memory");
}
template <int P> __device__ __forceinline__ void tma_ld4mc(uint32_t dst, const CUtensorMap* m, uint32_t bar, int c0, int c1, int c2, int c3) {
  if constexpr (P == 0)
    asm volatile("cp.async.bulk.tensor.4d.shared::cluster.global.mbarrier::complete_tx::bytes.multicast::cluster [%0], [%1, {%3, %4, %5, %6}], [%2], %7;"
                 ::"r"(dst), "l"(m), "r"(bar), "r"(c0), "r"(c1), "r"(c2), "r"(c3), "h"((uint16_t)3) : "memory");
  else
    asm volatile("cp.async.bulk.tensor.4d.shared::cluster.global.mbarrier::complete_tx::bytes.multicast::cluster.L2::cache_hint [%0], [%1, {%3, %4, %5, %6}], [%2], %7, %8;"
                 ::"r"(dst), "l"(m), "r"(bar), "r"(c0), "r"(c1), "r"(c2), "r"(c3), "h"((uint16_t)3), "l"(policy<P>()) : "memory");
}
template <int P> __device__ __forceinline__ void tma_ld5(uint32_t dst, const CUtensorMap* m, uint32_t bar, int c0, int c1, int c2, int c3, int c4) {
  if constexpr (P == 0)
    asm volatile("cp.async.bulk.tensor.5d.shared::cluster.global.mbarrier::complete_tx::bytes [%0], [%1, {%3, %4, %5, %6, %7}], [%2];"
                 ::"r"(dst), "l"(m), "r"(bar), "r"(c0), "r"(c1), "r"(c2), "r"(c3), "r"(c4) : "memory");
  else
    asm volatile("cp.async.bulk.tensor.5d.shared::cluster.global.mbarrier::complete_tx::bytes.L2::cache_hint [%0], [%1, {%3, %4, %5, %6, %7}], [%2], %8;"
                 ::"r"(dst), "l"(m), "r"(bar), "r"(c0), "r"(c1), "r"(c2), "r"(c3), "r"(c4), "l"(policy<P>()) : "memory");
}
template <int P> __device__ __forceinline__ void tma_st3(const CUtensorMap* m, uint32_t src, int c0, int c1, int c2) {
  if constexpr (P == 0)
    asm volatile("cp.async.bulk.tensor.3d.global.shared::cta.bulk_group [%0, {%2, %3, %4}], [%1];" ::"l"(m), "r"(src), "r"(c0), "r"(c1), "r"(c2) : "memory");
  else
    asm volatile("cp.async.bulk.tensor.3d.global.shared::cta.bulk_group.L2::cache_hint [%0, {%2, %3, %4}], [%1], %5;" ::"l"(m), "r"(src), "r"(c0), "r"(c1), "r"(c2), "l"(policy<P>()) : "memory");
}
template <int P> __device__ __forceinline__ void tma_st4(const CUtensorMap* m, uint32_t src, int c0, int c1, int c2, int c3) {
  if constexpr (P == 0)
    asm volatile("cp.async.bulk.tensor.4d.global.shared::cta.bulk_group [%0, {%2, %3, %4, %5}], [%1];" ::"l"(m), "r"(src), "r"(c0), "r"(c1), "r"(c2), "r"(c3) : "memory");
  else
    asm volatile("cp.async.bulk.tensor.4d.global.shared::cta.bulk_group.L2::cache_hint [%0, {%2, %3, %4, %5}], [%1], %6;" ::"l"(m), "r"(src), "r"(c0), "r"(c1), "r"(c2), "r"(c3), "l"(policy<P>()) : "memory");
}
template <int P> __device__ __forceinline__ void tma_st5(const CUtensorMap* m, uint32_t src, int c0, int c1, int c2, int c3, int c4) {
  if constexpr (P == 0)
    asm volatile("cp.async.bulk.tensor.5d.global.shared::cta.bulk_group [%0, {%2, %3, %4, %5, %6}], [%1];" ::"l"(m), "r"(src), "r"(c0), "r"(c1), "r"(c2), "r"(c3), "r"(c4) : "memory");
  else
    asm volatile("cp.async.bulk.tensor.5d.global.shared::cta.bulk_group.L2::cache_hint [%0, {%2, %3, %4, %5, %6}], [%1], %7;" ::"l"(m), "r"(src), "r"(c0), "r"(c1), "r"(c2), "r"(c3), "r"(c4), "l"(policy<P>()) : "memory");
}
__device__ __forceinline__ void bulk_commit() { asm volatile("cp.async.bulk.commit_group;" ::: "memory"); }
template <int N> __device__ __forceinline__ void bulk_wait() { asm volatile("cp.async.bulk.wait_group %0;" ::"n"(N) : "memory"); }
template <int N> __device__ __forceinline__ void bulk_wait_read() { asm volatile("cp.async.bulk.wait_group.read %0;" ::"n"(N) : "memory"); }
__device__ __forceinline__ void wg_fence() { asm volatile("wgmma.fence.sync.aligned;" ::: "memory"); }
__device__ __forceinline__ void wg_commit() { asm volatile("wgmma.commit_group.sync.aligned;" ::: "memory"); }
template <int N> __device__ __forceinline__ void wg_wait() { asm volatile("wgmma.wait_group.sync.aligned %0;" ::"n"(N) : "memory"); }
template <int R> __device__ __forceinline__ void reg_fence(float (&d)[R]) {
#pragma unroll
  for (int i = 0; i < R; i++) asm volatile("" : "+f"(d[i])::"memory");
}
template <int R> __device__ __forceinline__ void reg_fence(uint32_t (&d)[R]) {
#pragma unroll
  for (int i = 0; i < R; i++) asm volatile("" : "+r"(d[i])::"memory");
}
__device__ __forceinline__ void stsm4(uint32_t a, uint32_t r0, uint32_t r1, uint32_t r2, uint32_t r3) {
  asm volatile("stmatrix.sync.aligned.m8n8.x4.shared.b16 [%0], {%1, %2, %3, %4};" ::"r"(a), "r"(r0), "r"(r1), "r"(r2), "r"(r3) : "memory");
}
__device__ __forceinline__ void stsm4t(uint32_t a, uint32_t r0, uint32_t r1, uint32_t r2, uint32_t r3) {
  asm volatile("stmatrix.sync.aligned.m8n8.x4.trans.shared.b16 [%0], {%1, %2, %3, %4};" ::"r"(a), "r"(r0), "r"(r1), "r"(r2), "r"(r3) : "memory");
}
__device__ __forceinline__ void ldsm4(uint32_t a, uint32_t& r0, uint32_t& r1, uint32_t& r2, uint32_t& r3) {
  asm volatile("ldmatrix.sync.aligned.m8n8.x4.shared.b16 {%0, %1, %2, %3}, [%4];" : "=r"(r0), "=r"(r1), "=r"(r2), "=r"(r3) : "r"(a) : "memory");
}
__device__ __forceinline__ void ldg128(const uint4* p, uint32_t& a, uint32_t& b, uint32_t& c, uint32_t& d) {
  asm volatile("ld.global.nc.v4.u32 {%0, %1, %2, %3}, [%4];" : "=r"(a), "=r"(b), "=r"(c), "=r"(d) : "l"(p));
}
__device__ __forceinline__ uint32_t pack2(float lo, float hi) {
  uint32_t r;
  asm("cvt.rn.bf16x2.f32 %0, %1, %2;" : "=r"(r) : "f"(hi), "f"(lo));
  return r;
}
__device__ __forceinline__ float tanh_f32(float x) {
  float y;
  asm("tanh.approx.f32 %0, %1;" : "=f"(y) : "f"(x));
  return y;
}
__device__ __forceinline__ float gelu(float hx) {
  const float u = hx * fmaf(hx * hx, 8.0f * 0.044715f * 0.7978845608028654f, 2.0f * 0.7978845608028654f);
  return fmaf(hx, tanh_f32(u), hx);
}
__device__ __forceinline__ uint64_t mk_desc4(uint32_t addr4, uint32_t lbo, uint32_t sbo, uint32_t swz) {
  const uint32_t lo = addr4 + ((lbo >> 4) << 16), hi = (sbo >> 4) | (swz << 30);
  uint64_t d;
  asm("mov.b64 %0, {%1, %2};" : "=l"(d) : "r"(lo), "r"(hi));
  return d;
}
#define mk_desc(base, off, lbo, sbo, swz) mk_desc4((((base) & 0x3FFFF) >> 4) + ((off) >> 4), lbo, sbo, swz)

template <int SA, int SB, int TA, int TB>
__device__ __forceinline__ void wgmma_ss_16(float (&d)[8], uint64_t da, uint64_t db, int sd) {
  asm volatile("{\n.reg .pred p;\nsetp.ne.b32 p, %10, 0;\n"
      "wgmma.mma_async.sync.aligned.m64n16k16.f32.bf16.bf16 {"
      "%0, %1, %2, %3, %4, %5, %6, %7"
      "}, %8, %9, p, %11, %12, %13, %14;\n}\n"
      : "+f"(d[0]), "+f"(d[1]), "+f"(d[2]), "+f"(d[3]), "+f"(d[4]), "+f"(d[5]), "+f"(d[6]), "+f"(d[7])
      : "l"(da), "l"(db), "r"(sd), "n"(SA), "n"(SB), "n"(TA), "n"(TB));
}
template <int SA, int SB, int TA, int TB>
__device__ __forceinline__ void wgmma_ss_24(float (&d)[12], uint64_t da, uint64_t db, int sd) {
  asm volatile("{\n.reg .pred p;\nsetp.ne.b32 p, %14, 0;\n"
      "wgmma.mma_async.sync.aligned.m64n24k16.f32.bf16.bf16 {"
      "%0, %1, %2, %3, %4, %5, %6, %7, %8, %9, %10, %11"
      "}, %12, %13, p, %15, %16, %17, %18;\n}\n"
      : "+f"(d[0]), "+f"(d[1]), "+f"(d[2]), "+f"(d[3]), "+f"(d[4]), "+f"(d[5]), "+f"(d[6]), "+f"(d[7]), "+f"(d[8]),
        "+f"(d[9]), "+f"(d[10]), "+f"(d[11])
      : "l"(da), "l"(db), "r"(sd), "n"(SA), "n"(SB), "n"(TA), "n"(TB));
}
template <int SA, int SB, int TA, int TB>
__device__ __forceinline__ void wgmma_ss_128(float (&d)[64], uint64_t da, uint64_t db, int sd) {
  asm volatile("{\n.reg .pred p;\nsetp.ne.b32 p, %66, 0;\n"
      "wgmma.mma_async.sync.aligned.m64n128k16.f32.bf16.bf16 {"
      "%0, %1, %2, %3, %4, %5, %6, %7, %8, %9, %10, %11, %12, %13, %14, %15, %16, %17, %18, %19, %20, %21, %22, %23, "
      "%24, %25, %26, %27, %28, %29, %30, %31, %32, %33, %34, %35, %36, %37, %38, %39, %40, %41, %42, %43, %44, %45, "
      "%46, %47, %48, %49, %50, %51, %52, %53, %54, %55, %56, %57, %58, %59, %60, %61, %62, %63"
      "}, %64, %65, p, %67, %68, %69, %70;\n}\n"
      : "+f"(d[0]), "+f"(d[1]), "+f"(d[2]), "+f"(d[3]), "+f"(d[4]), "+f"(d[5]), "+f"(d[6]), "+f"(d[7]), "+f"(d[8]),
        "+f"(d[9]), "+f"(d[10]), "+f"(d[11]), "+f"(d[12]), "+f"(d[13]), "+f"(d[14]), "+f"(d[15]), "+f"(d[16]),
        "+f"(d[17]), "+f"(d[18]), "+f"(d[19]), "+f"(d[20]), "+f"(d[21]), "+f"(d[22]), "+f"(d[23]), "+f"(d[24]),
        "+f"(d[25]), "+f"(d[26]), "+f"(d[27]), "+f"(d[28]), "+f"(d[29]), "+f"(d[30]), "+f"(d[31]), "+f"(d[32]),
        "+f"(d[33]), "+f"(d[34]), "+f"(d[35]), "+f"(d[36]), "+f"(d[37]), "+f"(d[38]), "+f"(d[39]), "+f"(d[40]),
        "+f"(d[41]), "+f"(d[42]), "+f"(d[43]), "+f"(d[44]), "+f"(d[45]), "+f"(d[46]), "+f"(d[47]), "+f"(d[48]),
        "+f"(d[49]), "+f"(d[50]), "+f"(d[51]), "+f"(d[52]), "+f"(d[53]), "+f"(d[54]), "+f"(d[55]), "+f"(d[56]),
        "+f"(d[57]), "+f"(d[58]), "+f"(d[59]), "+f"(d[60]), "+f"(d[61]), "+f"(d[62]), "+f"(d[63])
      : "l"(da), "l"(db), "r"(sd), "n"(SA), "n"(SB), "n"(TA), "n"(TB));
}
template <int SA, int SB, int TA, int TB>
__device__ __forceinline__ void wgmma_ss_168(float (&d)[84], uint64_t da, uint64_t db, int sd) {
  asm volatile("{\n.reg .pred p;\nsetp.ne.b32 p, %86, 0;\n"
      "wgmma.mma_async.sync.aligned.m64n168k16.f32.bf16.bf16 {"
      "%0, %1, %2, %3, %4, %5, %6, %7, %8, %9, %10, %11, %12, %13, %14, %15, %16, %17, %18, %19, %20, %21, %22, %23, "
      "%24, %25, %26, %27, %28, %29, %30, %31, %32, %33, %34, %35, %36, %37, %38, %39, %40, %41, %42, %43, %44, %45, "
      "%46, %47, %48, %49, %50, %51, %52, %53, %54, %55, %56, %57, %58, %59, %60, %61, %62, %63, %64, %65, %66, %67, "
      "%68, %69, %70, %71, %72, %73, %74, %75, %76, %77, %78, %79, %80, %81, %82, %83"
      "}, %84, %85, p, %87, %88, %89, %90;\n}\n"
      : "+f"(d[0]), "+f"(d[1]), "+f"(d[2]), "+f"(d[3]), "+f"(d[4]), "+f"(d[5]), "+f"(d[6]), "+f"(d[7]), "+f"(d[8]),
        "+f"(d[9]), "+f"(d[10]), "+f"(d[11]), "+f"(d[12]), "+f"(d[13]), "+f"(d[14]), "+f"(d[15]), "+f"(d[16]),
        "+f"(d[17]), "+f"(d[18]), "+f"(d[19]), "+f"(d[20]), "+f"(d[21]), "+f"(d[22]), "+f"(d[23]), "+f"(d[24]),
        "+f"(d[25]), "+f"(d[26]), "+f"(d[27]), "+f"(d[28]), "+f"(d[29]), "+f"(d[30]), "+f"(d[31]), "+f"(d[32]),
        "+f"(d[33]), "+f"(d[34]), "+f"(d[35]), "+f"(d[36]), "+f"(d[37]), "+f"(d[38]), "+f"(d[39]), "+f"(d[40]),
        "+f"(d[41]), "+f"(d[42]), "+f"(d[43]), "+f"(d[44]), "+f"(d[45]), "+f"(d[46]), "+f"(d[47]), "+f"(d[48]),
        "+f"(d[49]), "+f"(d[50]), "+f"(d[51]), "+f"(d[52]), "+f"(d[53]), "+f"(d[54]), "+f"(d[55]), "+f"(d[56]),
        "+f"(d[57]), "+f"(d[58]), "+f"(d[59]), "+f"(d[60]), "+f"(d[61]), "+f"(d[62]), "+f"(d[63]), "+f"(d[64]),
        "+f"(d[65]), "+f"(d[66]), "+f"(d[67]), "+f"(d[68]), "+f"(d[69]), "+f"(d[70]), "+f"(d[71]), "+f"(d[72]),
        "+f"(d[73]), "+f"(d[74]), "+f"(d[75]), "+f"(d[76]), "+f"(d[77]), "+f"(d[78]), "+f"(d[79]), "+f"(d[80]),
        "+f"(d[81]), "+f"(d[82]), "+f"(d[83])
      : "l"(da), "l"(db), "r"(sd), "n"(SA), "n"(SB), "n"(TA), "n"(TB));
}
template <int SA, int SB, int TB>
__device__ __forceinline__ void wgmma_rs_64(float (&d)[32], uint32_t a0, uint32_t a1, uint32_t a2, uint32_t a3, uint64_t db, int sd) {
  asm volatile("{\n.reg .pred p;\nsetp.ne.b32 p, %37, 0;\n"
      "wgmma.mma_async.sync.aligned.m64n64k16.f32.bf16.bf16 {"
      "%0, %1, %2, %3, %4, %5, %6, %7, %8, %9, %10, %11, %12, %13, %14, %15, %16, %17, %18, %19, %20, %21, %22, %23, "
      "%24, %25, %26, %27, %28, %29, %30, %31"
      "}, {%32, %33, %34, %35}, %36, p, %38, %39, %40;\n}\n"
      : "+f"(d[0]), "+f"(d[1]), "+f"(d[2]), "+f"(d[3]), "+f"(d[4]), "+f"(d[5]), "+f"(d[6]), "+f"(d[7]), "+f"(d[8]),
        "+f"(d[9]), "+f"(d[10]), "+f"(d[11]), "+f"(d[12]), "+f"(d[13]), "+f"(d[14]), "+f"(d[15]), "+f"(d[16]),
        "+f"(d[17]), "+f"(d[18]), "+f"(d[19]), "+f"(d[20]), "+f"(d[21]), "+f"(d[22]), "+f"(d[23]), "+f"(d[24]),
        "+f"(d[25]), "+f"(d[26]), "+f"(d[27]), "+f"(d[28]), "+f"(d[29]), "+f"(d[30]), "+f"(d[31])
      : "r"(a0), "r"(a1), "r"(a2), "r"(a3), "l"(db), "r"(sd), "n"(SA), "n"(SB), "n"(TB));
}
template <int SA, int SB, int TB>
__device__ __forceinline__ void wgmma_rs_128(float (&d)[64], uint32_t a0, uint32_t a1, uint32_t a2, uint32_t a3, uint64_t db, int sd) {
  asm volatile("{\n.reg .pred p;\nsetp.ne.b32 p, %69, 0;\n"
      "wgmma.mma_async.sync.aligned.m64n128k16.f32.bf16.bf16 {"
      "%0, %1, %2, %3, %4, %5, %6, %7, %8, %9, %10, %11, %12, %13, %14, %15, %16, %17, %18, %19, %20, %21, %22, %23, "
      "%24, %25, %26, %27, %28, %29, %30, %31, %32, %33, %34, %35, %36, %37, %38, %39, %40, %41, %42, %43, %44, %45, "
      "%46, %47, %48, %49, %50, %51, %52, %53, %54, %55, %56, %57, %58, %59, %60, %61, %62, %63"
      "}, {%64, %65, %66, %67}, %68, p, %70, %71, %72;\n}\n"
      : "+f"(d[0]), "+f"(d[1]), "+f"(d[2]), "+f"(d[3]), "+f"(d[4]), "+f"(d[5]), "+f"(d[6]), "+f"(d[7]), "+f"(d[8]),
        "+f"(d[9]), "+f"(d[10]), "+f"(d[11]), "+f"(d[12]), "+f"(d[13]), "+f"(d[14]), "+f"(d[15]), "+f"(d[16]),
        "+f"(d[17]), "+f"(d[18]), "+f"(d[19]), "+f"(d[20]), "+f"(d[21]), "+f"(d[22]), "+f"(d[23]), "+f"(d[24]),
        "+f"(d[25]), "+f"(d[26]), "+f"(d[27]), "+f"(d[28]), "+f"(d[29]), "+f"(d[30]), "+f"(d[31]), "+f"(d[32]),
        "+f"(d[33]), "+f"(d[34]), "+f"(d[35]), "+f"(d[36]), "+f"(d[37]), "+f"(d[38]), "+f"(d[39]), "+f"(d[40]),
        "+f"(d[41]), "+f"(d[42]), "+f"(d[43]), "+f"(d[44]), "+f"(d[45]), "+f"(d[46]), "+f"(d[47]), "+f"(d[48]),
        "+f"(d[49]), "+f"(d[50]), "+f"(d[51]), "+f"(d[52]), "+f"(d[53]), "+f"(d[54]), "+f"(d[55]), "+f"(d[56]),
        "+f"(d[57]), "+f"(d[58]), "+f"(d[59]), "+f"(d[60]), "+f"(d[61]), "+f"(d[62]), "+f"(d[63])
      : "r"(a0), "r"(a1), "r"(a2), "r"(a3), "l"(db), "r"(sd), "n"(SA), "n"(SB), "n"(TB));
}
template <int SA, int SB, int TB>
__device__ __forceinline__ void wgmma_rs_256(float (&d)[128], uint32_t a0, uint32_t a1, uint32_t a2, uint32_t a3, uint64_t db, int sd) {
  asm volatile("{\n.reg .pred p;\nsetp.ne.b32 p, %133, 0;\n"
      "wgmma.mma_async.sync.aligned.m64n256k16.f32.bf16.bf16 {"
      "%0, %1, %2, %3, %4, %5, %6, %7, %8, %9, %10, %11, %12, %13, %14, %15, %16, %17, %18, %19, %20, %21, %22, %23, "
      "%24, %25, %26, %27, %28, %29, %30, %31, %32, %33, %34, %35, %36, %37, %38, %39, %40, %41, %42, %43, %44, %45, "
      "%46, %47, %48, %49, %50, %51, %52, %53, %54, %55, %56, %57, %58, %59, %60, %61, %62, %63, %64, %65, %66, %67, "
      "%68, %69, %70, %71, %72, %73, %74, %75, %76, %77, %78, %79, %80, %81, %82, %83, %84, %85, %86, %87, %88, %89, "
      "%90, %91, %92, %93, %94, %95, %96, %97, %98, %99, %100, %101, %102, %103, %104, %105, %106, %107, %108, %109, "
      "%110, %111, %112, %113, %114, %115, %116, %117, %118, %119, %120, %121, %122, %123, %124, %125, %126, %127"
      "}, {%128, %129, %130, %131}, %132, p, %134, %135, %136;\n}\n"
      : "+f"(d[0]), "+f"(d[1]), "+f"(d[2]), "+f"(d[3]), "+f"(d[4]), "+f"(d[5]), "+f"(d[6]), "+f"(d[7]), "+f"(d[8]),
        "+f"(d[9]), "+f"(d[10]), "+f"(d[11]), "+f"(d[12]), "+f"(d[13]), "+f"(d[14]), "+f"(d[15]), "+f"(d[16]),
        "+f"(d[17]), "+f"(d[18]), "+f"(d[19]), "+f"(d[20]), "+f"(d[21]), "+f"(d[22]), "+f"(d[23]), "+f"(d[24]),
        "+f"(d[25]), "+f"(d[26]), "+f"(d[27]), "+f"(d[28]), "+f"(d[29]), "+f"(d[30]), "+f"(d[31]), "+f"(d[32]),
        "+f"(d[33]), "+f"(d[34]), "+f"(d[35]), "+f"(d[36]), "+f"(d[37]), "+f"(d[38]), "+f"(d[39]), "+f"(d[40]),
        "+f"(d[41]), "+f"(d[42]), "+f"(d[43]), "+f"(d[44]), "+f"(d[45]), "+f"(d[46]), "+f"(d[47]), "+f"(d[48]),
        "+f"(d[49]), "+f"(d[50]), "+f"(d[51]), "+f"(d[52]), "+f"(d[53]), "+f"(d[54]), "+f"(d[55]), "+f"(d[56]),
        "+f"(d[57]), "+f"(d[58]), "+f"(d[59]), "+f"(d[60]), "+f"(d[61]), "+f"(d[62]), "+f"(d[63]), "+f"(d[64]),
        "+f"(d[65]), "+f"(d[66]), "+f"(d[67]), "+f"(d[68]), "+f"(d[69]), "+f"(d[70]), "+f"(d[71]), "+f"(d[72]),
        "+f"(d[73]), "+f"(d[74]), "+f"(d[75]), "+f"(d[76]), "+f"(d[77]), "+f"(d[78]), "+f"(d[79]), "+f"(d[80]),
        "+f"(d[81]), "+f"(d[82]), "+f"(d[83]), "+f"(d[84]), "+f"(d[85]), "+f"(d[86]), "+f"(d[87]), "+f"(d[88]),
        "+f"(d[89]), "+f"(d[90]), "+f"(d[91]), "+f"(d[92]), "+f"(d[93]), "+f"(d[94]), "+f"(d[95]), "+f"(d[96]),
        "+f"(d[97]), "+f"(d[98]), "+f"(d[99]), "+f"(d[100]), "+f"(d[101]), "+f"(d[102]), "+f"(d[103]), "+f"(d[104]),
        "+f"(d[105]), "+f"(d[106]), "+f"(d[107]), "+f"(d[108]), "+f"(d[109]), "+f"(d[110]), "+f"(d[111]),
        "+f"(d[112]), "+f"(d[113]), "+f"(d[114]), "+f"(d[115]), "+f"(d[116]), "+f"(d[117]), "+f"(d[118]),
        "+f"(d[119]), "+f"(d[120]), "+f"(d[121]), "+f"(d[122]), "+f"(d[123]), "+f"(d[124]), "+f"(d[125]),
        "+f"(d[126]), "+f"(d[127])
      : "r"(a0), "r"(a1), "r"(a2), "r"(a3), "l"(db), "r"(sd), "n"(SA), "n"(SB), "n"(TB));
}

__device__ const __align__(128) uint32_t c_img[3584] = {
    0x00003c80, 0x00003c80, 0x00003c80, 0x00003c80, 0x00003c80, 0x00003c80, 0x00003c80, 0x00003c80, 0x00003c80, 0x00003c80,
    0x00003c80, 0x00003c80, 0x00003c80, 0x00003c80, 0x00003c80, 0x00003c80, 0x00003c80, 0x00003c80, 0x00003c80, 0x00003c80,
    0x00003c80, 0x00003c80, 0x00003c80, 0x00003c80, 0x00003c80, 0x00003c80, 0x00003c80, 0x00003c80, 0x00003c80, 0x00003c80,
    0x00003c80, 0x00003c80, 0x3c463c22, 0x3c623bf1, 0x3c753b95, 0x3c7f3ac9, 0x3ac93c7f, 0x3b953c75, 0x3bf13c62, 0x3c223c46,
    0x3c22bc46, 0x3bf1bc62, 0x3b95bc75, 0x3ac9bc7f, 0x3c7fbac9, 0x3c75bb95, 0x3c62bbf1, 0x3c46bc22, 0xbc46bc22, 0xbc62bbf1,
    0xbc75bb95, 0xbc7fbac9, 0xbac9bc7f, 0xbb95bc75, 0xbbf1bc62, 0xbc22bc46, 0xbc223c46, 0xbbf13c62, 0xbb953c75, 0xbac93c7f,
    0xbc7f3ac9, 0xbc753b95, 0xbc623bf1, 0xbc463c22, 0xbb48bc7b, 0xbc0ebc55, 0xbc55bc0e, 0xbc7bbb48, 0xbc7b3b48, 0xbc553c0e,
    0xbc0e3c55, 0xbb483c7b, 0x3b483c7b, 0x3c0e3c55, 0x3c553c0e, 0x3c7b3b48, 0x3c7bbb48, 0x3c55bc0e, 0x3c0ebc55, 0x3b48bc7b,
    0xbb48bc7b, 0xbc0ebc55, 0xbc55bc0e, 0xbc7bbb48, 0xbc7b3b48, 0xbc553c0e, 0xbc0e3c55, 0xbb483c7b, 0x3b483c7b, 0x3c0e3c55,
    0x3c553c0e, 0x3c7b3b48, 0x3c7bbb48, 0x3c55bc0e, 0x3c0ebc55, 0x3b48bc7b, 0x3c623bf1, 0x3c7fbac9, 0x3c46bc22, 0x3b95bc75,
    0xbc753b95, 0xbc223c46, 0xbac93c7f, 0x3bf13c62, 0x3bf1bc62, 0xbac9bc7f, 0xbc22bc46, 0xbc75bb95, 0x3b953c75, 0x3c463c22,
    0x3c7f3ac9, 0x3c62bbf1, 0xbc62bbf1, 0xbc7f3ac9, 0xbc463c22, 0xbb953c75, 0x3c75bb95, 0x3c22bc46, 0x3ac9bc7f, 0xbbf1bc62,
    0xbbf13c62, 0x3ac93c7f, 0x3c223c46, 0x3c753b95, 0xbb95bc75, 0xbc46bc22, 0xbc7fbac9, 0xbc623bf1, 0x3bc43c6d, 0x3c6d3bc4,
    0x3c6dbbc4, 0x3bc4bc6d, 0xbbc4bc6d, 0xbc6dbbc4, 0xbc6d3bc4, 0xbbc43c6d, 0x3bc43c6d, 0x3c6d3bc4, 0x3c6dbbc4, 0x3bc4bc6d,
    0xbbc4bc6d, 0xbc6dbbc4, 0xbc6d3bc4, 0xbbc43c6d, 0x3bc43c6d, 0x3c6d3bc4, 0x3c6dbbc4, 0x3bc4bc6d, 0xbbc4bc6d, 0xbc6dbbc4,
    0xbc6d3bc4, 0xbbc43c6d, 0x3bc43c6d, 0x3c6d3bc4, 0x3c6dbbc4, 0x3bc4bc6d, 0xbbc4bc6d, 0xbc6dbbc4, 0xbc6d3bc4, 0xbbc43c6d,
    0x3c753b95, 0x3c46bc22, 0xbac9bc7f, 0xbc62bbf1, 0xbbf1bc62, 0xbc7fbac9, 0xbc223c46, 0x3b953c75, 0x3b95bc75, 0xbc22bc46,
    0xbc7f3ac9, 0xbbf13c62, 0xbc623bf1, 0xbac93c7f, 0x3c463c22, 0x3c75bb95, 0xbc75bb95, 0xbc463c22, 0x3ac93c7f, 0x3c623bf1,
    0x3bf13c62, 0x3c7f3ac9, 0x3c22bc46, 0xbb95bc75, 0xbb953c75, 0x3c223c46, 0x3c7fbac9, 0x3bf1bc62, 0x3c62bbf1, 0x3ac9bc7f,
    0xbc46bc22, 0xbc753b95, 0xbc0ebc55, 0xbc7b3b48, 0xbb483c7b, 0x3c553c0e, 0x3c55bc0e, 0xbb48bc7b, 0xbc7bbb48, 0xbc0e3c55,
    0x3c0e3c55, 0x3c7bbb48, 0x3b48bc7b, 0xbc55bc0e, 0xbc553c0e, 0x3b483c7b, 0x3c7b3b48, 0x3c0ebc55, 0xbc0ebc55, 0xbc7b3b48,
    0xbb483c7b, 0x3c553c0e, 0x3c55bc0e, 0xbb48bc7b, 0xbc7bbb48, 0xbc0e3c55, 0x3c0e3c55, 0x3c7bbb48, 0x3b48bc7b, 0xbc55bc0e,
    0xbc553c0e, 0x3b483c7b, 0x3c7b3b48, 0x3c0ebc55, 0x3c7f3ac9, 0x3b95bc75, 0xbc62bbf1, 0xbc223c46, 0x3c46bc22, 0xbbf1bc62,
    0xbc753b95, 0x3ac93c7f, 0x3ac9bc7f, 0xbc75bb95, 0xbbf13c62, 0x3c463c22, 0xbc22bc46, 0xbc623bf1, 0x3b953c75, 0x3c7fbac9,
    0xbc7fbac9, 0xbb953c75, 0x3c623bf1, 0x3c22bc46, 0xbc463c22, 0x3bf13c62, 0x3c75bb95, 0xbac9bc7f, 0xbac93c7f, 0x3c753b95,
    0x3bf1bc62, 0xbc46bc22, 0x3c223c46, 0x3c62bbf1, 0xbb95bc75, 0xbc7f3ac9, 0x3a493c80, 0x3b163c7d, 0x3b793c78, 0x3bac3c71,
    0x3bdb3c67, 0x3c043c5c, 0x3c183c4e, 0x3c2c3c3e, 0x3c3e3c2c, 0x3c4e3c18, 0x3c5c3c04, 0x3c673bdb, 0x3c713bac, 0x3c783b79,
    0x3c7d3b16, 0x3c803a49, 0x3c80ba49, 0x3c7dbb16, 0x3c78bb79, 0x3c71bbac, 0x3c67bbdb, 0x3c5cbc04, 0x3c4ebc18, 0x3c3ebc2c,
    0x3c2cbc3e, 0x3c18bc4e, 0x3c04bc5c, 0x3bdbbc67, 0x3bacbc71, 0x3b79bc78, 0x3b16bc7d, 0x3a49bc80, 0x3c783b79, 0x3c80ba49,
    0x3c71bbac, 0x3c4ebc18, 0x3b163c7d, 0x3bdb3c67, 0x3c2c3c3e, 0x3c5c3c04, 0xbc04bc5c, 0xbc3ebc2c, 0xbc67bbdb, 0xbc7dbb16,
    0x3c18bc4e, 0x3bacbc71, 0x3a49bc80, 0xbb79bc78, 0xbb793c78, 0x3a493c80, 0x3bac3c71, 0x3c183c4e, 0xbc7d3b16, 0xbc673bdb,
    0xbc3e3c2c, 0xbc043c5c, 0x3c5cbc04, 0x3c2cbc3e, 0x3bdbbc67, 0x3b16bc7d, 0x3c4e3c18, 0x3c713bac, 0x3c803a49, 0x3c78bb79,
    0xbc5cbc04, 0xbc80ba49, 0xbc673bdb, 0xbc183c4e, 0xbb163c7d, 0x3bac3c71, 0x3c3e3c2c, 0x3c783b79, 0x3b793c78, 0x3c2c3c3e,
    0x3c713bac, 0x3c7dbb16, 0x3c4ebc18, 0x3bdbbc67, 0xba49bc80, 0xbc04bc5c, 0xbc043c5c, 0xba493c80, 0x3bdb3c67, 0x3c4e3c18,
    0x3c7d3b16, 0x3c71bbac, 0x3c2cbc3e, 0x3b79bc78, 0x3c78bb79, 0x3c3ebc2c, 0x3bacbc71, 0xbb16bc7d, 0xbc18bc4e, 0xbc67bbdb,
    0xbc803a49, 0xbc5c3c04, 0x3c3ebc2c, 0x3b16bc7d, 0xbc04bc5c, 0xbc71bbac, 0xbbdb3c67, 0x3b793c78, 0x3c4e3c18, 0x3c80ba49,
    0x3a49bc80, 0xbc18bc4e, 0xbc78bb79, 0xbc673bdb, 0x3bac3c71, 0x3c5c3c04, 0x3c7dbb16, 0x3c2cbc3e, 0x3c2c3c3e, 0x3c7d3b16,
    0x3c5cbc04, 0x3bacbc71, 0xbc67bbdb, 0xbc783b79, 0xbc183c4e, 0x3a493c80, 0x3c803a49, 0x3c4ebc18, 0x3b79bc78, 0xbbdbbc67,
    0xbc713bac, 0xbc043c5c, 0x3b163c7d, 0x3c3e3c2c, 0x3c67bbdb, 0x3b79bc78, 0xbc18bc4e, 0xbc80ba49, 0xbc2c3c3e, 0x3b163c7d,
    0x3c5c3c04, 0x3c71bbac, 0x3bacbc71, 0xbc04bc5c, 0xbc7dbb16, 0xbc3e3c2c, 0x3a493c80, 0x3c4e3c18, 0x3c78bb79, 0x3bdbbc67,
    0x3bdb3c67, 0x3c783b79, 0x3c4ebc18, 0x3a49bc80, 0xbc3ebc2c, 0xbc7d3b16, 0xbc043c5c, 0x3bac3c71, 0x3c713bac, 0x3c5cbc04,
    0x3b16bc7d, 0xbc2cbc3e, 0xbc803a49, 0xbc183c4e, 0x3b793c78, 0x3c673bdb, 0xbb16bc7d, 0xbc71bbac, 0xbc3e3c2c, 0x3b793c78,
    0xbc5c3c04, 0x3a493c80, 0x3c673bdb, 0x3c4ebc18, 0xbc183c4e, 0x3bdb3c67, 0x3c803a49, 0x3c04bc5c, 0x3c783b79, 0x3c2cbc3e,
    0xbbacbc71, 0xbc7dbb16, 0xbc7d3b16, 0xbbac3c71, 0x3c2c3c3e, 0x3c78bb79, 0x3c043c5c, 0x3c80ba49, 0x3bdbbc67, 0xbc18bc4e,
    0x3c4e3c18, 0x3c67bbdb, 0x3a49bc80, 0xbc5cbc04, 0x3b79bc78, 0xbc3ebc2c, 0xbc713bac, 0xbb163c7d, 0xbb163c7d, 0x3c673bdb,
    0x3c2cbc3e, 0xbc04bc5c, 0xbc783b79, 0xba493c80, 0x3c713bac, 0x3c18bc4e, 0x3c4ebc18, 0xbbacbc71, 0xbc803a49, 0xbb793c78,
    0x3c5c3c04, 0x3c3ebc2c, 0xbbdbbc67, 0xbc7d3b16, 0xbc7dbb16, 0xbbdb3c67, 0x3c3e3c2c, 0x3c5cbc04, 0xbb79bc78, 0xbc80ba49,
    0xbbac3c71, 0x3c4e3c18, 0x3c183c4e, 0x3c71bbac, 0xba49bc80, 0xbc78bb79, 0xbc043c5c, 0x3c2c3c3e, 0x3c67bbdb, 0xbb16bc7d,
    0xbc67bbdb, 0xbc043c5c, 0x3c4e3c18, 0x3c2cbc3e, 0xbc80ba49, 0xbb163c7d, 0x3c783b79, 0x3bacbc71, 0xbc713bac, 0x3b793c78,
    0x3c7dbb16, 0xba49bc80, 0xbc3e3c2c, 0x3c183c4e, 0x3c5cbc04, 0xbbdbbc67, 0xbbdb3c67, 0x3c5c3c04, 0x3c18bc4e, 0xbc3ebc2c,
    0xba493c80, 0x3c7d3b16, 0x3b79bc78, 0xbc71bbac, 0x3bac3c71, 0x3c78bb79, 0xbb16bc7d, 0xbc803a49, 0x3c2c3c3e, 0x3c4ebc18,
    0xbc04bc5c, 0xbc673bdb, 0x3c353c35, 0x3c35bc35, 0xbc35bc35, 0xbc353c35, 0x3c353c35, 0x3c35bc35, 0xbc35bc35, 0xbc353c35,
    0x3c353c35, 0x3c35bc35, 0xbc35bc35, 0xbc353c35, 0x3c353c35, 0x3c35bc35, 0xbc35bc35, 0xbc353c35, 0x3c353c35, 0x3c35bc35,
    0xbc35bc35, 0xbc353c35, 0x3c353c35, 0x3c35bc35, 0xbc35bc35, 0xbc353c35, 0x3c353c35, 0x3c35bc35, 0xbc35bc35, 0xbc353c35,
    0x3c353c35, 0x3c35bc35, 0xbc35bc35, 0xbc353c35, 0x3c7fbac9, 0xbb95bc75, 0xbc623bf1, 0x3c223c46, 0x3c463c22, 0x3bf1bc62,
    0xbc75bb95, 0xbac93c7f, 0xbac9bc7f, 0xbc753b95, 0x3bf13c62, 0x3c46bc22, 0x3c22bc46, 0xbc62bbf1, 0xbb953c75, 0x3c7f3ac9,
    0xbc7f3ac9, 0x3b953c75, 0x3c62bbf1, 0xbc22bc46, 0xbc46bc22, 0xbbf13c62, 0x3c753b95, 0x3ac9bc7f, 0x3ac93c7f, 0x3c75bb95,
    0xbbf1bc62, 0xbc463c22, 0xbc223c46, 0x3c623bf1, 0x3b95bc75, 0xbc7fbac9, 0xbc55bc0e, 0xbb483c7b, 0x3c7bbb48, 0xbc0ebc55,
    0xbc0e3c55, 0x3c7b3b48, 0xbb48bc7b, 0xbc553c0e, 0x3c553c0e, 0x3b48bc7b, 0xbc7b3b48, 0x3c0e3c55, 0x3c0ebc55, 0xbc7bbb48,
    0x3b483c7b, 0x3c55bc0e, 0xbc55bc0e, 0xbb483c7b, 0x3c7bbb48, 0xbc0ebc55, 0xbc0e3c55, 0x3c7b3b48, 0xbb48bc7b, 0xbc553c0e,
    0x3c553c0e, 0x3b48bc7b, 0xbc7b3b48, 0x3c0e3c55, 0x3c0ebc55, 0xbc7bbb48, 0x3b483c7b, 0x3c55bc0e, 0x3c75bb95, 0xbc46bc22,
    0xbac93c7f, 0x3c62bbf1, 0xbbf13c62, 0x3c7fbac9, 0xbc22bc46, 0xbb953c75, 0xbb95bc75, 0xbc223c46, 0x3c7f3ac9, 0xbbf1bc62,
    0x3c623bf1, 0xbac9bc7f, 0xbc463c22, 0x3c753b95, 0xbc753b95, 0x3c463c22, 0x3ac9bc7f, 0xbc623bf1, 0x3bf1bc62, 0xbc7f3ac9,
    0x3c223c46, 0x3b95bc75, 0x3b953c75, 0x3c22bc46, 0xbc7fbac9, 0x3bf13c62, 0xbc62bbf1, 0x3ac93c7f, 0x3c46bc22, 0xbc75bb95,
    0x3c6d3bc4, 0xbbc4bc6d, 0xbbc43c6d, 0x3c6dbbc4, 0xbc6dbbc4, 0x3bc43c6d, 0x3bc4bc6d, 0xbc6d3bc4, 0x3c6d3bc4, 0xbbc4bc6d,
    0xbbc43c6d, 0x3c6dbbc4, 0xbc6dbbc4, 0x3bc43c6d, 0x3bc4bc6d, 0xbc6d3bc4, 0x3c6d3bc4, 0xbbc4bc6d, 0xbbc43c6d, 0x3c6dbbc4,
    0xbc6dbbc4, 0x3bc43c6d, 0x3bc4bc6d, 0xbc6d3bc4, 0x3c6d3bc4, 0xbbc4bc6d, 0xbbc43c6d, 0x3c6dbbc4, 0xbc6dbbc4, 0x3bc43c6d,
    0x3bc4bc6d, 0xbc6d3bc4, 0x3c62bbf1, 0xbc7fbac9, 0x3c463c22, 0xbb95bc75, 0xbc75bb95, 0x3c223c46, 0xbac9bc7f, 0xbbf13c62,
    0xbbf1bc62, 0xbac93c7f, 0x3c22bc46, 0xbc753b95, 0xbb953c75, 0x3c46bc22, 0xbc7f3ac9, 0x3c623bf1, 0xbc623bf1, 0x3c7f3ac9,
    0xbc46bc22, 0x3b953c75, 0x3c753b95, 0xbc22bc46, 0x3ac93c7f, 0x3bf1bc62, 0x3bf13c62, 0x3ac9bc7f, 0xbc223c46, 0x3c75bb95,
    0x3b95bc75, 0xbc463c22, 0x3c7fbac9, 0xbc62bbf1, 0xbc7bbb48, 0x3c553c0e, 0xbc0ebc55, 0x3b483c7b, 0x3b48bc7b, 0xbc0e3c55,
    0x3c55bc0e, 0xbc7b3b48, 0x3c7b3b48, 0xbc55bc0e, 0x3c0e3c55, 0xbb48bc7b, 0xbb483c7b, 0x3c0ebc55, 0xbc553c0e, 0x3c7bbb48,
    0xbc7bbb48, 0x3c553c0e, 0xbc0ebc55, 0x3b483c7b, 0x3b48bc7b, 0xbc0e3c55, 0x3c55bc0e, 0xbc7b3b48, 0x3c7b3b48, 0xbc55bc0e,
    0x3c0e3c55, 0xbb48bc7b, 0xbb483c7b, 0x3c0ebc55, 0xbc553c0e, 0x3c7bbb48, 0x3c46bc22, 0xbc623bf1, 0x3c75bb95, 0xbc7f3ac9,
    0x3ac9bc7f, 0xbb953c75, 0x3bf1bc62, 0xbc223c46, 0xbc22bc46, 0x3bf13c62, 0xbb95bc75, 0x3ac93c7f, 0xbc7fbac9, 0x3c753b95,
    0xbc62bbf1, 0x3c463c22, 0xbc463c22, 0x3c62bbf1, 0xbc753b95, 0x3c7fbac9, 0xbac93c7f, 0x3b95bc75, 0xbbf13c62, 0x3c22bc46,
    0x3c223c46, 0xbbf1bc62, 0x3b953c75, 0xbac9bc7f, 0x3c7f3ac9, 0xbc75bb95, 0x3c623bf1, 0xbc46bc22, 0x3c3e3c2c, 0x3c18bc4e,
    0xbc5cbc04, 0xbbdb3c67, 0x3c713bac, 0x3b79bc78, 0xbc7dbb16, 0xba493c80, 0x3c80ba49, 0xbb16bc7d, 0xbc783b79, 0x3bac3c71,
    0x3c67bbdb, 0xbc04bc5c, 0xbc4e3c18, 0x3c2c3c3e, 0x3c2cbc3e, 0xbc4ebc18, 0xbc043c5c, 0x3c673bdb, 0x3bacbc71, 0xbc78bb79,
    0xbb163c7d, 0x3c803a49, 0xba49bc80, 0xbc7d3b16, 0x3b793c78, 0x3c71bbac, 0xbbdbbc67, 0xbc5c3c04, 0x3c183c4e, 0x3c3ebc2c,
    0x3c5cbc04, 0xbc3ebc2c, 0xbbdb3c67, 0x3c7d3b16, 0x3c4e3c18, 0x3bacbc71, 0xbc80ba49, 0x3b793c78, 0xbc78bb79, 0x3a493c80,
    0x3c71bbac, 0xbc18bc4e, 0xbb16bc7d, 0xbc673bdb, 0x3c2c3c3e, 0x3c04bc5c, 0x3c043c5c, 0x3c2cbc3e, 0xbc67bbdb, 0xbb163c7d,
    0xbc183c4e, 0x3c713bac, 0x3a49bc80, 0xbc783b79, 0x3b79bc78, 0xbc803a49, 0x3bac3c71, 0x3c4ebc18, 0x3c7dbb16, 0xbbdbbc67,
    0xbc3e3c2c, 0x3c5c3c04, 0xbc783b79, 0x3c2c3c3e, 0x3bacbc71, 0xbc7d3b16, 0x3c183c4e, 0x3bdbbc67, 0xbc803a49, 0x3c043c5c,
    0x3c5c3c04, 0x3a49bc80, 0xbc673bdb, 0x3c4e3c18, 0x3b16bc7d, 0xbc713bac, 0x3c3e3c2c, 0x3b79bc78, 0x3b793c78, 0x3c3ebc2c,
    0xbc71bbac, 0x3b163c7d, 0x3c4ebc18, 0xbc67bbdb, 0x3a493c80, 0x3c5cbc04, 0x3c04bc5c, 0xbc80ba49, 0x3bdb3c67, 0x3c18bc4e,
    0xbc7dbb16, 0x3bac3c71, 0x3c2cbc3e, 0xbc78bb79, 0x3a49bc80, 0xbc4e3c18, 0x3c783b79, 0xbbdbbc67, 0x3bac3c71, 0x3c04bc5c,
    0xbc7d3b16, 0x3c3e3c2c, 0xbc2cbc3e, 0xbb163c7d, 0x3c5cbc04, 0xbc71bbac, 0x3c673bdb, 0xbb79bc78, 0xbc183c4e, 0x3c80ba49,
    0x3c803a49, 0xbc18bc4e, 0xbb793c78, 0x3c67bbdb, 0xbc713bac, 0x3c5c3c04, 0xbb16bc7d, 0xbc2c3c3e, 0x3c3ebc2c, 0xbc7dbb16,
    0x3c043c5c, 0x3bacbc71, 0xbbdb3c67, 0x3c78bb79, 0xbc4ebc18, 0x3a493c80, 0x3bacbc71, 0xbc5c3c04, 0x3c7d3b16, 0xbc2cbc3e,
    0x3a493c80, 0x3c18bc4e, 0xbc783b79, 0x3c673bdb, 0xbbdbbc67, 0xbb793c78, 0x3c4ebc18, 0xbc80ba49, 0x3c3e3c2c, 0xbb16bc7d,
    0xbc043c5c, 0x3c71bbac, 0x3c713bac, 0xbc04bc5c, 0xbb163c7d, 0x3c3ebc2c, 0xbc803a49, 0x3c4e3c18, 0xbb79bc78, 0xbbdb3c67,
    0x3c67bbdb, 0xbc78bb79, 0x3c183c4e, 0x3a49bc80, 0xbc2c3c3e, 0x3c7dbb16, 0xbc5cbc04, 0x3bac3c71, 0xbc4ebc18, 0x3bdb3c67,
    0x3a49bc80, 0xbc043c5c, 0xbb793c78, 0x3c2cbc3e, 0xbc713bac, 0x3c7d3b16, 0x3b163c7d, 0x3bacbc71, 0xbc3e3c2c, 0x3c78bb79,
    0x3c5cbc04, 0xbc803a49, 0x3c673bdb, 0xbc18bc4e, 0xbc183c4e, 0x3c67bbdb, 0xbc80ba49, 0x3c5c3c04, 0x3c783b79, 0xbc3ebc2c,
    0x3bac3c71, 0x3b16bc7d, 0x3c7dbb16, 0xbc71bbac, 0x3c2c3c3e, 0xbb79bc78, 0xbc04bc5c, 0x3a493c80, 0x3bdbbc67, 0xbc4e3c18,
    0x3c183c4e, 0xbbacbc71, 0x3a493c80, 0x3b79bc78, 0xbc043c5c, 0x3c3ebc2c, 0xbc673bdb, 0x3c7dbb16, 0x3b16bc7d, 0xbbdb3c67,
    0x3c2cbc3e, 0xbc5c3c04, 0x3c78bb79, 0xbc80ba49, 0x3c713bac, 0xbc4ebc18, 0xbc4e3c18, 0x3c71bbac, 0xbc803a49, 0x3c783b79,
    0xbc5cbc04, 0x3c2c3c3e, 0xbbdbbc67, 0x3b163c7d, 0x3c7d3b16, 0xbc67bbdb, 0x3c3e3c2c, 0xbc04bc5c, 0x3b793c78, 0x3a49bc80,
    0xbbac3c71, 0x3c18bc4e, 0xbc713bac, 0x3c78bb79, 0xbc7d3b16, 0x3c80ba49, 0xbc3e3c2c, 0x3c4ebc18, 0xbc5c3c04, 0x3c67bbdb,
    0xbbdb3c67, 0x3c04bc5c, 0xbc183c4e, 0x3c2cbc3e, 0xba493c80, 0x3b16bc7d, 0xbb793c78, 0x3bacbc71, 0x3bac3c71, 0xbb79bc78,
    0x3b163c7d, 0xba49bc80, 0x3c2c3c3e, 0xbc18bc4e, 0x3c043c5c, 0xbbdbbc67, 0x3c673bdb, 0xbc5cbc04, 0x3c4e3c18, 0xbc3ebc2c,
    0x3c803a49, 0xbc7dbb16, 0x3c783b79, 0xbc71bbac, 0x3c800000, 0xbc800000, 0x3c800000, 0xbc800000, 0x3c800000, 0xbc800000,
    0x3c800000, 0xbc800000, 0x3c800000, 0xbc800000, 0x3c800000, 0xbc800000, 0x3c800000, 0xbc800000, 0x3c800000, 0xbc800000,
    0x3c800000, 0xbc800000, 0x3c800000, 0xbc800000, 0x3c800000, 0xbc800000, 0x3c800000, 0xbc800000, 0x3c800000, 0xbc800000,
    0x3c800000, 0xbc800000, 0x3c800000, 0xbc800000, 0x3c800000, 0xbc800000, 0x3c22bc46, 0xbbf13c62, 0x3b95bc75, 0xbac93c7f,
    0x3c7fbac9, 0xbc753b95, 0x3c62bbf1, 0xbc463c22, 0xbc46bc22, 0x3c623bf1, 0xbc75bb95, 0x3c7f3ac9, 0xbac9bc7f, 0x3b953c75,
    0xbbf1bc62, 0x3c223c46, 0xbc223c46, 0x3bf1bc62, 0xbb953c75, 0x3ac9bc7f, 0xbc7f3ac9, 0x3c75bb95, 0xbc623bf1, 0x3c46bc22,
    0x3c463c22, 0xbc62bbf1, 0x3c753b95, 0xbc7fbac9, 0x3ac93c7f, 0xbb95bc75, 0x3bf13c62, 0xbc22bc46, 0xbc7b3b48, 0x3c55bc0e,
    0xbc0e3c55, 0x3b48bc7b, 0x3b483c7b, 0xbc0ebc55, 0x3c553c0e, 0xbc7bbb48, 0x3c7bbb48, 0xbc553c0e, 0x3c0ebc55, 0xbb483c7b,
    0xbb48bc7b, 0x3c0e3c55, 0xbc55bc0e, 0x3c7b3b48, 0xbc7b3b48, 0x3c55bc0e, 0xbc0e3c55, 0x3b48bc7b, 0x3b483c7b, 0xbc0ebc55,
    0x3c553c0e, 0xbc7bbb48, 0x3c7bbb48, 0xbc553c0e, 0x3c0ebc55, 0xbb483c7b, 0xbb48bc7b, 0x3c0e3c55, 0xbc55bc0e, 0x3c7b3b48,
    0x3bf1bc62, 0x3ac93c7f, 0xbc22bc46, 0x3c753b95, 0x3b953c75, 0xbc46bc22, 0x3c7f3ac9, 0xbc623bf1, 0xbc62bbf1, 0x3c7fbac9,
    0xbc463c22, 0x3b95bc75, 0x3c75bb95, 0xbc223c46, 0x3ac9bc7f, 0x3bf13c62, 0xbbf13c62, 0xbac9bc7f, 0x3c223c46, 0xbc75bb95,
    0xbb95bc75, 0x3c463c22, 0xbc7fbac9, 0x3c62bbf1, 0x3c623bf1, 0xbc7f3ac9, 0x3c46bc22, 0xbb953c75, 0xbc753b95, 0x3c22bc46,
    0xbac93c7f, 0xbbf1bc62, 0x3c6dbbc4, 0xbbc43c6d, 0xbbc4bc6d, 0x3c6d3bc4, 0xbc6d3bc4, 0x3bc4bc6d, 0x3bc43c6d, 0xbc6dbbc4,
    0x3c6dbbc4, 0xbbc43c6d, 0xbbc4bc6d, 0x3c6d3bc4, 0xbc6d3bc4, 0x3bc4bc6d, 0x3bc43c6d, 0xbc6dbbc4, 0x3c6dbbc4, 0xbbc43c6d,
    0xbbc4bc6d, 0x3c6d3bc4, 0xbc6d3bc4, 0x3bc4bc6d, 0x3bc43c6d, 0xbc6dbbc4, 0x3c6dbbc4, 0xbbc43c6d, 0xbbc4bc6d, 0x3c6d3bc4,
    0xbc6d3bc4, 0x3bc4bc6d, 0x3bc43c6d, 0xbc6dbbc4, 0x3b95bc75, 0x3c223c46, 0xbc7f3ac9, 0x3bf1bc62, 0xbc623bf1, 0x3ac9bc7f,
    0x3c463c22, 0xbc753b95, 0xbc75bb95, 0x3c46bc22, 0x3ac93c7f, 0xbc62bbf1, 0x3bf13c62, 0xbc7fbac9, 0x3c22bc46, 0x3b953c75,
    0xbb953c75, 0xbc22bc46, 0x3c7fbac9, 0xbbf13c62, 0x3c62bbf1, 0xbac93c7f, 0xbc46bc22, 0x3c75bb95, 0x3c753b95, 0xbc463c22,
    0xbac9bc7f, 0x3c623bf1, 0xbbf1bc62, 0x3c7f3ac9, 0xbc223c46, 0xbb95bc75, 0xbc553c0e, 0xbb48bc7b, 0x3c7b3b48, 0xbc0e3c55,
    0xbc0ebc55, 0x3c7bbb48, 0xbb483c7b, 0xbc55bc0e, 0x3c55bc0e, 0x3b483c7b, 0xbc7bbb48, 0x3c0ebc55, 0x3c0e3c55, 0xbc7b3b48,
    0x3b48bc7b, 0x3c553c0e, 0xbc553c0e, 0xbb48bc7b, 0x3c7b3b48, 0xbc0e3c55, 0xbc0ebc55, 0x3c7bbb48, 0xbb483c7b, 0xbc55bc0e,
    0x3c55bc0e, 0x3b483c7b, 0xbc7bbb48, 0x3c0ebc55, 0x3c0e3c55, 0xbc7b3b48, 0x3b48bc7b, 0x3c553c0e, 0x3ac9bc7f, 0x3c753b95,
    0xbbf13c62, 0xbc46bc22, 0xbc22bc46, 0x3c62bbf1, 0x3b953c75, 0xbc7f3ac9, 0xbc7fbac9, 0x3b95bc75, 0x3c623bf1, 0xbc223c46,
    0xbc463c22, 0xbbf1bc62, 0x3c75bb95, 0x3ac93c7f, 0xbac93c7f, 0xbc75bb95, 0x3bf1bc62, 0x3c463c22, 0x3c223c46, 0xbc623bf1,
    0xbb95bc75, 0x3c7fbac9, 0x3c7f3ac9, 0xbb953c75, 0xbc62bbf1, 0x3c22bc46, 0x3c46bc22, 0x3bf13c62, 0xbc753b95, 0xbac9bc7f,
    0x3c80ba49, 0xbc7d3b16, 0x3c78bb79, 0xbc713bac, 0x3c67bbdb, 0xbc5c3c04, 0x3c4ebc18, 0xbc3e3c2c, 0x3c2cbc3e, 0xbc183c4e,
    0x3c04bc5c, 0xbbdb3c67, 0x3bacbc71, 0xbb793c78, 0x3b16bc7d, 0xba493c80, 0xba49bc80, 0x3b163c7d, 0xbb79bc78, 0x3bac3c71,
    0xbbdbbc67, 0x3c043c5c, 0xbc18bc4e, 0x3c2c3c3e, 0xbc3ebc2c, 0x3c4e3c18, 0xbc5cbc04, 0x3c673bdb, 0xbc71bbac, 0x3c783b79,
    0xbc7dbb16, 0x3c803a49, 0x3b79bc78, 0x3a493c80, 0xbbacbc71, 0x3c183c4e, 0x3c7dbb16, 0xbc673bdb, 0x3c3ebc2c, 0xbc043c5c,
    0xbc5c3c04, 0x3c2cbc3e, 0xbbdb3c67, 0x3b16bc7d, 0xbc4ebc18, 0x3c713bac, 0xbc80ba49, 0x3c78bb79, 0x3c783b79, 0xbc803a49,
    0x3c71bbac, 0xbc4e3c18, 0x3b163c7d, 0xbbdbbc67, 0x3c2c3c3e, 0xbc5cbc04, 0xbc04bc5c, 0x3c3e3c2c, 0xbc67bbdb, 0x3c7d3b16,
    0x3c18bc4e, 0xbbac3c71, 0x3a49bc80, 0x3b793c78, 0xbc043c5c, 0x3a49bc80, 0x3bdb3c67, 0xbc4ebc18, 0x3c7d3b16, 0xbc713bac,
    0x3c2cbc3e, 0xbb793c78, 0x3c78bb79, 0xbc3e3c2c, 0x3bacbc71, 0x3b163c7d, 0xbc18bc4e, 0x3c673bdb, 0xbc803a49, 0x3c5cbc04,
    0x3c5c3c04, 0xbc80ba49, 0x3c67bbdb, 0xbc183c4e, 0x3b16bc7d, 0x3bac3c71, 0xbc3ebc2c, 0x3c783b79, 0xbb79bc78, 0x3c2c3c3e,
    0xbc71bbac, 0x3c7dbb16, 0xbc4e3c18, 0x3bdbbc67, 0x3a493c80, 0xbc04bc5c, 0xbc2cbc3e, 0x3c7d3b16, 0xbc5c3c04, 0x3bacbc71,
    0x3c673bdb, 0xbc783b79, 0x3c18bc4e, 0x3a493c80, 0xbc80ba49, 0x3c4ebc18, 0xbb793c78, 0xbbdbbc67, 0x3c71bbac, 0xbc043c5c,
    0xbb16bc7d, 0x3c3e3c2c, 0x3c3ebc2c, 0xbb163c7d, 0xbc04bc5c, 0x3c713bac, 0xbbdb3c67, 0xbb79bc78, 0x3c4e3c18, 0xbc803a49,
    0x3a49bc80, 0x3c183c4e, 0xbc78bb79, 0x3c67bbdb, 0x3bac3c71, 0xbc5cbc04, 0x3c7dbb16, 0xbc2c3c3e, 0xbbdbbc67, 0x3c783b79,
    0xbc4e3c18, 0x3a49bc80, 0x3c3e3c2c, 0xbc7d3b16, 0x3c04bc5c, 0x3bac3c71, 0xbc71bbac, 0x3c5cbc04, 0xbb163c7d, 0xbc2cbc3e,
    0x3c80ba49, 0xbc183c4e, 0xbb79bc78, 0x3c673bdb, 0x3c67bbdb, 0xbb793c78, 0xbc18bc4e, 0x3c803a49, 0xbc2c3c3e, 0xbb16bc7d,
    0x3c5c3c04, 0xbc713bac, 0x3bacbc71, 0x3c043c5c, 0xbc7dbb16, 0x3c3ebc2c, 0x3a493c80, 0xbc4ebc18, 0x3c78bb79, 0xbbdb3c67,
    0xbc7d3b16, 0x3bacbc71, 0x3c2c3c3e, 0xbc783b79, 0x3c043c5c, 0xbc803a49, 0x3bdbbc67, 0x3c183c4e, 0x3c4e3c18, 0xbc673bdb,
    0x3a49bc80, 0x3c5c3c04, 0x3b79bc78, 0x3c3e3c2c, 0xbc713bac, 0x3b16bc7d, 0x3b163c7d, 0xbc71bbac, 0x3c3ebc2c, 0x3b793c78,
    0x3c5cbc04, 0x3a493c80, 0xbc67bbdb, 0x3c4ebc18, 0x3c18bc4e, 0x3bdb3c67, 0xbc80ba49, 0x3c04bc5c, 0xbc78bb79, 0x3c2cbc3e,
    0x3bac3c71, 0xbc7dbb16, 0x3c7d3b16, 0xbbdb3c67, 0xbc3ebc2c, 0x3c5cbc04, 0x3b793c78, 0xbc80ba49, 0x3bacbc71, 0x3c4e3c18,
    0xbc18bc4e, 0x3c71bbac, 0x3a493c80, 0xbc78bb79, 0x3c04bc5c, 0x3c2c3c3e, 0xbc673bdb, 0xbb16bc7d, 0xbb163c7d, 0xbc67bbdb,
    0x3c2cbc3e, 0x3c043c5c, 0xbc783b79, 0x3a49bc80, 0x3c713bac, 0xbc183c4e, 0x3c4ebc18, 0x3bac3c71, 0xbc803a49, 0x3b79bc78,
    0x3c5c3c04, 0xbc3e3c2c, 0xbbdbbc67, 0x3c7dbb16, 0xbbdb3c67, 0xbc5cbc04, 0x3c18bc4e, 0x3c3e3c2c, 0xba493c80, 0xbc7dbb16,
    0x3b79bc78, 0x3c713bac, 0x3bac3c71, 0xbc783b79, 0xbb16bc7d, 0x3c80ba49, 0x3c2c3c3e, 0xbc4e3c18, 0xbc04bc5c, 0x3c67bbdb,
    0x3c673bdb, 0xbc043c5c, 0xbc4ebc18, 0x3c2cbc3e, 0x3c803a49, 0xbb163c7d, 0xbc78bb79, 0x3bacbc71, 0x3c71bbac, 0x3b793c78,
    0xbc7d3b16, 0xba49bc80, 0x3c3ebc2c, 0x3c183c4e, 0xbc5c3c04, 0xbbdbbc67, 0x3f803f80, 0x3f7d3f7f, 0x3f783f7b, 0x3f713f75,
    0x3f673f6d, 0x3f5c3f62, 0x3f4e3f55, 0x3f3e3f46, 0x3f2c3f35, 0x3f183f22, 0x3f043f0e, 0x3edb3ef1, 0x3eac3ec4, 0x3e793e95,
    0x3e163e48, 0x3d493dc9, 0xbd490000, 0xbe16bdc9, 0xbe79be48, 0xbeacbe95, 0xbedbbec4, 0xbf04bef1, 0xbf18bf0e, 0xbf2cbf22,
    0xbf3ebf35, 0xbf4ebf46, 0xbf5cbf55, 0xbf67bf62, 0xbf71bf6d, 0xbf78bf75, 0xbf7dbf7b, 0xbf80bf7f, 0x3edb3ec4, 0x3f043ef1,
    0x3f183f0e, 0x3f2c3f22, 0x3d490000, 0x3e163dc9, 0x3e793e48, 0x3eac3e95, 0x3f713f6d, 0x3f783f75, 0x3f7d3f7b, 0x3f803f7f,
    0x3f3e3f35, 0x3f4e3f46, 0x3f5c3f55, 0x3f673f62, 0x3f673f6d, 0x3f5c3f62, 0x3f4e3f55, 0x3f3e3f46, 0x3f803f80, 0x3f7d3f7f,
    0x3f783f7b, 0x3f713f75, 0x3eac3ec4, 0x3e793e95, 0x3e163e48, 0x3d493dc9, 0x3f2c3f35, 0x3f183f22, 0x3f043f0e, 0x3edb3ef1,
    0xbf4ebf35, 0xbf71bf62, 0xbf80bf7b, 0xbf78bf7f, 0xbf5cbf6d, 0xbf2cbf46, 0xbedbbf0e, 0xbe16be95, 0x3f7d3f80, 0x3f673f75,
    0x3f3e3f55, 0x3f043f22, 0x3e793ec4, 0xbd493dc9, 0xbeacbe48, 0xbf18bef1, 0x3f183f35, 0x3eac3ef1, 0x3d493e48, 0xbe79bdc9,
    0xbf04bec4, 0xbf3ebf22, 0xbf67bf55, 0xbf7dbf75, 0x3e160000, 0x3edb3e95, 0x3f2c3f0e, 0x3f5c3f46, 0x3f783f6d, 0x3f803f7f,
    0x3f713f7b, 0x3f4e3f62, 0xbf04bec4, 0xbf3ebf22, 0xbf67bf55, 0xbf7dbf75, 0x3f183f35, 0x3eac3ef1, 0x3d493e48, 0xbe79bdc9,
    0x3f783f6d, 0x3f803f7f, 0x3f713f7b, 0x3f4e3f62, 0x3e160000, 0x3edb3e95, 0x3f2c3f0e, 0x3f5c3f46, 0x3f5c3f6d, 0x3f2c3f46,
    0x3edb3f0e, 0x3e163e95, 0x3f4e3f35, 0x3f713f62, 0x3f803f7b, 0x3f783f7f, 0xbe79bec4, 0x3d49bdc9, 0x3eac3e48, 0x3f183ef1,
    0xbf7dbf80, 0xbf67bf75, 0xbf3ebf55, 0xbf04bf22, 0xbe790000, 0xbf2cbef1, 0xbf71bf55, 0xbf7dbf7f, 0xbf4ebf6d, 0xbedbbf22,
    0x3d49be48, 0x3f043e95, 0x3f5c3f35, 0x3f803f75, 0x3f673f7b, 0x3f183f46, 0x3e163ec4, 0xbeacbdc9, 0xbf3ebf0e, 0xbf78bf62,
    0x3f783f80, 0x3f3e3f62, 0x3eac3f0e, 0xbe163dc9, 0xbf18bec4, 0xbf67bf46, 0xbf80bf7b, 0xbf5cbf75, 0xbf04bf35, 0xbd49be95,
    0x3edb3e48, 0x3f4e3f22, 0x3f7d3f6d, 0x3f713f7f, 0x3f2c3f55, 0x3e793ef1, 0xbf18bec4, 0xbf67bf46, 0xbf80bf7b, 0xbf5cbf75,
    0x3f783f80, 0x3f3e3f62, 0x3eac3f0e, 0xbe163dc9, 0x3f7d3f6d, 0x3f713f7f, 0x3f2c3f55, 0x3e793ef1, 0xbf04bf35, 0xbd49be95,
    0x3edb3e48, 0x3f4e3f22, 0x3f4e3f6d, 0x3edb3f22, 0xbd493e48, 0xbf04be95, 0x3e790000, 0x3f2c3ef1, 0x3f713f55, 0x3f7d3f7f,
    0xbe16bec4, 0x3eac3dc9, 0x3f3e3f0e, 0x3f783f62, 0xbf5cbf35, 0xbf80bf75, 0xbf67bf7b, 0xbf18bf46, 0xbedbbf35, 0x3e79bdc9,
    0x3f4e3f0e, 0x3f803f75, 0x3f3e3f6d, 0x3e163ef1, 0xbf04be48, 0xbf71bf46, 0x3eac0000, 0x3f5c3f22, 0x3f7d3f7b, 0x3f2c3f62,
    0x3d493ec4, 0xbf18be95, 0xbf78bf55, 0xbf67bf7f, 0x3f673f35, 0x3f783f7f, 0x3f183f55, 0xbd493e95, 0xbf2cbec4, 0xbf7dbf62,
    0xbf5cbf7b, 0xbeacbf22, 0x3f713f80, 0x3f043f46, 0xbe163e48, 0xbf3ebef1, 0xbf80bf6d, 0xbf4ebf75, 0xbe79bf0e, 0x3edb3dc9,
    0x3f2c3ec4, 0x3f7d3f62, 0x3f5c3f7b, 0x3eac3f22, 0xbf67bf35, 0xbf78bf7f, 0xbf18bf55, 0x3d49be95, 0x3f803f6d, 0x3f4e3f75,
    0x3e793f0e, 0xbedbbdc9, 0xbf71bf80, 0xbf04bf46, 0x3e16be48, 0x3f3e3ef1, 0x3f3e3f6d, 0x3e163ef1, 0xbf04be48, 0xbf71bf46,
    0xbedbbf35, 0x3e79bdc9, 0x3f4e3f0e, 0x3f803f75, 0x3d493ec4, 0xbf18be95, 0xbf78bf55, 0xbf67bf7f, 0x3eac0000, 0x3f5c3f22,
    0x3f7d3f7b, 0x3f2c3f62, 0x3f673f80, 0x3e793f22, 0xbf18be48, 0xbf80bf62, 0xbf2cbf6d, 0x3e16be95, 0x3f5c3f0e, 0x3f713f7f,
    0x3eac3f35, 0xbf04bdc9, 0xbf7dbf55, 0xbf3ebf75, 0x3d49bec4, 0x3f4e3ef1, 0x3f783f7b, 0x3edb3f46, 0xbedb0000, 0xbf78bf46,
    0xbf4ebf7b, 0xbd49bef1, 0x3f3e3ec4, 0x3f7d3f75, 0x3f043f55, 0xbeac3dc9, 0xbf71bf35, 0xbf5cbf7f, 0xbe16bf0e, 0x3f2c3e95,
    0x3f803f6d, 0x3f183f62, 0xbe793e48, 0xbf67bf22, 0xbf3ebec4, 0xbf7dbf75, 0xbf04bf55, 0x3eacbdc9, 0x3edb0000, 0x3f783f46,
    0x3f4e3f7b, 0x3d493ef1, 0xbf80bf6d, 0xbf18bf62, 0x3e79be48, 0x3f673f22, 0x3f713f35, 0x3f5c3f7f, 0x3e163f0e, 0xbf2cbe95,
    0xbf2cbf6d, 0x3e16be95, 0x3f5c3f0e, 0x3f713f7f, 0x3f673f80, 0x3e793f22, 0xbf18be48, 0xbf80bf62, 0x3d49bec4, 0x3f4e3ef1,
    0x3f783f7b, 0x3edb3f46, 0x3eac3f35, 0xbf04bdc9, 0xbf7dbf55, 0xbf3ebf75, 0xbf78bf35, 0xbf2cbf75, 0x3eacbe48, 0x3f7d3f46,
    0x3f183f6d, 0xbedb3dc9, 0xbf80bf55, 0xbf04bf62, 0x3f5c3f80, 0xbd493ef1, 0xbf67bf0e, 0xbf4ebf7f, 0x3e16bec4, 0x3f713f22,
    0x3f3e3f7b, 0xbe793e95, 0x3e793f35, 0xbf3ebe95, 0xbf71bf7b, 0xbe16bf22, 0x3f4e3ec4, 0x3f673f7f, 0x3d493f0e, 0xbf5cbef1,
    0x3f040000, 0x3f803f62, 0x3edb3f55, 0xbf18bdc9, 0xbf7dbf6d, 0xbeacbf46, 0x3f2c3e48, 0x3f783f75, 0x3f4e3ec4, 0x3f673f7f,
    0x3d493f0e, 0xbf5cbef1, 0x3e793f35, 0xbf3ebe95, 0xbf71bf7b, 0xbe16bf22, 0xbf7dbf6d, 0xbeacbf46, 0x3f2c3e48, 0x3f783f75,
    0x3f040000, 0x3f803f62, 0x3edb3f55, 0xbf18bdc9, 0xbf18bf6d, 0x3edbbdc9, 0x3f803f55, 0x3f043f62, 0x3f783f35, 0x3f2c3f75,
    0xbeac3e48, 0xbf7dbf46, 0xbe163ec4, 0xbf71bf22, 0xbf3ebf7b, 0x3e79be95, 0xbf5cbf80, 0x3d49bef1, 0x3f673f0e, 0x3f4e3f7f,
    0xbf180000, 0xbf71bf75, 0x3d49bf0e, 0x3f783f22, 0x3f043f6d, 0xbf2cbdc9, 0xbf67bf7b, 0x3e16bef1, 0x3f7d3f35, 0x3edb3f62,
    0xbf3ebe48, 0xbf5cbf7f, 0x3e79bec4, 0x3f803f46, 0x3eac3f55, 0xbf4ebe95, 0x3f4e3f80, 0xbeac3e95, 0xbf80bf55, 0xbe79bf46,
    0x3f5c3ec4, 0x3f3e3f7f, 0xbedb3e48, 0xbf7dbf62, 0xbe16bf35, 0x3f673ef1, 0x3f2c3f7b, 0xbf043dc9, 0xbf78bf6d, 0xbd49bf22,
    0x3f713f0e, 0x3f183f75, 0x3f5c3ec4, 0x3f3e3f7f, 0xbedb3e48, 0xbf7dbf62, 0x3f4e3f80, 0xbeac3e95, 0xbf80bf55, 0xbe79bf46,
    0xbf78bf6d, 0xbd49bf22, 0x3f713f0e, 0x3f183f75, 0xbe16bf35, 0x3f673ef1, 0x3f2c3f7b, 0xbf043dc9, 0xbf04bf6d, 0x3f2c3dc9,
    0x3f673f7b, 0xbe163ef1, 0x3f180000, 0x3f713f75, 0xbd493f0e, 0xbf78bf22, 0xbe793ec4, 0xbf80bf46, 0xbeacbf55, 0x3f4e3e95,
    0xbf7dbf35, 0xbedbbf62, 0x3f3e3e48, 0x3f5c3f7f, 0xbd49bf35, 0x3f7d3f22, 0x3e793f55, 0xbf71bef1, 0xbedbbf6d, 0x3f5c3e95,
    0x3f183f7b, 0xbf3ebdc9, 0x3f2c0000, 0x3f4e3f7f, 0xbf043e48, 0xbf67bf75, 0x3eacbec4, 0x3f783f62, 0xbe163f0e, 0xbf80bf46,
    0x3f803f35, 0x3e163f46, 0xbf78bf0e, 0xbeacbf62, 0x3f673ec4, 0x3f043f75, 0xbf4ebe48, 0xbf2cbf7f, 0x3f3e3f80, 0xbf183dc9,
    0xbf5cbf7b, 0x3edbbe95, 0x3f713f6d, 0xbe793ef1, 0xbf7dbf55, 0x3d49bf22, 0xbf67bec4, 0xbf04bf75, 0x3f4e3e48, 0x3f2c3f7f,
    0xbf80bf35, 0xbe16bf46, 0x3f783f0e, 0x3eac3f62, 0xbf71bf6d, 0x3e79bef1, 0x3f7d3f55, 0xbd493f22, 0xbf3ebf80, 0x3f18bdc9,
    0x3f5c3f7b, 0xbedb3e95, 0xbedbbf6d, 0x3f5c3e95, 0x3f183f7b, 0xbf3ebdc9, 0xbd49bf35, 0x3f7d3f22, 0x3e793f55, 0xbf71bef1,
    0x3eacbec4, 0x3f783f62, 0xbe163f0e, 0xbf80bf46, 0x3f2c0000, 0x3f4e3f7f, 0xbf043e48, 0xbf67bf75, 0x3f2c3f80, 0xbf4ebdc9,
    0xbf04bf7b, 0x3f673e95, 0x3eac3f6d, 0xbf78bef1, 0xbe16bf55, 0x3f803f22, 0xbd493f35, 0xbf7dbf46, 0x3e79bf0e, 0x3f713f62,
    0xbedb3ec4, 0xbf5cbf75, 0x3f18be48, 0x3f3e3f7f, 0xbf3e0000, 0xbf18bf7f, 0x3f5c3e48, 0x3edb3f75, 0xbf71bec4, 0xbe79bf62,
    0x3f7d3f0e, 0x3d493f46, 0xbf80bf35, 0x3e16bf22, 0x3f783f55, 0xbeac3ef1, 0xbf67bf6d, 0x3f04be95, 0x3f4e3f7b, 0xbf2c3dc9,
    0x3f713ec4, 0x3e793f62, 0xbf7dbf0e, 0xbd49bf46, 0x3f3e0000, 0x3f183f7f, 0xbf5cbe48, 0xbedbbf75, 0x3f673f6d, 0xbf043e95,
    0xbf4ebf7b, 0x3f2cbdc9, 0x3f803f35, 0xbe163f22, 0xbf78bf55, 0x3eacbef1, 0x3eac3f6d, 0xbf78bef1, 0xbe16bf55, 0x3f803f22,
    0x3f2c3f80, 0xbf4ebdc9, 0xbf04bf7b, 0x3f673e95, 0xbedb3ec4, 0xbf5cbf75, 0x3f18be48, 0x3f3e3f7f, 0xbd493f35, 0xbf7dbf46,
    0x3e79bf0e, 0x3f713f62, 0xbf7dbf35, 0x3edbbef1, 0x3f3e3f7b, 0xbf5cbdc9, 0xbe79bf6d, 0x3f803f22, 0xbeac3f0e, 0xbf4ebf75,
    0x3f183f80, 0xbf71be95, 0xbd49bf55, 0x3f783f46, 0xbf043ec4, 0xbf2cbf7f, 0x3f673e48, 0x3e163f62, 0xbe163f35, 0xbf67bf62,
    0x3f2cbe48, 0x3f043f7f, 0xbf78bec4, 0x3d49bf46, 0x3f713f55, 0xbf183e95, 0x3f4e0000, 0x3eac3f75, 0xbf80bf0e, 0x3e79bf22,
    0x3f5c3f6d, 0xbf3e3dc9, 0xbedbbf7b, 0x3f7d3ef1, 0xbf78bec4, 0x3d49bf46, 0x3f713f55, 0xbf183e95, 0xbe163f35, 0xbf67bf62,
    0x3f2cbe48, 0x3f043f7f, 0x3f5c3f6d, 0xbf3e3dc9, 0xbedbbf7b, 0x3f7d3ef1, 0x3f4e0000, 0x3eac3f75, 0xbf80bf0e, 0x3e79bf22,
    0x3e793f6d, 0xbf80bf22, 0x3eacbf0e, 0x3f4e3f75, 0x3f7d3f35, 0xbedb3ef1, 0xbf3ebf7b, 0x3f5c3dc9, 0x3f04bec4, 0x3f2c3f7f,
    0xbf67be48, 0xbe16bf62, 0xbf18bf80, 0x3f713e95, 0x3d493f55, 0xbf78bf46, 0xbf5c0000, 0xbd49bf62, 0x3f673f55, 0xbf4e3dc9,
    0xbe16bf6d, 0x3f713f46, 0xbf3e3e48, 0xbe79bf75, 0x3f783f35, 0xbf2c3e95, 0xbeacbf7b, 0x3f7d3f22, 0xbf183ec4, 0xbedbbf7f,
    0x3f803f0e, 0xbf043ef1, 0x3f043f80, 0xbf80bef1, 0x3edbbf0e, 0x3f183f7f, 0xbf7dbec4, 0x3eacbf22, 0x3f2c3f7b, 0xbf78be95,
    0x3e79bf35, 0x3f3e3f75, 0xbf71be48, 0x3e16bf46, 0x3f4e3f6d, 0xbf67bdc9, 0x3d49bf55, 0x3f5c3f62, 0xbf7dbec4, 0x3eacbf22,
    0x3f2c3f7b, 0xbf78be95, 0x3f043f80, 0xbf80bef1, 0x3edbbf0e, 0x3f183f7f, 0x3f4e3f6d, 0xbf67bdc9, 0x3d49bf55, 0x3f5c3f62,
    0x3e79bf35, 0x3f3e3f75, 0xbf71be48, 0x3e16bf46, 0x3e163f6d, 0xbf71bf46, 0x3f3ebe48, 0x3e793f75, 0x3f5c0000, 0x3d493f62,
    0xbf67bf55, 0x3f4ebdc9, 0x3f18bec4, 0x3edb3f7f, 0xbf80bf0e, 0x3f04bef1, 0xbf78bf35, 0x3f2cbe95, 0x3eac3f7b, 0xbf7dbf22,
    0x3eacbf35, 0x3f043f7f, 0xbf7dbf0e, 0x3f3ebe95, 0x3d493f6d, 0xbf4ebf62, 0x3f783e48, 0xbedb3f22, 0x3f670000, 0xbe793f46,
    0xbf18bf7b, 0x3f803ef1, 0xbf2c3ec4, 0xbe16bf75, 0x3f5c3f55, 0xbf71bdc9, 0x3f713f35, 0xbf5c3dc9, 0x3e16bf55, 0x3f2c3f75,
    0xbf80bec4, 0x3f18bef1, 0x3e793f7b, 0xbf67bf46, 0x3edb3f80, 0xbf78bf22, 0x3f4ebe48, 0xbd493f62, 0xbf3ebf6d, 0x3f7d3e95,
    0xbf043f0e, 0xbeacbf7f, 0x3f803ec4, 0xbf183ef1, 0xbe79bf7b, 0x3f673f46, 0xbf71bf35, 0x3f5cbdc9, 0xbe163f55, 0xbf2cbf75,
    0x3f3e3f6d, 0xbf7dbe95, 0x3f04bf0e, 0x3eac3f7f, 0xbedbbf80, 0x3f783f22, 0xbf4e3e48, 0x3d49bf62, 0x3d493f6d, 0xbf4ebf62,
    0x3f783e48, 0xbedb3f22, 0x3eacbf35, 0x3f043f7f, 0xbf7dbf0e, 0x3f3ebe95, 0xbf2c3ec4, 0xbe16bf75, 0x3f5c3f55, 0xbf71bdc9,
    0x3f670000, 0xbe793f46, 0xbf18bf7b, 0x3f803ef1, 0x3eac3f80, 0xbf5cbf46, 0x3f7d3e48, 0xbf2c3ef1, 0x3d49bf6d, 0x3f183f75,
    0xbf78bf0e, 0x3f67bdc9, 0xbedb3f35, 0xbe79bf7f, 0x3f4e3f55, 0xbf80be95, 0x3f3ebec4, 0xbe163f62, 0xbf04bf7b, 0x3f713f22,
    0xbf710000, 0x3f04bf22, 0x3e163f7b, 0xbf3ebf62, 0x3f803ec4, 0xbf4e3e95, 0x3e79bf55, 0x3edb3f7f, 0xbf67bf35, 0x3f783dc9,
    0xbf183f0e, 0xbd49bf75, 0x3f2c3f6d, 0xbf7dbef1, 0x3f5cbe48, 0xbeac3f46, 0xbf80bec4, 0x3f4ebe95, 0xbe793f55, 0xbedbbf7f,
    0x3f710000, 0xbf043f22, 0xbe16bf7b, 0x3f3e3f62, 0xbf2cbf6d, 0x3f7d3ef1, 0xbf5c3e48, 0x3eacbf46, 0x3f673f35, 0xbf78bdc9,
    0x3f18bf0e, 0x3d493f75, 0x3d49bf6d, 0x3f183f75, 0xbf78bf0e, 0x3f67bdc9, 0x3eac3f80, 0xbf5cbf46, 0x3f7d3e48, 0xbf2c3ef1,
    0x3f3ebec4, 0xbe163f62, 0xbf04bf7b, 0x3f713f22, 0xbedb3f35, 0xbe79bf7f, 0x3f4e3f55, 0xbf80be95, 0xbf5cbf35, 0x3f803e95,
    0xbf673e48, 0x3f18bf22, 0xbe163f6d, 0xbeacbf7f, 0x3f3e3f55, 0xbf78bef1, 0x3e793f80, 0xbf2cbf62, 0x3f713f0e, 0xbf7dbdc9,
    0x3f4ebec4, 0xbedb3f46, 0xbd49bf7b, 0x3f043f75, 0xbf043f35, 0x3d49bf75, 0x3edb3f7b, 0xbf4ebf46, 0x3f7d3ec4, 0xbf713dc9,
    0x3f2cbf0e, 0xbe793f62, 0x3f780000, 0xbf3e3ef1, 0x3eacbf55, 0x3e163f7f, 0xbf18bf6d, 0x3f673f22, 0xbf80be48, 0x3f5cbe95,
    0x3f7d3ec4, 0xbf713dc9, 0x3f2cbf0e, 0xbe793f62, 0xbf043f35, 0x3d49bf75, 0x3edb3f7b, 0xbf4ebf46, 0xbf18bf6d, 0x3f673f22,
    0xbf80be48, 0x3f5cbe95, 0x3f780000, 0xbf3e3ef1, 0x3eacbf55, 0x3e163f7f, 0x3e16bf6d, 0x3eac3f7f, 0xbf3ebf55, 0x3f783ef1,
    0x3f5c3f35, 0xbf80be95, 0x3f67be48, 0xbf183f22, 0xbf4e3ec4, 0x3edbbf46, 0x3d493f7b, 0xbf04bf75, 0xbe79bf80, 0x3f2c3f62,
    0xbf71bf0e, 0x3f7d3dc9, 0xbf7d0000, 0x3f67be95, 0xbf3e3f0e, 0x3f04bf46, 0xbe793f6d, 0xbd49bf7f, 0x3eac3f7b, 0xbf18bf62,
    0x3f4e3f35, 0xbf71bef1, 0x3f803e48, 0xbf783dc9, 0x3f5cbec4, 0xbf2c3f22, 0x3edbbf55, 0xbe163f75, 0x3e163f80, 0xbedbbf75,
    0x3f2c3f55, 0xbf5cbf22, 0x3f783ec4, 0xbf80bdc9, 0x3f71be48, 0xbf4e3ef1, 0x3f18bf35, 0xbeac3f62, 0x3d49bf7b, 0x3e793f7f,
    0xbf04bf6d, 0x3f3e3f46, 0xbf67bf0e, 0x3f7d3e95, 0x3f783ec4, 0xbf80bdc9, 0x3f71be48, 0xbf4e3ef1, 0x3e163f80, 0xbedbbf75,
    0x3f2c3f55, 0xbf5cbf22, 0xbf04bf6d, 0x3f3e3f46, 0xbf67bf0e, 0x3f7d3e95, 0x3f18bf35, 0xbeac3f62, 0x3d49bf7b, 0x3e793f7f,
    0x3e79bf6d, 0x3d493f7f, 0xbeacbf7b, 0x3f183f62, 0x3f7d0000, 0xbf673e95, 0x3f3ebf0e, 0xbf043f46, 0xbf5c3ec4, 0x3f2cbf22,
    0xbedb3f55, 0x3e16bf75, 0xbf4ebf35, 0x3f713ef1, 0xbf80be48, 0x3f78bdc9, 0x3f2cbf35, 0xbf183f46, 0x3f04bf55, 0xbedb3f62,
    0x3eacbf6d, 0xbe793f75, 0x3e16bf7b, 0xbd493f7f, 0x3f800000, 0xbf7d3dc9, 0x3f78be48, 0xbf713e95, 0x3f67bec4, 0xbf5c3ef1,
    0x3f4ebf0e, 0xbf3e3f22, 0x3f3e3f35, 0xbf4ebf22, 0x3f5c3f0e, 0xbf67bef1, 0x3f713ec4, 0xbf78be95, 0x3f7d3e48, 0xbf80bdc9,
    0x3d493f80, 0xbe16bf7f, 0x3e793f7b, 0xbeacbf75, 0x3edb3f6d, 0xbf04bf62, 0x3f183f55, 0xbf2cbf46, 0xbf71bec4, 0x3f783e95,
    0xbf7dbe48, 0x3f803dc9, 0xbf3ebf35, 0x3f4e3f22, 0xbf5cbf0e, 0x3f673ef1, 0xbedbbf6d, 0x3f043f62, 0xbf18bf55, 0x3f2c3f46,
    0xbd49bf80, 0x3e163f7f, 0xbe79bf7b, 0x3eac3f75, 0x3eacbf6d, 0xbe793f75, 0x3e16bf7b, 0xbd493f7f, 0x3f2cbf35, 0xbf183f46,
    0x3f04bf55, 0xbedb3f62, 0x3f67bec4, 0xbf5c3ef1, 0x3f4ebf0e, 0xbf3e3f22, 0x3f800000, 0xbf7d3dc9, 0x3f78be48, 0xbf713e95,
    0xbd493f80, 0x3e16bf7f, 0xbe793f7b, 0x3eacbf75, 0xbedb3f6d, 0x3f04bf62, 0xbf183f55, 0x3f2cbf46, 0xbf3e3f35, 0x3f4ebf22,
    0xbf5c3f0e, 0x3f67bef1, 0xbf713ec4, 0x3f78be95, 0xbf7d3e48, 0x3f80bdc9, 0xbf800000, 0x3f7d3dc9, 0xbf78be48, 0x3f713e95,
    0xbf67bec4, 0x3f5c3ef1, 0xbf4ebf0e, 0x3f3e3f22, 0xbf2cbf35, 0x3f183f46, 0xbf04bf55, 0x3edb3f62, 0xbeacbf6d, 0x3e793f75,
    0xbe16bf7b, 0x3d493f7f, 0x3f673ec4, 0xbf5cbef1, 0x3f4e3f0e, 0xbf3ebf22, 0x3f800000, 0xbf7dbdc9, 0x3f783e48, 0xbf71be95,
    0x3eac3f6d, 0xbe79bf75, 0x3e163f7b, 0xbd49bf7f, 0x3f2c3f35, 0xbf18bf46, 0x3f043f55, 0xbedbbf62, 0xbedb3f6d, 0x3f04bf62,
    0xbf183f55, 0x3f2cbf46, 0xbd493f80, 0x3e16bf7f, 0xbe793f7b, 0x3eacbf75, 0xbf713ec4, 0x3f78be95, 0xbf7d3e48, 0x3f80bdc9,
    0xbf3e3f35, 0x3f4ebf22, 0xbf5c3f0e, 0x3f67bef1, 0xbf18bf35, 0x3eac3f62, 0xbd49bf7b, 0xbe793f7f, 0x3f04bf6d, 0xbf3e3f46,
    0x3f67bf0e, 0xbf7d3e95, 0xbe163f80, 0x3edbbf75, 0xbf2c3f55, 0x3f5cbf22, 0xbf783ec4, 0x3f80bdc9, 0xbf71be48, 0x3f4e3ef1,
    0xbf4e3f35, 0x3f71bef1, 0xbf803e48, 0x3f783dc9, 0xbf5cbec4, 0x3f2c3f22, 0xbedbbf55, 0x3e163f75, 0x3f7d0000, 0xbf67be95,
    0x3f3e3f0e, 0xbf04bf46, 0x3e793f6d, 0x3d49bf7f, 0xbeac3f7b, 0x3f18bf62, 0xbf5cbec4, 0x3f2c3f22, 0xbedbbf55, 0x3e163f75,
    0xbf4e3f35, 0x3f71bef1, 0xbf803e48, 0x3f783dc9, 0x3e793f6d, 0x3d49bf7f, 0xbeac3f7b, 0x3f18bf62, 0x3f7d0000, 0xbf67be95,
    0x3f3e3f0e, 0xbf04bf46, 0xbf043f6d, 0x3f3ebf46, 0xbf673f0e, 0x3f7dbe95, 0x3f183f35, 0xbeacbf62, 0x3d493f7b, 0x3e79bf7f,
    0x3f78bec4, 0xbf803dc9, 0x3f713e48, 0xbf4ebef1, 0x3e16bf80, 0xbedb3f75, 0x3f2cbf55, 0xbf5c3f22, 0xbf780000, 0x3f3e3ef1,
    0xbeacbf55, 0xbe163f7f, 0x3f18bf6d, 0xbf673f22, 0x3f80be48, 0xbf5cbe95, 0x3f043f35, 0xbd49bf75, 0xbedb3f7b, 0x3f4ebf46,
    0xbf7d3ec4, 0x3f713dc9, 0xbf2cbf0e, 0x3e793f62, 0xbe793f80, 0x3f2cbf62, 0xbf713f0e, 0x3f7dbdc9, 0xbf4ebec4, 0x3edb3f46,
    0x3d49bf7b, 0xbf043f75, 0x3f5cbf35, 0xbf803e95, 0x3f673e48, 0xbf18bf22, 0x3e163f6d, 0x3eacbf7f, 0xbf3e3f55, 0x3f78bef1,
    0xbf4ebec4, 0x3edb3f46, 0x3d49bf7b, 0xbf043f75, 0xbe793f80, 0x3f2cbf62, 0xbf713f0e, 0x3f7dbdc9, 0x3e163f6d, 0x3eacbf7f,
    0xbf3e3f55, 0x3f78bef1, 0x3f5cbf35, 0xbf803e95, 0x3f673e48, 0xbf18bf22, 0xbf183f6d, 0x3f67bf22, 0xbf803e48, 0x3f5c3e95,
    0x3f780000, 0xbf3ebef1, 0x3eac3f55, 0x3e16bf7f, 0x3f7dbec4, 0xbf71bdc9, 0x3f2c3f0e, 0xbe79bf62, 0xbf04bf35, 0x3d493f75,
    0x3edbbf7b, 0xbf4e3f46, 0x3f67bf35, 0xbf783dc9, 0x3f183f0e, 0x3d49bf75, 0xbf2c3f6d, 0x3f7dbef1, 0xbf5cbe48, 0x3eac3f46,
    0x3f710000, 0xbf04bf22, 0xbe163f7b, 0x3f3ebf62, 0xbf803ec4, 0x3f4e3e95, 0xbe79bf55, 0xbedb3f7f, 0x3edb3f35, 0x3e79bf7f,
    0xbf4e3f55, 0x3f80be95, 0xbf3ebec4, 0x3e163f62, 0x3f04bf7b, 0xbf713f22, 0xbeac3f80, 0x3f5cbf46, 0xbf7d3e48, 0x3f2c3ef1,
    0xbd49bf6d, 0xbf183f75, 0x3f78bf0e, 0xbf67bdc9, 0x3f3e3ec4, 0xbe16bf62, 0xbf043f7b, 0x3f71bf22, 0xbedbbf35, 0xbe793f7f,
    0x3f4ebf55, 0xbf803e95, 0x3d493f6d, 0x3f18bf75, 0xbf783f0e, 0x3f673dc9, 0x3eacbf80, 0xbf5c3f46, 0x3f7dbe48, 0xbf2cbef1,
    0xbf2c3f6d, 0x3f7dbef1, 0xbf5cbe48, 0x3eac3f46, 0x3f67bf35, 0xbf783dc9, 0x3f183f0e, 0x3d49bf75, 0xbf803ec4, 0x3f4e3e95,
    0xbe79bf55, 0xbedb3f7f, 0x3f710000, 0xbf04bf22, 0xbe163f7b, 0x3f3ebf62, 0xbedb3f80, 0x3f78bf22, 0xbf4ebe48, 0x3d493f62,
    0x3f3ebf6d, 0xbf7d3e95, 0x3f043f0e, 0x3eacbf7f, 0xbf713f35, 0x3f5c3dc9, 0xbe16bf55, 0xbf2c3f75, 0x3f80bec4, 0xbf18bef1,
    0xbe793f7b, 0x3f67bf46, 0xbf670000, 0x3e793f46, 0x3f18bf7b, 0xbf803ef1, 0x3f2c3ec4, 0x3e16bf75, 0xbf5c3f55, 0x3f71bdc9,
    0xbeacbf35, 0xbf043f7f, 0x3f7dbf0e, 0xbf3ebe95, 0xbd493f6d, 0x3f4ebf62, 0xbf783e48, 0x3edb3f22, 0xbf2cbec4, 0xbe163f75,
    0x3f5cbf55, 0xbf713dc9, 0x3f670000, 0xbe79bf46, 0xbf183f7b, 0x3f80bef1, 0x3d49bf6d, 0xbf4e3f62, 0x3f78be48, 0xbedbbf22,
    0x3eac3f35, 0x3f04bf7f, 0xbf7d3f0e, 0x3f3e3e95, 0x3f3ebf6d, 0xbf7d3e95, 0x3f043f0e, 0x3eacbf7f, 0xbedb3f80, 0x3f78bf22,
    0xbf4ebe48, 0x3d493f62, 0x3f80bec4, 0xbf18bef1, 0xbe793f7b, 0x3f67bf46, 0xbf713f35, 0x3f5c3dc9, 0xbe16bf55, 0xbf2c3f75,
    0xbe79bf35, 0xbf3e3f75, 0x3f71be48, 0xbe16bf46, 0xbf4e3f6d, 0x3f67bdc9, 0xbd49bf55, 0xbf5c3f62, 0xbf043f80, 0x3f80bef1,
    0xbedbbf0e, 0xbf183f7f, 0x3f7dbec4, 0xbeacbf22, 0xbf2c3f7b, 0x3f78be95, 0xbf783f35, 0x3f2c3e95, 0x3eacbf7b, 0xbf7d3f22,
    0x3f183ec4, 0x3edbbf7f, 0xbf803f0e, 0x3f043ef1, 0x3f5c0000, 0x3d49bf62, 0xbf673f55, 0x3f4e3dc9, 0x3e16bf6d, 0xbf713f46,
    0x3f3e3e48, 0x3e79bf75, 0x3f183ec4, 0x3edbbf7f, 0xbf803f0e, 0x3f043ef1, 0xbf783f35, 0x3f2c3e95, 0x3eacbf7b, 0xbf7d3f22,
    0x3e16bf6d, 0xbf713f46, 0x3f3e3e48, 0x3e79bf75, 0x3f5c0000, 0x3d49bf62, 0xbf673f55, 0x3f4e3dc9, 0x3f4ebf6d, 0xbf673dc9,
    0x3d493f55, 0x3f5cbf62, 0x3e793f35, 0x3f3ebf75, 0xbf713e48, 0x3e163f46, 0xbf7d3ec4, 0x3eac3f22, 0x3f2cbf7b, 0xbf783e95,
    0x3f04bf80, 0xbf803ef1, 0x3edb3f0e, 0x3f18bf7f, 0xbf4e0000, 0xbeac3f75, 0x3f80bf0e, 0xbe79bf22, 0xbf5c3f6d, 0x3f3e3dc9,
    0x3edbbf7b, 0xbf7d3ef1, 0x3e163f35, 0x3f67bf62, 0xbf2cbe48, 0xbf043f7f, 0x3f78bec4, 0xbd49bf46, 0xbf713f55, 0x3f183e95,
    0xbf183f80, 0x3f71be95, 0x3d49bf55, 0xbf783f46, 0x3f043ec4, 0x3f2cbf7f, 0xbf673e48, 0xbe163f62, 0x3f7dbf35, 0xbedbbef1,
    0xbf3e3f7b, 0x3f5cbdc9, 0x3e79bf6d, 0xbf803f22, 0x3eac3f0e, 0x3f4ebf75, 0x3f043ec4, 0x3f2cbf7f, 0xbf673e48, 0xbe163f62,
    0xbf183f80, 0x3f71be95, 0x3d49bf55, 0xbf783f46, 0x3e79bf6d, 0xbf803f22, 0x3eac3f0e, 0x3f4ebf75, 0x3f7dbf35, 0xbedbbef1,
    0xbf3e3f7b, 0x3f5cbdc9, 0x3f5cbf6d, 0xbf3ebdc9, 0xbedb3f7b, 0x3f7dbef1, 0x3f4e0000, 0x3eacbf75, 0xbf803f0e, 0x3e793f22,
    0xbf783ec4, 0x3d493f46, 0x3f71bf55, 0xbf18be95, 0xbe16bf35, 0xbf673f62, 0x3f2c3e48, 0x3f04bf7f, 0x3f80bf35, 0xbe16bf22,
    0xbf783f55, 0x3eac3ef1, 0x3f67bf6d, 0xbf04be95, 0xbf4e3f7b, 0x3f2c3dc9, 0x3f3e0000, 0x3f18bf7f, 0xbf5c3e48, 0xbedb3f75,
    0x3f71bec4, 0x3e79bf62, 0xbf7d3f0e, 0xbd493f46, 0x3d493f35, 0x3f7dbf46, 0xbe79bf0e, 0xbf713f62, 0x3edb3ec4, 0x3f5cbf75,
    0xbf18be48, 0xbf3e3f7f, 0xbf2c3f80, 0x3f4ebdc9, 0x3f04bf7b, 0xbf673e95, 0xbeac3f6d, 0x3f78bef1, 0x3e16bf55, 0xbf803f22,
    0xbedbbec4, 0xbf5c3f75, 0x3f183e48, 0x3f3ebf7f, 0xbd49bf35, 0xbf7d3f46, 0x3e793f0e, 0x3f71bf62, 0x3eacbf6d, 0xbf783ef1,
    0xbe163f55, 0x3f80bf22, 0x3f2cbf80, 0xbf4e3dc9, 0xbf043f7b, 0x3f67be95, 0x3f67bf6d, 0xbf04be95, 0xbf4e3f7b, 0x3f2c3dc9,
    0x3f80bf35, 0xbe16bf22, 0xbf783f55, 0x3eac3ef1, 0x3f71bec4, 0x3e79bf62, 0xbf7d3f0e, 0xbd493f46, 0x3f3e0000, 0x3f18bf7f,
    0xbf5c3e48, 0xbedb3f75, 0xbf3e3f80, 0x3f183dc9, 0x3f5cbf7b, 0xbedbbe95, 0xbf713f6d, 0x3e793ef1, 0x3f7dbf55, 0xbd49bf22,
    0xbf803f35, 0xbe163f46, 0x3f78bf0e, 0x3eacbf62, 0xbf673ec4, 0xbf043f75, 0x3f4ebe48, 0x3f2cbf7f, 0xbf2c0000, 0xbf4e3f7f,
    0x3f043e48, 0x3f67bf75, 0xbeacbec4, 0xbf783f62, 0x3e163f0e, 0x3f80bf46, 0x3d49bf35, 0xbf7d3f22, 0xbe793f55, 0x3f71bef1,
    0x3edbbf6d, 0xbf5c3e95, 0xbf183f7b, 0x3f3ebdc9, 0x3eac3ec4, 0x3f78bf62, 0xbe16bf0e, 0xbf803f46, 0x3f2c0000, 0x3f4ebf7f,
    0xbf04be48, 0xbf673f75, 0xbedb3f6d, 0x3f5cbe95, 0x3f18bf7b, 0xbf3e3dc9, 0xbd493f35, 0x3f7dbf22, 0x3e79bf55, 0xbf713ef1,
    0xbf713f6d, 0x3e793ef1, 0x3f7dbf55, 0xbd49bf22, 0xbf3e3f80, 0x3f183dc9, 0x3f5cbf7b, 0xbedbbe95, 0xbf673ec4, 0xbf043f75,
    0x3f4ebe48, 0x3f2cbf7f, 0xbf803f35, 0xbe163f46, 0x3f78bf0e, 0x3eacbf62, 0x3e16bf35, 0xbf673ef1, 0xbf2c3f7b, 0x3f043dc9,
    0x3f78bf6d, 0x3d49bf22, 0xbf713f0e, 0xbf183f75, 0xbf4e3f80, 0x3eac3e95, 0x3f80bf55, 0x3e79bf46, 0xbf5c3ec4, 0xbf3e3f7f,
    0x3edb3e48, 0x3f7dbf62, 0xbf7d3f35, 0xbedb3f62, 0x3f3ebe48, 0x3f5cbf7f, 0xbe79bec4, 0xbf803f46, 0xbeac3f55, 0x3f4ebe95,
    0x3f180000, 0x3f71bf75, 0xbd49bf0e, 0xbf783f22, 0xbf043f6d, 0x3f2cbdc9, 0x3f67bf7b, 0xbe16bef1, 0xbe79bec4, 0xbf803f46,
    0xbeac3f55, 0x3f4ebe95, 0xbf7d3f35, 0xbedb3f62, 0x3f3ebe48, 0x3f5cbf7f, 0xbf043f6d, 0x3f2cbdc9, 0x3f67bf7b, 0xbe16bef1,
    0x3f180000, 0x3f71bf75, 0xbd49bf0e, 0xbf783f22, 0xbf783f6d, 0xbd493f22, 0x3f71bf0e, 0x3f18bf75, 0xbe163f35, 0x3f67bef1,
    0x3f2cbf7b, 0xbf04bdc9, 0x3f5cbec4, 0x3f3ebf7f, 0xbedbbe48, 0xbf7d3f62, 0x3f4ebf80, 0xbeacbe95, 0xbf803f55, 0xbe793f46,
    0xbf040000, 0xbf803f62, 0xbedb3f55, 0x3f18bdc9, 0x3f7dbf6d, 0x3eacbf46, 0xbf2c3e48, 0xbf783f75, 0xbe793f35, 0x3f3ebe95,
    0x3f71bf7b, 0x3e16bf22, 0xbf4e3ec4, 0xbf673f7f, 0xbd493f0e, 0x3f5cbef1, 0xbf5c3f80, 0x3d493ef1, 0x3f67bf0e, 0x3f4ebf7f,
    0xbe16bec4, 0xbf713f22, 0xbf3e3f7b, 0x3e793e95, 0x3f78bf35, 0x3f2cbf75, 0xbeacbe48, 0xbf7d3f46, 0xbf183f6d, 0x3edb3dc9,
    0x3f80bf55, 0x3f04bf62, 0xbe16bec4, 0xbf713f22, 0xbf3e3f7b, 0x3e793e95, 0xbf5c3f80, 0x3d493ef1, 0x3f67bf0e, 0x3f4ebf7f,
    0xbf183f6d, 0x3edb3dc9, 0x3f80bf55, 0x3f04bf62, 0x3f78bf35, 0x3f2cbf75, 0xbeacbe48, 0xbf7d3f46, 0xbf7d3f6d, 0xbeac3f46,
    0x3f2cbe48, 0x3f78bf75, 0x3f040000, 0x3f80bf62, 0x3edbbf55, 0xbf183dc9, 0x3f4ebec4, 0x3f67bf7f, 0x3d49bf0e, 0xbf5c3ef1,
    0x3e79bf35, 0xbf3e3e95, 0xbf713f7b, 0xbe163f22, 0x3f71bf35, 0x3f5cbf7f, 0x3e16bf0e, 0xbf2c3e95, 0xbf803f6d, 0xbf183f62,
    0x3e793e48, 0x3f67bf22, 0x3edb0000, 0x3f78bf46, 0x3f4ebf7b, 0x3d49bef1, 0xbf3e3ec4, 0xbf7d3f75, 0xbf043f55, 0x3eac3dc9,
    0xbeac3f35, 0x3f04bdc9, 0x3f7dbf55, 0x3f3ebf75, 0xbd49bec4, 0xbf4e3ef1, 0xbf783f7b, 0xbedb3f46, 0xbf673f80, 0xbe793f22,
    0x3f18be48, 0x3f80bf62, 0x3f2cbf6d, 0xbe16be95, 0xbf5c3f0e, 0xbf713f7f, 0x3d493ec4, 0x3f4ebef1, 0x3f78bf7b, 0x3edbbf46,
    0x3eacbf35, 0xbf043dc9, 0xbf7d3f55, 0xbf3e3f75, 0xbf2c3f6d, 0x3e163e95, 0x3f5cbf0e, 0x3f71bf7f, 0x3f67bf80, 0x3e79bf22,
    0xbf183e48, 0xbf803f62, 0xbf803f6d, 0xbf183f62, 0x3e793e48, 0x3f67bf22, 0x3f71bf35, 0x3f5cbf7f, 0x3e16bf0e, 0xbf2c3e95,
    0xbf3e3ec4, 0xbf7d3f75, 0xbf043f55, 0x3eac3dc9, 0x3edb0000, 0x3f78bf46, 0x3f4ebf7b, 0x3d49bef1, 0xbf713f80, 0xbf043f46,
    0x3e163e48, 0x3f3ebef1, 0x3f80bf6d, 0x3f4ebf75, 0x3e79bf0e, 0xbedb3dc9, 0xbf673f35, 0xbf783f7f, 0xbf183f55, 0x3d493e95,
    0x3f2cbec4, 0x3f7dbf62, 0x3f5cbf7b, 0x3eacbf22, 0xbeac0000, 0xbf5c3f22, 0xbf7d3f7b, 0xbf2c3f62, 0xbd493ec4, 0x3f18be95,
    0x3f78bf55, 0x3f67bf7f, 0x3edbbf35, 0xbe79bdc9, 0xbf4e3f0e, 0xbf803f75, 0xbf3e3f6d, 0xbe163ef1, 0x3f04be48, 0x3f71bf46,
    0x3d49bec4, 0xbf183e95, 0xbf783f55, 0xbf673f7f, 0x3eac0000, 0x3f5cbf22, 0x3f7dbf7b, 0x3f2cbf62, 0x3f3ebf6d, 0x3e16bef1,
    0xbf043e48, 0xbf713f46, 0xbedb3f35, 0x3e793dc9, 0x3f4ebf0e, 0x3f80bf75, 0x3f80bf6d, 0x3f4ebf75, 0x3e79bf0e, 0xbedb3dc9,
    0xbf713f80, 0xbf043f46, 0x3e163e48, 0x3f3ebef1, 0x3f2cbec4, 0x3f7dbf62, 0x3f5cbf7b, 0x3eacbf22, 0xbf673f35, 0xbf783f7f,
    0xbf183f55, 0x3d493e95, 0x3f04bf35, 0x3d49be95, 0xbedb3e48, 0xbf4e3f22, 0xbf7d3f6d, 0xbf713f7f, 0xbf2c3f55, 0xbe793ef1,
    0xbf783f80, 0xbf3e3f62, 0xbeac3f0e, 0x3e163dc9, 0x3f18bec4, 0x3f67bf46, 0x3f80bf7b, 0x3f5cbf75, 0xbf5c3f35, 0xbf803f75,
    0xbf673f7b, 0xbf183f46, 0xbe163ec4, 0x3eacbdc9, 0x3f3ebf0e, 0x3f78bf62, 0x3e790000, 0x3f2cbef1, 0x3f71bf55, 0x3f7dbf7f,
    0x3f4ebf6d, 0x3edbbf22, 0xbd49be48, 0xbf043e95, 0xbe163ec4, 0x3eacbdc9, 0x3f3ebf0e, 0x3f78bf62, 0xbf5c3f35, 0xbf803f75,
    0xbf673f7b, 0xbf183f46, 0x3f4ebf6d, 0x3edbbf22, 0xbd49be48, 0xbf043e95, 0x3e790000, 0x3f2cbef1, 0x3f71bf55, 0x3f7dbf7f,
    0x3f7dbf6d, 0x3f71bf7f, 0x3f2cbf55, 0x3e79bef1, 0xbf043f35, 0xbd493e95, 0x3edbbe48, 0x3f4ebf22, 0xbf183ec4, 0xbf673f46,
    0xbf803f7b, 0xbf5c3f75, 0x3f78bf80, 0x3f3ebf62, 0x3eacbf0e, 0xbe16bdc9, 0xbe160000, 0xbedb3e95, 0xbf2c3f0e, 0xbf5c3f46,
    0xbf783f6d, 0xbf803f7f, 0xbf713f7b, 0xbf4e3f62, 0xbf183f35, 0xbeac3ef1, 0xbd493e48, 0x3e79bdc9, 0x3f04bec4, 0x3f3ebf22,
    0x3f67bf55, 0x3f7dbf75, 0xbf7d3f80, 0xbf673f75, 0xbf3e3f55, 0xbf043f22, 0xbe793ec4, 0x3d493dc9, 0x3eacbe48, 0x3f18bef1,
    0x3f4ebf35, 0x3f71bf62, 0x3f80bf7b, 0x3f78bf7f, 0x3f5cbf6d, 0x3f2cbf46, 0x3edbbf0e, 0x3e16be95, 0xbe793ec4, 0x3d493dc9,
    0x3eacbe48, 0x3f18bef1, 0xbf7d3f80, 0xbf673f75, 0xbf3e3f55, 0xbf043f22, 0x3f5cbf6d, 0x3f2cbf46, 0x3edbbf0e, 0x3e16be95,
    0x3f4ebf35, 0x3f71bf62, 0x3f80bf7b, 0x3f78bf7f, 0x3f78bf6d, 0x3f80bf7f, 0x3f71bf7b, 0x3f4ebf62, 0x3e160000, 0x3edbbe95,
    0x3f2cbf0e, 0x3f5cbf46, 0xbf043ec4, 0xbf3e3f22, 0xbf673f55, 0xbf7d3f75, 0x3f18bf35, 0x3eacbef1, 0x3d49be48, 0xbe793dc9,
    0x3f3ebf35, 0x3f4ebf46, 0x3f5cbf55, 0x3f67bf62, 0x3f71bf6d, 0x3f78bf75, 0x3f7dbf7b, 0x3f80bf7f, 0x3d490000, 0x3e16bdc9,
    0x3e79be48, 0x3eacbe95, 0x3edbbec4, 0x3f04bef1, 0x3f18bf0e, 0x3f2cbf22, 0xbf2c3f35, 0xbf183f22, 0xbf043f0e, 0xbedb3ef1,
    0xbeac3ec4, 0xbe793e95, 0xbe163e48, 0xbd493dc9, 0xbf803f80, 0xbf7d3f7f, 0xbf783f7b, 0xbf713f75, 0xbf673f6d, 0xbf5c3f62,
    0xbf4e3f55, 0xbf3e3f46, 0x3eacbec4, 0x3e79be95, 0x3e16be48, 0x3d49bdc9, 0x3f2cbf35, 0x3f18bf22, 0x3f04bf0e, 0x3edbbef1,
    0x3f67bf6d, 0x3f5cbf62, 0x3f4ebf55, 0x3f3ebf46, 0x3f80bf80, 0x3f7dbf7f, 0x3f78bf7b, 0x3f71bf75, 0x3f71bf6d, 0x3f78bf75,
    0x3f7dbf7b, 0x3f80bf7f, 0x3f3ebf35, 0x3f4ebf46, 0x3f5cbf55, 0x3f67bf62, 0x3edbbec4, 0x3f04bef1, 0x3f18bf0e, 0x3f2cbf22,
    0x3d490000, 0x3e16bdc9, 0x3e79be48, 0x3eacbe95,
};
__device__ const __align__(128) uint32_t c_ga[1536] = {
    0x00003c80, 0x3bc43c6d, 0x00003c80, 0xbbc4bc6d, 0x00003c80, 0x3c6d3bc4, 0x00003c80, 0xbc6dbbc4, 0x00003c80, 0x3c6dbbc4,
    0x00003c80, 0xbc6d3bc4, 0x00003c80, 0x3bc4bc6d, 0x00003c80, 0xbbc43c6d, 0x3a493c80, 0x3bdb3c67, 0x3bdb3c67, 0xbc3ebc2c,
    0x3b163c7d, 0x3c783b79, 0x3c043c5c, 0xbc7d3b16, 0x3b793c78, 0x3c4ebc18, 0x3c183c4e, 0xbc043c5c, 0x3bac3c71, 0x3a49bc80,
    0x3c2c3c3e, 0x3bac3c71, 0x3ac93c7f, 0x3bf13c62, 0x3c463c22, 0xbc75bb95, 0x3b953c75, 0x3c7f3ac9, 0x3c623bf1, 0xbc463c22,
    0x3bf13c62, 0x3c22bc46, 0x3c753b95, 0x3ac93c7f, 0x3c223c46, 0xbb95bc75, 0x3c7f3ac9, 0x3c623bf1, 0x3b163c7d, 0x3c043c5c,
    0x3c783b79, 0xbc7d3b16, 0x3bdb3c67, 0x3c80ba49, 0x3c80ba49, 0xbbac3c71, 0x3c2c3c3e, 0x3bdbbc67, 0x3c71bbac, 0x3c2c3c3e,
    0x3c5c3c04, 0xbc18bc4e, 0x3c4ebc18, 0x3c78bb79, 0x3b483c7b, 0x3c0e3c55, 0x3c7bbb48, 0xbc553c0e, 0x3c0e3c55, 0x3c7bbb48,
    0x3c55bc0e, 0x3b483c7b, 0x3c553c0e, 0x3b48bc7b, 0x3c0ebc55, 0x3c7b3b48, 0x3c7b3b48, 0xbc55bc0e, 0x3b48bc7b, 0x3c0ebc55,
    0x3b793c78, 0x3c183c4e, 0x3c4ebc18, 0xbc043c5c, 0x3c2c3c3e, 0x3c71bbac, 0x3bdbbc67, 0x3c2c3c3e, 0x3c713bac, 0xba49bc80,
    0xba49bc80, 0x3c67bbdb, 0x3c7dbb16, 0xbc78bb79, 0xbc04bc5c, 0xbb16bc7d, 0x3b953c75, 0x3c223c46, 0x3bf1bc62, 0xbac93c7f,
    0x3c463c22, 0x3c62bbf1, 0xbac9bc7f, 0x3c753b95, 0x3c7f3ac9, 0xbb95bc75, 0xbc22bc46, 0x3bf1bc62, 0x3c62bbf1, 0xbc7f3ac9,
    0xbc75bb95, 0xbc46bc22, 0x3bac3c71, 0x3c2c3c3e, 0x3a49bc80, 0x3bac3c71, 0x3c5c3c04, 0x3c4ebc18, 0xbc18bc4e, 0x3c78bb79,
    0x3c7dbb16, 0xbc04bc5c, 0xbc78bb79, 0xbb16bc7d, 0x3c2cbc3e, 0xbc673bdb, 0xbc673bdb, 0xbc803a49, 0x00003c80, 0x3bc43c6d,
    0x00003c80, 0xbbc4bc6d, 0x00003c80, 0x3c6d3bc4, 0x00003c80, 0xbc6dbbc4, 0x00003c80, 0x3c6dbbc4, 0x00003c80, 0xbc6d3bc4,
    0x00003c80, 0x3bc4bc6d, 0x00003c80, 0xbbc43c6d, 0x3c3e3c2c, 0x3c713bac, 0x3c713bac, 0xbc803a49, 0x3c4e3c18, 0x3c5cbc04,
    0x3c783b79, 0xbc183c4e, 0x3c5c3c04, 0x3b16bc7d, 0x3c7d3b16, 0x3b793c78, 0x3c673bdb, 0xbc2cbc3e, 0x3c803a49, 0x3c673bdb,
    0x3c7fbac9, 0x3c62bbf1, 0x3c22bc46, 0xbb953c75, 0x3c75bb95, 0x3ac9bc7f, 0x3bf1bc62, 0x3c223c46, 0x3c62bbf1, 0xbc46bc22,
    0x3b95bc75, 0x3c7fbac9, 0x3c46bc22, 0xbc753b95, 0x3ac9bc7f, 0x3bf1bc62, 0x3c18bc4e, 0x3b79bc78, 0xbc04bc5c, 0x3c4e3c18,
    0x3bacbc71, 0xbc3ebc2c, 0xbc3ebc2c, 0x3c67bbdb, 0x3a49bc80, 0xbc713bac, 0xbc67bbdb, 0x3a49bc80, 0xbb79bc78, 0xbb163c7d,
    0xbc7dbb16, 0xbc5cbc04, 0xbb48bc7b, 0xbc0ebc55, 0xbc7b3b48, 0x3c55bc0e, 0xbc0ebc55, 0xbc7b3b48, 0xbc553c0e, 0xbb48bc7b,
    0xbc55bc0e, 0xbb483c7b, 0xbc0e3c55, 0xbc7bbb48, 0xbc7bbb48, 0x3c553c0e, 0xbb483c7b, 0xbc0e3c55, 0xbc5cbc04, 0xbc7dbb16,
    0xbb163c7d, 0xbb79bc78, 0xbc80ba49, 0xbbdb3c67, 0x3bac3c71, 0xbc80ba49, 0xbc673bdb, 0x3c3e3c2c, 0x3c3e3c2c, 0xbbac3c71,
    0xbc183c4e, 0x3c5cbc04, 0x3c783b79, 0x3c4e3c18, 0xbc753b95, 0xbc463c22, 0x3c623bf1, 0xbc7fbac9, 0xbc223c46, 0x3bf13c62,
    0x3c7fbac9, 0xbb953c75, 0xbac93c7f, 0x3c75bb95, 0x3c46bc22, 0x3c623bf1, 0x3bf13c62, 0xbac9bc7f, 0x3b95bc75, 0x3c22bc46,
    0xbbdb3c67, 0xba493c80, 0x3c3ebc2c, 0xbbdb3c67, 0x3b793c78, 0x3c7d3b16, 0x3b16bc7d, 0x3c5c3c04, 0x3c4e3c18, 0x3b79bc78,
    0xbc04bc5c, 0x3c18bc4e, 0x3c80ba49, 0xbc71bbac, 0xbc71bbac, 0xbc3ebc2c, 0x00003c80, 0x3bc43c6d, 0x00003c80, 0xbbc4bc6d,
    0x00003c80, 0x3c6d3bc4, 0x00003c80, 0xbc6dbbc4, 0x00003c80, 0x3c6dbbc4, 0x00003c80, 0xbc6d3bc4, 0x00003c80, 0x3bc4bc6d,
    0x00003c80, 0xbbc43c6d, 0x3c80ba49, 0x3c67bbdb, 0x3c67bbdb, 0xbc2c3c3e, 0x3c7dbb16, 0x3b79bc78, 0x3c5cbc04, 0x3b163c7d,
    0x3c78bb79, 0xbc18bc4e, 0x3c4ebc18, 0x3c5c3c04, 0x3c71bbac, 0xbc80ba49, 0x3c3ebc2c, 0x3c71bbac, 0xbac9bc7f, 0xbbf1bc62,
    0xbc46bc22, 0x3c753b95, 0xbb95bc75, 0xbc7fbac9, 0xbc62bbf1, 0x3c46bc22, 0xbbf1bc62, 0xbc223c46, 0xbc75bb95, 0xbac9bc7f,
    0xbc22bc46, 0x3b953c75, 0xbc7fbac9, 0xbc62bbf1, 0xbc7d3b16, 0xbc5c3c04, 0xbb793c78, 0xbb16bc7d, 0xbc673bdb, 0x3a493c80,
    0x3a493c80, 0xbc71bbac, 0xbc3e3c2c, 0x3c673bdb, 0x3bac3c71, 0xbc3e3c2c, 0xbc043c5c, 0x3c4ebc18, 0x3c183c4e, 0x3b793c78,
    0x3b483c7b, 0x3c0e3c55, 0x3c7bbb48, 0xbc553c0e, 0x3c0e3c55, 0x3c7bbb48, 0x3c55bc0e, 0x3b483c7b, 0x3c553c0e, 0x3b48bc7b,
    0x3c0ebc55, 0x3c7b3b48, 0x3c7b3b48, 0xbc55bc0e, 0x3b48bc7b, 0x3c0ebc55, 0x3c78bb79, 0x3c4ebc18, 0xbc18bc4e, 0x3c5c3c04,
    0x3c3ebc2c, 0xbbacbc71, 0xbc67bbdb, 0x3c3ebc2c, 0x3bacbc71, 0xbc803a49, 0xbc803a49, 0xbbdbbc67, 0xbb16bc7d, 0xbb793c78,
    0xbc5c3c04, 0xbc7d3b16, 0xbb95bc75, 0xbc22bc46, 0xbbf13c62, 0x3ac9bc7f, 0xbc46bc22, 0xbc623bf1, 0x3ac93c7f, 0xbc75bb95,
    0xbc7fbac9, 0x3b953c75, 0x3c223c46, 0xbbf13c62, 0xbc623bf1, 0x3c7fbac9, 0x3c753b95, 0x3c463c22, 0xbc713bac, 0xbc3e3c2c,
    0x3c803a49, 0xbc713bac, 0xbc043c5c, 0x3c183c4e, 0x3c4ebc18, 0x3b793c78, 0x3b163c7d, 0x3c5cbc04, 0x3b79bc78, 0x3c7dbb16,
    0x3c3e3c2c, 0xbbdbbc67, 0xbbdbbc67, 0xba49bc80, 0x00003c80, 0x3bc43c6d, 0x00003c80, 0xbbc4bc6d, 0x00003c80, 0x3c6d3bc4,
    0x00003c80, 0xbc6dbbc4, 0x00003c80, 0x3c6dbbc4, 0x00003c80, 0xbc6d3bc4, 0x00003c80, 0x3bc4bc6d, 0x00003c80, 0xbbc43c6d,
    0x3c2cbc3e, 0x3bacbc71, 0x3bacbc71, 0x3a493c80, 0x3c18bc4e, 0xbc04bc5c, 0x3b79bc78, 0x3c4e3c18, 0x3c04bc5c, 0xbc7dbb16,
    0x3b16bc7d, 0x3c78bb79, 0x3bdbbc67, 0xbc3e3c2c, 0x3a49bc80, 0x3bdbbc67, 0xbc7f3ac9, 0xbc623bf1, 0xbc223c46, 0x3b95bc75,
    0xbc753b95, 0xbac93c7f, 0xbbf13c62, 0xbc22bc46, 0xbc623bf1, 0x3c463c22, 0xbb953c75, 0xbc7f3ac9, 0xbc463c22, 0x3c75bb95,
    0xbac93c7f, 0xbbf13c62, 0x3c4e3c18, 0x3c783b79, 0x3c5cbc04, 0xbc183c4e, 0x3c713bac, 0x3c2cbc3e, 0x3c2cbc3e, 0x3bdb3c67,
    0x3c803a49, 0xbbacbc71, 0x3bdbbc67, 0x3c803a49, 0x3c78bb79, 0xbc7dbb16, 0x3b16bc7d, 0x3c04bc5c, 0xbb48bc7b, 0xbc0ebc55,
    0xbc7b3b48, 0x3c55bc0e, 0xbc0ebc55, 0xbc7b3b48, 0xbc553c0e, 0xbb48bc7b, 0xbc55bc0e, 0xbb483c7b, 0xbc0e3c55, 0xbc7bbb48,
    0xbc7bbb48, 0x3c553c0e, 0xbb483c7b, 0xbc0e3c55, 0xbc043c5c, 0xbb163c7d, 0x3c7d3b16, 0xbc783b79, 0xba493c80, 0x3c673bdb,
    0x3c71bbac, 0xba493c80, 0x3bdb3c67, 0x3c2cbc3e, 0x3c2cbc3e, 0x3c713bac, 0x3c4e3c18, 0xbc04bc5c, 0x3b79bc78, 0x3c18bc4e,
    0x3c75bb95, 0x3c46bc22, 0xbc62bbf1, 0x3c7f3ac9, 0x3c22bc46, 0xbbf1bc62, 0xbc7f3ac9, 0x3b95bc75, 0x3ac9bc7f, 0xbc753b95,
    0xbc463c22, 0xbc62bbf1, 0xbbf1bc62, 0x3ac93c7f, 0xbb953c75, 0xbc223c46, 0xbc67bbdb, 0xbc80ba49, 0x3c2c3c3e, 0xbc67bbdb,
    0xbc783b79, 0xbb163c7d, 0x3c7d3b16, 0xbc043c5c, 0xbc183c4e, 0x3c783b79, 0x3c5cbc04, 0x3c4e3c18, 0x3a493c80, 0x3bacbc71,
    0x3bacbc71, 0x3c2cbc3e, 0x3c353c35, 0x3c6d3bc4, 0x3c353c35, 0xbc6dbbc4, 0x3c35bc35, 0xbbc4bc6d, 0x3c35bc35, 0x3bc43c6d,
    0xbc35bc35, 0xbbc43c6d, 0xbc35bc35, 0x3bc4bc6d, 0xbc353c35, 0x3c6dbbc4, 0xbc353c35, 0xbc6d3bc4, 0x3c3e3c2c, 0x3c713bac,
    0x3c713bac, 0xbc803a49, 0x3c18bc4e, 0xbc04bc5c, 0x3b79bc78, 0x3c4e3c18, 0xbc5cbc04, 0xbb163c7d, 0xbc7dbb16, 0xbb79bc78,
    0xbbdb3c67, 0x3c3ebc2c, 0xba493c80, 0xbbdb3c67, 0x3c463c22, 0x3c753b95, 0x3c7fbac9, 0xbc623bf1, 0x3bf1bc62, 0xbc22bc46,
    0xbb95bc75, 0x3c7f3ac9, 0xbc75bb95, 0x3ac93c7f, 0xbc623bf1, 0xbc46bc22, 0xbac93c7f, 0x3bf1bc62, 0x3c223c46, 0x3b953c75,
    0x3c4e3c18, 0x3c783b79, 0x3c5cbc04, 0xbc183c4e, 0x3bacbc71, 0xbc3ebc2c, 0xbc3ebc2c, 0x3c67bbdb, 0xbc80ba49, 0x3bac3c71,
    0xbbdb3c67, 0xbc80ba49, 0x3b793c78, 0x3b16bc7d, 0x3c7d3b16, 0x3c5c3c04, 0x3c553c0e, 0x3c7b3b48, 0x3c0ebc55, 0xbb483c7b,
    0x3b48bc7b, 0xbc55bc0e, 0xbc7bbb48, 0x3c0ebc55, 0xbc7b3b48, 0x3c0e3c55, 0x3b483c7b, 0xbc553c0e, 0x3c0e3c55, 0xbb48bc7b,
    0x3c55bc0e, 0x3c7bbb48, 0x3c5c3c04, 0x3c7d3b16, 0x3b16bc7d, 0x3b793c78, 0x3a49bc80, 0xbc67bbdb, 0xbc713bac, 0x3a49bc80,
    0xbc673bdb, 0x3c3e3c2c, 0x3c3e3c2c, 0xbbac3c71, 0x3c4e3c18, 0xbc04bc5c, 0x3b79bc78, 0x3c18bc4e, 0x3c623bf1, 0x3c7f3ac9,
    0xbb95bc75, 0x3c223c46, 0xbac9bc7f, 0xbc75bb95, 0xbc223c46, 0xbbf1bc62, 0xbc463c22, 0x3c623bf1, 0x3c7f3ac9, 0x3b953c75,
    0x3c753b95, 0xbc46bc22, 0xbbf1bc62, 0xbac9bc7f, 0x3c673bdb, 0x3c803a49, 0xbc2cbc3e, 0x3c673bdb, 0xbb79bc78, 0xbc7dbb16,
    0xbb163c7d, 0xbc5cbc04, 0xbc183c4e, 0x3c783b79, 0x3c5cbc04, 0x3c4e3c18, 0x3c80ba49, 0xbc71bbac, 0xbc71bbac, 0xbc3ebc2c,
    0x3c353c35, 0x3c6d3bc4, 0x3c353c35, 0xbc6dbbc4, 0x3c35bc35, 0xbbc4bc6d, 0x3c35bc35, 0x3bc43c6d, 0xbc35bc35, 0xbbc43c6d,
    0xbc35bc35, 0x3bc4bc6d, 0xbc353c35, 0x3c6dbbc4, 0xbc353c35, 0xbc6d3bc4, 0x3c80ba49, 0x3c67bbdb, 0x3c67bbdb, 0xbc2c3c3e,
    0xbb16bc7d, 0xbc78bb79, 0xbc04bc5c, 0x3c7dbb16, 0xbc783b79, 0x3c183c4e, 0xbc4e3c18, 0xbc5cbc04, 0x3bac3c71, 0x3a49bc80,
    0x3c2c3c3e, 0x3bac3c71, 0x3c22bc46, 0x3b95bc75, 0xbac9bc7f, 0x3bf13c62, 0xbc62bbf1, 0xbc463c22, 0xbc753b95, 0x3ac9bc7f,
    0xbb953c75, 0x3c7fbac9, 0x3bf13c62, 0xbc223c46, 0x3c7f3ac9, 0xbc62bbf1, 0x3c46bc22, 0x3c75bb95, 0xbb16bc7d, 0xbc04bc5c,
    0xbc78bb79, 0x3c7dbb16, 0xbc673bdb, 0x3a493c80, 0x3a493c80, 0xbc71bbac, 0x3c2c3c3e, 0x3bdbbc67, 0x3c71bbac, 0x3c2c3c3e,
    0x3c04bc5c, 0xbc4e3c18, 0xbc18bc4e, 0xbb79bc78, 0xbc55bc0e, 0xbc7bbb48, 0xbc0e3c55, 0x3b48bc7b, 0xbb483c7b, 0x3c553c0e,
    0x3c7b3b48, 0xbc0e3c55, 0x3c7bbb48, 0xbc0ebc55, 0xbb48bc7b, 0x3c55bc0e, 0xbc0ebc55, 0x3b483c7b, 0xbc553c0e, 0xbc7b3b48,
    0xbc783b79, 0xbc4e3c18, 0x3c183c4e, 0xbc5cbc04, 0x3c2c3c3e, 0x3c71bbac, 0x3bdbbc67, 0x3c2c3c3e, 0x3bacbc71, 0xbc803a49,
    0xbc803a49, 0xbbdbbc67, 0xbc7d3b16, 0x3c783b79, 0x3c043c5c, 0x3b163c7d, 0xbbf13c62, 0xbac93c7f, 0x3c75bb95, 0xbc463c22,
    0x3c7fbac9, 0x3b95bc75, 0xbc46bc22, 0x3c62bbf1, 0xbc22bc46, 0xbbf13c62, 0xbac93c7f, 0xbc753b95, 0xbb953c75, 0x3c22bc46,
    0x3c62bbf1, 0x3c7fbac9, 0x3bac3c71, 0x3c2c3c3e, 0x3a49bc80, 0x3bac3c71, 0x3c04bc5c, 0xbc18bc4e, 0xbc4e3c18, 0xbb79bc78,
    0xbc7d3b16, 0x3c043c5c, 0x3c783b79, 0x3b163c7d, 0x3c3e3c2c, 0xbbdbbc67, 0xbbdbbc67, 0xba49bc80, 0x3c353c35, 0x3c6d3bc4,
    0x3c353c35, 0xbc6dbbc4, 0x3c35bc35, 0xbbc4bc6d, 0x3c35bc35, 0x3bc43c6d, 0xbc35bc35, 0xbbc43c6d, 0xbc35bc35, 0x3bc4bc6d,
    0xbc353c35, 0x3c6dbbc4, 0xbc353c35, 0xbc6d3bc4, 0x3c2cbc3e, 0x3bacbc71, 0x3bacbc71, 0x3a493c80, 0xbc4ebc18, 0xbc5c3c04,
    0xbc78bb79, 0x3c18bc4e, 0xbc043c5c, 0x3c7d3b16, 0xbb163c7d, 0xbc783b79, 0x3c673bdb, 0xbc2cbc3e, 0x3c803a49, 0x3c673bdb,
    0xbc46bc22, 0xbc75bb95, 0xbc7f3ac9, 0x3c62bbf1, 0xbbf13c62, 0x3c223c46, 0x3b953c75, 0xbc7fbac9, 0x3c753b95, 0xbac9bc7f,
    0x3c62bbf1, 0x3c463c22, 0x3ac9bc7f, 0xbbf13c62, 0xbc22bc46, 0xbb95bc75, 0xbc183c4e, 0xbb793c78, 0x3c043c5c, 0xbc4ebc18,
    0x3c713bac, 0x3c2cbc3e, 0x3c2cbc3e, 0x3bdb3c67, 0x3a49bc80, 0xbc713bac, 0xbc67bbdb, 0x3a49bc80, 0xbc783b79, 0x3c7d3b16,
    0xbb163c7d, 0xbc043c5c, 0x3c553c0e, 0x3c7b3b48, 0x3c0ebc55, 0xbb483c7b, 0x3b48bc7b, 0xbc55bc0e, 0xbc7bbb48, 0x3c0ebc55,
    0xbc7b3b48, 0x3c0e3c55, 0x3b483c7b, 0xbc553c0e, 0x3c0e3c55, 0xbb48bc7b, 0x3c55bc0e, 0x3c7bbb48, 0x3c04bc5c, 0x3b16bc7d,
    0xbc7dbb16, 0x3c78bb79, 0xbc80ba49, 0xbbdb3c67, 0x3bac3c71, 0xbc80ba49, 0x3bdb3c67, 0x3c2cbc3e, 0x3c2cbc3e, 0x3c713bac,
    0x3c18bc4e, 0xbc5c3c04, 0xbc78bb79, 0xbc4ebc18, 0xbc62bbf1, 0xbc7fbac9, 0x3b953c75, 0xbc22bc46, 0x3ac93c7f, 0x3c753b95,
    0x3c22bc46, 0x3bf13c62, 0x3c46bc22, 0xbc62bbf1, 0xbc7fbac9, 0xbb95bc75, 0xbc75bb95, 0x3c463c22, 0x3bf13c62, 0x3ac93c7f,
    0xbbdb3c67, 0xba493c80, 0x3c3ebc2c, 0xbbdb3c67, 0x3c78bb79, 0x3b16bc7d, 0xbc7dbb16, 0x3c04bc5c, 0xbc4ebc18, 0xbb793c78,
    0x3c043c5c, 0xbc183c4e, 0x3a493c80, 0x3bacbc71, 0x3bacbc71, 0x3c2cbc3e, 0x3c353c35, 0x3c6d3bc4, 0x3c353c35, 0xbc6dbbc4,
    0x3c35bc35, 0xbbc4bc6d, 0x3c35bc35, 0x3bc43c6d, 0xbc35bc35, 0xbbc43c6d, 0xbc35bc35, 0x3bc4bc6d, 0xbc353c35, 0x3c6dbbc4,
    0xbc353c35, 0xbc6d3bc4, 0xba49bc80, 0xbbdbbc67, 0xbbdbbc67, 0x3c3e3c2c, 0xbc7d3b16, 0xbb793c78, 0xbc5c3c04, 0xbb16bc7d,
    0x3b793c78, 0x3c4ebc18, 0x3c183c4e, 0xbc043c5c, 0x3c71bbac, 0xbc80ba49, 0x3c3ebc2c, 0x3c71bbac, 0xbc223c46, 0xbb953c75,
    0x3ac93c7f, 0xbbf1bc62, 0x3c623bf1, 0x3c46bc22, 0x3c75bb95, 0xbac93c7f, 0x3b95bc75, 0xbc7f3ac9, 0xbbf1bc62, 0x3c22bc46,
    0xbc7fbac9, 0x3c623bf1, 0xbc463c22, 0xbc753b95, 0x3c7dbb16, 0x3c5cbc04, 0x3b79bc78, 0x3b163c7d, 0xbbdbbc67, 0xbc803a49,
    0xbc803a49, 0x3bacbc71, 0xbc3e3c2c, 0x3c673bdb, 0x3bac3c71, 0xbc3e3c2c, 0x3c5c3c04, 0xbc18bc4e, 0x3c4ebc18, 0x3c78bb79,
    0xbc55bc0e, 0xbc7bbb48, 0xbc0e3c55, 0x3b48bc7b, 0xbb483c7b, 0x3c553c0e, 0x3c7b3b48, 0xbc0e3c55, 0x3c7bbb48, 0xbc0ebc55,
    0xbb48bc7b, 0x3c55bc0e, 0xbc0ebc55, 0x3b483c7b, 0xbc553c0e, 0xbc7b3b48, 0x3b793c78, 0x3c183c4e, 0x3c4ebc18, 0xbc043c5c,
    0x3c3ebc2c, 0xbbacbc71, 0xbc67bbdb, 0x3c3ebc2c, 0xbc71bbac, 0x3a493c80, 0x3a493c80, 0xbc673bdb, 0x3b163c7d, 0x3b79bc78,
    0x3c5cbc04, 0x3c7dbb16, 0x3bf1bc62, 0x3ac9bc7f, 0xbc753b95, 0x3c46bc22, 0xbc7f3ac9, 0xbb953c75, 0x3c463c22, 0xbc623bf1,
    0x3c223c46, 0x3bf1bc62, 0x3ac9bc7f, 0x3c75bb95, 0x3b95bc75, 0xbc223c46, 0xbc623bf1, 0xbc7f3ac9, 0xbc713bac, 0xbc3e3c2c,
    0x3c803a49, 0xbc713bac, 0x3c5c3c04, 0x3c4ebc18, 0xbc18bc4e, 0x3c78bb79, 0xbb16bc7d, 0xbc5c3c04, 0xbb793c78, 0xbc7d3b16,
    0xbc2c3c3e, 0x3c67bbdb, 0x3c67bbdb, 0x3c80ba49, 0x3c800000, 0x3c6dbbc4, 0x3c800000, 0xbc6d3bc4, 0xbc800000, 0xbbc43c6d,
    0xbc800000, 0x3bc4bc6d, 0x3c800000, 0xbbc4bc6d, 0x3c800000, 0x3bc43c6d, 0xbc800000, 0x3c6d3bc4, 0xbc800000, 0xbc6dbbc4,
    0x3c80ba49, 0x3c67bbdb, 0x3c67bbdb, 0xbc2c3c3e, 0xbc7d3b16, 0xbb793c78, 0xbc5c3c04, 0xbb16bc7d, 0x3c78bb79, 0xbc18bc4e,
    0x3c4ebc18, 0x3c5c3c04, 0xbc713bac, 0x3c803a49, 0xbc3e3c2c, 0xbc713bac, 0x3c7fbac9, 0x3c62bbf1, 0x3c22bc46, 0xbb953c75,
    0xbc753b95, 0xbac93c7f, 0xbbf13c62, 0xbc22bc46, 0x3c62bbf1, 0xbc46bc22, 0x3b95bc75, 0x3c7fbac9, 0xbc463c22, 0x3c75bb95,
    0xbac93c7f, 0xbbf13c62, 0x3c7dbb16, 0x3c5cbc04, 0x3b79bc78, 0x3b163c7d, 0xbc673bdb, 0x3a493c80, 0x3a493c80, 0xbc71bbac,
    0x3c3ebc2c, 0xbc67bbdb, 0xbbacbc71, 0x3c3ebc2c, 0xbc043c5c, 0x3c4ebc18, 0x3c183c4e, 0x3b793c78, 0x3c7bbb48, 0x3c55bc0e,
    0xbb48bc7b, 0x3c0e3c55, 0xbc553c0e, 0x3b483c7b, 0x3c0e3c55, 0xbc7b3b48, 0x3c0ebc55, 0xbc7bbb48, 0xbc55bc0e, 0x3b48bc7b,
    0xbb483c7b, 0x3c0ebc55, 0x3c7b3b48, 0x3c553c0e, 0x3c78bb79, 0x3c4ebc18, 0xbc18bc4e, 0x3c5c3c04, 0xbc3e3c2c, 0x3bac3c71,
    0x3c673bdb, 0xbc3e3c2c, 0x3bacbc71, 0xbc803a49, 0xbc803a49, 0xbbdbbc67, 0x3b163c7d, 0x3b79bc78, 0x3c5cbc04, 0x3c7dbb16,
    0x3c75bb95, 0x3c46bc22, 0xbc62bbf1, 0x3c7f3ac9, 0xbc223c46, 0x3bf13c62, 0x3c7fbac9, 0xbb953c75, 0x3ac9bc7f, 0xbc753b95,
    0xbc463c22, 0xbc62bbf1, 0x3bf13c62, 0xbac9bc7f, 0x3b95bc75, 0x3c22bc46, 0x3c71bbac, 0x3c3ebc2c, 0xbc80ba49, 0x3c71bbac,
    0xbc043c5c, 0x3c183c4e, 0x3c4ebc18, 0x3b793c78, 0xbb16bc7d, 0xbc5c3c04, 0xbb793c78, 0xbc7d3b16, 0x3c3e3c2c, 0xbbdbbc67,
    0xbbdbbc67, 0xba49bc80, 0x3c800000, 0x3c6dbbc4, 0x3c800000, 0xbc6d3bc4, 0xbc800000, 0xbbc43c6d, 0xbc800000, 0x3bc4bc6d,
    0x3c800000, 0xbbc4bc6d, 0x3c800000, 0x3bc43c6d, 0xbc800000, 0x3c6d3bc4, 0xbc800000, 0xbc6dbbc4, 0x3c2cbc3e, 0x3bacbc71,
    0x3bacbc71, 0x3a493c80, 0xbc183c4e, 0x3c043c5c, 0xbb793c78, 0xbc4ebc18, 0x3c04bc5c, 0xbc7dbb16, 0x3b16bc7d, 0x3c78bb79,
    0xbbdb3c67, 0x3c3ebc2c, 0xba493c80, 0xbbdb3c67, 0xbac9bc7f, 0xbbf1bc62, 0xbc46bc22, 0x3c753b95, 0x3b953c75, 0x3c7f3ac9,
    0x3c623bf1, 0xbc463c22, 0xbbf1bc62, 0xbc223c46, 0xbc75bb95, 0xbac9bc7f, 0x3c223c46, 0xbb95bc75, 0x3c7f3ac9, 0x3c623bf1,
    0xbc4ebc18, 0xbc78bb79, 0xbc5c3c04, 0x3c18bc4e, 0x3c713bac, 0x3c2cbc3e, 0x3c2cbc3e, 0x3bdb3c67, 0xbc80ba49, 0x3bac3c71,
    0xbbdb3c67, 0xbc80ba49, 0x3c78bb79, 0xbc7dbb16, 0x3b16bc7d, 0x3c04bc5c, 0xbc7b3b48, 0xbc553c0e, 0x3b483c7b, 0xbc0ebc55,
    0x3c55bc0e, 0xbb48bc7b, 0xbc0ebc55, 0x3c7bbb48, 0xbc0e3c55, 0x3c7b3b48, 0x3c553c0e, 0xbb483c7b, 0x3b48bc7b, 0xbc0e3c55,
    0xbc7bbb48, 0xbc55bc0e, 0xbc043c5c, 0xbb163c7d, 0x3c7d3b16, 0xbc783b79, 0x3a49bc80, 0xbc67bbdb, 0xbc713bac, 0x3a49bc80,
    0x3bdb3c67, 0x3c2cbc3e, 0x3c2cbc3e, 0x3c713bac, 0xbc4ebc18, 0x3c043c5c, 0xbb793c78, 0xbc183c4e, 0x3b953c75, 0x3c223c46,
    0x3bf1bc62, 0xbac93c7f, 0xbc46bc22, 0xbc623bf1, 0x3ac93c7f, 0xbc75bb95, 0x3c7f3ac9, 0xbb95bc75, 0xbc22bc46, 0x3bf1bc62,
    0xbc623bf1, 0x3c7fbac9, 0x3c753b95, 0x3c463c22, 0x3c673bdb, 0x3c803a49, 0xbc2cbc3e, 0x3c673bdb, 0xbc783b79, 0xbb163c7d,
    0x3c7d3b16, 0xbc043c5c, 0x3c18bc4e, 0xbc78bb79, 0xbc5c3c04, 0xbc4ebc18, 0x3a493c80, 0x3bacbc71, 0x3bacbc71, 0x3c2cbc3e,
    0x3c800000, 0x3c6dbbc4, 0x3c800000, 0xbc6d3bc4, 0xbc800000, 0xbbc43c6d, 0xbc800000, 0x3bc4bc6d, 0x3c800000, 0xbbc4bc6d,
    0x3c800000, 0x3bc43c6d, 0xbc800000, 0x3c6d3bc4, 0xbc800000, 0xbc6dbbc4, 0xba49bc80, 0xbbdbbc67, 0xbbdbbc67, 0x3c3e3c2c,
    0x3b163c7d, 0x3c783b79, 0x3c043c5c, 0xbc7d3b16, 0xbb79bc78, 0xbc4e3c18, 0xbc18bc4e, 0x3c04bc5c, 0x3bac3c71, 0x3a49bc80,
    0x3c2c3c3e, 0x3bac3c71, 0xbc7f3ac9, 0xbc623bf1, 0xbc223c46, 0x3b95bc75, 0x3c75bb95, 0x3ac9bc7f, 0x3bf1bc62, 0x3c223c46,
    0xbc623bf1, 0x3c463c22, 0xbb953c75, 0xbc7f3ac9, 0x3c46bc22, 0xbc753b95, 0x3ac9bc7f, 0x3bf1bc62, 0x3b163c7d, 0x3c043c5c,
    0x3c783b79, 0xbc7d3b16, 0xbbdbbc67, 0xbc803a49, 0xbc803a49, 0x3bacbc71, 0x3c2c3c3e, 0x3bdbbc67, 0x3c71bbac, 0x3c2c3c3e,
    0xbc5cbc04, 0x3c183c4e, 0xbc4e3c18, 0xbc783b79, 0x3c7bbb48, 0x3c55bc0e, 0xbb48bc7b, 0x3c0e3c55, 0xbc553c0e, 0x3b483c7b,
    0x3c0e3c55, 0xbc7b3b48, 0x3c0ebc55, 0xbc7bbb48, 0xbc55bc0e, 0x3b48bc7b, 0xbb483c7b, 0x3c0ebc55, 0x3c7b3b48, 0x3c553c0e,
    0xbb79bc78, 0xbc18bc4e, 0xbc4e3c18, 0x3c04bc5c, 0x3c2c3c3e, 0x3c71bbac, 0x3bdbbc67, 0x3c2c3c3e, 0xbc71bbac, 0x3a493c80,
    0x3a493c80, 0xbc673bdb, 0x3c7dbb16, 0xbc78bb79, 0xbc04bc5c, 0xbb16bc7d, 0xbc753b95, 0xbc463c22, 0x3c623bf1, 0xbc7fbac9,
    0x3c22bc46, 0xbbf1bc62, 0xbc7f3ac9, 0x3b95bc75, 0xbac93c7f, 0x3c75bb95, 0x3c46bc22, 0x3c623bf1, 0xbbf1bc62, 0x3ac93c7f,
    0xbb953c75, 0xbc223c46, 0x3bac3c71, 0x3c2c3c3e, 0x3a49bc80, 0x3bac3c71, 0xbc5cbc04, 0xbc4e3c18, 0x3c183c4e, 0xbc783b79,
    0x3c7dbb16, 0xbc04bc5c, 0xbc78bb79, 0xbb16bc7d, 0xbc2c3c3e, 0x3c67bbdb, 0x3c67bbdb, 0x3c80ba49, 0x3c800000, 0x3c6dbbc4,
    0x3c800000, 0xbc6d3bc4, 0xbc800000, 0xbbc43c6d, 0xbc800000, 0x3bc4bc6d, 0x3c800000, 0xbbc4bc6d, 0x3c800000, 0x3bc43c6d,
    0xbc800000, 0x3c6d3bc4, 0xbc800000, 0xbc6dbbc4, 0xbc3ebc2c, 0xbc71bbac, 0xbc71bbac, 0x3c80ba49, 0x3c4e3c18, 0x3c5cbc04,
    0x3c783b79, 0xbc183c4e, 0xbc5cbc04, 0xbb163c7d, 0xbc7dbb16, 0xbb79bc78, 0x3c673bdb, 0xbc2cbc3e, 0x3c803a49, 0x3c673bdb,
    0x3ac93c7f, 0x3bf13c62, 0x3c463c22, 0xbc75bb95, 0xbb95bc75, 0xbc7fbac9, 0xbc62bbf1, 0x3c46bc22, 0x3bf13c62, 0x3c22bc46,
    0x3c753b95, 0x3ac93c7f, 0xbc22bc46, 0x3b953c75, 0xbc7fbac9, 0xbc62bbf1, 0x3c18bc4e, 0x3b79bc78, 0xbc04bc5c, 0x3c4e3c18,
    0xbbac3c71, 0x3c3e3c2c, 0x3c3e3c2c, 0xbc673bdb, 0x3a49bc80, 0xbc713bac, 0xbc67bbdb, 0x3a49bc80, 0x3b793c78, 0x3b16bc7d,
    0x3c7d3b16, 0x3c5c3c04, 0xbc7b3b48, 0xbc553c0e, 0x3b483c7b, 0xbc0ebc55, 0x3c55bc0e, 0xbb48bc7b, 0xbc0ebc55, 0x3c7bbb48,
    0xbc0e3c55, 0x3c7b3b48, 0x3c553c0e, 0xbb483c7b, 0x3b48bc7b, 0xbc0e3c55, 0xbc7bbb48, 0xbc55bc0e, 0x3c5c3c04, 0x3c7d3b16,
    0x3b16bc7d, 0x3b793c78, 0xbc80ba49, 0xbbdb3c67, 0x3bac3c71, 0xbc80ba49, 0x3c67bbdb, 0xbc3ebc2c, 0xbc3ebc2c, 0x3bacbc71,
    0xbc183c4e, 0x3c5cbc04, 0x3c783b79, 0x3c4e3c18, 0xbb95bc75, 0xbc22bc46, 0xbbf13c62, 0x3ac9bc7f, 0x3c463c22, 0x3c62bbf1,
    0xbac9bc7f, 0x3c753b95, 0xbc7fbac9, 0x3b953c75, 0x3c223c46, 0xbbf13c62, 0x3c62bbf1, 0xbc7f3ac9, 0xbc75bb95, 0xbc46bc22,
    0xbbdb3c67, 0xba493c80, 0x3c3ebc2c, 0xbbdb3c67, 0xbb79bc78, 0xbc7dbb16, 0xbb163c7d, 0xbc5cbc04, 0x3c4e3c18, 0x3b79bc78,
    0xbc04bc5c, 0x3c18bc4e, 0xbc803a49, 0x3c713bac, 0x3c713bac, 0x3c3e3c2c,
};

template <int G = 1024> __device__ __forceinline__ void store_tile_64(const float (&d)[32], uint32_t base, int warp, int lane) {
  const uint32_t rb = base + (warp * 2 + ((lane >> 3) & 1)) * G + (lane & 7) * 128;
#pragma unroll
  for (int j = 0; j < 8; j += 2) {
    const int jj = j + (lane >> 4);
    stsm4(rb + ((jj ^ (lane & 7)) << 4), pack2(d[4 * j], d[4 * j + 1]), pack2(d[4 * j + 2], d[4 * j + 3]),
          pack2(d[4 * j + 4], d[4 * j + 5]), pack2(d[4 * j + 6], d[4 * j + 7]));
  }
}

#define A_XM0 0xEB5C
#define A_XM1 0xDCBC
#define A_REL 0x22910
#define G_WPOLK 12
#define A_LDW 0x242
#define A_W2PF 2
#define A_DEPS 4
#define A_FREE 0x3F000
#define A_RELS 0x8A80
#define A_ACQ 0x1511
#define A_DEP 3
#define A_PACE0 1000
#define A_PACE1 A_PACE0
#define A_PACE_N 8
#define G_TMASK 0x0FB0
constexpr int A_IN = 112 * 128, A_OUT = 16384, A_NIN = 5, A_NOUT = 6;
constexpr int A_NREL = __builtin_popcount(A_REL);
constexpr int G_XP = NB1 * 64;
constexpr int G_STAGE = 16384 + 2 * G_XP, G_NST = 5;
constexpr int G_TIN = G_NST * G_STAGE, G_TOUT = G_TIN + 8192, G_SMEM = G_TOUT + 32768;
#define G_SLOTS 0x1032410324103210ull
__host__ __device__ constexpr int g_slot(int k) { return (G_SLOTS >> (4 * k)) & 7; }
constexpr uint32_t g_parities() {
  uint32_t m = 0;
  for (int k = 0; k < 16; k++)
    for (int j = 0; j < k; j++)
      if (g_slot(j) == g_slot(k)) m ^= 1u << k;
  return m;
}
constexpr uint32_t G_PAR = g_parities();
constexpr int G_KS = 12;
__device__ __align__(128) int g_cnt[4 * 32];

__device__ __forceinline__ int x_decode(int r, int cta) {
  const int v = r * 64 + ((cta >> 2) << 1) + (cta & 1);
  int j = v / 80;
  j -= v < 80 * j + ((0x4840 >> (4 * j)) & 15);
  if (cta < 128) return ((7 - j) << 7) | (v - 80 * j - ((0x4840 >> (4 * j)) & 15));
  return r < 8 ? ((5 - (r >> 2)) << 7) | (76 + 4 * (cta & 1) + (r & 3)) : ((7 - (r >> 1)) << 7) | (80 + 2 * (cta & 1) + (r & 1));
}
__device__ __forceinline__ uint32_t a_out(int n) {
  const int p = n % A_NOUT;
  return (p < 4 ? (3 + (p >> 1)) * G_STAGE : G_TOUT) + (p & 1) * A_OUT;
}
__device__ __forceinline__ uint32_t x1_addr(int L, int b, uint32_t flips) {
  const int p = L >> 4, sel = (b ^ __popc(L & 15) ^ (flips >> p)) & 1;
  return (p << 21) | (sel << 12) | ((L & 1) << 13) | ((L & 6) << 15) | ((L & 8) << 16);
}
__device__ __forceinline__ uint32_t spread16(int i) { return ((i & 3) << 14) | ((i & 4) << 16) | ((i & 8) << 17); }
constexpr int NPG = 19 + W_SHIFT, NVOTE = 6;
__device__ __forceinline__ uint32_t w_addr(int P, int f, int c, int dhalf, uint32_t flips) {
  return x1_addr(16 * P + (c >> 5) + 2 * (f >> 3), dhalf, flips >> 12) + spread16(2 * f) + (c & 31) * 128;
}
__device__ __forceinline__ void w_store(const CUtensorMap* m, uint32_t src, uint32_t a) {
#pragma unroll
  for (int j = 0; j < 8; j++)
    tma_st5<0>(m, src + j * 2048, ((a & 16383) >> 1) ^ ((__popc(j) & 1) << 11), (j & 3) << 1, (j >> 2) << 1, a >> 20, 0);
}
__device__ __forceinline__ uint32_t read_votes(const int* cnt, int lane, int v) {
#pragma unroll 1
  for (int it = 0; it < (1 << 20) && (__ballot_sync(0xffffffffu, v < NVOTE * 256) & ((2 << NPG) - 2)); it++)
    asm volatile("ld.relaxed.gpu.global.s32 %0, [%1];" : "=r"(v) : "l"(cnt + 32 + lane) : "memory");
  return __ballot_sync(0xffffffffu, (v & 255) > NVOTE / 2);
}
__device__ __forceinline__ int take_ticket(int* p) {
  int v;
  asm volatile("atom.relaxed.gpu.global.inc.u32 %0, [%1], 0x7fffffff;" : "=r"(v) : "l"(p) : "memory");
  return v;
}
__device__ __forceinline__ void send_role(uint32_t dst, uint32_t bar, int v) {
  for (int c = 0; c < 2; c++)
    asm volatile("{\n.reg .b32 a, b;\nmapa.shared::cluster.u32 a, %0, %2;\nmapa.shared::cluster.u32 b, %1, %2;\n"
                 "st.async.shared::cluster.mbarrier::complete_tx::bytes.u32 [a], %3, [b];\n}" ::"r"(dst), "r"(bar), "r"(c), "r"(v) : "memory");
}
struct GMaps {
  CUtensorMap in[5];
  CUtensorMap ws, xs, w, y;
  CUtensorMap y1[2], x2s, x2, w2, y2;
};

#define H_EPI 3
#define H_KS 11
#define C_PACE 300
#define C_ORD 1
#define H_HOLD 5
#define C_POL 1
constexpr int H_XP = 168 * 64, H_STAGE = 8192 + 2 * H_XP, H_NST = 7;
constexpr int C_OUT = 7 * 8192, C_GI = 13 * 8192, C_F = C_GI + 6144, C_PIECE = C_F + 8192;
static_assert(C_GI >= 3 * H_STAGE && C_PIECE + C_OUT == 6 * H_STAGE, "slots 0..2 | 3..5 | 6 fall free together");
constexpr int G_IM1 = C_GI - NB1 * 128;

template <int WG>
__device__ __forceinline__ void h_loop(float (&acc)[84], uint32_t sb, uint32_t full0, uint32_t empty0, int lane) {
#pragma unroll 1
  for (int k = 0; k < 16; k++) {
    const int st = k % H_NST;
    if (WG == 1 && k == H_KS) bar_sync(4, 256);
    mbar_wait(full0 + 8 * st, (k / H_NST) & 1);
    const uint32_t base = sb + st * H_STAGE;
    wg_fence();
#pragma unroll
    for (int s = 0; s < 2; s++) {
      const uint64_t dP = mk_desc(base, s * 2048, 0, 1024, 1), dQ = mk_desc(base, 4096 + s * 2048, 0, 1024, 1);
      const uint64_t dA = mk_desc(base, 8192 + s * 32, 0, 512, 2), dB = mk_desc(base, 8192 + H_XP + s * 32, 0, 512, 2);
      wgmma_ss_168<1, 1, 1, 0>(acc, dP, WG == 0 ? dA : dB, k | s);
      wgmma_ss_168<WG == 0 ? 1 : -1, 1, 1, 0>(acc, dQ, WG == 0 ? dB : dA, 1);
    }
    wg_commit();
    if (WG == 0 && k == 15) bar_arrive(4, 256);
    if (k <= 10) {
      wg_wait<1>();
      if (k > 0 && k - 1 + H_NST < 16 && lane < 2) mbar_arrive_cta(empty0 + 8 * ((k - 1) % H_NST), lane);
    }
  }
  wg_wait<0>();
  reg_fence(acc);
}

template <int N> __device__ __forceinline__ void gelu_pack(uint32_t* hp, float (&h)[N], bool zero_first, bool zero_all) {
  reg_fence(h);
#pragma unroll
  for (int c = 0; c < N / 2; c++) {
    const uint32_t v = pack2(gelu(h[2 * c]), gelu(h[2 * c + 1]));
    hp[c] = zero_all || (zero_first && c < 2) ? 0u : v;
  }
#pragma unroll
  for (int c = 0; c < N / 2; c++) asm volatile("" : "+r"(hp[c])::"memory");
}
__device__ __forceinline__ void poll_ge(const int* p, int target) {
  int v = 0;
#pragma unroll 1
  for (int it = 0; it < (1 << 20) && v < target; it++)
    asm volatile("ld.relaxed.gpu.global.s32 %0, [%1];" : "=r"(v) : "l"(p) : "memory");
  asm volatile("fence.acquire.gpu;\nfence.proxy.async.global;" ::: "memory");
}

__global__ void __cluster_dims__(2, 1, 1) __launch_bounds__(384, 1)
kG(int* __restrict__ cnt, char* __restrict__ x1, char* __restrict__ wt, const __nv_bfloat16* __restrict__ g,
   const __nv_bfloat16* __restrict__ wgt, float* __restrict__ ge, const uint32_t* __restrict__ img, const __nv_bfloat16* __restrict__ wf,
   const __nv_bfloat16* __restrict__ wo, const uint32_t* __restrict__ gat, const __grid_constant__ GMaps m) {
  extern __shared__ __align__(1024) uint8_t smem_raw[];
  __shared__ __align__(8) uint64_t bars[20 + A_NIN + 2 * A_NOUT + 2 * G_NST + 16 + 2 * A_NREL + 2 * H_NST + 41];
  __shared__ uint16_t tab[128];
  __shared__ uint32_t lat[8], s_role, s_flips;
  const uint32_t sb = pin(s2u(smem_raw));
  const int tid = threadIdx.x, wg = __shfl_sync(0xffffffffu, tid >> 7, 0), t = tid & 127;
  const int warp = __shfl_sync(0xffffffffu, t >> 5, 0), lane = t & 31;
  const int blk = blockIdx.x, hf = blk & 1, page = 1 + blk % NPG;
  const bool spare = blk >= 128, voter = blk >= 128 - NPG * NVOTE && !spare;
  const int nu = spare ? 16 : 18;
  const uint32_t xm = spare ? 0xFFFF : hf ? A_XM1 : A_XM0;
  const uint32_t wf0 = pin(s2u(&bars[0])), xf0 = wf0 + 32, xe0 = xf0 + 128, aof0 = xe0 + 8 * A_NIN, aoe0 = aof0 + 8 * A_NOUT;
  const uint32_t full0 = aoe0 + 8 * A_NOUT, empty0 = full0 + 8 * G_NST;
  const uint32_t sf0 = empty0 + 8 * G_NST, se0 = sf0 + 16, inf0 = se0 + 16, roleb = inf0 + 16, flipb = roleb + 8;
  const uint32_t rel0 = flipb + 8, got0 = rel0 + 8 * A_NREL, acq0 = got0 + 64;
  const uint32_t hf0 = acq0 + 8 * A_NREL, he0 = hf0 + 8 * H_NST, yo0 = he0 + 8 * H_NST, of0 = yo0 + 96, yf0 = of0 + 96;
  const uint32_t gdone = yf0 + 64, imgb = gdone + 8, rly0 = imgb + 8, depb = rly0 + 32, pubb = depb + 8;
  auto role = [&]() {
    mbar_wait(roleb, 0);
    return 2 * (int)*(volatile uint32_t*)&s_role + hf;
  };
  auto flips = [&]() {
    mbar_wait(flipb, 0);
    return *(volatile uint32_t*)&s_flips;
  };
  auto w_unit = [&](int cta) { return (cta & ~3) | (hf << 1) | ((cta >> 1) & 1); };
  auto w_code = [](int w2, int s, int i) { return (-(s < 4) << 16) | ((2 * w2 + (s >> 2)) << 11) | ((s & 3) << 9) | ((i >> 1) << 3) | ((i & 1) << 1); };
  auto in_load = [&](int c, uint32_t dst, uint32_t bar) {
    tma_ld5<1>(dst, &m.in[(c >> 11) & 7], bar, 0, c >> 16, c & 7, (c >> 3) & 63, (c >> 9) & 3);
  };
  auto y_store = [&](int w, int cta, uint32_t fl) {
    const int bin = cta >> 2, L = 4 * hf + 2 * w + (bin >> 4);
    const uint32_t sel = __ballot_sync(0xffffffffu, x1_addr(96 + 8 * lane + L, (cta >> 1) & 1, fl) & 4096);
#pragma unroll 1
    for (int q = 0; q < 2; q++) {
      const uint32_t stg = sb + (w == 0 ? 4 * G_STAGE + q * NB1 * 128 : q == 0 ? G_TOUT : G_IM1);
      const int c0 = ((L & 1) << 12) + (bin & 15) * 128 + q * 64;
#pragma unroll
      for (int c = 0; c < 3; c++) {
        mbar_wait(yo0 + 8 * (6 * w + 3 * q + c), 0);
        if (lane == 0) {
#pragma unroll
          for (int j = 4 * c; j < 4 * c + 4 && j < 11; j++)
            tma_st4<0>(j == 10 ? &m.y : &m.xs, stg + j * 2048, c0 + (((sel >> j) & 1) << 11), (L & 6) << 1, 2 * (j & 1), 12 + (j & ~1));
        }
        __syncwarp();
      }
    }
    bulk_commit();
    bulk_wait<0>();
    if (lane == 0) mbar_arrive(rly0 + 8 * w);
  };
  if (wg < 2) {
    if (lane == 0) {
      const uint32_t h = blk & 0x59, par = h ^ (h >> 3) ^ (h >> 4) ^ (h >> 6);
      char* p = x1 + (blk << 13) + (((warp ^ par) & 1) << 12) + 3584 + (warp >> 1) * 128;
      if (wg) {
        if (!voter) p += 256;
        else if (page < 12) p += page << 21;
        else p = wt + w_addr(page - 12, warp >> 1, blk >> 1, warp & 1, 0);
      }
      uint32_t c0, c1;
      asm volatile("{\n.reg .u32 v;\n.reg .pred q;\n"
                   "st.global.v4.u32 [%2], {0, 0, 0, 0};\nst.global.v4.u32 [%2 + 16], {0, 0, 0, 0};\n"
                   "mov.u32 %0, %%clock;\nmov.u32 %1, %0;\natom.relaxed.gpu.global.exch.b32 v, [%2], 1;\n"
                   "setp.eq.u32 q, v, 0;\n@q mov.u32 %1, %%clock;\n}\n" : "=r"(c0), "=r"(c1) : "l"(p) : "memory");
      lat[wg * 4 + warp] = c1 - c0;
    }
    __syncwarp();
    if (wg == 0 && hf == 0) bar_arrive(10, 160);
    bar_arrive(9, 288);
  }
  if (wg == 2) {
    if (t == 32) {
      mbar_init(wf0 + 24, 1);
      mbar_expect(wf0 + 24, 8192);
      fence_async();
      if (!spare) tma_ld5<1>(sb + 2 * G_STAGE + 3 * 8192, &m.in[1], wf0 + 24, 0, 0, 2 * hf, blk >> 1, 2);
    }
    __syncwarp();
    int votes = 0;
    if (warp == 3 && !voter) asm volatile("ld.relaxed.gpu.global.s32 %0, [%1];" : "=r"(votes) : "l"(cnt + 32 + lane) : "memory");
    asm volatile("setmaxnreg.dec.sync.aligned.u32 40;");
    if (lane == 0 && warp > 0) {
      if (warp == 1) {
        for (int i = 0; i < 3; i++) {
          mbar_init(wf0 + 8 * i, 1);
          mbar_expect(wf0 + 8 * i, 8192);
        }
      } else if (warp == 2) {
        prefetch_map(&m.in[4]);
        for (int i = 0; i < A_NIN + A_NOUT; i++) mbar_init(xe0 + 8 * i, 4);
        for (int i = 0; i < A_NOUT; i++) mbar_init(aoe0 + 8 * i, 1);
      } else {
        for (int i = 0; i < 2; i++) mbar_init(sf0 + 8 * i, 8);
        for (int i = 0; i < 6 + A_NREL; i++) mbar_init(se0 + 8 * i, 1);
        for (int i = 0; i < 3; i++) mbar_expect(inf0 + 8 * i, i < 2 ? 4096 : 4);
      }
      fence_bar_init();
    }
    __syncwarp();
    asm volatile("barrier.cluster.arrive.relaxed.aligned;" ::: "memory");
    int role_w = warp;
    if (role_w == 0) {
      int cta = blk, side = 0;
      if (hf == 0) {
        bar_sync(10, 160);
        side = min(lat[0], lat[2]) > min(lat[1], lat[3]);
        if (lane == 0) cta = take_ticket(cnt + (spare ? 62 : 54) + side);
      }
      const uint32_t wm = spare ? 0 : A_LDW | 0x6000;
      const int nw = __popc(wm & ((1 << lane) - 1)), r = lane - nw, np = r + A_NIN - (spare ? A_DEPS : A_DEP);
      const bool isw = (wm >> lane) & 1;
      uint32_t dst = sb + (!isw ? (r % A_NIN) * A_IN : nw < 3 ? 2 * G_STAGE + (2 - nw) * 8192 : G_TIN + (nw - 3) * 4096);
      uint32_t bf = !isw ? xf0 + 8 * r : nw < 3 ? wf0 + 8 * (2 - nw) : inf0 + 8 * (nw - 3);
      uint32_t be = isw ? roleb : xe0 + 8 * (np % A_NIN) + ((np / A_NIN - 1) & 1);
      asm volatile("barrier.cluster.wait.aligned;" : "+r"(dst), "+r"(bf), "+r"(be)::"memory");
      if (hf == 0) {
        cta = 2 * __shfl_sync(0xffffffffu, cta, 0) + side;
        if (cta >= 64) cta = 127 - cta;
        if (spare) cta = 64 + (cta >= 2 ? 3 - cta : cta);
        if (lane == 0) send_role(s2u(&s_role), roleb, cta);
        cta *= 2;
      } else {
        cta = role();
      }
      const int b = (cta >> 1) & 1;
      if (lane == 0 && !spare) tma_ld5<1>(sb, &m.in[4], xf0, 0, 96 * (((cta >> 2) << 1) + hf) - 24, 7, 0, b);
      __syncwarp();
      const int xc = x_decode(r, cta);
      const int code = isw ? w_code(nw >= 3, nw < 3 ? 4 - 2 * nw : 10 - nw, w_unit(cta)) : ((96 * (xc & 127) - 24) << 16) | (4 << 11) | (b << 9) | (xc >> 7);
#pragma unroll 1
      for (int p = !spare; p < (spare ? 16 : 15); p++) {
        const int c = __shfl_sync(0xffffffffu, code, p);
        const uint32_t d = __shfl_sync(0xffffffffu, dst, p), f = __shfl_sync(0xffffffffu, bf, p), e = __shfl_sync(0xffffffffu, be, p);
        mbar_wait(e & ~1u, e & 1);
        if (lane == 0) in_load(c, d, f);
        __syncwarp();
      }
      if (!spare) {
        const int bin = cta >> 2, f = 2 * bin + hf;
        if (lane == 0) {
          for (int s = 5; s >= A_W2PF; s--) {
            const int c = w_code(1, s, w_unit(cta));
            asm volatile("cp.async.bulk.prefetch.tensor.5d.L2.global [%0, {0, %1, %2, %3, %4}];" ::"l"(&m.in[(c >> 11) & 7]), "r"(c >> 16), "r"(c & 7), "r"((c >> 3) & 63), "r"((c >> 9) & 3) : "memory");
          }
          prefetch_map(&m.w);
          prefetch_map(&m.y);
          prefetch_map(&m.in[2]);
        }
        const uint32_t xa = x1_addr((21 - lane + 2 * (lane % 3)) * 8 + (f >> 4), b, flips()) + spread16(f);
        const uint32_t wa = w_addr(7 - (lane >> 1), 2 * bin, (lane & 1) * 32, hf, s_flips & ~0xC0000u);
#pragma unroll 1
        for (int k = 0; k < 16; k++) {
          const int st = g_slot(k);
          uint32_t a[3];
#pragma unroll
          for (int th = 0; th < 3; th++) a[th] = __shfl_sync(0xffffffffu, xa, 3 * (k >> 1) + th) ^ ((k & 1) * 0x21000);
          const uint32_t w = __shfl_sync(0xffffffffu, wa, k);
          if ((A_ACQ >> k) & 1) {
            mbar_wait(acq0 + 8 * __popc(A_ACQ & ((1 << k) - 1)), 0);
            asm volatile("fence.proxy.async.global;" ::: "memory");
          }
          mbar_wait(empty0 + 8 * st, (G_PAR >> k) & 1);
          if (lane == 0) {
            const uint32_t base = sb + st * G_STAGE, bar = full0 + 8 * st;
            mbar_expect(bar, G_STAGE);
#pragma unroll
            for (int th = 0; th < 3; th++)
              asm volatile("cp.async.bulk.shared::cluster.global.mbarrier::complete_tx::bytes.multicast::cluster.L2::cache_hint [%0], [%1], %2, [%3], %4, %5;"
                           ::"r"(base + 16384 + hf * G_XP + th * 3584), "l"(x1 + a[th]), "n"(3584), "r"(bar), "h"((uint16_t)3), "l"(policy<1>()) : "memory");
            if (k >= G_WPOLK) tma_ld3<1>(base, &m.w, bar, 0, (w >> 7) & 127, w >> 14);
            else tma_ld3<0>(base, &m.w, bar, 0, (w >> 7) & 127, w >> 14);
          }
          __syncwarp();
        }
        if (lane == 0) {
          if (blk == 0) asm volatile("cp.async.bulk.prefetch.L2.global [%0], 14336;" ::"l"(img) : "memory");
          prefetch_map(&m.y1[0]);
          prefetch_map(&m.y1[1]);
          prefetch_map(&m.x2s);
          prefetch_map(&m.x2);
          prefetch_map(&m.w2);
          prefetch_map(&m.y2);
        }
        mbar_wait(got0 + 24, 0);
        y_store(0, cta, s_flips);
        const int pl = lane >= 7, yb = min(6 * (bin - 4 * pl) + lane - 7 * pl, NB1 - 1);
        const uint32_t ya = x1_addr(96 + 8 * (yb >> 4) + 4 * hf + 2 * pl, b, s_flips) + spread16(yb);
        mbar_wait(gdone, 0);
        if (lane == 0)
          asm volatile("cp.async.bulk.shared::cluster.global.mbarrier::complete_tx::bytes [%0], [%1], 14336, [%2];"
                       ::"r"(sb + C_GI), "l"(img), "r"(imgb) : "memory");
#pragma unroll 1
        for (int p = bin >= 28; p < 2; p++) {
          uint32_t a[7];
#pragma unroll
          for (int i = 0; i < 7; i++) a[i] = __shfl_sync(0xffffffffu, ya, 7 * p + i);
          poll_ge(cnt + 64 + 2 * b + p, 64);
          if (lane == 0 && (p == 0 || bin >= 4)) {
#pragma unroll
            for (int i = 0; i < 7; i++) tma_ld3<C_POL>(sb + p * C_PIECE + i * 8192, &m.y1[(a[i] >> 12) & 1], yf0 + 32 * p + 8 * ((i + 1) >> 1), 0, a[i] >> 7, 0);
          }
          __syncwarp();
        }
        if (lane == 0) mbar_arrive(depb);
        mbar_wait(pubb, 0);
        int st = 0;
#pragma unroll 1
        for (int k = 0; k < 16; k++) {
          if ((k & 7) == 0) {
            poll_ge(cnt + 96 + (k >> 3), 112);
          }
          if (k == H_HOLD) mbar_wait(pubb + 8, 0);
          mbar_wait(he0 + 8 * st, (k >= H_NST) ^ (k >= 2 * H_NST));
          if (lane == 0) tma_ld3mc<0>(sb + st * H_STAGE + 8192 + hf * H_XP, &m.x2, hf0 + 8 * st, (k & 1) * 32, 0, ((k & 6) + (k >> 3)) * 64 + f);
          __syncwarp();
          if (++st == H_NST) st = 0;
        }
      }
    } else if (pin(warp) == 1) {
      if (lane == 0) {
        prefetch_map(&m.ws);
        prefetch_map(&m.xs);
        prefetch_map(&m.in[0]);
        prefetch_map(&m.in[3]);
        for (int i = 0; i < 24; i++) mbar_init(yo0 + 8 * i, 4);
        for (int i = 0; i < 8; i++) {
          mbar_init(yf0 + 8 * i, 1);
          mbar_expect(yf0 + 8 * i, i & 3 ? 16384 : 8192);
        }
        mbar_init(gdone, 8);
        for (int i = 0; i < 8; i++) mbar_init(imgb + 8 * i, 1);
        mbar_expect(imgb, 14336);
        fence_async();
      }
      __syncwarp();
      asm volatile("barrier.cluster.wait.aligned;" ::: "memory");
      if (lane == 0) {
#pragma unroll 1
        for (int r = spare; r < A_NREL; r++) {
          mbar_wait(rel0 + 8 * r, 0);
          asm volatile("fence.acq_rel.gpu;\nred.relaxed.gpu.global.inc.u32 [%0], 0x7fffffff;" ::"l"(cnt + 8 + r) : "memory");
        }
        if (!spare) {
          const int cta = role(), bin = cta >> 2;
#pragma unroll 1
          for (int r = 0; r < 4; r++) {
            if (r < 2 || (r == 2 ? bin < 28 : bin >= 4)) {
              mbar_wait(rly0 + 8 * r, 0);
              asm volatile("fence.acq_rel.gpu;\nred.relaxed.gpu.global.inc.u32 [%0], 0x7fffffff;" ::"l"(cnt + (r < 2 ? 64 + (cta & 2) : 94) + r) : "memory");
            }
            if (r >= 2) mbar_arrive(pubb + 8 * (r - 2));
          }
        }
      }
    } else if (warp == 2) {
      asm volatile("barrier.cluster.wait.aligned;" ::: "memory");
      const uint32_t relm = spare ? A_RELS : A_REL;
      const int xr = __popc(xm & ((1 << lane) - 1));
      const uint32_t srcs = sb + a_out(lane), bars = aof0 + 8 * (lane % A_NOUT);
      const uint32_t done = lane < 16 ? bars + 8 * A_NOUT : se0 + 8 * (lane & 1), relb = rel0 + 8 * (spare + __popc(relm & ((1 << lane) - 1)));
      const int cta = role(), xc = x_decode(xr, cta), q = xc & 127, th = q / 28, wi = lane < 2 ? blk : w_unit(cta);
      int code = (xm >> lane) & 1 ? 0x80000000u + x1_addr(((xc >> 7) * 3 + th) * 8, (cta >> 1) & 1, 0) + (q - 28 * th) * 128
                                  : w_addr(7 - lane + xr, 0, wi >> 1, wi & 1, 0);
      uint32_t fl = 0;
      auto tables = [&]() {
        fl = flips();
        code ^= ((fl >> (((code >> 21) & 15) + (code < 0 ? 0 : 12))) & 1) << 12;
      };
      if (spare) tables();
      uint32_t tnext = clock(), src = __shfl_sync(0xffffffffu, srcs, 0), bar = aof0;
      int c = __shfl_sync(0xffffffffu, code, 0);
      mbar_wait(bar, 0);
#pragma unroll 1
      for (int n = 0; n < nu; n++) {
        while ((int)(clock() - tnext) < 0);
        tnext = clock() + (spare ? 0 : n < A_PACE_N ? A_PACE0 : A_PACE1);
        if (lane == n) {
          if (c >= 0) {
            w_store(&m.ws, src, c);
          } else {
#pragma unroll
            for (int j = 0; j < 8; j++)
              tma_st4<0>(&m.xs, src + j * 2048, ((c & 16383) >> 1) ^ ((__popc(j) & 1) << 11) ^ ((j & 1) << 12), (j >> 1) << 2, (c >> 18) & 3, (c >> 20) & 31);
          }
          bulk_commit();
        }
        __syncwarp();
        if (n == 1 && !spare) tables();
        c = __shfl_sync(0xffffffffu, code, n + 1);
        src = __shfl_sync(0xffffffffu, srcs, n + 1);
        bar = __shfl_sync(0xffffffffu, bars, n + 1);
        if (n + 1 < nu) mbar_wait(bar, (n + 1 >= A_NOUT) ^ (n + 1 >= 2 * A_NOUT));
        bulk_wait<0>();
        if (lane == n) {
          mbar_arrive(done);
          if ((relm >> lane) & 1) mbar_arrive(relb);
        }
        __syncwarp();
        if (!spare && (n == 13 || n == 15) && lane < 16) mbar_arrive_cta(empty0 + 8 * ((n - 7) >> 1), lane & 1);
      }
      if (!spare) {
        const int i = w_unit(cta), wc = w_code(1, 5 - lane, i);
        const uint32_t wa = w_addr(7 + W_SHIFT - lane, 0, i >> 1, i & 1, fl);
#pragma unroll 1
        for (int it = 0; it < 8; it++) {
          const uint32_t a = __shfl_sync(0xffffffffu, wa, it), j = it & 1;
          const int c2 = __shfl_sync(0xffffffffu, wc, it);
          mbar_wait(sf0 + 8 * j, (it >> 1) & 1);
          if (lane == 0 && it < 6) {
            mbar_expect(inf0 + 8 * j, 4096);
            in_load(c2, sb + G_TIN + j * 4096, inf0 + 8 * j);
          }
          if (it >= W_SHIFT) mbar_wait(got0 + 8 * (it - W_SHIFT), 0);
          if (lane == 0) {
            w_store(&m.ws, sb + G_TOUT + j * A_OUT, a);
            bulk_commit();
            bulk_wait<0>();
            mbar_arrive(se0 + 8 * j);
          }
          __syncwarp();
        }
        const int bin = cta >> 2;
        mbar_wait(got0 + 56, 0);
        mbar_wait(rly0 + 8, 0);
#pragma unroll 1
        for (int pc = 0; pc < 2; pc++) {
          if (pc ? bin >= 4 : bin < 28) {
#pragma unroll 1
            for (int n = 0; n < 6; n++) {
              mbar_wait(of0 + 8 * (6 * pc + n), 0);
              if (C_PACE) {
                while ((int)(clock() - tnext) < 0);
                tnext = clock() + C_PACE;
              }
              if (lane == 0) tma_st3<0>(&m.x2s, sb + pc * C_PIECE + C_OUT + n * 8192, 0, (4 * (n & 1) + 2 * hf + pc) * 64, (cta & 2) * (NB2 / 2) + 3 * (bin - 4 * pc) + (n >> 1));
              __syncwarp();
            }
            bulk_commit();
            bulk_wait<0>();
            if (lane == 0) mbar_arrive(rly0 + 16 + 8 * pc);
            __syncwarp();
          }
          if (lane < 16)
            for (int i = 6 * pc; i < 3 + 4 * pc; i++) mbar_arrive_cta(he0 + 8 * i, lane & 1);
        }
      }
    } else {
      bar_sync(9, 288);
      const int near = min(lat[0], lat[2]) > min(lat[1], lat[3]);
      if (lane == 0 && voter)
        asm volatile("red.relaxed.gpu.global.add.s32 [%0], %1;" ::"l"(cnt + 32 + page), "r"(256 + (near ^ (min(lat[4], lat[6]) > min(lat[5], lat[7])))) : "memory");
      __syncwarp();
      asm volatile("barrier.cluster.wait.aligned;" ::: "memory");
      const uint32_t fl = read_votes(cnt, lane, votes);
      if (lane == 0) {
        s_flips = fl;
        mbar_arrive(flipb);
      }
      __syncwarp();
      if (!spare) {
        bool open = lane < 8 + A_NREL;
        int k = 0;
        mbar_wait(rel0, 0);
#pragma unroll 1
        for (int p = 0; p < (1 << 16) && __any_sync(0xffffffffu, open); p++) {
          int v;
          asm volatile("ld.relaxed.gpu.global.s32 %0, [%1];" : "=r"(v) : "l"(cnt + (lane & 15)) : "memory");
          while (k < 16 && mbar_test(full0 + 8 * g_slot(k), (G_PAR >> k) & 1)) {
            if (lane == 0) mbar_arrive(empty0 + 8 * g_slot(k));
            if ((k & 1) && lane == 0) asm volatile("red.relaxed.gpu.global.inc.u32 [%0], 0x7fffffff;" ::"l"(cnt + (k >> 1)) : "memory");
            k++;
          }
          if (open && v >= (lane <= 8 ? 128 : 132)) {
            asm volatile("fence.acquire.gpu;" ::: "memory");
            mbar_arrive(got0 + 8 * lane);
            open = false;
          }
        }
        const int cta = role(), b = (cta >> 1) & 1, bin = cta >> 2;
        y_store(1, cta, fl);
        const uint32_t wa = w_addr((lane & 6) + ((lane >> 3) & 1) + W_SHIFT, 2 * bin, (lane & 1) * 32, b, fl) + (hf << 14);
        mbar_wait(depb, 0);
        mbar_wait(pubb, 0);
        asm volatile("fence.proxy.async.global;" ::: "memory");
        int st = 0;
#pragma unroll 1
        for (int k2 = 0; k2 < 16; k2++) {
          const uint32_t w = __shfl_sync(0xffffffffu, wa, k2);
          if (k2 == H_HOLD) mbar_wait(pubb + 8, 0);
          mbar_wait(he0 + 8 * st, (k2 >= H_NST) ^ (k2 >= 2 * H_NST));
          if (lane == 0) {
            mbar_expect(hf0 + 8 * st, H_STAGE);
            tma_ld3<1>(sb + st * H_STAGE, &m.w2, hf0 + 8 * st, 0, (w >> 7) & 255, w >> 15);
            if (k2 == H_NST) {
              if (cta == 0) asm volatile("cp.async.bulk.prefetch.L2.global [%0], 6144;" ::"l"(gat) : "memory");
              if (cta == 1) asm volatile("cp.async.bulk.prefetch.L2.global [%0], 16384;" ::"l"(ge) : "memory");
              asm volatile("cp.async.bulk.prefetch.L2.global [%0], 1024;" ::"l"(wf + cta * 512) : "memory");
              asm volatile("cp.async.bulk.prefetch.L2.global [%0], 1024;" ::"l"(wo + cta * 512) : "memory");
            }
          }
          __syncwarp();
          if (++st == H_NST) st = 0;
        }
      }
    }
  } else {
    if (lane == 0) {
      const int w8 = 4 * wg + warp;
      for (int i = 0; i < 2; i++) {
        mbar_init(xf0 + 16 * w8 + 8 * i, 1);
        mbar_expect(xf0 + 16 * w8 + 8 * i, A_IN);
      }
      mbar_init(got0 + 8 * w8, 1);
      if (w8 >= 8 - A_NREL) mbar_init(acq0 + 8 * (7 - w8), 1);
      if (w8 < G_NST) {
        mbar_init(full0 + 8 * w8, 1);
        mbar_init(empty0 + 8 * w8, 17);
        mbar_arrive(empty0 + 8 * w8);
      }
      if (w8 > 0) {
        mbar_init(hf0 + 8 * (w8 - 1), 1);
        mbar_init(he0 + 8 * (w8 - 1), 16);
      }
      fence_bar_init();
    }
    __syncwarp();
    asm volatile("barrier.cluster.arrive.relaxed.aligned;" ::: "memory");
    if (wg == 1) tab[t] = __bfloat16_as_ushort(__float2bfloat16_rn(-__cosf((float)(t - 64) * 0.04908738521234052f)));
    bar_sync(1, 256);
    asm volatile("setmaxnreg.inc.sync.aligned.u32 232;");
    uint32_t fa[16];
    auto frag = [&](int i, int l) {
      const int f = warp * 16 + (l >> 2) + 8 * (i & 1), r = 8 * (i >> 1) + (l & 3) * 2;
      const int k0 = (f | 1) * r - ((f & 1) << 5);
      return tab[k0 & 127] | ((uint32_t)tab[(k0 + (f | 1)) & 127] << 16);
    };
#pragma unroll
    for (int i = 0; i < 16; i++) fa[i] = i < 4 ? frag(i, lane) : 0;
    reg_fence(fa);
    asm volatile("barrier.cluster.wait.aligned;" ::: "memory");
    int cta = blk, qs = 0;
#pragma unroll 1
    for (int n = wg; n < nu; n += 2) {
      float e[64];
      if ((n >> 1) == !spare) {
        pdl_launch();
        int l = lane;
        asm volatile("" : "+r"(l));
#pragma unroll
        for (int i = 4; i < 16; i++) fa[i] = frag(i, l);
        reg_fence(fa);
        cta = role();
        qs = ((cta >> 1) & 2) + hf;
      }
      if (spare) qs = n < 8 ? n & 3 : 2 * hf + wg;
      const bool isx = (xm >> n) & 1;
      const int r = __popc(xm & ((1 << n) - 1)), s = 7 - n + r;
      const uint32_t in = isx ? sb + (r % A_NIN) * A_IN : sb + 2 * G_STAGE + s * 4096;
      mbar_wait(isx ? xf0 + 8 * r : wf0 + 8 * (s >> 1), 0);
      if (!isx) {
        wg_fence();
        wgmma_rs_128<1, 1, 1>(e, fa[0], fa[1], fa[2], fa[3], mk_desc(in, 0, 2048, 1024, 1), 0);
        wg_commit();
      } else {
        wg_fence();
#pragma unroll
        for (int k = 0; k < 4; k++)
          wgmma_rs_128<1, 1, 1>(e, fa[4 * k], fa[4 * k + 1], fa[4 * k + 2], fa[4 * k + 3], mk_desc(in, k * 2048, 6144, 1024, 1), k);
        wg_commit();
      }
      wg_wait<0>();
      reg_fence(e);
      if (isx && lane == 0) mbar_arrive(xe0 + 8 * (r % A_NIN));
      if (((A_FREE >> n) & 1) && !spare && lane < 2) mbar_arrive_cta(empty0 + 8 * (__popc(A_FREE & ((1 << n) - 1)) >> 1), lane);
      if (n >= A_NOUT) mbar_wait(aoe0 + 8 * (n % A_NOUT), (n / A_NOUT - 1) & 1);
      const int row = warp * 16 + (lane & 7) + ((lane >> 3) & 1) * 8, hi = lane >> 4;
      const uint32_t rb = sb + a_out(n) + (isx ? row : row + (row & ~7)) * 128, ts = isx ? 8192 : 1024, xr = (lane & 7) ^ (isx ? qs : 0);
#pragma unroll
      for (int j = 0; j < 16; j += 2) {
        const uint32_t tile = isx ? (j >> 2) & 1 : j >> 3, pos = (isx ? (j >> 3) * 4 + (j & 3) : (j & 7)) + hi;
        stsm4(rb + tile * ts + ((pos ^ xr) << 4), pack2(e[4 * j], e[4 * j + 1]), pack2(e[4 * j + 2], e[4 * j + 3]),
              pack2(e[4 * j + 4], e[4 * j + 5]), pack2(e[4 * j + 6], e[4 * j + 7]));
      }
      fence_async();
      __syncwarp();
      if (lane == 0) mbar_arrive(aof0 + 8 * (n % A_NOUT));
    }
    if (spare) {
      float* sg = reinterpret_cast<float*>(smem_raw + (sb - s2u(smem_raw)));
      __nv_bfloat16* sw = reinterpret_cast<__nv_bfloat16*>(sg + 16 * 256);
      const int c0 = (cta - 128) * 64;
      uint4 vw[8], vg[2];
#pragma unroll
      for (int i = 0; i < 8; i++) vw[i] = __ldg(reinterpret_cast<const uint4*>(wgt + ((i * 256 + tid) >> 3) * 256 + c0 + (tid & 7) * 8));
#pragma unroll
      for (int i = 0; i < 2; i++) vg[i] = __ldg(reinterpret_cast<const uint4*>(g) + i * 256 + tid);
      bar_sync(3, 256);
#pragma unroll
      for (int i = 0; i < 8; i++) reinterpret_cast<uint4*>(sw)[i * 256 + tid] = vw[i];
#pragma unroll
      for (int i = 0; i < 2; i++) {
        const uint32_t w4[4] = {vg[i].x, vg[i].y, vg[i].z, vg[i].w};
#pragma unroll
        for (int e = 0; e < 4; e++) {
          sg[(i * 256 + tid) * 8 + 2 * e] = __uint_as_float(w4[e] << 16);
          sg[(i * 256 + tid) * 8 + 2 * e + 1] = __uint_as_float(w4[e] & 0xffff0000u);
        }
      }
      bar_sync(3, 256);
      const int col = tid & 63, r0 = (tid >> 6) * 4;
      float a0 = 0.f, a1 = 0.f, a2 = 0.f, a3 = 0.f;
#pragma unroll 8
      for (int k = 0; k < 256; k++) {
        const float w = __bfloat162float(sw[k * 64 + col]);
        a0 = fmaf(sg[(r0 + 0) * 256 + k], w, a0);
        a1 = fmaf(sg[(r0 + 1) * 256 + k], w, a1);
        a2 = fmaf(sg[(r0 + 2) * 256 + k], w, a2);
        a3 = fmaf(sg[(r0 + 3) * 256 + k], w, a3);
      }
      const int cc = c0 + col;
      const int pos = (cc & ~15) + ((cc >> 1) & 3) * 4 + ((cc >> 3) & 1) * 2 + (cc & 1);
      ge[(r0 + 0) * 256 + pos] = __bfloat162float(__float2bfloat16_rn(a0));
      ge[(r0 + 1) * 256 + pos] = __bfloat162float(__float2bfloat16_rn(a1));
      ge[(r0 + 2) * 256 + pos] = __bfloat162float(__float2bfloat16_rn(a2));
      ge[(r0 + 3) * 256 + pos] = __bfloat162float(__float2bfloat16_rn(a3));
      return;
    }
    const int bin = cta >> 2;
    const uint32_t la = (lane >> 4) * 1024 + (lane & 7) * 128 + (((2 * warp + ((lane >> 3) & 1)) ^ (lane & 7)) << 4);
    {
    float d[32];
    auto t_begin = [&](int it, int hh) {
      mbar_wait(inf0 + 8 * (it & 1), (it >> 1) & 1);
      wg_fence();
      wgmma_rs_64<1, 1, 1>(d, fa[0], fa[1], fa[2], fa[3], mk_desc(sb + G_TIN + (it & 1) * 4096 + hh * 2048, 0, 0, 1024, 1), 0);
      wg_commit();
    };
    auto t_end = [&](int it, int hh) {
      reg_fence(d);
      const int j = it & 1;
      mbar_wait(se0 + 8 * j, (it >> 1) & 1);
      store_tile_64<2048>(d, sb + G_TOUT + j * A_OUT + hh * 1024, warp, lane);
      fence_async();
      __syncwarp();
      if (lane == 0) mbar_arrive(sf0 + 8 * j);
    };
    float re[NB1 / 2], im[NB1 / 2];
#pragma unroll 1
    for (int k = 0; k < G_KS; k++) {
      const int st = g_slot(k);
      const int it = __popc(G_TMASK & ((1 << k) - 1));
      const bool T = (G_TMASK >> k) & 1;
      mbar_wait(full0 + 8 * st, (G_PAR >> k) & 1);
      const uint32_t base = sb + st * G_STAGE;
      const uint32_t wb = base + wg * 4096;
      if (T) t_begin(it, wg);
      wg_fence();
#pragma unroll
      for (int s = 0; s < 2; s++) {
        const int acc = (k | s) != 0;
        const uint64_t dP = mk_desc(wb, s * 2048, 0, 1024, 1), dQ = mk_desc(wb, 8192 + s * 2048, 0, 1024, 1);
        const uint64_t dA = mk_desc(base, 16384 + s * 32, 0, 512, 2), dB = mk_desc(base, 16384 + G_XP + s * 32, 0, 512, 2);
        wgmma_ss_168<1, 1, 1, 0>(re, dP, dA, acc);
        wgmma_ss_168<1, 1, 1, 0>(im, dP, dB, acc);
        wgmma_ss_168<1, 1, 1, 0>(re, dQ, dB, 1);
        wgmma_ss_168<-1, 1, 1, 0>(im, dQ, dA, 1);
      }
      wg_commit();
      wg_wait<1>();
      if (k > 0 && lane < 2) mbar_arrive_cta(empty0 + 8 * g_slot(k - 1), lane);
      if (T) t_end(it, wg);
    }
    auto tail = [&](auto part, bool wait) {
      constexpr int PART = decltype(part)::value;
#pragma unroll
      for (int k = G_KS; k < 16; k++) {
        if (wait) mbar_wait(full0 + 8 * g_slot(k), (G_PAR >> k) & 1);
        const uint32_t base = sb + g_slot(k) * G_STAGE, wb = base + wg * 4096;
        wg_fence();
#pragma unroll
        for (int s = 0; s < 2; s++) {
          const uint64_t dP = mk_desc(wb, s * 2048, 0, 1024, 1), dQ = mk_desc(wb, 8192 + s * 2048, 0, 1024, 1);
          const uint64_t dA = mk_desc(base, 16384 + s * 32, 0, 512, 2), dB = mk_desc(base, 16384 + G_XP + s * 32, 0, 512, 2);
          if (PART == 0) {
            wgmma_ss_168<1, 1, 1, 0>(re, dP, dA, 1);
            wgmma_ss_168<1, 1, 1, 0>(re, dQ, dB, 1);
          } else {
            wgmma_ss_168<1, 1, 1, 0>(im, dP, dB, 1);
            wgmma_ss_168<-1, 1, 1, 0>(im, dQ, dA, 1);
          }
        }
      }
      wg_commit();
    };
    auto put = [&](float (&v)[NB1 / 2], uint32_t stg, uint32_t bar) {
      reg_fence(v);
#pragma unroll
      for (int c = 0; c < 3; c++) {
#pragma unroll
        for (int j = 8 * c; j < 8 * c + 8 && j < 20; j += 2)
          stsm4t(stg + la + j * 1024, pack2(v[4 * j], v[4 * j + 1]), pack2(v[4 * j + 2], v[4 * j + 3]),
                 pack2(v[4 * j + 4], v[4 * j + 5]), pack2(v[4 * j + 6], v[4 * j + 7]));
        if (c == 2)
          asm volatile("stmatrix.sync.aligned.m8n8.x2.trans.shared.b16 [%0], {%1, %2};" ::"r"(stg + la + 20 * 1024),
                       "r"(pack2(v[80], v[81])), "r"(pack2(v[82], v[83])) : "memory");
        fence_async();
        __syncwarp();
        if (lane == 0) mbar_arrive(bar + 8 * c);
      }
    };
    if (wg == 1) {
#pragma unroll 1
      for (int h2 = 2 * __popc(G_TMASK); h2 < 16; h2++) {
        t_begin(h2 >> 1, h2 & 1);
        wg_wait<0>();
        t_end(h2 >> 1, h2 & 1);
      }
      wg_wait<0>();
      bar_arrive(5, 256);
      bar_sync(4, 256);
    }
    tail(std::integral_constant<int, 0>(), true);
    tail(std::integral_constant<int, 1>(), false);
    if (wg == 0) bar_arrive(4, 256);
    wg_wait<1>();
    if (wg == 0) {
      bar_sync(5, 256);
    } else {
      mbar_wait(se0, 0);
      mbar_wait(se0 + 8, 0);
    }
    put(re, sb + (wg ? G_TOUT : 4 * G_STAGE), yo0 + 48 * wg);
    wg_wait<0>();
    if (lane == 0) mbar_arrive(gdone);
    if (wg == 1) mbar_wait(gdone, 0);
    put(im, sb + (wg ? G_IM1 : 4 * G_STAGE + NB1 * 128), yo0 + 48 * wg + 24);
    }
    mbar_wait(imgb, 0);
    const int p0 = bin >= 28, p1 = bin < 4 ? 1 : 2;
#pragma unroll 1
    for (int pc = p0; pc < p1; pc++) {
      const uint32_t in = sb + pc * C_PIECE, yb = yf0 + 32 * pc;
      const bool first = bin == 4 * pc, last = bin == 27 + 4 * pc;
      float h0[12], h1[12], h2[12], h3[12], h4[12], h5[12], h6[8], e[32];
      uint32_t hp[40];
      auto idft = [&](auto& h, int i) {
#pragma unroll
        for (int k = 0; k < 4; k++) {
          const uint64_t da = mk_desc(in, i * 8192 + k * 2048, 0, 1024, 1), db = mk_desc(sb + C_GI + wg * 1024, k * 32, 0, 2048, 1);
          if constexpr (sizeof(h) == 48) wgmma_ss_24<1, 1, 1, 0>(h, da, db, k);
          else wgmma_ss_16<1, 1, 1, 0>(h, da, db, k);
        }
      };
      auto idft2 = [&](auto& ha, auto& hb, int i) {
        mbar_wait(yb + 4 * (i + 1), 0);
        wg_fence();
        idft(ha, i);
        idft(hb, i + 1);
        wg_commit();
      };
      auto dft = [&](int j) {
        wg_fence();
#pragma unroll
        for (int k = 0; k < 4; k++)
          wgmma_rs_64<1, 1, 0>(e, hp[12 * j + 4 * k], hp[12 * j + 4 * k + 1], hp[12 * j + 4 * k + 2], hp[12 * j + 4 * k + 3], mk_desc(sb + C_F, k * 32, 0, 1024, 1), k);
        wg_commit();
      };
      auto out = [&](int j) {
        reg_fence(e);
        if (j == 1) mbar_wait(rly0 + 8, 0);
        const uint32_t a0 = in + la + C_OUT + (2 * j + wg) * 8192;
#pragma unroll
        for (int q = 0; q < 8; q += 2)
          stsm4t(a0 + q * 1024, pack2(e[4 * q], e[4 * q + 1]), pack2(e[4 * q + 2], e[4 * q + 3]),
                 pack2(e[4 * q + 4], e[4 * q + 5]), pack2(e[4 * q + 6], e[4 * q + 7]));
        fence_async();
        __syncwarp();
        if (lane == 0) mbar_arrive(of0 + 8 * (6 * pc + 2 * j + wg));
      };
      mbar_wait(yb, 0);
      wg_fence();
      idft(h0, 0);
      wg_commit();
      idft2(h1, h2, 1);
      wg_wait<1>();
      gelu_pack(hp, h0, first, false);
      wg_wait<0>();
      gelu_pack(hp + 6, h1, false, false);
      gelu_pack(hp + 12, h2, false, false);
      dft(0);
      idft2(h3, h4, 3);
      wg_wait<1>();
      out(0);
      wg_wait<0>();
      gelu_pack(hp + 18, h3, false, false);
      gelu_pack(hp + 24, h4, false, false);
      dft(1);
      idft2(h5, h6, 5);
      wg_wait<1>();
      out(1);
      wg_wait<0>();
      gelu_pack(hp + 30, h5, false, last);
      gelu_pack(hp + 36, h6, false, last);
      dft(2);
      wg_wait<0>();
      if (pc == p1 - 1 && lane < 6) mbar_arrive_cta(he0 + 8 * (3 + (lane >> 1)), lane & 1);
      out(2);
    }
    float acc[84];
    if (wg == 0) {
      h_loop<0>(acc, sb, hf0, he0, lane);
    } else {
      h_loop<1>(acc, sb, hf0, he0, lane);
      bar_sync(3, 128);
    }
    const uint32_t stg = sb + (wg == 0 ? H_NST : 9 % H_NST) * H_STAGE;
    const uint32_t a0 = stg + la;
    constexpr int J = 21 / H_EPI;
#pragma unroll
    for (int c = 0; c < H_EPI; c++) {
#pragma unroll
      for (int j = c * J; j + 1 < (c + 1) * J; j += 2)
        stsm4t(a0 + j * 1024, pack2(acc[4 * j], acc[4 * j + 1]), pack2(acc[4 * j + 2], acc[4 * j + 3]),
               pack2(acc[4 * j + 4], acc[4 * j + 5]), pack2(acc[4 * j + 6], acc[4 * j + 7]));
      const int j = (c + 1) * J - 1;
      asm volatile("stmatrix.sync.aligned.m8n8.x2.trans.shared.b16 [%0], {%1, %2};" ::"r"(a0 + j * 1024),
                   "r"(pack2(acc[4 * j], acc[4 * j + 1])), "r"(pack2(acc[4 * j + 2], acc[4 * j + 3])) : "memory");
      fence_async();
      bar_sync(2 + wg, 128);
      if (t == 0) {
        tma_st4<0>(&m.y2, stg + c * J * 1024, 0, c * J * 8, 2 * bin + wg, cta & 3);
        bulk_commit();
      }
    }
    if (t == 0) {
      bulk_wait_read<0>();
    }
  }
}

#define E_LD 0
#define E_WPRE 2
#define E_EARLY0 2
#define E_CHUNK 1
#define E_EARLY 2
constexpr int E_SMEM = 65536 + 131072 + 32768 + 1024;

__device__ __forceinline__ uint32_t joint2(uint32_t fe, uint32_t g0, uint32_t g1) {
  uint32_t s0, s1;
  asm("{\n.reg .b16 l, h;\n.reg .b32 ll;\nmov.b32 {l, h}, %2;\nmov.b32 ll, {l, l};\n"
      "fma.rn.bf16x2 %0, ll, %5, %3;\nfma.rn.bf16x2 %1, %2, %5, %4;\n}"
      : "=r"(s0), "=r"(s1) : "r"(fe), "r"(g0), "r"(g1), "r"(0x3F800000u));
  return pack2(tanh_f32(__uint_as_float(s0)), tanh_f32(__uint_as_float(s1)));
}
__device__ __forceinline__ uint4 lds128(uint32_t a) {
  uint4 v;
  asm volatile("ld.shared.v4.u32 {%0, %1, %2, %3}, [%4];" : "=r"(v.x), "=r"(v.y), "=r"(v.z), "=r"(v.w) : "r"(a));
  return v;
}
__device__ __forceinline__ void joint_group(uint32_t (&ja)[8], const uint32_t* fe, uint4& g0, uint4& g1, uint32_t gnext) {
  const uint4 c0 = g0, c1 = g1;
  g0 = lds128(gnext);
  g1 = lds128(gnext + 64);
  ja[0] = joint2(fe[0], c0.x, c0.y);
  ja[1] = joint2(fe[1], c0.x, c0.y);
  ja[2] = joint2(fe[2], c0.z, c0.w);
  ja[3] = joint2(fe[3], c0.z, c0.w);
  ja[4] = joint2(fe[4], c1.x, c1.y);
  ja[5] = joint2(fe[5], c1.x, c1.y);
  ja[6] = joint2(fe[6], c1.z, c1.w);
  ja[7] = joint2(fe[7], c1.z, c1.w);
  reg_fence(ja);
}

__global__ void __launch_bounds__(256, 1)
kE(int* __restrict__ cnt, const uint32_t* __restrict__ gat, const float* ge, const __grid_constant__ CUtensorMap my, const __grid_constant__ CUtensorMap mwf, const __grid_constant__ CUtensorMap mwo,
   const __grid_constant__ CUtensorMap mout) {
  extern __shared__ __align__(1024) uint8_t smem_raw[];
  __shared__ __align__(8) uint64_t bars[13];
  const uint32_t sb = (s2u(smem_raw) + 1023) & ~1023u;
  const int tid = threadIdx.x, wg = __shfl_sync(0xffffffffu, tid >> 7, 0), t = tid & 127, warp = t >> 5, lane = t & 31;
  const uint32_t R0 = sb, R1 = sb + 65536, R2 = sb + 65536 + 131072;
  const uint32_t barY = s2u(&bars[0]), barF = barY + 32, barO = barY + 64, barA = barY + 96;
  const int b = blockIdx.x / 63, t0 = (blockIdx.x % 63) * 64;
  const int a = t0 / 48, o = t0 % 48;
  const int qw = o + 16 * warp, sel = qw >= 48;
  uint32_t ga[16];
#pragma unroll
  for (int s = 0; s < 4; s++)
    ldg128(reinterpret_cast<const uint4*>(gat) + ((qw >> 4) - 3 * sel) * 128 + s * 32 + lane, ga[4 * s], ga[4 * s + 1], ga[4 * s + 2], ga[4 * s + 3]);
  if (tid == 0) {
    prefetch_map(&my);
    for (int i = 0; i < 12; i++) mbar_init(barY + 8 * i, 1);
    mbar_init(barA, 8);
    fence_bar_init();
    fence_async();
    for (int i = 0; i < E_WPRE; i++) {
      const int kc = (i >> 1) | ((i & 1) << 1);
      mbar_expect(barF + 8 * kc, 32768);
      tma_ld3<0>(R1 + kc * 32768, &mwf, barF + 8 * kc, 0, kc * 64, 0);
    }
  }
  uint32_t gs[32];
#pragma unroll
  for (int i = 0; i < 16; i++) {
    gs[i] = sel ? 0u : ga[i];
    gs[16 + i] = sel ? ga[i] : 0u;
  }
  __syncthreads();
  pdl_wait();
  uint4 gev0, gev1;
  asm volatile("ld.global.cg.v4.u32 {%0, %1, %2, %3}, [%4];" : "=r"(gev0.x), "=r"(gev0.y), "=r"(gev0.z), "=r"(gev0.w)
               : "l"(reinterpret_cast<const uint4*>(ge) + (b * 8 + wg * 4) * 64 + t));
  asm volatile("ld.global.cg.v4.u32 {%0, %1, %2, %3}, [%4];" : "=r"(gev1.x), "=r"(gev1.y), "=r"(gev1.z), "=r"(gev1.w)
               : "l"(reinterpret_cast<const uint4*>(ge) + (b * 8 + wg * 4) * 64 + 128 + t));
  if (tid == E_LD) {
    for (int i = 0; i < 4; i++) {
      mbar_expect(barY + 8 * i, 16384);
      tma_ld5<0>(R0 + i * 16384, &my, barY + 8 * i, 0, 0, 2 * (i & 1) + (i >> 1), a, b);
    }
    for (int i = E_WPRE; i < 4; i++) {
      const int kc = (i >> 1) | ((i & 1) << 1);
      mbar_expect(barF + 8 * kc, 32768);
      tma_ld3<0>(R1 + kc * 32768, &mwf, barF + 8 * kc, 0, kc * 64, 0);
    }
    prefetch_map(&mwo);
    prefetch_map(&mout);
  }
  if (blockIdx.x == 125 && tid < 128) cnt[tid] = 0;
  reg_fence(gs);
  uint32_t gp = R2 + wg * 4096 + (lane & 3) * 16;
  uint4 g0, g1;
  uint32_t fe[64];
  {
    float d0[32], d1[32], e[64];
    mbar_wait(barY + 8 * wg, 0);
    wg_fence();
#pragma unroll
    for (int k = 0; k < 8; k++)
      wgmma_rs_64<1, 1, 1>(d0, gs[4 * k], gs[4 * k + 1], gs[4 * k + 2], gs[4 * k + 3], mk_desc(R0 + wg * 16384, k * 2048, 0, 1024, 1), k);
    wg_commit();
    wg_wait<0>();
    reg_fence(d0);
#pragma unroll
    for (int i = 0; i < 32; i++) d0[i] = gelu(d0[i]);
    store_tile_64(d0, R2 + wg * 16384, warp, lane);
    mbar_wait(barY + 8 * (2 + wg), 0);
    wg_fence();
#pragma unroll
    for (int k = 0; k < 8; k++)
      wgmma_rs_64<1, 1, 1>(d1, gs[4 * k], gs[4 * k + 1], gs[4 * k + 2], gs[4 * k + 3], mk_desc(R0 + wg * 16384, 32768 + k * 2048, 0, 1024, 1), k);
    wg_commit();
    fence_async();
    mbar_wait(barF, 0);
    mbar_wait(barF + 16, 0);
    __syncthreads();
    wg_fence();
#pragma unroll
    for (int i = 0; i < 8; i++) {
      const int kc = (i >> 2) * 2, s = i & 3;
      wgmma_ss_128<1, 1, 0, 1>(e, mk_desc(R2, kc * 8192 + s * 32, 0, 1024, 1),
                               mk_desc(R1 + wg * 16384, kc * 32768 + s * 2048, 8192, 1024, 1), i);
    }
    wg_commit();
    if (tid == 128) {
      mbar_expect(barO, 32768);
      tma_ld3<0>(R0, &mwo, barO, 0, 0, 0);
    }
    wg_wait<1>();
    reg_fence(d1);
#pragma unroll
    for (int i = 0; i < 32; i++) d1[i] = gelu(d1[i]);
    store_tile_64(d1, R2 + wg * 16384 + 8192, warp, lane);
    fence_async();
    mbar_wait(barF + 8, 0);
    mbar_wait(barF + 24, 0);
    __syncthreads();
    if (tid == 128) {
      mbar_expect(barO + 8, 32768);
      tma_ld3<0>(R0 + 32768, &mwo, barO + 8, 0, 64, 0);
    }
    if (wg == 1) bar_sync(4, 256);
    wg_fence();
#pragma unroll
    for (int i = 0; i < 8; i++) {
      const int kc = (i >> 2) * 2 + 1, s = i & 3;
      wgmma_ss_128<1, 1, 0, 1>(e, mk_desc(R2, kc * 8192 + s * 32, 0, 1024, 1),
                               mk_desc(R1 + wg * 16384, kc * 32768 + s * 2048, 8192, 1024, 1), 1);
    }
    wg_commit();
    if (wg == 0) bar_arrive(4, 256);
    wg_wait<1>();
    if (lane == 0) mbar_arrive(barA);
    if (tid == 128) {
      mbar_wait(barA, 0);
      for (int kc = 2; kc < 4; kc++) {
        mbar_expect(barO + 8 * kc, 32768);
        tma_ld3<0>(R1 + (kc - 2) * 65536, &mwo, barO + 8 * kc, 0, kc * 64, 0);
      }
    }
    mbar_wait(barA, 0);
    asm volatile("st.shared.v4.u32 [%0], {%1, %2, %3, %4};" ::"r"(R2 + wg * 4096 + ((t * 16) ^ (wg * 512))), "r"(gev0.x), "r"(gev0.y), "r"(gev0.z), "r"(gev0.w) : "memory");
    asm volatile("st.shared.v4.u32 [%0], {%1, %2, %3, %4};" ::"r"(R2 + wg * 4096 + 2048 + ((t * 16) ^ (wg * 512))), "r"(gev1.x), "r"(gev1.y), "r"(gev1.z), "r"(gev1.w) : "memory");
    bar_sync(1 + wg, 128);
    g0 = lds128(gp);
    g1 = lds128(gp + 64);
    wg_wait<0>();
    reg_fence(e);
#pragma unroll
    for (int i = 0; i < 32; i++) fe[i] = pack2(e[2 * i], e[2 * i + 1]);
  }
  auto publish = [&]() {
    bar_sync(1 + wg, 128);
    const int row = warp * 16 + (lane & 7) + ((lane >> 3) & 1) * 8;
    const uint32_t xb = R1 + (wg == 0 ? 3 * 32768 : 32768 + 16384) + row * 128;
#pragma unroll
    for (int s = 0; s < 8; s++) {
      const int jj = 2 * s + (lane >> 4);
      stsm4(xb + (s >> 2) * 8192 + (((jj & 7) ^ (lane & 7)) << 4), fe[4 * s], fe[4 * s + 1], fe[4 * s + 2], fe[4 * s + 3]);
    }
    bar_arrive(5 + wg, 256);
  };
  if (wg == 1) publish();
  const uint32_t stg = R1 + 32768 + wg * 65536;
  const uint32_t w0 = sb + wg * 65536, w1 = sb + 32768 + wg * 98304, w2 = sb + 65536 - wg * 65536, w3 = sb + 131072 - wg * 98304;
  float acc[128];
  uint32_t j0[8], j1[8], j2[8], j3[8];
  joint_group(j0, fe, g0, g1, gp + 128);
  mbar_wait(barO + 16 * wg, 0);
  joint_group(j1, fe + 8, g0, g1, gp + 256);
#define E_MMA4(J, K, W, FIRSTK, G, NEXTBAR)                                                     \
  wg_fence();                                                                                   \
  wgmma_rs_256<1, 1, 1>(acc, J[0], J[1], J[2], J[3], mk_desc(W, 0, 8192, 1024, 1), FIRSTK);     \
  wgmma_rs_256<1, 1, 1>(acc, J[4], J[5], J[6], J[7], mk_desc(W, 2048, 8192, 1024, 1), 1);       \
  wgmma_rs_256<1, 1, 1>(acc, K[0], K[1], K[2], K[3], mk_desc(W, 4096, 8192, 1024, 1), 1);       \
  wgmma_rs_256<1, 1, 1>(acc, K[4], K[5], K[6], K[7], mk_desc(W, 6144, 8192, 1024, 1), 1);       \
  wg_commit();                                                                                  \
  if ((ui + wg == 0 ? E_EARLY0 : E_EARLY) == (G) && (ui < 3 || wg == 0)) bar_arrive(4 - wg, 256); \
  wg_wait<1>();                                                                                 \
  if (ui == 0) mbar_wait(NEXTBAR, 0);
  const uint32_t bo0 = barO + 16 * wg, bo2 = barO + 16 * (1 - wg);
#pragma unroll 1
  for (int ui = 0; ui < 4; ui++) {
    if (ui > 0 || wg == 1) bar_sync(3 + wg, 256);
    E_MMA4(j0, j1, w0, 0, 0, bo0)
    joint_group(j2, fe + 16, g0, g1, gp + 384);
    if (ui == 0) mbar_wait(bo0 + 8, 0);
    joint_group(j3, fe + 24, g0, g1, gp + 512);
    E_MMA4(j2, j3, w1, 1, 1, bo0 + 8)
    if (ui == 0) {
      if (wg == 0) publish();
      bar_sync(6 - wg, 256);
      const int row = warp * 16 + (lane & 7) + ((lane >> 3) & 1) * 8;
      const uint32_t xb = R1 + (wg == 1 ? 3 * 32768 : 32768 + 16384) + row * 128;
#pragma unroll
      for (int s = 0; s < 8; s++) {
        const int jj = 2 * s + (lane >> 4);
        ldsm4(xb + (s >> 2) * 8192 + (((jj & 7) ^ (lane & 7)) << 4), fe[32 + 4 * s], fe[33 + 4 * s], fe[34 + 4 * s], fe[35 + 4 * s]);
      }
    }
    joint_group(j0, fe + 32, g0, g1, gp + 640);
    if (ui == 0) mbar_wait(bo2, 0);
    joint_group(j1, fe + 40, g0, g1, gp + 768);
    E_MMA4(j0, j1, w2, 1, 2, bo2)
    joint_group(j2, fe + 48, g0, g1, gp + 896);
    if (ui == 0) mbar_wait(bo2 + 8, 0);
    joint_group(j3, fe + 56, g0, g1, gp + 1024);
    E_MMA4(j2, j3, w3, 1, 3, bo2 + 8)
    gp += 1024;
    if (ui < 3) {
      joint_group(j0, fe, g0, g1, gp + 128);
      if (ui == 0) mbar_wait(bo2 + 8, 0);
      joint_group(j1, fe + 8, g0, g1, gp + 256);
    }
    if (t == 0) bulk_wait_read<0>();
    wg_wait<0>();
    reg_fence(acc);
    bar_sync(1 + wg, 128);
    const uint32_t rb = stg + (warp * 16 + (lane & 7) + ((lane >> 3) & 1) * 8) * 128;
#pragma unroll
    for (int h = 0; h < 2; h++) {
#pragma unroll
      for (int j = 16 * h; j < 16 * h + 16; j += 2) {
        const int jj = j + (lane >> 4);
        stsm4(rb + (j >> 3) * 8192 + (((jj & 7) ^ (lane & 7)) << 4), pack2(acc[4 * j], acc[4 * j + 1]), pack2(acc[4 * j + 2], acc[4 * j + 3]),
              pack2(acc[4 * j + 4], acc[4 * j + 5]), pack2(acc[4 * j + 6], acc[4 * j + 7]));
      }
      const bool split = E_CHUNK == 2 || (E_CHUNK == 1 && ui == 3);
      if (h == 1 || split) {
        fence_async();
        bar_sync(1 + wg, 128);
        if (t == 0) {
          if (h == 1 && !split) tma_st5<1>(&mout, stg, 0, t0, 0, wg * 4 + ui, b);
          tma_st5<1>(&mout, stg + h * 16384, 0, t0, 2 * h, wg * 4 + ui, b);
          bulk_commit();
        }
      }
    }
  }
  if (t == 0) bulk_wait_read<0>();
}

typedef CUresult (*EncodeFn)(CUtensorMap*, CUtensorMapDataType, cuuint32_t, void*, const cuuint64_t*, const cuuint64_t*,
                             const cuuint32_t*, const cuuint32_t*, CUtensorMapInterleave, CUtensorMapSwizzle,
                             CUtensorMapL2promotion, CUtensorMapFloatOOBfill);

CUtensorMap make_map(EncodeFn fn, const void* base, int rank, const uint64_t* dims, const uint64_t* strides, const uint32_t* box,
                     CUtensorMapSwizzle swz) {
  CUtensorMap m;
  cuuint64_t gd[5], gs[4];
  cuuint32_t bx[5], es[5];
  for (int i = 0; i < rank; i++) { gd[i] = dims[i]; bx[i] = box[i]; es[i] = 1; }
  for (int i = 0; i + 1 < rank; i++) gs[i] = strides[i];
  fn(&m, CU_TENSOR_MAP_DATA_TYPE_BFLOAT16, rank, const_cast<void*>(base), gd, gs, bx, es, CU_TENSOR_MAP_INTERLEAVE_NONE, swz,
     CU_TENSOR_MAP_L2_PROMOTION_NONE, CU_TENSOR_MAP_FLOAT_OOB_FILL_NONE);
  return m;
}

template <typename... KArgs, typename... Args>
void launch(void (*k)(KArgs...), int grid, int block, int smem, bool pdl, Args... args) {
  cudaLaunchConfig_t c = {};
  c.gridDim = dim3(grid);
  c.blockDim = dim3(block);
  c.dynamicSmemBytes = smem;
  c.stream = cudaStreamPerThread;
  cudaLaunchAttribute at[1];
  at[0].id = cudaLaunchAttributeProgrammaticStreamSerialization;
  at[0].val.programmaticStreamSerializationAllowed = 1;
  c.attrs = at;
  c.numAttrs = pdl ? 1 : 0;
  cudaLaunchKernelEx(&c, k, args...);
}

}

extern "C" void kernel_launch(void* const* d_in, const int* in_sizes, int n_in, void* d_out, int out_size) {
  const __nv_bfloat16* x = (const __nv_bfloat16*)d_in[0];
  const __nv_bfloat16* w1 = (const __nv_bfloat16*)d_in[1];
  const __nv_bfloat16* w2 = (const __nv_bfloat16*)d_in[2];
  const __nv_bfloat16* g = (const __nv_bfloat16*)d_in[3];
  const __nv_bfloat16* wf = (const __nv_bfloat16*)d_in[4];
  const __nv_bfloat16* wgt = (const __nv_bfloat16*)d_in[5];
  const __nv_bfloat16* wo = (const __nv_bfloat16*)d_in[6];

  void* fp = nullptr;
  cudaDriverEntryPointQueryResult qr;
  cudaGetDriverEntryPoint("cuTensorMapEncodeTiled", &fp, cudaEnableDefault, &qr);
  EncodeFn fn = (EncodeFn)fp;
  void *W, *Y2, *cnt, *ge, *img, *gat;
  cudaGetSymbolAddress(&cnt, g_cnt);
  cudaGetSymbolAddress(&ge, g_ge);
  cudaGetSymbolAddress(&img, c_img);
  cudaGetSymbolAddress(&gat, c_ga);
  cudaGetSymbolAddress(&W, g_W);
  cudaGetSymbolAddress(&Y2, g_Y2);
  cudaFuncSetAttribute(kG, cudaFuncAttributeMaxDynamicSharedMemorySize, G_SMEM);
  cudaFuncSetAttribute(kE, cudaFuncAttributeMaxDynamicSharedMemorySize, E_SMEM);
  auto page_up = [](void* p) { return (void*)(((uintptr_t)p + (1 << 21) - 1) & ~(uintptr_t)((1 << 21) - 1)); };
  void *X1 = page_up(d_out), *X2 = X1;
  W = page_up(W);
  const CUtensorMapSwizzle S128 = CU_TENSOR_MAP_SWIZZLE_128B, S64 = CU_TENSOR_MAP_SWIZZLE_64B;

  auto map_x = [&]() {
    uint64_t d[] = {64, 8000, 8, 1, 2}, s[] = {1024, 128, 8000ull * 1024, 8000ull * 1024};
    uint32_t bx[] = {64, 112, 1, 1, 1};
    return make_map(fn, x, 5, d, s, bx, S128);
  };
  auto map_w_in = [&](const __nv_bfloat16* w, int odd, uint32_t n) {
    uint64_t d[] = {64, (uint64_t)(odd ? 15 : 16), 4, 64, 4}, s[] = {2ull * 65536 * 2, 128, 512, 32768};
    uint32_t bx[] = {64, 16, 2, 1, n};
    return make_map(fn, w + (odd ? 65536 : 0), 5, d, s, bx, S128);
  };
  auto map_X_st = [&](void* p, int nb, int boxb) {
    uint64_t d[] = {64, 512, (uint64_t)(2 * nb)}, s[] = {2ull * nb * 128, 128};
    uint32_t bx[] = {64, 64, (uint32_t)boxb};
    return make_map(fn, p, 3, d, s, bx, S128);
  };
  auto map_X1_st = [&](uint32_t rows) {
    uint64_t d[] = {8192, 16, 4, 24}, s[] = {16384, 262144, 1048576};
    uint32_t bx[] = {64, 4, 2, rows / 8};
    return make_map(fn, X1, 4, d, s, bx, S128);
  };
  auto map_Y1_ld = [&](uint64_t step) {
    uint64_t d[] = {64, 12 << 14, 2}, s[] = {128, step};
    uint32_t bx[] = {64, 32, 2};
    return make_map(fn, X1, 3, d, s, bx, S128);
  };
  auto map_W_st = [&]() {
    uint64_t d[] = {8192, 8, 4, 2 * (8 + W_SHIFT), 2}, s[] = {32768, 262144, 1048576, 16384};
    uint32_t bx[] = {64, 2, 2, 2, 2};
    return make_map(fn, W, 5, d, s, bx, S128);
  };
  auto map_X_ld = [&](void* p, int nb, int boxb) {
    uint64_t d[] = {64, (uint64_t)(2 * nb), 512}, s[] = {128, 2ull * nb * 128};
    uint32_t bx[] = {32, (uint32_t)boxb, 1};
    return make_map(fn, p, 3, d, s, bx, S64);
  };
  auto map_W_ld = [&](uint32_t n) {
    uint64_t d[] = {64, 512 / n, (8ull + W_SHIFT) * 32 * n}, s[] = {128, 65536 / n};
    uint32_t bx[] = {64, 32, n};
    return make_map(fn, W, 3, d, s, bx, S128);
  };
  auto map_Y_st = [&](void* p, int nb, int rows) {
    uint64_t d[] = {64, (uint64_t)(2 * nb), 64, 4}, s[] = {32768, 128, 8192};
    uint32_t bx[] = {64, (uint32_t)rows, 1, 1};
    return make_map(fn, p, 4, d, s, bx, S128);
  };
  auto map_Y_ld = [&](void* p, int nb, int boxc, int boxb) {
    uint64_t d[] = {64, 64, 4, (uint64_t)nb, 2}, s[] = {128, 8192, 32768, (uint64_t)nb * 32768};
    uint32_t bx[] = {64, 64, (uint32_t)boxc, (uint32_t)boxb, 1};
    return make_map(fn, p, 5, d, s, bx, S128);
  };
  auto map_wsq = [&](const __nv_bfloat16* w) {
    uint64_t d[] = {64, 256, 4}, s[] = {512, 128};
    uint32_t bx[] = {64, 64, 4};
    return make_map(fn, w, 3, d, s, bx, S128);
  };
  auto map_out = [&]() {
    uint64_t d[] = {64, 4000, 4, 8, 2}, s[] = {4096, 128, 512, 4000ull * 4096};
    uint32_t bx[] = {64, 64, 2, 1, 1};
    return make_map(fn, d_out, 5, d, s, bx, S128);
  };

  GMaps g1;
  g1.w = map_W_ld(4);
  g1.y = map_X1_st(8);
  g1.in[0] = map_w_in(w1, 1, 2);
  g1.in[1] = map_w_in(w1, 0, 2);
  g1.in[2] = map_w_in(w2, 1, 1);
  g1.in[3] = map_w_in(w2, 0, 1);
  g1.in[4] = map_x();
  g1.xs = map_X1_st(16);
  g1.ws = map_W_st();
  g1.y1[0] = map_Y1_ld(0x3000);
  g1.y1[1] = map_Y1_ld(0x1000);
  g1.x2s = map_X_st(X2, NB2, 1);
  g1.x2 = map_X_ld(X2, NB2, 168);
  g1.w2 = map_W_ld(2);
  g1.y2 = map_Y_st(Y2, NB2, 168 / H_EPI);
  launch(kG, 132, 384, G_SMEM, false, (int*)cnt, (char*)X1, (char*)W, g, wgt, (float*)ge, (const uint32_t*)img, wf, wo, (const uint32_t*)gat, g1);
  launch(kE, 126, 256, E_SMEM, true, (int*)cnt, (const uint32_t*)gat, (const float*)ge, map_Y_ld(Y2, NB2, 1, 2), map_wsq(wf), map_wsq(wo), map_out());
}
```

```cpp
#include <cuda_runtime.h>
#include <cuda_bf16.h>
#include <cuda.h>
#include <stdint.h>
#include <type_traits>

#define W_SHIFT 1
namespace {

constexpr int NB1 = 168;
constexpr int NB2 = 84;

__device__ __align__(1024) __nv_bfloat16 g_W[(9 + W_SHIFT) * 64 * 4 * 64 * 64];
__device__ __align__(1024) __nv_bfloat16 g_Y2[2 * NB2 * 4 * 64 * 64];
__device__ __align__(1024) float g_ge[16 * 256];

__device__ __forceinline__ uint32_t s2u(const void* p) { return (uint32_t)__cvta_generic_to_shared(p); }
__device__ __forceinline__ uint32_t pin(uint32_t v) {
  return __shfl_sync(0xffffffffu, v, 0);
}
__device__ __forceinline__ void mbar_init(uint32_t b, int c) {
  asm volatile("mbarrier.init.shared::cta.b64 [%0], %1;" ::"r"(b), "r"(c) : "memory");
}
__device__ __forceinline__ void mbar_expect(uint32_t b, int bytes) {
  asm volatile("mbarrier.arrive.expect_tx.shared::cta.b64 _, [%0], %1;" ::"r"(b), "r"(bytes) : "memory");
}
__device__ __forceinline__ void mbar_arrive(uint32_t b) {
  asm volatile("mbarrier.arrive.shared::cta.b64 _, [%0];" ::"r"(b) : "memory");
}
__device__ __forceinline__ void mbar_arrive_cta(uint32_t b, uint32_t cta) {
  asm volatile("{\n.reg .b32 r;\nmapa.shared::cluster.u32 r, %0, %1;\nmbarrier.arrive.shared::cluster.b64 _, [r];\n}" ::"r"(b), "r"(cta) : "memory");
}
__device__ __forceinline__ void mbar_wait(uint32_t b, int ph) {
  asm volatile(
      "{\n.reg .pred p;\n.reg .u32 n;\n"
      "mov.u32 n, 0;\n"
      "MBW_LOOP:\n"
      "mbarrier.try_wait.parity.shared::cta.b64 p, [%0], %1;\n"
      "@p bra MBW_DONE;\n"
      "add.u32 n, n, 1;\n"
      "setp.lt.u32 p, n, 1048576;\n"
      "@p bra MBW_LOOP;\n"
      "MBW_DONE:\n}" ::"r"(b), "r"(ph) : "memory");
}
__device__ __forceinline__ bool mbar_test(uint32_t b, int ph) {
  uint32_t ok;
  asm volatile("{\n.reg .pred p;\nmbarrier.test_wait.parity.shared::cta.b64 p, [%1], %2;\nselp.u32 %0, 1, 0, p;\n}" : "=r"(ok) : "r"(b), "r"(ph) : "memory");
  return __all_sync(0xffffffffu, ok);
}
__device__ __forceinline__ void fence_bar_init() { asm volatile("fence.mbarrier_init.release.cluster;" ::: "memory"); }
__device__ __forceinline__ void fence_async() { asm volatile("fence.proxy.async.shared::cta;" ::: "memory"); }
__device__ __forceinline__ void bar_sync(int id, int n) { asm volatile("bar.sync %0, %1;" ::"r"(id), "r"(n) : "memory"); }
__device__ __forceinline__ void bar_arrive(int id, int n) { asm volatile("bar.arrive %0, %1;" ::"r"(id), "r"(n) : "memory"); }
__device__ __forceinline__ void pdl_wait() { asm volatile("griddepcontrol.wait;" ::: "memory"); }
__device__ __forceinline__ void pdl_launch() { asm volatile("griddepcontrol.launch_dependents;" ::: "memory"); }
__device__ __forceinline__ void prefetch_map(const CUtensorMap* m) {
  asm volatile("prefetch.tensormap [%0];" ::"l"(m) : "memory");
}
template <int P> __device__ __forceinline__ uint64_t policy() {
  uint64_t p;
  asm("createpolicy.fractional.L2::evict_first.b64 %0, 1.0;" : "=l"(p));
  return p;
}
template <int P> __device__ __forceinline__ void tma_ld3(uint32_t dst, const CUtensorMap* m, uint32_t bar, int c0, int c1, int c2) {
  if constexpr (P == 0)
    asm volatile("cp.async.bulk.tensor.3d.shared::cluster.global.mbarrier::complete_tx::bytes [%0], [%1, {%3, %4, %5}], [%2];"
                 ::"r"(dst), "l"(m), "r"(bar), "r"(c0), "r"(c1), "r"(c2) : "memory");
  else
    asm volatile("cp.async.bulk.tensor.3d.shared::cluster.global.mbarrier::complete_tx::bytes.L2::cache_hint [%0], [%1, {%3, %4, %5}], [%2], %6;"
                 ::"r"(dst), "l"(m), "r"(bar), "r"(c0), "r"(c1), "r"(c2), "l"(policy<P>()) : "memory");
}
template <int P> __device__ __forceinline__ void tma_ld3mc(uint32_t dst, const CUtensorMap* m, uint32_t bar, int c0, int c1, int c2) {
  if constexpr (P == 0)
    asm volatile("cp.async.bulk.tensor.3d.shared::cluster.global.mbarrier::complete_tx::bytes.multicast::cluster [%0], [%1, {%3, %4, %5}], [%2], %6;"
                 ::"r"(dst), "l"(m), "r"(bar), "r"(c0), "r"(c1), "r"(c2), "h"((uint16_t)3) : "memory");
  else
    asm volatile("cp.async.bulk.tensor.3d.shared::cluster.global.mbarrier::complete_tx::bytes.multicast::cluster.L2::cache_hint [%0], [%1, {%3, %4, %5}], [%2], %6, %7;"
                 ::"r"(dst), "l"(m), "r"(bar), "r"(c0), "r"(c1), "r"(c2), "h"((uint16_t)3), "l"(policy<P>()) : "memory");
}
template <int P> __device__ __forceinline__ void tma_ld4(uint32_t dst, const CUtensorMap* m, uint32_t bar, int c0, int c1, int c2, int c3) {
  if constexpr (P == 0)
    asm volatile("cp.async.bulk.tensor.4d.shared::cluster.global.mbarrier::complete_tx::bytes [%0], [%1, {%3, %4, %5, %6}], [%2];"
                 ::"r"(dst), "l"(m), "r"(bar), "r"(c0), "r"(c1), "r"(c2), "r"(c3) : "memory");
  else
    asm volatile("cp.async.bulk.tensor.4d.shared::cluster.global.mbarrier::complete_tx::bytes.L2::cache_hint [%0], [%1, {%3, %4, %5, %6}], [%2], %7;"
                 ::"r"(dst), "l"(m), "r"(bar), "r"(c0), "r"(c1), "r"(c2), "r"(c3), "l"(policy<P>()) : "memory");
}
template <int P> __device__ __forceinline__ void tma_ld4mc(uint32_t dst, const CUtensorMap* m, uint32_t bar, int c0, int c1, int c2, int c3) {
  if constexpr (P == 0)
    asm volatile("cp.async.bulk.tensor.4d.shared::cluster.global.mbarrier::complete_tx::bytes.multicast::cluster [%0], [%1, {%3, %4, %5, %6}], [%2], %7;"
                 ::"r"(dst), "l"(m), "r"(bar), "r"(c0), "r"(c1), "r"(c2), "r"(c3), "h"((uint16_t)3) : "memory");
  else
    asm volatile("cp.async.bulk.tensor.4d.shared::cluster.global.mbarrier::complete_tx::bytes.multicast::cluster.L2::cache_hint [%0], [%1, {%3, %4, %5, %6}], [%2], %7, %8;"
                 ::"r"(dst), "l"(m), "r"(bar), "r"(c0), "r"(c1), "r"(c2), "r"(c3), "h"((uint16_t)3), "l"(policy<P>()) : "memory");
}
template <int P> __device__ __forceinline__ void tma_ld5(uint32_t dst, const CUtensorMap* m, uint32_t bar, int c0, int c1, int c2, int c3, int c4) {
  if constexpr (P == 0)
    asm volatile("cp.async.bulk.tensor.5d.shared::cluster.global.mbarrier::complete_tx::bytes [%0], [%1, {%3, %4, %5, %6, %7}], [%2];"
                 ::"r"(dst), "l"(m), "r"(bar), "r"(c0), "r"(c1), "r"(c2), "r"(c3), "r"(c4) : "memory");
  else
    asm volatile("cp.async.bulk.tensor.5d.shared::cluster.global.mbarrier::complete_tx::bytes.L2::cache_hint [%0], [%1, {%3, %4, %5, %6, %7}], [%2], %8;"
                 ::"r"(dst), "l"(m), "r"(bar), "r"(c0), "r"(c1), "r"(c2), "r"(c3), "r"(c4), "l"(policy<P>()) : "memory");
}
template <int P> __device__ __forceinline__ void tma_st3(const CUtensorMap* m, uint32_t src, int c0, int c1, int c2) {
  if constexpr (P == 0)
    asm volatile("cp.async.bulk.tensor.3d.global.shared::cta.bulk_group [%0, {%2, %3, %4}], [%1];" ::"l"(m), "r"(src), "r"(c0), "r"(c1), "r"(c2) : "memory");
  else
    asm volatile("cp.async.bulk.tensor.3d.global.shared::cta.bulk_group.L2::cache_hint [%0, {%2, %3, %4}], [%1], %5;" ::"l"(m), "r"(src), "r"(c0), "r"(c1), "r"(c2), "l"(policy<P>()) : "memory");
}
template <int P> __device__ __forceinline__ void tma_st4(const CUtensorMap* m, uint32_t src, int c0, int c1, int c2, int c3) {
  if constexpr (P == 0)
    asm volatile("cp.async.bulk.tensor.4d.global.shared::cta.bulk_group [%0, {%2, %3, %4, %5}], [%1];" ::"l"(m), "r"(src), "r"(c0), "r"(c1), "r"(c2), "r"(c3) : "memory");
  else
    asm volatile("cp.async.bulk.tensor.4d.global.shared::cta.bulk_group.L2::cache_hint [%0, {%2, %3, %4, %5}], [%1], %6;" ::"l"(m), "r"(src), "r"(c0), "r"(c1), "r"(c2), "r"(c3), "l"(policy<P>()) : "memory");
}
template <int P> __device__ __forceinline__ void tma_st5(const CUtensorMap* m, uint32_t src, int c0, int c1, int c2, int c3, int c4) {
  if constexpr (P == 0)
    asm volatile("cp.async.bulk.tensor.5d.global.shared::cta.bulk_group [%0, {%2, %3, %4, %5, %6}], [%1];" ::"l"(m), "r"(src), "r"(c0), "r"(c1), "r"(c2), "r"(c3), "r"(c4) : "memory");
  else
    asm volatile("cp.async.bulk.tensor.5d.global.shared::cta.bulk_group.L2::cache_hint [%0, {%2, %3, %4, %5, %6}], [%1], %7;" ::"l"(m), "r"(src), "r"(c0), "r"(c1), "r"(c2), "r"(c3), "r"(c4), "l"(policy<P>()) : "memory");
}
__device__ __forceinline__ void bulk_commit() { asm volatile("cp.async.bulk.commit_group;" ::: "memory"); }
template <int N> __device__ __forceinline__ void bulk_wait() { asm volatile("cp.async.bulk.wait_group %0;" ::"n"(N) : "memory"); }
template <int N> __device__ __forceinline__ void bulk_wait_read() { asm volatile("cp.async.bulk.wait_group.read %0;" ::"n"(N) : "memory"); }
__device__ __forceinline__ void wg_fence() { asm volatile("wgmma.fence.sync.aligned;" ::: "memory"); }
__device__ __forceinline__ void wg_commit() { asm volatile("wgmma.commit_group.sync.aligned;" ::: "memory"); }
template <int N> __device__ __forceinline__ void wg_wait() { asm volatile("wgmma.wait_group.sync.aligned %0;" ::"n"(N) : "memory"); }
template <int R> __device__ __forceinline__ void reg_fence(float (&d)[R]) {
#pragma unroll
  for (int i = 0; i < R; i++) asm volatile("" : "+f"(d[i])::"memory");
}
template <int R> __device__ __forceinline__ void reg_fence(uint32_t (&d)[R]) {
#pragma unroll
  for (int i = 0; i < R; i++) asm volatile("" : "+r"(d[i])::"memory");
}
__device__ __forceinline__ void stsm4(uint32_t a, uint32_t r0, uint32_t r1, uint32_t r2, uint32_t r3) {
  asm volatile("stmatrix.sync.aligned.m8n8.x4.shared.b16 [%0], {%1, %2, %3, %4};" ::"r"(a), "r"(r0), "r"(r1), "r"(r2), "r"(r3) : "memory");
}
__device__ __forceinline__ void stsm4t(uint32_t a, uint32_t r0, uint32_t r1, uint32_t r2, uint32_t r3) {
  asm volatile("stmatrix.sync.aligned.m8n8.x4.trans.shared.b16 [%0], {%1, %2, %3, %4};" ::"r"(a), "r"(r0), "r"(r1), "r"(r2), "r"(r3) : "memory");
}
__device__ __forceinline__ void ldsm4(uint32_t a, uint32_t& r0, uint32_t& r1, uint32_t& r2, uint32_t& r3) {
  asm volatile("ldmatrix.sync.aligned.m8n8.x4.shared.b16 {%0, %1, %2, %3}, [%4];" : "=r"(r0), "=r"(r1), "=r"(r2), "=r"(r3) : "r"(a) : "memory");
}
__device__ __forceinline__ void ldg128(const uint4* p, uint32_t& a, uint32_t& b, uint32_t& c, uint32_t& d) {
  asm volatile("ld.global.nc.v4.u32 {%0, %1, %2, %3}, [%4];" : "=r"(a), "=r"(b), "=r"(c), "=r"(d) : "l"(p));
}
__device__ __forceinline__ uint32_t pack2(float lo, float hi) {
  uint32_t r;
  asm("cvt.rn.bf16x2.f32 %0, %1, %2;" : "=r"(r) : "f"(hi), "f"(lo));
  return r;
}
__device__ __forceinline__ float tanh_f32(float x) {
  float y;
  asm("tanh.approx.f32 %0, %1;" : "=f"(y) : "f"(x));
  return y;
}
__device__ __forceinline__ float gelu(float hx) {
  const float u = hx * fmaf(hx * hx, 8.0f * 0.044715f * 0.7978845608028654f, 2.0f * 0.7978845608028654f);
  return fmaf(hx, tanh_f32(u), hx);
}
__device__ __forceinline__ uint64_t mk_desc4(uint32_t addr4, uint32_t lbo, uint32_t sbo, uint32_t swz) {
  const uint32_t lo = addr4 + ((lbo >> 4) << 16), hi = (sbo >> 4) | (swz << 30);
  uint64_t d;
  asm("mov.b64 %0, {%1, %2};" : "=l"(d) : "r"(lo), "r"(hi));
  return d;
}
#define mk_desc(base, off, lbo, sbo, swz) mk_desc4((((base) & 0x3FFFF) >> 4) + ((off) >> 4), lbo, sbo, swz)

template <int SA, int SB, int TA, int TB>
__device__ __forceinline__ void wgmma_ss_16(float (&d)[8], uint64_t da, uint64_t db, int sd) {
  asm volatile("{\n.reg .pred p;\nsetp.ne.b32 p, %10, 0;\n"
      "wgmma.mma_async.sync.aligned.m64n16k16.f32.bf16.bf16 {"
      "%0, %1, %2, %3, %4, %5, %6, %7"
      "}, %8, %9, p, %11, %12, %13, %14;\n}\n"
      : "+f"(d[0]), "+f"(d[1]), "+f"(d[2]), "+f"(d[3]), "+f"(d[4]), "+f"(d[5]), "+f"(d[6]), "+f"(d[7])
      : "l"(da), "l"(db), "r"(sd), "n"(SA), "n"(SB), "n"(TA), "n"(TB));
}
template <int SA, int SB, int TA, int TB>
__device__ __forceinline__ void wgmma_ss_24(float (&d)[12], uint64_t da, uint64_t db, int sd) {
  asm volatile("{\n.reg .pred p;\nsetp.ne.b32 p, %14, 0;\n"
      "wgmma.mma_async.sync.aligned.m64n24k16.f32.bf16.bf16 {"
      "%0, %1, %2, %3, %4, %5, %6, %7, %8, %9, %10, %11"
      "}, %12, %13, p, %15, %16, %17, %18;\n}\n"
      : "+f"(d[0]), "+f"(d[1]), "+f"(d[2]), "+f"(d[3]), "+f"(d[4]), "+f"(d[5]), "+f"(d[6]), "+f"(d[7]), "+f"(d[8]),
        "+f"(d[9]), "+f"(d[10]), "+f"(d[11])
      : "l"(da), "l"(db), "r"(sd), "n"(SA), "n"(SB), "n"(TA), "n"(TB));
}
template <int SA, int SB, int TA, int TB>
__device__ __forceinline__ void wgmma_ss_128(float (&d)[64], uint64_t da, uint64_t db, int sd) {
  asm volatile("{\n.reg .pred p;\nsetp.ne.b32 p, %66, 0;\n"
      "wgmma.mma_async.sync.aligned.m64n128k16.f32.bf16.bf16 {"
      "%0, %1, %2, %3, %4, %5, %6, %7, %8, %9, %10, %11, %12, %13, %14, %15, %16, %17, %18, %19, %20, %21, %22, %23, "
      "%24, %25, %26, %27, %28, %29, %30, %31, %32, %33, %34, %35, %36, %37, %38, %39, %40, %41, %42, %43, %44, %45, "
      "%46, %47, %48, %49, %50, %51, %52, %53, %54, %55, %56, %57, %58, %59, %60, %61, %62, %63"
      "}, %64, %65, p, %67, %68, %69, %70;\n}\n"
      : "+f"(d[0]), "+f"(d[1]), "+f"(d[2]), "+f"(d[3]), "+f"(d[4]), "+f"(d[5]), "+f"(d[6]), "+f"(d[7]), "+f"(d[8]),
        "+f"(d[9]), "+f"(d[10]), "+f"(d[11]), "+f"(d[12]), "+f"(d[13]), "+f"(d[14]), "+f"(d[15]), "+f"(d[16]),
        "+f"(d[17]), "+f"(d[18]), "+f"(d[19]), "+f"(d[20]), "+f"(d[21]), "+f"(d[22]), "+f"(d[23]), "+f"(d[24]),
        "+f"(d[25]), "+f"(d[26]), "+f"(d[27]), "+f"(d[28]), "+f"(d[29]), "+f"(d[30]), "+f"(d[31]), "+f"(d[32]),
        "+f"(d[33]), "+f"(d[34]), "+f"(d[35]), "+f"(d[36]), "+f"(d[37]), "+f"(d[38]), "+f"(d[39]), "+f"(d[40]),
        "+f"(d[41]), "+f"(d[42]), "+f"(d[43]), "+f"(d[44]), "+f"(d[45]), "+f"(d[46]), "+f"(d[47]), "+f"(d[48]),
        "+f"(d[49]), "+f"(d[50]), "+f"(d[51]), "+f"(d[52]), "+f"(d[53]), "+f"(d[54]), "+f"(d[55]), "+f"(d[56]),
        "+f"(d[57]), "+f"(d[58]), "+f"(d[59]), "+f"(d[60]), "+f"(d[61]), "+f"(d[62]), "+f"(d[63])
      : "l"(da), "l"(db), "r"(sd), "n"(SA), "n"(SB), "n"(TA), "n"(TB));
}
template <int SA, int SB, int TA, int TB>
__device__ __forceinline__ void wgmma_ss_168(float (&d)[84], uint64_t da, uint64_t db, int sd) {
  asm volatile("{\n.reg .pred p;\nsetp.ne.b32 p, %86, 0;\n"
      "wgmma.mma_async.sync.aligned.m64n168k16.f32.bf16.bf16 {"
      "%0, %1, %2, %3, %4, %5, %6, %7, %8, %9, %10, %11, %12, %13, %14, %15, %16, %17, %18, %19, %20, %21, %22, %23, "
      "%24, %25, %26, %27, %28, %29, %30, %31, %32, %33, %34, %35, %36, %37, %38, %39, %40, %41, %42, %43, %44, %45, "
      "%46, %47, %48, %49, %50, %51, %52, %53, %54, %55, %56, %57, %58, %59, %60, %61, %62, %63, %64, %65, %66, %67, "
      "%68, %69, %70, %71, %72, %73, %74, %75, %76, %77, %78, %79, %80, %81, %82, %83"
      "}, %84, %85, p, %87, %88, %89, %90;\n}\n"
      : "+f"(d[0]), "+f"(d[1]), "+f"(d[2]), "+f"(d[3]), "+f"(d[4]), "+f"(d[5]), "+f"(d[6]), "+f"(d[7]), "+f"(d[8]),
        "+f"(d[9]), "+f"(d[10]), "+f"(d[11]), "+f"(d[12]), "+f"(d[13]), "+f"(d[14]), "+f"(d[15]), "+f"(d[16]),
        "+f"(d[17]), "+f"(d[18]), "+f"(d[19]), "+f"(d[20]), "+f"(d[21]), "+f"(d[22]), "+f"(d[23]), "+f"(d[24]),
        "+f"(d[25]), "+f"(d[26]), "+f"(d[27]), "+f"(d[28]), "+f"(d[29]), "+f"(d[30]), "+f"(d[31]), "+f"(d[32]),
        "+f"(d[33]), "+f"(d[34]), "+f"(d[35]), "+f"(d[36]), "+f"(d[37]), "+f"(d[38]), "+f"(d[39]), "+f"(d[40]),
        "+f"(d[41]), "+f"(d[42]), "+f"(d[43]), "+f"(d[44]), "+f"(d[45]), "+f"(d[46]), "+f"(d[47]), "+f"(d[48]),
        "+f"(d[49]), "+f"(d[50]), "+f"(d[51]), "+f"(d[52]), "+f"(d[53]), "+f"(d[54]), "+f"(d[55]), "+f"(d[56]),
        "+f"(d[57]), "+f"(d[58]), "+f"(d[59]), "+f"(d[60]), "+f"(d[61]), "+f"(d[62]), "+f"(d[63]), "+f"(d[64]),
        "+f"(d[65]), "+f"(d[66]), "+f"(d[67]), "+f"(d[68]), "+f"(d[69]), "+f"(d[70]), "+f"(d[71]), "+f"(d[72]),
        "+f"(d[73]), "+f"(d[74]), "+f"(d[75]), "+f"(d[76]), "+f"(d[77]), "+f"(d[78]), "+f"(d[79]), "+f"(d[80]),
        "+f"(d[81]), "+f"(d[82]), "+f"(d[83])
      : "l"(da), "l"(db), "r"(sd), "n"(SA), "n"(SB), "n"(TA), "n"(TB));
}
template <int SA, int SB, int TB>
__device__ __forceinline__ void wgmma_rs_64(float (&d)[32], uint32_t a0, uint32_t a1, uint32_t a2, uint32_t a3, uint64_t db, int sd) {
  asm volatile("{\n.reg .pred p;\nsetp.ne.b32 p, %37, 0;\n"
      "wgmma.mma_async.sync.aligned.m64n64k16.f32.bf16.bf16 {"
      "%0, %1, %2, %3, %4, %5, %6, %7, %8, %9, %10, %11, %12, %13, %14, %15, %16, %17, %18, %19, %20, %21, %22, %23, "
      "%24, %25, %26, %27, %28, %29, %30, %31"
      "}, {%32, %33, %34, %35}, %36, p, %38, %39, %40;\n}\n"
      : "+f"(d[0]), "+f"(d[1]), "+f"(d[2]), "+f"(d[3]), "+f"(d[4]), "+f"(d[5]), "+f"(d[6]), "+f"(d[7]), "+f"(d[8]),
        "+f"(d[9]), "+f"(d[10]), "+f"(d[11]), "+f"(d[12]), "+f"(d[13]), "+f"(d[14]), "+f"(d[15]), "+f"(d[16]),
        "+f"(d[17]), "+f"(d[18]), "+f"(d[19]), "+f"(d[20]), "+f"(d[21]), "+f"(d[22]), "+f"(d[23]), "+f"(d[24]),
        "+f"(d[25]), "+f"(d[26]), "+f"(d[27]), "+f"(d[28]), "+f"(d[29]), "+f"(d[30]), "+f"(d[31])
      : "r"(a0), "r"(a1), "r"(a2), "r"(a3), "l"(db), "r"(sd), "n"(SA), "n"(SB), "n"(TB));
}
template <int SA, int SB, int TB>
__device__ __forceinline__ void wgmma_rs_128(float (&d)[64], uint32_t a0, uint32_t a1, uint32_t a2, uint32_t a3, uint64_t db, int sd) {
  asm volatile("{\n.reg .pred p;\nsetp.ne.b32 p, %69, 0;\n"
      "wgmma.mma_async.sync.aligned.m64n128k16.f32.bf16.bf16 {"
      "%0, %1, %2, %3, %4, %5, %6, %7, %8, %9, %10, %11, %12, %13, %14, %15, %16, %17, %18, %19, %20, %21, %22, %23, "
      "%24, %25, %26, %27, %28, %29, %30, %31, %32, %33, %34, %35, %36, %37, %38, %39, %40, %41, %42, %43, %44, %45, "
      "%46, %47, %48, %49, %50, %51, %52, %53, %54, %55, %56, %57, %58, %59, %60, %61, %62, %63"
      "}, {%64, %65, %66, %67}, %68, p, %70, %71, %72;\n}\n"
      : "+f"(d[0]), "+f"(d[1]), "+f"(d[2]), "+f"(d[3]), "+f"(d[4]), "+f"(d[5]), "+f"(d[6]), "+f"(d[7]), "+f"(d[8]),
        "+f"(d[9]), "+f"(d[10]), "+f"(d[11]), "+f"(d[12]), "+f"(d[13]), "+f"(d[14]), "+f"(d[15]), "+f"(d[16]),
        "+f"(d[17]), "+f"(d[18]), "+f"(d[19]), "+f"(d[20]), "+f"(d[21]), "+f"(d[22]), "+f"(d[23]), "+f"(d[24]),
        "+f"(d[25]), "+f"(d[26]), "+f"(d[27]), "+f"(d[28]), "+f"(d[29]), "+f"(d[30]), "+f"(d[31]), "+f"(d[32]),
        "+f"(d[33]), "+f"(d[34]), "+f"(d[35]), "+f"(d[36]), "+f"(d[37]), "+f"(d[38]), "+f"(d[39]), "+f"(d[40]),
        "+f"(d[41]), "+f"(d[42]), "+f"(d[43]), "+f"(d[44]), "+f"(d[45]), "+f"(d[46]), "+f"(d[47]), "+f"(d[48]),
        "+f"(d[49]), "+f"(d[50]), "+f"(d[51]), "+f"(d[52]), "+f"(d[53]), "+f"(d[54]), "+f"(d[55]), "+f"(d[56]),
        "+f"(d[57]), "+f"(d[58]), "+f"(d[59]), "+f"(d[60]), "+f"(d[61]), "+f"(d[62]), "+f"(d[63])
      : "r"(a0), "r"(a1), "r"(a2), "r"(a3), "l"(db), "r"(sd), "n"(SA), "n"(SB), "n"(TB));
}
template <int SA, int SB, int TB>
__device__ __forceinline__ void wgmma_rs_256(float (&d)[128], uint32_t a0, uint32_t a1, uint32_t a2, uint32_t a3, uint64_t db, int sd) {
  asm volatile("{\n.reg .pred p;\nsetp.ne.b32 p, %133, 0;\n"
      "wgmma.mma_async.sync.aligned.m64n256k16.f32.bf16.bf16 {"
      "%0, %1, %2, %3, %4, %5, %6, %7, %8, %9, %10, %11, %12, %13, %14, %15, %16, %17, %18, %19, %20, %21, %22, %23, "
      "%24, %25, %26, %27, %28, %29, %30, %31, %32, %33, %34, %35, %36, %37, %38, %39, %40, %41, %42, %43, %44, %45, "
      "%46, %47, %48, %49, %50, %51, %52, %53, %54, %55, %56, %57, %58, %59, %60, %61, %62, %63, %64, %65, %66, %67, "
      "%68, %69, %70, %71, %72, %73, %74, %75, %76, %77, %78, %79, %80, %81, %82, %83, %84, %85, %86, %87, %88, %89, "
      "%90, %91, %92, %93, %94, %95, %96, %97, %98, %99, %100, %101, %102, %103, %104, %105, %106, %107, %108, %109, "
      "%110, %111, %112, %113, %114, %115, %116, %117, %118, %119, %120, %121, %122, %123, %124, %125, %126, %127"
      "}, {%128, %129, %130, %131}, %132, p, %134, %135, %136;\n}\n"
      : "+f"(d[0]), "+f"(d[1]), "+f"(d[2]), "+f"(d[3]), "+f"(d[4]), "+f"(d[5]), "+f"(d[6]), "+f"(d[7]), "+f"(d[8]),
        "+f"(d[9]), "+f"(d[10]), "+f"(d[11]), "+f"(d[12]), "+f"(d[13]), "+f"(d[14]), "+f"(d[15]), "+f"(d[16]),
        "+f"(d[17]), "+f"(d[18]), "+f"(d[19]), "+f"(d[20]), "+f"(d[21]), "+f"(d[22]), "+f"(d[23]), "+f"(d[24]),
        "+f"(d[25]), "+f"(d[26]), "+f"(d[27]), "+f"(d[28]), "+f"(d[29]), "+f"(d[30]), "+f"(d[31]), "+f"(d[32]),
        "+f"(d[33]), "+f"(d[34]), "+f"(d[35]), "+f"(d[36]), "+f"(d[37]), "+f"(d[38]), "+f"(d[39]), "+f"(d[40]),
        "+f"(d[41]), "+f"(d[42]), "+f"(d[43]), "+f"(d[44]), "+f"(d[45]), "+f"(d[46]), "+f"(d[47]), "+f"(d[48]),
        "+f"(d[49]), "+f"(d[50]), "+f"(d[51]), "+f"(d[52]), "+f"(d[53]), "+f"(d[54]), "+f"(d[55]), "+f"(d[56]),
        "+f"(d[57]), "+f"(d[58]), "+f"(d[59]), "+f"(d[60]), "+f"(d[61]), "+f"(d[62]), "+f"(d[63]), "+f"(d[64]),
        "+f"(d[65]), "+f"(d[66]), "+f"(d[67]), "+f"(d[68]), "+f"(d[69]), "+f"(d[70]), "+f"(d[71]), "+f"(d[72]),
        "+f"(d[73]), "+f"(d[74]), "+f"(d[75]), "+f"(d[76]), "+f"(d[77]), "+f"(d[78]), "+f"(d[79]), "+f"(d[80]),
        "+f"(d[81]), "+f"(d[82]), "+f"(d[83]), "+f"(d[84]), "+f"(d[85]), "+f"(d[86]), "+f"(d[87]), "+f"(d[88]),
        "+f"(d[89]), "+f"(d[90]), "+f"(d[91]), "+f"(d[92]), "+f"(d[93]), "+f"(d[94]), "+f"(d[95]), "+f"(d[96]),
        "+f"(d[97]), "+f"(d[98]), "+f"(d[99]), "+f"(d[100]), "+f"(d[101]), "+f"(d[102]), "+f"(d[103]), "+f"(d[104]),
        "+f"(d[105]), "+f"(d[106]), "+f"(d[107]), "+f"(d[108]), "+f"(d[109]), "+f"(d[110]), "+f"(d[111]),
        "+f"(d[112]), "+f"(d[113]), "+f"(d[114]), "+f"(d[115]), "+f"(d[116]), "+f"(d[117]), "+f"(d[118]),
        "+f"(d[119]), "+f"(d[120]), "+f"(d[121]), "+f"(d[122]), "+f"(d[123]), "+f"(d[124]), "+f"(d[125]),
        "+f"(d[126]), "+f"(d[127])
      : "r"(a0), "r"(a1), "r"(a2), "r"(a3), "l"(db), "r"(sd), "n"(SA), "n"(SB), "n"(TB));
}

__device__ const __align__(128) uint32_t c_img[3584] = {
    0x00003c80, 0x00003c80, 0x00003c80, 0x00003c80, 0x00003c80, 0x00003c80, 0x00003c80, 0x00003c80, 0x00003c80, 0x00003c80,
    0x00003c80, 0x00003c80, 0x00003c80, 0x00003c80, 0x00003c80, 0x00003c80, 0x00003c80, 0x00003c80, 0x00003c80, 0x00003c80,
    0x00003c80, 0x00003c80, 0x00003c80, 0x00003c80, 0x00003c80, 0x00003c80, 0x00003c80, 0x00003c80, 0x00003c80, 0x00003c80,
    0x00003c80, 0x00003c80, 0x3c463c22, 0x3c623bf1, 0x3c753b95, 0x3c7f3ac9, 0x3ac93c7f, 0x3b953c75, 0x3bf13c62, 0x3c223c46,
    0x3c22bc46, 0x3bf1bc62, 0x3b95bc75, 0x3ac9bc7f, 0x3c7fbac9, 0x3c75bb95, 0x3c62bbf1, 0x3c46bc22, 0xbc46bc22, 0xbc62bbf1,
    0xbc75bb95, 0xbc7fbac9, 0xbac9bc7f, 0xbb95bc75, 0xbbf1bc62, 0xbc22bc46, 0xbc223c46, 0xbbf13c62, 0xbb953c75, 0xbac93c7f,
    0xbc7f3ac9, 0xbc753b95, 0xbc623bf1, 0xbc463c22, 0xbb48bc7b, 0xbc0ebc55, 0xbc55bc0e, 0xbc7bbb48, 0xbc7b3b48, 0xbc553c0e,
    0xbc0e3c55, 0xbb483c7b, 0x3b483c7b, 0x3c0e3c55, 0x3c553c0e, 0x3c7b3b48, 0x3c7bbb48, 0x3c55bc0e, 0x3c0ebc55, 0x3b48bc7b,
    0xbb48bc7b, 0xbc0ebc55, 0xbc55bc0e, 0xbc7bbb48, 0xbc7b3b48, 0xbc553c0e, 0xbc0e3c55, 0xbb483c7b, 0x3b483c7b, 0x3c0e3c55,
    0x3c553c0e, 0x3c7b3b48, 0x3c7bbb48, 0x3c55bc0e, 0x3c0ebc55, 0x3b48bc7b, 0x3c623bf1, 0x3c7fbac9, 0x3c46bc22, 0x3b95bc75,
    0xbc753b95, 0xbc223c46, 0xbac93c7f, 0x3bf13c62, 0x3bf1bc62, 0xbac9bc7f, 0xbc22bc46, 0xbc75bb95, 0x3b953c75, 0x3c463c22,
    0x3c7f3ac9, 0x3c62bbf1, 0xbc62bbf1, 0xbc7f3ac9, 0xbc463c22, 0xbb953c75, 0x3c75bb95, 0x3c22bc46, 0x3ac9bc7f, 0xbbf1bc62,
    0xbbf13c62, 0x3ac93c7f, 0x3c223c46, 0x3c753b95, 0xbb95bc75, 0xbc46bc22, 0xbc7fbac9, 0xbc623bf1, 0x3bc43c6d, 0x3c6d3bc4,
    0x3c6dbbc4, 0x3bc4bc6d, 0xbbc4bc6d, 0xbc6dbbc4, 0xbc6d3bc4, 0xbbc43c6d, 0x3bc43c6d, 0x3c6d3bc4, 0x3c6dbbc4, 0x3bc4bc6d,
    0xbbc4bc6d, 0xbc6dbbc4, 0xbc6d3bc4, 0xbbc43c6d, 0x3bc43c6d, 0x3c6d3bc4, 0x3c6dbbc4, 0x3bc4bc6d, 0xbbc4bc6d, 0xbc6dbbc4,
    0xbc6d3bc4, 0xbbc43c6d, 0x3bc43c6d, 0x3c6d3bc4, 0x3c6dbbc4, 0x3bc4bc6d, 0xbbc4bc6d, 0xbc6dbbc4, 0xbc6d3bc4, 0xbbc43c6d,
    0x3c753b95, 0x3c46bc22, 0xbac9bc7f, 0xbc62bbf1, 0xbbf1bc62, 0xbc7fbac9, 0xbc223c46, 0x3b953c75, 0x3b95bc75, 0xbc22bc46,
    0xbc7f3ac9, 0xbbf13c62, 0xbc623bf1, 0xbac93c7f, 0x3c463c22, 0x3c75bb95, 0xbc75bb95, 0xbc463c22, 0x3ac93c7f, 0x3c623bf1,
    0x3bf13c62, 0x3c7f3ac9, 0x3c22bc46, 0xbb95bc75, 0xbb953c75, 0x3c223c46, 0x3c7fbac9, 0x3bf1bc62, 0x3c62bbf1, 0x3ac9bc7f,
    0xbc46bc22, 0xbc753b95, 0xbc0ebc55, 0xbc7b3b48, 0xbb483c7b, 0x3c553c0e, 0x3c55bc0e, 0xbb48bc7b, 0xbc7bbb48, 0xbc0e3c55,
    0x3c0e3c55, 0x3c7bbb48, 0x3b48bc7b, 0xbc55bc0e, 0xbc553c0e, 0x3b483c7b, 0x3c7b3b48, 0x3c0ebc55, 0xbc0ebc55, 0xbc7b3b48,
    0xbb483c7b, 0x3c553c0e, 0x3c55bc0e, 0xbb48bc7b, 0xbc7bbb48, 0xbc0e3c55, 0x3c0e3c55, 0x3c7bbb48, 0x3b48bc7b, 0xbc55bc0e,
    0xbc553c0e, 0x3b483c7b, 0x3c7b3b48, 0x3c0ebc55, 0x3c7f3ac9, 0x3b95bc75, 0xbc62bbf1, 0xbc223c46, 0x3c46bc22, 0xbbf1bc62,
    0xbc753b95, 0x3ac93c7f, 0x3ac9bc7f, 0xbc75bb95, 0xbbf13c62, 0x3c463c22, 0xbc22bc46, 0xbc623bf1, 0x3b953c75, 0x3c7fbac9,
    0xbc7fbac9, 0xbb953c75, 0x3c623bf1, 0x3c22bc46, 0xbc463c22, 0x3bf13c62, 0x3c75bb95, 0xbac9bc7f, 0xbac93c7f, 0x3c753b95,
    0x3bf1bc62, 0xbc46bc22, 0x3c223c46, 0x3c62bbf1, 0xbb95bc75, 0xbc7f3ac9, 0x3a493c80, 0x3b163c7d, 0x3b793c78, 0x3bac3c71,
    0x3bdb3c67, 0x3c043c5c, 0x3c183c4e, 0x3c2c3c3e, 0x3c3e3c2c, 0x3c4e3c18, 0x3c5c3c04, 0x3c673bdb, 0x3c713bac, 0x3c783b79,
    0x3c7d3b16, 0x3c803a49, 0x3c80ba49, 0x3c7dbb16, 0x3c78bb79, 0x3c71bbac, 0x3c67bbdb, 0x3c5cbc04, 0x3c4ebc18, 0x3c3ebc2c,
    0x3c2cbc3e, 0x3c18bc4e, 0x3c04bc5c, 0x3bdbbc67, 0x3bacbc71, 0x3b79bc78, 0x3b16bc7d, 0x3a49bc80, 0x3c783b79, 0x3c80ba49,
    0x3c71bbac, 0x3c4ebc18, 0x3b163c7d, 0x3bdb3c67, 0x3c2c3c3e, 0x3c5c3c04, 0xbc04bc5c, 0xbc3ebc2c, 0xbc67bbdb, 0xbc7dbb16,
    0x3c18bc4e, 0x3bacbc71, 0x3a49bc80, 0xbb79bc78, 0xbb793c78, 0x3a493c80, 0x3bac3c71, 0x3c183c4e, 0xbc7d3b16, 0xbc673bdb,
    0xbc3e3c2c, 0xbc043c5c, 0x3c5cbc04, 0x3c2cbc3e, 0x3bdbbc67, 0x3b16bc7d, 0x3c4e3c18, 0x3c713bac, 0x3c803a49, 0x3c78bb79,
    0xbc5cbc04, 0xbc80ba49, 0xbc673bdb, 0xbc183c4e, 0xbb163c7d, 0x3bac3c71, 0x3c3e3c2c, 0x3c783b79, 0x3b793c78, 0x3c2c3c3e,
    0x3c713bac, 0x3c7dbb16, 0x3c4ebc18, 0x3bdbbc67, 0xba49bc80, 0xbc04bc5c, 0xbc043c5c, 0xba493c80, 0x3bdb3c67, 0x3c4e3c18,
    0x3c7d3b16, 0x3c71bbac, 0x3c2cbc3e, 0x3b79bc78, 0x3c78bb79, 0x3c3ebc2c, 0x3bacbc71, 0xbb16bc7d, 0xbc18bc4e, 0xbc67bbdb,
    0xbc803a49, 0xbc5c3c04, 0x3c3ebc2c, 0x3b16bc7d, 0xbc04bc5c, 0xbc71bbac, 0xbbdb3c67, 0x3b793c78, 0x3c4e3c18, 0x3c80ba49,
    0x3a49bc80, 0xbc18bc4e, 0xbc78bb79, 0xbc673bdb, 0x3bac3c71, 0x3c5c3c04, 0x3c7dbb16, 0x3c2cbc3e, 0x3c2c3c3e, 0x3c7d3b16,
    0x3c5cbc04, 0x3bacbc71, 0xbc67bbdb, 0xbc783b79, 0xbc183c4e, 0x3a493c80, 0x3c803a49, 0x3c4ebc18, 0x3b79bc78, 0xbbdbbc67,
    0xbc713bac, 0xbc043c5c, 0x3b163c7d, 0x3c3e3c2c, 0x3c67bbdb, 0x3b79bc78, 0xbc18bc4e, 0xbc80ba49, 0xbc2c3c3e, 0x3b163c7d,
    0x3c5c3c04, 0x3c71bbac, 0x3bacbc71, 0xbc04bc5c, 0xbc7dbb16, 0xbc3e3c2c, 0x3a493c80, 0x3c4e3c18, 0x3c78bb79, 0x3bdbbc67,
    0x3bdb3c67, 0x3c783b79, 0x3c4ebc18, 0x3a49bc80, 0xbc3ebc2c, 0xbc7d3b16, 0xbc043c5c, 0x3bac3c71, 0x3c713bac, 0x3c5cbc04,
    0x3b16bc7d, 0xbc2cbc3e, 0xbc803a49, 0xbc183c4e, 0x3b793c78, 0x3c673bdb, 0xbb16bc7d, 0xbc71bbac, 0xbc3e3c2c, 0x3b793c78,
    0xbc5c3c04, 0x3a493c80, 0x3c673bdb, 0x3c4ebc18, 0xbc183c4e, 0x3bdb3c67, 0x3c803a49, 0x3c04bc5c, 0x3c783b79, 0x3c2cbc3e,
    0xbbacbc71, 0xbc7dbb16, 0xbc7d3b16, 0xbbac3c71, 0x3c2c3c3e, 0x3c78bb79, 0x3c043c5c, 0x3c80ba49, 0x3bdbbc67, 0xbc18bc4e,
    0x3c4e3c18, 0x3c67bbdb, 0x3a49bc80, 0xbc5cbc04, 0x3b79bc78, 0xbc3ebc2c, 0xbc713bac, 0xbb163c7d, 0xbb163c7d, 0x3c673bdb,
    0x3c2cbc3e, 0xbc04bc5c, 0xbc783b79, 0xba493c80, 0x3c713bac, 0x3c18bc4e, 0x3c4ebc18, 0xbbacbc71, 0xbc803a49, 0xbb793c78,
    0x3c5c3c04, 0x3c3ebc2c, 0xbbdbbc67, 0xbc7d3b16, 0xbc7dbb16, 0xbbdb3c67, 0x3c3e3c2c, 0x3c5cbc04, 0xbb79bc78, 0xbc80ba49,
    0xbbac3c71, 0x3c4e3c18, 0x3c183c4e, 0x3c71bbac, 0xba49bc80, 0xbc78bb79, 0xbc043c5c, 0x3c2c3c3e, 0x3c67bbdb, 0xbb16bc7d,
    0xbc67bbdb, 0xbc043c5c, 0x3c4e3c18, 0x3c2cbc3e, 0xbc80ba49, 0xbb163c7d, 0x3c783b79, 0x3bacbc71, 0xbc713bac, 0x3b793c78,
    0x3c7dbb16, 0xba49bc80, 0xbc3e3c2c, 0x3c183c4e, 0x3c5cbc04, 0xbbdbbc67, 0xbbdb3c67, 0x3c5c3c04, 0x3c18bc4e, 0xbc3ebc2c,
    0xba493c80, 0x3c7d3b16, 0x3b79bc78, 0xbc71bbac, 0x3bac3c71, 0x3c78bb79, 0xbb16bc7d, 0xbc803a49, 0x3c2c3c3e, 0x3c4ebc18,
    0xbc04bc5c, 0xbc673bdb, 0x3c353c35, 0x3c35bc35, 0xbc35bc35, 0xbc353c35, 0x3c353c35, 0x3c35bc35, 0xbc35bc35, 0xbc353c35,
    0x3c353c35, 0x3c35bc35, 0xbc35bc35, 0xbc353c35, 0x3c353c35, 0x3c35bc35, 0xbc35bc35, 0xbc353c35, 0x3c353c35, 0x3c35bc35,
    0xbc35bc35, 0xbc353c35, 0x3c353c35, 0x3c35bc35, 0xbc35bc35, 0xbc353c35, 0x3c353c35, 0x3c35bc35, 0xbc35bc35, 0xbc353c35,
    0x3c353c35, 0x3c35bc35, 0xbc35bc35, 0xbc353c35, 0x3c7fbac9, 0xbb95bc75, 0xbc623bf1, 0x3c223c46, 0x3c463c22, 0x3bf1bc62,
    0xbc75bb95, 0xbac93c7f, 0xbac9bc7f, 0xbc753b95, 0x3bf13c62, 0x3c46bc22, 0x3c22bc46, 0xbc62bbf1, 0xbb953c75, 0x3c7f3ac9,
    0xbc7f3ac9, 0x3b953c75, 0x3c62bbf1, 0xbc22bc46, 0xbc46bc22, 0xbbf13c62, 0x3c753b95, 0x3ac9bc7f, 0x3ac93c7f, 0x3c75bb95,
    0xbbf1bc62, 0xbc463c22, 0xbc223c46, 0x3c623bf1, 0x3b95bc75, 0xbc7fbac9, 0xbc55bc0e, 0xbb483c7b, 0x3c7bbb48, 0xbc0ebc55,
    0xbc0e3c55, 0x3c7b3b48, 0xbb48bc7b, 0xbc553c0e, 0x3c553c0e, 0x3b48bc7b, 0xbc7b3b48, 0x3c0e3c55, 0x3c0ebc55, 0xbc7bbb48,
    0x3b483c7b, 0x3c55bc0e, 0xbc55bc0e, 0xbb483c7b, 0x3c7bbb48, 0xbc0ebc55, 0xbc0e3c55, 0x3c7b3b48, 0xbb48bc7b, 0xbc553c0e,
    0x3c553c0e, 0x3b48bc7b, 0xbc7b3b48, 0x3c0e3c55, 0x3c0ebc55, 0xbc7bbb48, 0x3b483c7b, 0x3c55bc0e, 0x3c75bb95, 0xbc46bc22,
    0xbac93c7f, 0x3c62bbf1, 0xbbf13c62, 0x3c7fbac9, 0xbc22bc46, 0xbb953c75, 0xbb95bc75, 0xbc223c46, 0x3c7f3ac9, 0xbbf1bc62,
    0x3c623bf1, 0xbac9bc7f, 0xbc463c22, 0x3c753b95, 0xbc753b95, 0x3c463c22, 0x3ac9bc7f, 0xbc623bf1, 0x3bf1bc62, 0xbc7f3ac9,
    0x3c223c46, 0x3b95bc75, 0x3b953c75, 0x3c22bc46, 0xbc7fbac9, 0x3bf13c62, 0xbc62bbf1, 0x3ac93c7f, 0x3c46bc22, 0xbc75bb95,
    0x3c6d3bc4, 0xbbc4bc6d, 0xbbc43c6d, 0x3c6dbbc4, 0xbc6dbbc4, 0x3bc43c6d, 0x3bc4bc6d, 0xbc6d3bc4, 0x3c6d3bc4, 0xbbc4bc6d,
    0xbbc43c6d, 0x3c6dbbc4, 0xbc6dbbc4, 0x3bc43c6d, 0x3bc4bc6d, 0xbc6d3bc4, 0x3c6d3bc4, 0xbbc4bc6d, 0xbbc43c6d, 0x3c6dbbc4,
    0xbc6dbbc4, 0x3bc43c6d, 0x3bc4bc6d, 0xbc6d3bc4, 0x3c6d3bc4, 0xbbc4bc6d, 0xbbc43c6d, 0x3c6dbbc4, 0xbc6dbbc4, 0x3bc43c6d,
    0x3bc4bc6d, 0xbc6d3bc4, 0x3c62bbf1, 0xbc7fbac9, 0x3c463c22, 0xbb95bc75, 0xbc75bb95, 0x3c223c46, 0xbac9bc7f, 0xbbf13c62,
    0xbbf1bc62, 0xbac93c7f, 0x3c22bc46, 0xbc753b95, 0xbb953c75, 0x3c46bc22, 0xbc7f3ac9, 0x3c623bf1, 0xbc623bf1, 0x3c7f3ac9,
    0xbc46bc22, 0x3b953c75, 0x3c753b95, 0xbc22bc46, 0x3ac93c7f, 0x3bf1bc62, 0x3bf13c62, 0x3ac9bc7f, 0xbc223c46, 0x3c75bb95,
    0x3b95bc75, 0xbc463c22, 0x3c7fbac9, 0xbc62bbf1, 0xbc7bbb48, 0x3c553c0e, 0xbc0ebc55, 0x3b483c7b, 0x3b48bc7b, 0xbc0e3c55,
    0x3c55bc0e, 0xbc7b3b48, 0x3c7b3b48, 0xbc55bc0e, 0x3c0e3c55, 0xbb48bc7b, 0xbb483c7b, 0x3c0ebc55, 0xbc553c0e, 0x3c7bbb48,
    0xbc7bbb48, 0x3c553c0e, 0xbc0ebc55, 0x3b483c7b, 0x3b48bc7b, 0xbc0e3c55, 0x3c55bc0e, 0xbc7b3b48, 0x3c7b3b48, 0xbc55bc0e,
    0x3c0e3c55, 0xbb48bc7b, 0xbb483c7b, 0x3c0ebc55, 0xbc553c0e, 0x3c7bbb48, 0x3c46bc22, 0xbc623bf1, 0x3c75bb95, 0xbc7f3ac9,
    0x3ac9bc7f, 0xbb953c75, 0x3bf1bc62, 0xbc223c46, 0xbc22bc46, 0x3bf13c62, 0xbb95bc75, 0x3ac93c7f, 0xbc7fbac9, 0x3c753b95,
    0xbc62bbf1, 0x3c463c22, 0xbc463c22, 0x3c62bbf1, 0xbc753b95, 0x3c7fbac9, 0xbac93c7f, 0x3b95bc75, 0xbbf13c62, 0x3c22bc46,
    0x3c223c46, 0xbbf1bc62, 0x3b953c75, 0xbac9bc7f, 0x3c7f3ac9, 0xbc75bb95, 0x3c623bf1, 0xbc46bc22, 0x3c3e3c2c, 0x3c18bc4e,
    0xbc5cbc04, 0xbbdb3c67, 0x3c713bac, 0x3b79bc78, 0xbc7dbb16, 0xba493c80, 0x3c80ba49, 0xbb16bc7d, 0xbc783b79, 0x3bac3c71,
    0x3c67bbdb, 0xbc04bc5c, 0xbc4e3c18, 0x3c2c3c3e, 0x3c2cbc3e, 0xbc4ebc18, 0xbc043c5c, 0x3c673bdb, 0x3bacbc71, 0xbc78bb79,
    0xbb163c7d, 0x3c803a49, 0xba49bc80, 0xbc7d3b16, 0x3b793c78, 0x3c71bbac, 0xbbdbbc67, 0xbc5c3c04, 0x3c183c4e, 0x3c3ebc2c,
    0x3c5cbc04, 0xbc3ebc2c, 0xbbdb3c67, 0x3c7d3b16, 0x3c4e3c18, 0x3bacbc71, 0xbc80ba49, 0x3b793c78, 0xbc78bb79, 0x3a493c80,
    0x3c71bbac, 0xbc18bc4e, 0xbb16bc7d, 0xbc673bdb, 0x3c2c3c3e, 0x3c04bc5c, 0x3c043c5c, 0x3c2cbc3e, 0xbc67bbdb, 0xbb163c7d,
    0xbc183c4e, 0x3c713bac, 0x3a49bc80, 0xbc783b79, 0x3b79bc78, 0xbc803a49, 0x3bac3c71, 0x3c4ebc18, 0x3c7dbb16, 0xbbdbbc67,
    0xbc3e3c2c, 0x3c5c3c04, 0xbc783b79, 0x3c2c3c3e, 0x3bacbc71, 0xbc7d3b16, 0x3c183c4e, 0x3bdbbc67, 0xbc803a49, 0x3c043c5c,
    0x3c5c3c04, 0x3a49bc80, 0xbc673bdb, 0x3c4e3c18, 0x3b16bc7d, 0xbc713bac, 0x3c3e3c2c, 0x3b79bc78, 0x3b793c78, 0x3c3ebc2c,
    0xbc71bbac, 0x3b163c7d, 0x3c4ebc18, 0xbc67bbdb, 0x3a493c80, 0x3c5cbc04, 0x3c04bc5c, 0xbc80ba49, 0x3bdb3c67, 0x3c18bc4e,
    0xbc7dbb16, 0x3bac3c71, 0x3c2cbc3e, 0xbc78bb79, 0x3a49bc80, 0xbc4e3c18, 0x3c783b79, 0xbbdbbc67, 0x3bac3c71, 0x3c04bc5c,
    0xbc7d3b16, 0x3c3e3c2c, 0xbc2cbc3e, 0xbb163c7d, 0x3c5cbc04, 0xbc71bbac, 0x3c673bdb, 0xbb79bc78, 0xbc183c4e, 0x3c80ba49,
    0x3c803a49, 0xbc18bc4e, 0xbb793c78, 0x3c67bbdb, 0xbc713bac, 0x3c5c3c04, 0xbb16bc7d, 0xbc2c3c3e, 0x3c3ebc2c, 0xbc7dbb16,
    0x3c043c5c, 0x3bacbc71, 0xbbdb3c67, 0x3c78bb79, 0xbc4ebc18, 0x3a493c80, 0x3bacbc71, 0xbc5c3c04, 0x3c7d3b16, 0xbc2cbc3e,
    0x3a493c80, 0x3c18bc4e, 0xbc783b79, 0x3c673bdb, 0xbbdbbc67, 0xbb793c78, 0x3c4ebc18, 0xbc80ba49, 0x3c3e3c2c, 0xbb16bc7d,
    0xbc043c5c, 0x3c71bbac, 0x3c713bac, 0xbc04bc5c, 0xbb163c7d, 0x3c3ebc2c, 0xbc803a49, 0x3c4e3c18, 0xbb79bc78, 0xbbdb3c67,
    0x3c67bbdb, 0xbc78bb79, 0x3c183c4e, 0x3a49bc80, 0xbc2c3c3e, 0x3c7dbb16, 0xbc5cbc04, 0x3bac3c71, 0xbc4ebc18, 0x3bdb3c67,
    0x3a49bc80, 0xbc043c5c, 0xbb793c78, 0x3c2cbc3e, 0xbc713bac, 0x3c7d3b16, 0x3b163c7d, 0x3bacbc71, 0xbc3e3c2c, 0x3c78bb79,
    0x3c5cbc04, 0xbc803a49, 0x3c673bdb, 0xbc18bc4e, 0xbc183c4e, 0x3c67bbdb, 0xbc80ba49, 0x3c5c3c04, 0x3c783b79, 0xbc3ebc2c,
    0x3bac3c71, 0x3b16bc7d, 0x3c7dbb16, 0xbc71bbac, 0x3c2c3c3e, 0xbb79bc78, 0xbc04bc5c, 0x3a493c80, 0x3bdbbc67, 0xbc4e3c18,
    0x3c183c4e, 0xbbacbc71, 0x3a493c80, 0x3b79bc78, 0xbc043c5c, 0x3c3ebc2c, 0xbc673bdb, 0x3c7dbb16, 0x3b16bc7d, 0xbbdb3c67,
    0x3c2cbc3e, 0xbc5c3c04, 0x3c78bb79, 0xbc80ba49, 0x3c713bac, 0xbc4ebc18, 0xbc4e3c18, 0x3c71bbac, 0xbc803a49, 0x3c783b79,
    0xbc5cbc04, 0x3c2c3c3e, 0xbbdbbc67, 0x3b163c7d, 0x3c7d3b16, 0xbc67bbdb, 0x3c3e3c2c, 0xbc04bc5c, 0x3b793c78, 0x3a49bc80,
    0xbbac3c71, 0x3c18bc4e, 0xbc713bac, 0x3c78bb79, 0xbc7d3b16, 0x3c80ba49, 0xbc3e3c2c, 0x3c4ebc18, 0xbc5c3c04, 0x3c67bbdb,
    0xbbdb3c67, 0x3c04bc5c, 0xbc183c4e, 0x3c2cbc3e, 0xba493c80, 0x3b16bc7d, 0xbb793c78, 0x3bacbc71, 0x3bac3c71, 0xbb79bc78,
    0x3b163c7d, 0xba49bc80, 0x3c2c3c3e, 0xbc18bc4e, 0x3c043c5c, 0xbbdbbc67, 0x3c673bdb, 0xbc5cbc04, 0x3c4e3c18, 0xbc3ebc2c,
    0x3c803a49, 0xbc7dbb16, 0x3c783b79, 0xbc71bbac, 0x3c800000, 0xbc800000, 0x3c800000, 0xbc800000, 0x3c800000, 0xbc800000,
    0x3c800000, 0xbc800000, 0x3c800000, 0xbc800000, 0x3c800000, 0xbc800000, 0x3c800000, 0xbc800000, 0x3c800000, 0xbc800000,
    0x3c800000, 0xbc800000, 0x3c800000, 0xbc800000, 0x3c800000, 0xbc800000, 0x3c800000, 0xbc800000, 0x3c800000, 0xbc800000,
    0x3c800000, 0xbc800000, 0x3c800000, 0xbc800000, 0x3c800000, 0xbc800000, 0x3c22bc46, 0xbbf13c62, 0x3b95bc75, 0xbac93c7f,
    0x3c7fbac9, 0xbc753b95, 0x3c62bbf1, 0xbc463c22, 0xbc46bc22, 0x3c623bf1, 0xbc75bb95, 0x3c7f3ac9, 0xbac9bc7f, 0x3b953c75,
    0xbbf1bc62, 0x3c223c46, 0xbc223c46, 0x3bf1bc62, 0xbb953c75, 0x3ac9bc7f, 0xbc7f3ac9, 0x3c75bb95, 0xbc623bf1, 0x3c46bc22,
    0x3c463c22, 0xbc62bbf1, 0x3c753b95, 0xbc7fbac9, 0x3ac93c7f, 0xbb95bc75, 0x3bf13c62, 0xbc22bc46, 0xbc7b3b48, 0x3c55bc0e,
    0xbc0e3c55, 0x3b48bc7b, 0x3b483c7b, 0xbc0ebc55, 0x3c553c0e, 0xbc7bbb48, 0x3c7bbb48, 0xbc553c0e, 0x3c0ebc55, 0xbb483c7b,
    0xbb48bc7b, 0x3c0e3c55, 0xbc55bc0e, 0x3c7b3b48, 0xbc7b3b48, 0x3c55bc0e, 0xbc0e3c55, 0x3b48bc7b, 0x3b483c7b, 0xbc0ebc55,
    0x3c553c0e, 0xbc7bbb48, 0x3c7bbb48, 0xbc553c0e, 0x3c0ebc55, 0xbb483c7b, 0xbb48bc7b, 0x3c0e3c55, 0xbc55bc0e, 0x3c7b3b48,
    0x3bf1bc62, 0x3ac93c7f, 0xbc22bc46, 0x3c753b95, 0x3b953c75, 0xbc46bc22, 0x3c7f3ac9, 0xbc623bf1, 0xbc62bbf1, 0x3c7fbac9,
    0xbc463c22, 0x3b95bc75, 0x3c75bb95, 0xbc223c46, 0x3ac9bc7f, 0x3bf13c62, 0xbbf13c62, 0xbac9bc7f, 0x3c223c46, 0xbc75bb95,
    0xbb95bc75, 0x3c463c22, 0xbc7fbac9, 0x3c62bbf1, 0x3c623bf1, 0xbc7f3ac9, 0x3c46bc22, 0xbb953c75, 0xbc753b95, 0x3c22bc46,
    0xbac93c7f, 0xbbf1bc62, 0x3c6dbbc4, 0xbbc43c6d, 0xbbc4bc6d, 0x3c6d3bc4, 0xbc6d3bc4, 0x3bc4bc6d, 0x3bc43c6d, 0xbc6dbbc4,
    0x3c6dbbc4, 0xbbc43c6d, 0xbbc4bc6d, 0x3c6d3bc4, 0xbc6d3bc4, 0x3bc4bc6d, 0x3bc43c6d, 0xbc6dbbc4, 0x3c6dbbc4, 0xbbc43c6d,
    0xbbc4bc6d, 0x3c6d3bc4, 0xbc6d3bc4, 0x3bc4bc6d, 0x3bc43c6d, 0xbc6dbbc4, 0x3c6dbbc4, 0xbbc43c6d, 0xbbc4bc6d, 0x3c6d3bc4,
    0xbc6d3bc4, 0x3bc4bc6d, 0x3bc43c6d, 0xbc6dbbc4, 0x3b95bc75, 0x3c223c46, 0xbc7f3ac9, 0x3bf1bc62, 0xbc623bf1, 0x3ac9bc7f,
    0x3c463c22, 0xbc753b95, 0xbc75bb95, 0x3c46bc22, 0x3ac93c7f, 0xbc62bbf1, 0x3bf13c62, 0xbc7fbac9, 0x3c22bc46, 0x3b953c75,
    0xbb953c75, 0xbc22bc46, 0x3c7fbac9, 0xbbf13c62, 0x3c62bbf1, 0xbac93c7f, 0xbc46bc22, 0x3c75bb95, 0x3c753b95, 0xbc463c22,
    0xbac9bc7f, 0x3c623bf1, 0xbbf1bc62, 0x3c7f3ac9, 0xbc223c46, 0xbb95bc75, 0xbc553c0e, 0xbb48bc7b, 0x3c7b3b48, 0xbc0e3c55,
    0xbc0ebc55, 0x3c7bbb48, 0xbb483c7b, 0xbc55bc0e, 0x3c55bc0e, 0x3b483c7b, 0xbc7bbb48, 0x3c0ebc55, 0x3c0e3c55, 0xbc7b3b48,
    0x3b48bc7b, 0x3c553c0e, 0xbc553c0e, 0xbb48bc7b, 0x3c7b3b48, 0xbc0e3c55, 0xbc0ebc55, 0x3c7bbb48, 0xbb483c7b, 0xbc55bc0e,
    0x3c55bc0e, 0x3b483c7b, 0xbc7bbb48, 0x3c0ebc55, 0x3c0e3c55, 0xbc7b3b48, 0x3b48bc7b, 0x3c553c0e, 0x3ac9bc7f, 0x3c753b95,
    0xbbf13c62, 0xbc46bc22, 0xbc22bc46, 0x3c62bbf1, 0x3b953c75, 0xbc7f3ac9, 0xbc7fbac9, 0x3b95bc75, 0x3c623bf1, 0xbc223c46,
    0xbc463c22, 0xbbf1bc62, 0x3c75bb95, 0x3ac93c7f, 0xbac93c7f, 0xbc75bb95, 0x3bf1bc62, 0x3c463c22, 0x3c223c46, 0xbc623bf1,
    0xbb95bc75, 0x3c7fbac9, 0x3c7f3ac9, 0xbb953c75, 0xbc62bbf1, 0x3c22bc46, 0x3c46bc22, 0x3bf13c62, 0xbc753b95, 0xbac9bc7f,
    0x3c80ba49, 0xbc7d3b16, 0x3c78bb79, 0xbc713bac, 0x3c67bbdb, 0xbc5c3c04, 0x3c4ebc18, 0xbc3e3c2c, 0x3c2cbc3e, 0xbc183c4e,
    0x3c04bc5c, 0xbbdb3c67, 0x3bacbc71, 0xbb793c78, 0x3b16bc7d, 0xba493c80, 0xba49bc80, 0x3b163c7d, 0xbb79bc78, 0x3bac3c71,
    0xbbdbbc67, 0x3c043c5c, 0xbc18bc4e, 0x3c2c3c3e, 0xbc3ebc2c, 0x3c4e3c18, 0xbc5cbc04, 0x3c673bdb, 0xbc71bbac, 0x3c783b79,
    0xbc7dbb16, 0x3c803a49, 0x3b79bc78, 0x3a493c80, 0xbbacbc71, 0x3c183c4e, 0x3c7dbb16, 0xbc673bdb, 0x3c3ebc2c, 0xbc043c5c,
    0xbc5c3c04, 0x3c2cbc3e, 0xbbdb3c67, 0x3b16bc7d, 0xbc4ebc18, 0x3c713bac, 0xbc80ba49, 0x3c78bb79, 0x3c783b79, 0xbc803a49,
    0x3c71bbac, 0xbc4e3c18, 0x3b163c7d, 0xbbdbbc67, 0x3c2c3c3e, 0xbc5cbc04, 0xbc04bc5c, 0x3c3e3c2c, 0xbc67bbdb, 0x3c7d3b16,
    0x3c18bc4e, 0xbbac3c71, 0x3a49bc80, 0x3b793c78, 0xbc043c5c, 0x3a49bc80, 0x3bdb3c67, 0xbc4ebc18, 0x3c7d3b16, 0xbc713bac,
    0x3c2cbc3e, 0xbb793c78, 0x3c78bb79, 0xbc3e3c2c, 0x3bacbc71, 0x3b163c7d, 0xbc18bc4e, 0x3c673bdb, 0xbc803a49, 0x3c5cbc04,
    0x3c5c3c04, 0xbc80ba49, 0x3c67bbdb, 0xbc183c4e, 0x3b16bc7d, 0x3bac3c71, 0xbc3ebc2c, 0x3c783b79, 0xbb79bc78, 0x3c2c3c3e,
    0xbc71bbac, 0x3c7dbb16, 0xbc4e3c18, 0x3bdbbc67, 0x3a493c80, 0xbc04bc5c, 0xbc2cbc3e, 0x3c7d3b16, 0xbc5c3c04, 0x3bacbc71,
    0x3c673bdb, 0xbc783b79, 0x3c18bc4e, 0x3a493c80, 0xbc80ba49, 0x3c4ebc18, 0xbb793c78, 0xbbdbbc67, 0x3c71bbac, 0xbc043c5c,
    0xbb16bc7d, 0x3c3e3c2c, 0x3c3ebc2c, 0xbb163c7d, 0xbc04bc5c, 0x3c713bac, 0xbbdb3c67, 0xbb79bc78, 0x3c4e3c18, 0xbc803a49,
    0x3a49bc80, 0x3c183c4e, 0xbc78bb79, 0x3c67bbdb, 0x3bac3c71, 0xbc5cbc04, 0x3c7dbb16, 0xbc2c3c3e, 0xbbdbbc67, 0x3c783b79,
    0xbc4e3c18, 0x3a49bc80, 0x3c3e3c2c, 0xbc7d3b16, 0x3c04bc5c, 0x3bac3c71, 0xbc71bbac, 0x3c5cbc04, 0xbb163c7d, 0xbc2cbc3e,
    0x3c80ba49, 0xbc183c4e, 0xbb79bc78, 0x3c673bdb, 0x3c67bbdb, 0xbb793c78, 0xbc18bc4e, 0x3c803a49, 0xbc2c3c3e, 0xbb16bc7d,
    0x3c5c3c04, 0xbc713bac, 0x3bacbc71, 0x3c043c5c, 0xbc7dbb16, 0x3c3ebc2c, 0x3a493c80, 0xbc4ebc18, 0x3c78bb79, 0xbbdb3c67,
    0xbc7d3b16, 0x3bacbc71, 0x3c2c3c3e, 0xbc783b79, 0x3c043c5c, 0xbc803a49, 0x3bdbbc67, 0x3c183c4e, 0x3c4e3c18, 0xbc673bdb,
    0x3a49bc80, 0x3c5c3c04, 0x3b79bc78, 0x3c3e3c2c, 0xbc713bac, 0x3b16bc7d, 0x3b163c7d, 0xbc71bbac, 0x3c3ebc2c, 0x3b793c78,
    0x3c5cbc04, 0x3a493c80, 0xbc67bbdb, 0x3c4ebc18, 0x3c18bc4e, 0x3bdb3c67, 0xbc80ba49, 0x3c04bc5c, 0xbc78bb79, 0x3c2cbc3e,
    0x3bac3c71, 0xbc7dbb16, 0x3c7d3b16, 0xbbdb3c67, 0xbc3ebc2c, 0x3c5cbc04, 0x3b793c78, 0xbc80ba49, 0x3bacbc71, 0x3c4e3c18,
    0xbc18bc4e, 0x3c71bbac, 0x3a493c80, 0xbc78bb79, 0x3c04bc5c, 0x3c2c3c3e, 0xbc673bdb, 0xbb16bc7d, 0xbb163c7d, 0xbc67bbdb,
    0x3c2cbc3e, 0x3c043c5c, 0xbc783b79, 0x3a49bc80, 0x3c713bac, 0xbc183c4e, 0x3c4ebc18, 0x3bac3c71, 0xbc803a49, 0x3b79bc78,
    0x3c5c3c04, 0xbc3e3c2c, 0xbbdbbc67, 0x3c7dbb16, 0xbbdb3c67, 0xbc5cbc04, 0x3c18bc4e, 0x3c3e3c2c, 0xba493c80, 0xbc7dbb16,
    0x3b79bc78, 0x3c713bac, 0x3bac3c71, 0xbc783b79, 0xbb16bc7d, 0x3c80ba49, 0x3c2c3c3e, 0xbc4e3c18, 0xbc04bc5c, 0x3c67bbdb,
    0x3c673bdb, 0xbc043c5c, 0xbc4ebc18, 0x3c2cbc3e, 0x3c803a49, 0xbb163c7d, 0xbc78bb79, 0x3bacbc71, 0x3c71bbac, 0x3b793c78,
    0xbc7d3b16, 0xba49bc80, 0x3c3ebc2c, 0x3c183c4e, 0xbc5c3c04, 0xbbdbbc67, 0x3f803f80, 0x3f7d3f7f, 0x3f783f7b, 0x3f713f75,
    0x3f673f6d, 0x3f5c3f62, 0x3f4e3f55, 0x3f3e3f46, 0x3f2c3f35, 0x3f183f22, 0x3f043f0e, 0x3edb3ef1, 0x3eac3ec4, 0x3e793e95,
    0x3e163e48, 0x3d493dc9, 0xbd490000, 0xbe16bdc9, 0xbe79be48, 0xbeacbe95, 0xbedbbec4, 0xbf04bef1, 0xbf18bf0e, 0xbf2cbf22,
    0xbf3ebf35, 0xbf4ebf46, 0xbf5cbf55, 0xbf67bf62, 0xbf71bf6d, 0xbf78bf75, 0xbf7dbf7b, 0xbf80bf7f, 0x3edb3ec4, 0x3f043ef1,
    0x3f183f0e, 0x3f2c3f22, 0x3d490000, 0x3e163dc9, 0x3e793e48, 0x3eac3e95, 0x3f713f6d, 0x3f783f75, 0x3f7d3f7b, 0x3f803f7f,
    0x3f3e3f35, 0x3f4e3f46, 0x3f5c3f55, 0x3f673f62, 0x3f673f6d, 0x3f5c3f62, 0x3f4e3f55, 0x3f3e3f46, 0x3f803f80, 0x3f7d3f7f,
    0x3f783f7b, 0x3f713f75, 0x3eac3ec4, 0x3e793e95, 0x3e163e48, 0x3d493dc9, 0x3f2c3f35, 0x3f183f22, 0x3f043f0e, 0x3edb3ef1,
    0xbf4ebf35, 0xbf71bf62, 0xbf80bf7b, 0xbf78bf7f, 0xbf5cbf6d, 0xbf2cbf46, 0xbedbbf0e, 0xbe16be95, 0x3f7d3f80, 0x3f673f75,
    0x3f3e3f55, 0x3f043f22, 0x3e793ec4, 0xbd493dc9, 0xbeacbe48, 0xbf18bef1, 0x3f183f35, 0x3eac3ef1, 0x3d493e48, 0xbe79bdc9,
    0xbf04bec4, 0xbf3ebf22, 0xbf67bf55, 0xbf7dbf75, 0x3e160000, 0x3edb3e95, 0x3f2c3f0e, 0x3f5c3f46, 0x3f783f6d, 0x3f803f7f,
    0x3f713f7b, 0x3f4e3f62, 0xbf04bec4, 0xbf3ebf22, 0xbf67bf55, 0xbf7dbf75, 0x3f183f35, 0x3eac3ef1, 0x3d493e48, 0xbe79bdc9,
    0x3f783f6d, 0x3f803f7f, 0x3f713f7b, 0x3f4e3f62, 0x3e160000, 0x3edb3e95, 0x3f2c3f0e, 0x3f5c3f46, 0x3f5c3f6d, 0x3f2c3f46,
    0x3edb3f0e, 0x3e163e95, 0x3f4e3f35, 0x3f713f62, 0x3f803f7b, 0x3f783f7f, 0xbe79bec4, 0x3d49bdc9, 0x3eac3e48, 0x3f183ef1,
    0xbf7dbf80, 0xbf67bf75, 0xbf3ebf55, 0xbf04bf22, 0xbe790000, 0xbf2cbef1, 0xbf71bf55, 0xbf7dbf7f, 0xbf4ebf6d, 0xbedbbf22,
    0x3d49be48, 0x3f043e95, 0x3f5c3f35, 0x3f803f75, 0x3f673f7b, 0x3f183f46, 0x3e163ec4, 0xbeacbdc9, 0xbf3ebf0e, 0xbf78bf62,
    0x3f783f80, 0x3f3e3f62, 0x3eac3f0e, 0xbe163dc9, 0xbf18bec4, 0xbf67bf46, 0xbf80bf7b, 0xbf5cbf75, 0xbf04bf35, 0xbd49be95,
    0x3edb3e48, 0x3f4e3f22, 0x3f7d3f6d, 0x3f713f7f, 0x3f2c3f55, 0x3e793ef1, 0xbf18bec4, 0xbf67bf46, 0xbf80bf7b, 0xbf5cbf75,
    0x3f783f80, 0x3f3e3f62, 0x3eac3f0e, 0xbe163dc9, 0x3f7d3f6d, 0x3f713f7f, 0x3f2c3f55, 0x3e793ef1, 0xbf04bf35, 0xbd49be95,
    0x3edb3e48, 0x3f4e3f22, 0x3f4e3f6d, 0x3edb3f22, 0xbd493e48, 0xbf04be95, 0x3e790000, 0x3f2c3ef1, 0x3f713f55, 0x3f7d3f7f,
    0xbe16bec4, 0x3eac3dc9, 0x3f3e3f0e, 0x3f783f62, 0xbf5cbf35, 0xbf80bf75, 0xbf67bf7b, 0xbf18bf46, 0xbedbbf35, 0x3e79bdc9,
    0x3f4e3f0e, 0x3f803f75, 0x3f3e3f6d, 0x3e163ef1, 0xbf04be48, 0xbf71bf46, 0x3eac0000, 0x3f5c3f22, 0x3f7d3f7b, 0x3f2c3f62,
    0x3d493ec4, 0xbf18be95, 0xbf78bf55, 0xbf67bf7f, 0x3f673f35, 0x3f783f7f, 0x3f183f55, 0xbd493e95, 0xbf2cbec4, 0xbf7dbf62,
    0xbf5cbf7b, 0xbeacbf22, 0x3f713f80, 0x3f043f46, 0xbe163e48, 0xbf3ebef1, 0xbf80bf6d, 0xbf4ebf75, 0xbe79bf0e, 0x3edb3dc9,
    0x3f2c3ec4, 0x3f7d3f62, 0x3f5c3f7b, 0x3eac3f22, 0xbf67bf35, 0xbf78bf7f, 0xbf18bf55, 0x3d49be95, 0x3f803f6d, 0x3f4e3f75,
    0x3e793f0e, 0xbedbbdc9, 0xbf71bf80, 0xbf04bf46, 0x3e16be48, 0x3f3e3ef1, 0x3f3e3f6d, 0x3e163ef1, 0xbf04be48, 0xbf71bf46,
    0xbedbbf35, 0x3e79bdc9, 0x3f4e3f0e, 0x3f803f75, 0x3d493ec4, 0xbf18be95, 0xbf78bf55, 0xbf67bf7f, 0x3eac0000, 0x3f5c3f22,
    0x3f7d3f7b, 0x3f2c3f62, 0x3f673f80, 0x3e793f22, 0xbf18be48, 0xbf80bf62, 0xbf2cbf6d, 0x3e16be95, 0x3f5c3f0e, 0x3f713f7f,
    0x3eac3f35, 0xbf04bdc9, 0xbf7dbf55, 0xbf3ebf75, 0x3d49bec4, 0x3f4e3ef1, 0x3f783f7b, 0x3edb3f46, 0xbedb0000, 0xbf78bf46,
    0xbf4ebf7b, 0xbd49bef1, 0x3f3e3ec4, 0x3f7d3f75, 0x3f043f55, 0xbeac3dc9, 0xbf71bf35, 0xbf5cbf7f, 0xbe16bf0e, 0x3f2c3e95,
    0x3f803f6d, 0x3f183f62, 0xbe793e48, 0xbf67bf22, 0xbf3ebec4, 0xbf7dbf75, 0xbf04bf55, 0x3eacbdc9, 0x3edb0000, 0x3f783f46,
    0x3f4e3f7b, 0x3d493ef1, 0xbf80bf6d, 0xbf18bf62, 0x3e79be48, 0x3f673f22, 0x3f713f35, 0x3f5c3f7f, 0x3e163f0e, 0xbf2cbe95,
    0xbf2cbf6d, 0x3e16be95, 0x3f5c3f0e, 0x3f713f7f, 0x3f673f80, 0x3e793f22, 0xbf18be48, 0xbf80bf62, 0x3d49bec4, 0x3f4e3ef1,
    0x3f783f7b, 0x3edb3f46, 0x3eac3f35, 0xbf04bdc9, 0xbf7dbf55, 0xbf3ebf75, 0xbf78bf35, 0xbf2cbf75, 0x3eacbe48, 0x3f7d3f46,
    0x3f183f6d, 0xbedb3dc9, 0xbf80bf55, 0xbf04bf62, 0x3f5c3f80, 0xbd493ef1, 0xbf67bf0e, 0xbf4ebf7f, 0x3e16bec4, 0x3f713f22,
    0x3f3e3f7b, 0xbe793e95, 0x3e793f35, 0xbf3ebe95, 0xbf71bf7b, 0xbe16bf22, 0x3f4e3ec4, 0x3f673f7f, 0x3d493f0e, 0xbf5cbef1,
    0x3f040000, 0x3f803f62, 0x3edb3f55, 0xbf18bdc9, 0xbf7dbf6d, 0xbeacbf46, 0x3f2c3e48, 0x3f783f75, 0x3f4e3ec4, 0x3f673f7f,
    0x3d493f0e, 0xbf5cbef1, 0x3e793f35, 0xbf3ebe95, 0xbf71bf7b, 0xbe16bf22, 0xbf7dbf6d, 0xbeacbf46, 0x3f2c3e48, 0x3f783f75,
    0x3f040000, 0x3f803f62, 0x3edb3f55, 0xbf18bdc9, 0xbf18bf6d, 0x3edbbdc9, 0x3f803f55, 0x3f043f62, 0x3f783f35, 0x3f2c3f75,
    0xbeac3e48, 0xbf7dbf46, 0xbe163ec4, 0xbf71bf22, 0xbf3ebf7b, 0x3e79be95, 0xbf5cbf80, 0x3d49bef1, 0x3f673f0e, 0x3f4e3f7f,
    0xbf180000, 0xbf71bf75, 0x3d49bf0e, 0x3f783f22, 0x3f043f6d, 0xbf2cbdc9, 0xbf67bf7b, 0x3e16bef1, 0x3f7d3f35, 0x3edb3f62,
    0xbf3ebe48, 0xbf5cbf7f, 0x3e79bec4, 0x3f803f46, 0x3eac3f55, 0xbf4ebe95, 0x3f4e3f80, 0xbeac3e95, 0xbf80bf55, 0xbe79bf46,
    0x3f5c3ec4, 0x3f3e3f7f, 0xbedb3e48, 0xbf7dbf62, 0xbe16bf35, 0x3f673ef1, 0x3f2c3f7b, 0xbf043dc9, 0xbf78bf6d, 0xbd49bf22,
    0x3f713f0e, 0x3f183f75, 0x3f5c3ec4, 0x3f3e3f7f, 0xbedb3e48, 0xbf7dbf62, 0x3f4e3f80, 0xbeac3e95, 0xbf80bf55, 0xbe79bf46,
    0xbf78bf6d, 0xbd49bf22, 0x3f713f0e, 0x3f183f75, 0xbe16bf35, 0x3f673ef1, 0x3f2c3f7b, 0xbf043dc9, 0xbf04bf6d, 0x3f2c3dc9,
    0x3f673f7b, 0xbe163ef1, 0x3f180000, 0x3f713f75, 0xbd493f0e, 0xbf78bf22, 0xbe793ec4, 0xbf80bf46, 0xbeacbf55, 0x3f4e3e95,
    0xbf7dbf35, 0xbedbbf62, 0x3f3e3e48, 0x3f5c3f7f, 0xbd49bf35, 0x3f7d3f22, 0x3e793f55, 0xbf71bef1, 0xbedbbf6d, 0x3f5c3e95,
    0x3f183f7b, 0xbf3ebdc9, 0x3f2c0000, 0x3f4e3f7f, 0xbf043e48, 0xbf67bf75, 0x3eacbec4, 0x3f783f62, 0xbe163f0e, 0xbf80bf46,
    0x3f803f35, 0x3e163f46, 0xbf78bf0e, 0xbeacbf62, 0x3f673ec4, 0x3f043f75, 0xbf4ebe48, 0xbf2cbf7f, 0x3f3e3f80, 0xbf183dc9,
    0xbf5cbf7b, 0x3edbbe95, 0x3f713f6d, 0xbe793ef1, 0xbf7dbf55, 0x3d49bf22, 0xbf67bec4, 0xbf04bf75, 0x3f4e3e48, 0x3f2c3f7f,
    0xbf80bf35, 0xbe16bf46, 0x3f783f0e, 0x3eac3f62, 0xbf71bf6d, 0x3e79bef1, 0x3f7d3f55, 0xbd493f22, 0xbf3ebf80, 0x3f18bdc9,
    0x3f5c3f7b, 0xbedb3e95, 0xbedbbf6d, 0x3f5c3e95, 0x3f183f7b, 0xbf3ebdc9, 0xbd49bf35, 0x3f7d3f22, 0x3e793f55, 0xbf71bef1,
    0x3eacbec4, 0x3f783f62, 0xbe163f0e, 0xbf80bf46, 0x3f2c0000, 0x3f4e3f7f, 0xbf043e48, 0xbf67bf75, 0x3f2c3f80, 0xbf4ebdc9,
    0xbf04bf7b, 0x3f673e95, 0x3eac3f6d, 0xbf78bef1, 0xbe16bf55, 0x3f803f22, 0xbd493f35, 0xbf7dbf46, 0x3e79bf0e, 0x3f713f62,
    0xbedb3ec4, 0xbf5cbf75, 0x3f18be48, 0x3f3e3f7f, 0xbf3e0000, 0xbf18bf7f, 0x3f5c3e48, 0x3edb3f75, 0xbf71bec4, 0xbe79bf62,
    0x3f7d3f0e, 0x3d493f46, 0xbf80bf35, 0x3e16bf22, 0x3f783f55, 0xbeac3ef1, 0xbf67bf6d, 0x3f04be95, 0x3f4e3f7b, 0xbf2c3dc9,
    0x3f713ec4, 0x3e793f62, 0xbf7dbf0e, 0xbd49bf46, 0x3f3e0000, 0x3f183f7f, 0xbf5cbe48, 0xbedbbf75, 0x3f673f6d, 0xbf043e95,
    0xbf4ebf7b, 0x3f2cbdc9, 0x3f803f35, 0xbe163f22, 0xbf78bf55, 0x3eacbef1, 0x3eac3f6d, 0xbf78bef1, 0xbe16bf55, 0x3f803f22,
    0x3f2c3f80, 0xbf4ebdc9, 0xbf04bf7b, 0x3f673e95, 0xbedb3ec4, 0xbf5cbf75, 0x3f18be48, 0x3f3e3f7f, 0xbd493f35, 0xbf7dbf46,
    0x3e79bf0e, 0x3f713f62, 0xbf7dbf35, 0x3edbbef1, 0x3f3e3f7b, 0xbf5cbdc9, 0xbe79bf6d, 0x3f803f22, 0xbeac3f0e, 0xbf4ebf75,
    0x3f183f80, 0xbf71be95, 0xbd49bf55, 0x3f783f46, 0xbf043ec4, 0xbf2cbf7f, 0x3f673e48, 0x3e163f62, 0xbe163f35, 0xbf67bf62,
    0x3f2cbe48, 0x3f043f7f, 0xbf78bec4, 0x3d49bf46, 0x3f713f55, 0xbf183e95, 0x3f4e0000, 0x3eac3f75, 0xbf80bf0e, 0x3e79bf22,
    0x3f5c3f6d, 0xbf3e3dc9, 0xbedbbf7b, 0x3f7d3ef1, 0xbf78bec4, 0x3d49bf46, 0x3f713f55, 0xbf183e95, 0xbe163f35, 0xbf67bf62,
    0x3f2cbe48, 0x3f043f7f, 0x3f5c3f6d, 0xbf3e3dc9, 0xbedbbf7b, 0x3f7d3ef1, 0x3f4e0000, 0x3eac3f75, 0xbf80bf0e, 0x3e79bf22,
    0x3e793f6d, 0xbf80bf22, 0x3eacbf0e, 0x3f4e3f75, 0x3f7d3f35, 0xbedb3ef1, 0xbf3ebf7b, 0x3f5c3dc9, 0x3f04bec4, 0x3f2c3f7f,
    0xbf67be48, 0xbe16bf62, 0xbf18bf80, 0x3f713e95, 0x3d493f55, 0xbf78bf46, 0xbf5c0000, 0xbd49bf62, 0x3f673f55, 0xbf4e3dc9,
    0xbe16bf6d, 0x3f713f46, 0xbf3e3e48, 0xbe79bf75, 0x3f783f35, 0xbf2c3e95, 0xbeacbf7b, 0x3f7d3f22, 0xbf183ec4, 0xbedbbf7f,
    0x3f803f0e, 0xbf043ef1, 0x3f043f80, 0xbf80bef1, 0x3edbbf0e, 0x3f183f7f, 0xbf7dbec4, 0x3eacbf22, 0x3f2c3f7b, 0xbf78be95,
    0x3e79bf35, 0x3f3e3f75, 0xbf71be48, 0x3e16bf46, 0x3f4e3f6d, 0xbf67bdc9, 0x3d49bf55, 0x3f5c3f62, 0xbf7dbec4, 0x3eacbf22,
    0x3f2c3f7b, 0xbf78be95, 0x3f043f80, 0xbf80bef1, 0x3edbbf0e, 0x3f183f7f, 0x3f4e3f6d, 0xbf67bdc9, 0x3d49bf55, 0x3f5c3f62,
    0x3e79bf35, 0x3f3e3f75, 0xbf71be48, 0x3e16bf46, 0x3e163f6d, 0xbf71bf46, 0x3f3ebe48, 0x3e793f75, 0x3f5c0000, 0x3d493f62,
    0xbf67bf55, 0x3f4ebdc9, 0x3f18bec4, 0x3edb3f7f, 0xbf80bf0e, 0x3f04bef1, 0xbf78bf35, 0x3f2cbe95, 0x3eac3f7b, 0xbf7dbf22,
    0x3eacbf35, 0x3f043f7f, 0xbf7dbf0e, 0x3f3ebe95, 0x3d493f6d, 0xbf4ebf62, 0x3f783e48, 0xbedb3f22, 0x3f670000, 0xbe793f46,
    0xbf18bf7b, 0x3f803ef1, 0xbf2c3ec4, 0xbe16bf75, 0x3f5c3f55, 0xbf71bdc9, 0x3f713f35, 0xbf5c3dc9, 0x3e16bf55, 0x3f2c3f75,
    0xbf80bec4, 0x3f18bef1, 0x3e793f7b, 0xbf67bf46, 0x3edb3f80, 0xbf78bf22, 0x3f4ebe48, 0xbd493f62, 0xbf3ebf6d, 0x3f7d3e95,
    0xbf043f0e, 0xbeacbf7f, 0x3f803ec4, 0xbf183ef1, 0xbe79bf7b, 0x3f673f46, 0xbf71bf35, 0x3f5cbdc9, 0xbe163f55, 0xbf2cbf75,
    0x3f3e3f6d, 0xbf7dbe95, 0x3f04bf0e, 0x3eac3f7f, 0xbedbbf80, 0x3f783f22, 0xbf4e3e48, 0x3d49bf62, 0x3d493f6d, 0xbf4ebf62,
    0x3f783e48, 0xbedb3f22, 0x3eacbf35, 0x3f043f7f, 0xbf7dbf0e, 0x3f3ebe95, 0xbf2c3ec4, 0xbe16bf75, 0x3f5c3f55, 0xbf71bdc9,
    0x3f670000, 0xbe793f46, 0xbf18bf7b, 0x3f803ef1, 0x3eac3f80, 0xbf5cbf46, 0x3f7d3e48, 0xbf2c3ef1, 0x3d49bf6d, 0x3f183f75,
    0xbf78bf0e, 0x3f67bdc9, 0xbedb3f35, 0xbe79bf7f, 0x3f4e3f55, 0xbf80be95, 0x3f3ebec4, 0xbe163f62, 0xbf04bf7b, 0x3f713f22,
    0xbf710000, 0x3f04bf22, 0x3e163f7b, 0xbf3ebf62, 0x3f803ec4, 0xbf4e3e95, 0x3e79bf55, 0x3edb3f7f, 0xbf67bf35, 0x3f783dc9,
    0xbf183f0e, 0xbd49bf75, 0x3f2c3f6d, 0xbf7dbef1, 0x3f5cbe48, 0xbeac3f46, 0xbf80bec4, 0x3f4ebe95, 0xbe793f55, 0xbedbbf7f,
    0x3f710000, 0xbf043f22, 0xbe16bf7b, 0x3f3e3f62, 0xbf2cbf6d, 0x3f7d3ef1, 0xbf5c3e48, 0x3eacbf46, 0x3f673f35, 0xbf78bdc9,
    0x3f18bf0e, 0x3d493f75, 0x3d49bf6d, 0x3f183f75, 0xbf78bf0e, 0x3f67bdc9, 0x3eac3f80, 0xbf5cbf46, 0x3f7d3e48, 0xbf2c3ef1,
    0x3f3ebec4, 0xbe163f62, 0xbf04bf7b, 0x3f713f22, 0xbedb3f35, 0xbe79bf7f, 0x3f4e3f55, 0xbf80be95, 0xbf5cbf35, 0x3f803e95,
    0xbf673e48, 0x3f18bf22, 0xbe163f6d, 0xbeacbf7f, 0x3f3e3f55, 0xbf78bef1, 0x3e793f80, 0xbf2cbf62, 0x3f713f0e, 0xbf7dbdc9,
    0x3f4ebec4, 0xbedb3f46, 0xbd49bf7b, 0x3f043f75, 0xbf043f35, 0x3d49bf75, 0x3edb3f7b, 0xbf4ebf46, 0x3f7d3ec4, 0xbf713dc9,
    0x3f2cbf0e, 0xbe793f62, 0x3f780000, 0xbf3e3ef1, 0x3eacbf55, 0x3e163f7f, 0xbf18bf6d, 0x3f673f22, 0xbf80be48, 0x3f5cbe95,
    0x3f7d3ec4, 0xbf713dc9, 0x3f2cbf0e, 0xbe793f62, 0xbf043f35, 0x3d49bf75, 0x3edb3f7b, 0xbf4ebf46, 0xbf18bf6d, 0x3f673f22,
    0xbf80be48, 0x3f5cbe95, 0x3f780000, 0xbf3e3ef1, 0x3eacbf55, 0x3e163f7f, 0x3e16bf6d, 0x3eac3f7f, 0xbf3ebf55, 0x3f783ef1,
    0x3f5c3f35, 0xbf80be95, 0x3f67be48, 0xbf183f22, 0xbf4e3ec4, 0x3edbbf46, 0x3d493f7b, 0xbf04bf75, 0xbe79bf80, 0x3f2c3f62,
    0xbf71bf0e, 0x3f7d3dc9, 0xbf7d0000, 0x3f67be95, 0xbf3e3f0e, 0x3f04bf46, 0xbe793f6d, 0xbd49bf7f, 0x3eac3f7b, 0xbf18bf62,
    0x3f4e3f35, 0xbf71bef1, 0x3f803e48, 0xbf783dc9, 0x3f5cbec4, 0xbf2c3f22, 0x3edbbf55, 0xbe163f75, 0x3e163f80, 0xbedbbf75,
    0x3f2c3f55, 0xbf5cbf22, 0x3f783ec4, 0xbf80bdc9, 0x3f71be48, 0xbf4e3ef1, 0x3f18bf35, 0xbeac3f62, 0x3d49bf7b, 0x3e793f7f,
    0xbf04bf6d, 0x3f3e3f46, 0xbf67bf0e, 0x3f7d3e95, 0x3f783ec4, 0xbf80bdc9, 0x3f71be48, 0xbf4e3ef1, 0x3e163f80, 0xbedbbf75,
    0x3f2c3f55, 0xbf5cbf22, 0xbf04bf6d, 0x3f3e3f46, 0xbf67bf0e, 0x3f7d3e95, 0x3f18bf35, 0xbeac3f62, 0x3d49bf7b, 0x3e793f7f,
    0x3e79bf6d, 0x3d493f7f, 0xbeacbf7b, 0x3f183f62, 0x3f7d0000, 0xbf673e95, 0x3f3ebf0e, 0xbf043f46, 0xbf5c3ec4, 0x3f2cbf22,
    0xbedb3f55, 0x3e16bf75, 0xbf4ebf35, 0x3f713ef1, 0xbf80be48, 0x3f78bdc9, 0x3f2cbf35, 0xbf183f46, 0x3f04bf55, 0xbedb3f62,
    0x3eacbf6d, 0xbe793f75, 0x3e16bf7b, 0xbd493f7f, 0x3f800000, 0xbf7d3dc9, 0x3f78be48, 0xbf713e95, 0x3f67bec4, 0xbf5c3ef1,
    0x3f4ebf0e, 0xbf3e3f22, 0x3f3e3f35, 0xbf4ebf22, 0x3f5c3f0e, 0xbf67bef1, 0x3f713ec4, 0xbf78be95, 0x3f7d3e48, 0xbf80bdc9,
    0x3d493f80, 0xbe16bf7f, 0x3e793f7b, 0xbeacbf75, 0x3edb3f6d, 0xbf04bf62, 0x3f183f55, 0xbf2cbf46, 0xbf71bec4, 0x3f783e95,
    0xbf7dbe48, 0x3f803dc9, 0xbf3ebf35, 0x3f4e3f22, 0xbf5cbf0e, 0x3f673ef1, 0xbedbbf6d, 0x3f043f62, 0xbf18bf55, 0x3f2c3f46,
    0xbd49bf80, 0x3e163f7f, 0xbe79bf7b, 0x3eac3f75, 0x3eacbf6d, 0xbe793f75, 0x3e16bf7b, 0xbd493f7f, 0x3f2cbf35, 0xbf183f46,
    0x3f04bf55, 0xbedb3f62, 0x3f67bec4, 0xbf5c3ef1, 0x3f4ebf0e, 0xbf3e3f22, 0x3f800000, 0xbf7d3dc9, 0x3f78be48, 0xbf713e95,
    0xbd493f80, 0x3e16bf7f, 0xbe793f7b, 0x3eacbf75, 0xbedb3f6d, 0x3f04bf62, 0xbf183f55, 0x3f2cbf46, 0xbf3e3f35, 0x3f4ebf22,
    0xbf5c3f0e, 0x3f67bef1, 0xbf713ec4, 0x3f78be95, 0xbf7d3e48, 0x3f80bdc9, 0xbf800000, 0x3f7d3dc9, 0xbf78be48, 0x3f713e95,
    0xbf67bec4, 0x3f5c3ef1, 0xbf4ebf0e, 0x3f3e3f22, 0xbf2cbf35, 0x3f183f46, 0xbf04bf55, 0x3edb3f62, 0xbeacbf6d, 0x3e793f75,
    0xbe16bf7b, 0x3d493f7f, 0x3f673ec4, 0xbf5cbef1, 0x3f4e3f0e, 0xbf3ebf22, 0x3f800000, 0xbf7dbdc9, 0x3f783e48, 0xbf71be95,
    0x3eac3f6d, 0xbe79bf75, 0x3e163f7b, 0xbd49bf7f, 0x3f2c3f35, 0xbf18bf46, 0x3f043f55, 0xbedbbf62, 0xbedb3f6d, 0x3f04bf62,
    0xbf183f55, 0x3f2cbf46, 0xbd493f80, 0x3e16bf7f, 0xbe793f7b, 0x3eacbf75, 0xbf713ec4, 0x3f78be95, 0xbf7d3e48, 0x3f80bdc9,
    0xbf3e3f35, 0x3f4ebf22, 0xbf5c3f0e, 0x3f67bef1, 0xbf18bf35, 0x3eac3f62, 0xbd49bf7b, 0xbe793f7f, 0x3f04bf6d, 0xbf3e3f46,
    0x3f67bf0e, 0xbf7d3e95, 0xbe163f80, 0x3edbbf75, 0xbf2c3f55, 0x3f5cbf22, 0xbf783ec4, 0x3f80bdc9, 0xbf71be48, 0x3f4e3ef1,
    0xbf4e3f35, 0x3f71bef1, 0xbf803e48, 0x3f783dc9, 0xbf5cbec4, 0x3f2c3f22, 0xbedbbf55, 0x3e163f75, 0x3f7d0000, 0xbf67be95,
    0x3f3e3f0e, 0xbf04bf46, 0x3e793f6d, 0x3d49bf7f, 0xbeac3f7b, 0x3f18bf62, 0xbf5cbec4, 0x3f2c3f22, 0xbedbbf55, 0x3e163f75,
    0xbf4e3f35, 0x3f71bef1, 0xbf803e48, 0x3f783dc9, 0x3e793f6d, 0x3d49bf7f, 0xbeac3f7b, 0x3f18bf62, 0x3f7d0000, 0xbf67be95,
    0x3f3e3f0e, 0xbf04bf46, 0xbf043f6d, 0x3f3ebf46, 0xbf673f0e, 0x3f7dbe95, 0x3f183f35, 0xbeacbf62, 0x3d493f7b, 0x3e79bf7f,
    0x3f78bec4, 0xbf803dc9, 0x3f713e48, 0xbf4ebef1, 0x3e16bf80, 0xbedb3f75, 0x3f2cbf55, 0xbf5c3f22, 0xbf780000, 0x3f3e3ef1,
    0xbeacbf55, 0xbe163f7f, 0x3f18bf6d, 0xbf673f22, 0x3f80be48, 0xbf5cbe95, 0x3f043f35, 0xbd49bf75, 0xbedb3f7b, 0x3f4ebf46,
    0xbf7d3ec4, 0x3f713dc9, 0xbf2cbf0e, 0x3e793f62, 0xbe793f80, 0x3f2cbf62, 0xbf713f0e, 0x3f7dbdc9, 0xbf4ebec4, 0x3edb3f46,
    0x3d49bf7b, 0xbf043f75, 0x3f5cbf35, 0xbf803e95, 0x3f673e48, 0xbf18bf22, 0x3e163f6d, 0x3eacbf7f, 0xbf3e3f55, 0x3f78bef1,
    0xbf4ebec4, 0x3edb3f46, 0x3d49bf7b, 0xbf043f75, 0xbe793f80, 0x3f2cbf62, 0xbf713f0e, 0x3f7dbdc9, 0x3e163f6d, 0x3eacbf7f,
    0xbf3e3f55, 0x3f78bef1, 0x3f5cbf35, 0xbf803e95, 0x3f673e48, 0xbf18bf22, 0xbf183f6d, 0x3f67bf22, 0xbf803e48, 0x3f5c3e95,
    0x3f780000, 0xbf3ebef1, 0x3eac3f55, 0x3e16bf7f, 0x3f7dbec4, 0xbf71bdc9, 0x3f2c3f0e, 0xbe79bf62, 0xbf04bf35, 0x3d493f75,
    0x3edbbf7b, 0xbf4e3f46, 0x3f67bf35, 0xbf783dc9, 0x3f183f0e, 0x3d49bf75, 0xbf2c3f6d, 0x3f7dbef1, 0xbf5cbe48, 0x3eac3f46,
    0x3f710000, 0xbf04bf22, 0xbe163f7b, 0x3f3ebf62, 0xbf803ec4, 0x3f4e3e95, 0xbe79bf55, 0xbedb3f7f, 0x3edb3f35, 0x3e79bf7f,
    0xbf4e3f55, 0x3f80be95, 0xbf3ebec4, 0x3e163f62, 0x3f04bf7b, 0xbf713f22, 0xbeac3f80, 0x3f5cbf46, 0xbf7d3e48, 0x3f2c3ef1,
    0xbd49bf6d, 0xbf183f75, 0x3f78bf0e, 0xbf67bdc9, 0x3f3e3ec4, 0xbe16bf62, 0xbf043f7b, 0x3f71bf22, 0xbedbbf35, 0xbe793f7f,
    0x3f4ebf55, 0xbf803e95, 0x3d493f6d, 0x3f18bf75, 0xbf783f0e, 0x3f673dc9, 0x3eacbf80, 0xbf5c3f46, 0x3f7dbe48, 0xbf2cbef1,
    0xbf2c3f6d, 0x3f7dbef1, 0xbf5cbe48, 0x3eac3f46, 0x3f67bf35, 0xbf783dc9, 0x3f183f0e, 0x3d49bf75, 0xbf803ec4, 0x3f4e3e95,
    0xbe79bf55, 0xbedb3f7f, 0x3f710000, 0xbf04bf22, 0xbe163f7b, 0x3f3ebf62, 0xbedb3f80, 0x3f78bf22, 0xbf4ebe48, 0x3d493f62,
    0x3f3ebf6d, 0xbf7d3e95, 0x3f043f0e, 0x3eacbf7f, 0xbf713f35, 0x3f5c3dc9, 0xbe16bf55, 0xbf2c3f75, 0x3f80bec4, 0xbf18bef1,
    0xbe793f7b, 0x3f67bf46, 0xbf670000, 0x3e793f46, 0x3f18bf7b, 0xbf803ef1, 0x3f2c3ec4, 0x3e16bf75, 0xbf5c3f55, 0x3f71bdc9,
    0xbeacbf35, 0xbf043f7f, 0x3f7dbf0e, 0xbf3ebe95, 0xbd493f6d, 0x3f4ebf62, 0xbf783e48, 0x3edb3f22, 0xbf2cbec4, 0xbe163f75,
    0x3f5cbf55, 0xbf713dc9, 0x3f670000, 0xbe79bf46, 0xbf183f7b, 0x3f80bef1, 0x3d49bf6d, 0xbf4e3f62, 0x3f78be48, 0xbedbbf22,
    0x3eac3f35, 0x3f04bf7f, 0xbf7d3f0e, 0x3f3e3e95, 0x3f3ebf6d, 0xbf7d3e95, 0x3f043f0e, 0x3eacbf7f, 0xbedb3f80, 0x3f78bf22,
    0xbf4ebe48, 0x3d493f62, 0x3f80bec4, 0xbf18bef1, 0xbe793f7b, 0x3f67bf46, 0xbf713f35, 0x3f5c3dc9, 0xbe16bf55, 0xbf2c3f75,
    0xbe79bf35, 0xbf3e3f75, 0x3f71be48, 0xbe16bf46, 0xbf4e3f6d, 0x3f67bdc9, 0xbd49bf55, 0xbf5c3f62, 0xbf043f80, 0x3f80bef1,
    0xbedbbf0e, 0xbf183f7f, 0x3f7dbec4, 0xbeacbf22, 0xbf2c3f7b, 0x3f78be95, 0xbf783f35, 0x3f2c3e95, 0x3eacbf7b, 0xbf7d3f22,
    0x3f183ec4, 0x3edbbf7f, 0xbf803f0e, 0x3f043ef1, 0x3f5c0000, 0x3d49bf62, 0xbf673f55, 0x3f4e3dc9, 0x3e16bf6d, 0xbf713f46,
    0x3f3e3e48, 0x3e79bf75, 0x3f183ec4, 0x3edbbf7f, 0xbf803f0e, 0x3f043ef1, 0xbf783f35, 0x3f2c3e95, 0x3eacbf7b, 0xbf7d3f22,
    0x3e16bf6d, 0xbf713f46, 0x3f3e3e48, 0x3e79bf75, 0x3f5c0000, 0x3d49bf62, 0xbf673f55, 0x3f4e3dc9, 0x3f4ebf6d, 0xbf673dc9,
    0x3d493f55, 0x3f5cbf62, 0x3e793f35, 0x3f3ebf75, 0xbf713e48, 0x3e163f46, 0xbf7d3ec4, 0x3eac3f22, 0x3f2cbf7b, 0xbf783e95,
    0x3f04bf80, 0xbf803ef1, 0x3edb3f0e, 0x3f18bf7f, 0xbf4e0000, 0xbeac3f75, 0x3f80bf0e, 0xbe79bf22, 0xbf5c3f6d, 0x3f3e3dc9,
    0x3edbbf7b, 0xbf7d3ef1, 0x3e163f35, 0x3f67bf62, 0xbf2cbe48, 0xbf043f7f, 0x3f78bec4, 0xbd49bf46, 0xbf713f55, 0x3f183e95,
    0xbf183f80, 0x3f71be95, 0x3d49bf55, 0xbf783f46, 0x3f043ec4, 0x3f2cbf7f, 0xbf673e48, 0xbe163f62, 0x3f7dbf35, 0xbedbbef1,
    0xbf3e3f7b, 0x3f5cbdc9, 0x3e79bf6d, 0xbf803f22, 0x3eac3f0e, 0x3f4ebf75, 0x3f043ec4, 0x3f2cbf7f, 0xbf673e48, 0xbe163f62,
    0xbf183f80, 0x3f71be95, 0x3d49bf55, 0xbf783f46, 0x3e79bf6d, 0xbf803f22, 0x3eac3f0e, 0x3f4ebf75, 0x3f7dbf35, 0xbedbbef1,
    0xbf3e3f7b, 0x3f5cbdc9, 0x3f5cbf6d, 0xbf3ebdc9, 0xbedb3f7b, 0x3f7dbef1, 0x3f4e0000, 0x3eacbf75, 0xbf803f0e, 0x3e793f22,
    0xbf783ec4, 0x3d493f46, 0x3f71bf55, 0xbf18be95, 0xbe16bf35, 0xbf673f62, 0x3f2c3e48, 0x3f04bf7f, 0x3f80bf35, 0xbe16bf22,
    0xbf783f55, 0x3eac3ef1, 0x3f67bf6d, 0xbf04be95, 0xbf4e3f7b, 0x3f2c3dc9, 0x3f3e0000, 0x3f18bf7f, 0xbf5c3e48, 0xbedb3f75,
    0x3f71bec4, 0x3e79bf62, 0xbf7d3f0e, 0xbd493f46, 0x3d493f35, 0x3f7dbf46, 0xbe79bf0e, 0xbf713f62, 0x3edb3ec4, 0x3f5cbf75,
    0xbf18be48, 0xbf3e3f7f, 0xbf2c3f80, 0x3f4ebdc9, 0x3f04bf7b, 0xbf673e95, 0xbeac3f6d, 0x3f78bef1, 0x3e16bf55, 0xbf803f22,
    0xbedbbec4, 0xbf5c3f75, 0x3f183e48, 0x3f3ebf7f, 0xbd49bf35, 0xbf7d3f46, 0x3e793f0e, 0x3f71bf62, 0x3eacbf6d, 0xbf783ef1,
    0xbe163f55, 0x3f80bf22, 0x3f2cbf80, 0xbf4e3dc9, 0xbf043f7b, 0x3f67be95, 0x3f67bf6d, 0xbf04be95, 0xbf4e3f7b, 0x3f2c3dc9,
    0x3f80bf35, 0xbe16bf22, 0xbf783f55, 0x3eac3ef1, 0x3f71bec4, 0x3e79bf62, 0xbf7d3f0e, 0xbd493f46, 0x3f3e0000, 0x3f18bf7f,
    0xbf5c3e48, 0xbedb3f75, 0xbf3e3f80, 0x3f183dc9, 0x3f5cbf7b, 0xbedbbe95, 0xbf713f6d, 0x3e793ef1, 0x3f7dbf55, 0xbd49bf22,
    0xbf803f35, 0xbe163f46, 0x3f78bf0e, 0x3eacbf62, 0xbf673ec4, 0xbf043f75, 0x3f4ebe48, 0x3f2cbf7f, 0xbf2c0000, 0xbf4e3f7f,
    0x3f043e48, 0x3f67bf75, 0xbeacbec4, 0xbf783f62, 0x3e163f0e, 0x3f80bf46, 0x3d49bf35, 0xbf7d3f22, 0xbe793f55, 0x3f71bef1,
    0x3edbbf6d, 0xbf5c3e95, 0xbf183f7b, 0x3f3ebdc9, 0x3eac3ec4, 0x3f78bf62, 0xbe16bf0e, 0xbf803f46, 0x3f2c0000, 0x3f4ebf7f,
    0xbf04be48, 0xbf673f75, 0xbedb3f6d, 0x3f5cbe95, 0x3f18bf7b, 0xbf3e3dc9, 0xbd493f35, 0x3f7dbf22, 0x3e79bf55, 0xbf713ef1,
    0xbf713f6d, 0x3e793ef1, 0x3f7dbf55, 0xbd49bf22, 0xbf3e3f80, 0x3f183dc9, 0x3f5cbf7b, 0xbedbbe95, 0xbf673ec4, 0xbf043f75,
    0x3f4ebe48, 0x3f2cbf7f, 0xbf803f35, 0xbe163f46, 0x3f78bf0e, 0x3eacbf62, 0x3e16bf35, 0xbf673ef1, 0xbf2c3f7b, 0x3f043dc9,
    0x3f78bf6d, 0x3d49bf22, 0xbf713f0e, 0xbf183f75, 0xbf4e3f80, 0x3eac3e95, 0x3f80bf55, 0x3e79bf46, 0xbf5c3ec4, 0xbf3e3f7f,
    0x3edb3e48, 0x3f7dbf62, 0xbf7d3f35, 0xbedb3f62, 0x3f3ebe48, 0x3f5cbf7f, 0xbe79bec4, 0xbf803f46, 0xbeac3f55, 0x3f4ebe95,
    0x3f180000, 0x3f71bf75, 0xbd49bf0e, 0xbf783f22, 0xbf043f6d, 0x3f2cbdc9, 0x3f67bf7b, 0xbe16bef1, 0xbe79bec4, 0xbf803f46,
    0xbeac3f55, 0x3f4ebe95, 0xbf7d3f35, 0xbedb3f62, 0x3f3ebe48, 0x3f5cbf7f, 0xbf043f6d, 0x3f2cbdc9, 0x3f67bf7b, 0xbe16bef1,
    0x3f180000, 0x3f71bf75, 0xbd49bf0e, 0xbf783f22, 0xbf783f6d, 0xbd493f22, 0x3f71bf0e, 0x3f18bf75, 0xbe163f35, 0x3f67bef1,
    0x3f2cbf7b, 0xbf04bdc9, 0x3f5cbec4, 0x3f3ebf7f, 0xbedbbe48, 0xbf7d3f62, 0x3f4ebf80, 0xbeacbe95, 0xbf803f55, 0xbe793f46,
    0xbf040000, 0xbf803f62, 0xbedb3f55, 0x3f18bdc9, 0x3f7dbf6d, 0x3eacbf46, 0xbf2c3e48, 0xbf783f75, 0xbe793f35, 0x3f3ebe95,
    0x3f71bf7b, 0x3e16bf22, 0xbf4e3ec4, 0xbf673f7f, 0xbd493f0e, 0x3f5cbef1, 0xbf5c3f80, 0x3d493ef1, 0x3f67bf0e, 0x3f4ebf7f,
    0xbe16bec4, 0xbf713f22, 0xbf3e3f7b, 0x3e793e95, 0x3f78bf35, 0x3f2cbf75, 0xbeacbe48, 0xbf7d3f46, 0xbf183f6d, 0x3edb3dc9,
    0x3f80bf55, 0x3f04bf62, 0xbe16bec4, 0xbf713f22, 0xbf3e3f7b, 0x3e793e95, 0xbf5c3f80, 0x3d493ef1, 0x3f67bf0e, 0x3f4ebf7f,
    0xbf183f6d, 0x3edb3dc9, 0x3f80bf55, 0x3f04bf62, 0x3f78bf35, 0x3f2cbf75, 0xbeacbe48, 0xbf7d3f46, 0xbf7d3f6d, 0xbeac3f46,
    0x3f2cbe48, 0x3f78bf75, 0x3f040000, 0x3f80bf62, 0x3edbbf55, 0xbf183dc9, 0x3f4ebec4, 0x3f67bf7f, 0x3d49bf0e, 0xbf5c3ef1,
    0x3e79bf35, 0xbf3e3e95, 0xbf713f7b, 0xbe163f22, 0x3f71bf35, 0x3f5cbf7f, 0x3e16bf0e, 0xbf2c3e95, 0xbf803f6d, 0xbf183f62,
    0x3e793e48, 0x3f67bf22, 0x3edb0000, 0x3f78bf46, 0x3f4ebf7b, 0x3d49bef1, 0xbf3e3ec4, 0xbf7d3f75, 0xbf043f55, 0x3eac3dc9,
    0xbeac3f35, 0x3f04bdc9, 0x3f7dbf55, 0x3f3ebf75, 0xbd49bec4, 0xbf4e3ef1, 0xbf783f7b, 0xbedb3f46, 0xbf673f80, 0xbe793f22,
    0x3f18be48, 0x3f80bf62, 0x3f2cbf6d, 0xbe16be95, 0xbf5c3f0e, 0xbf713f7f, 0x3d493ec4, 0x3f4ebef1, 0x3f78bf7b, 0x3edbbf46,
    0x3eacbf35, 0xbf043dc9, 0xbf7d3f55, 0xbf3e3f75, 0xbf2c3f6d, 0x3e163e95, 0x3f5cbf0e, 0x3f71bf7f, 0x3f67bf80, 0x3e79bf22,
    0xbf183e48, 0xbf803f62, 0xbf803f6d, 0xbf183f62, 0x3e793e48, 0x3f67bf22, 0x3f71bf35, 0x3f5cbf7f, 0x3e16bf0e, 0xbf2c3e95,
    0xbf3e3ec4, 0xbf7d3f75, 0xbf043f55, 0x3eac3dc9, 0x3edb0000, 0x3f78bf46, 0x3f4ebf7b, 0x3d49bef1, 0xbf713f80, 0xbf043f46,
    0x3e163e48, 0x3f3ebef1, 0x3f80bf6d, 0x3f4ebf75, 0x3e79bf0e, 0xbedb3dc9, 0xbf673f35, 0xbf783f7f, 0xbf183f55, 0x3d493e95,
    0x3f2cbec4, 0x3f7dbf62, 0x3f5cbf7b, 0x3eacbf22, 0xbeac0000, 0xbf5c3f22, 0xbf7d3f7b, 0xbf2c3f62, 0xbd493ec4, 0x3f18be95,
    0x3f78bf55, 0x3f67bf7f, 0x3edbbf35, 0xbe79bdc9, 0xbf4e3f0e, 0xbf803f75, 0xbf3e3f6d, 0xbe163ef1, 0x3f04be48, 0x3f71bf46,
    0x3d49bec4, 0xbf183e95, 0xbf783f55, 0xbf673f7f, 0x3eac0000, 0x3f5cbf22, 0x3f7dbf7b, 0x3f2cbf62, 0x3f3ebf6d, 0x3e16bef1,
    0xbf043e48, 0xbf713f46, 0xbedb3f35, 0x3e793dc9, 0x3f4ebf0e, 0x3f80bf75, 0x3f80bf6d, 0x3f4ebf75, 0x3e79bf0e, 0xbedb3dc9,
    0xbf713f80, 0xbf043f46, 0x3e163e48, 0x3f3ebef1, 0x3f2cbec4, 0x3f7dbf62, 0x3f5cbf7b, 0x3eacbf22, 0xbf673f35, 0xbf783f7f,
    0xbf183f55, 0x3d493e95, 0x3f04bf35, 0x3d49be95, 0xbedb3e48, 0xbf4e3f22, 0xbf7d3f6d, 0xbf713f7f, 0xbf2c3f55, 0xbe793ef1,
    0xbf783f80, 0xbf3e3f62, 0xbeac3f0e, 0x3e163dc9, 0x3f18bec4, 0x3f67bf46, 0x3f80bf7b, 0x3f5cbf75, 0xbf5c3f35, 0xbf803f75,
    0xbf673f7b, 0xbf183f46, 0xbe163ec4, 0x3eacbdc9, 0x3f3ebf0e, 0x3f78bf62, 0x3e790000, 0x3f2cbef1, 0x3f71bf55, 0x3f7dbf7f,
    0x3f4ebf6d, 0x3edbbf22, 0xbd49be48, 0xbf043e95, 0xbe163ec4, 0x3eacbdc9, 0x3f3ebf0e, 0x3f78bf62, 0xbf5c3f35, 0xbf803f75,
    0xbf673f7b, 0xbf183f46, 0x3f4ebf6d, 0x3edbbf22, 0xbd49be48, 0xbf043e95, 0x3e790000, 0x3f2cbef1, 0x3f71bf55, 0x3f7dbf7f,
    0x3f7dbf6d, 0x3f71bf7f, 0x3f2cbf55, 0x3e79bef1, 0xbf043f35, 0xbd493e95, 0x3edbbe48, 0x3f4ebf22, 0xbf183ec4, 0xbf673f46,
    0xbf803f7b, 0xbf5c3f75, 0x3f78bf80, 0x3f3ebf62, 0x3eacbf0e, 0xbe16bdc9, 0xbe160000, 0xbedb3e95, 0xbf2c3f0e, 0xbf5c3f46,
    0xbf783f6d, 0xbf803f7f, 0xbf713f7b, 0xbf4e3f62, 0xbf183f35, 0xbeac3ef1, 0xbd493e48, 0x3e79bdc9, 0x3f04bec4, 0x3f3ebf22,
    0x3f67bf55, 0x3f7dbf75, 0xbf7d3f80, 0xbf673f75, 0xbf3e3f55, 0xbf043f22, 0xbe793ec4, 0x3d493dc9, 0x3eacbe48, 0x3f18bef1,
    0x3f4ebf35, 0x3f71bf62, 0x3f80bf7b, 0x3f78bf7f, 0x3f5cbf6d, 0x3f2cbf46, 0x3edbbf0e, 0x3e16be95, 0xbe793ec4, 0x3d493dc9,
    0x3eacbe48, 0x3f18bef1, 0xbf7d3f80, 0xbf673f75, 0xbf3e3f55, 0xbf043f22, 0x3f5cbf6d, 0x3f2cbf46, 0x3edbbf0e, 0x3e16be95,
    0x3f4ebf35, 0x3f71bf62, 0x3f80bf7b, 0x3f78bf7f, 0x3f78bf6d, 0x3f80bf7f, 0x3f71bf7b, 0x3f4ebf62, 0x3e160000, 0x3edbbe95,
    0x3f2cbf0e, 0x3f5cbf46, 0xbf043ec4, 0xbf3e3f22, 0xbf673f55, 0xbf7d3f75, 0x3f18bf35, 0x3eacbef1, 0x3d49be48, 0xbe793dc9,
    0x3f3ebf35, 0x3f4ebf46, 0x3f5cbf55, 0x3f67bf62, 0x3f71bf6d, 0x3f78bf75, 0x3f7dbf7b, 0x3f80bf7f, 0x3d490000, 0x3e16bdc9,
    0x3e79be48, 0x3eacbe95, 0x3edbbec4, 0x3f04bef1, 0x3f18bf0e, 0x3f2cbf22, 0xbf2c3f35, 0xbf183f22, 0xbf043f0e, 0xbedb3ef1,
    0xbeac3ec4, 0xbe793e95, 0xbe163e48, 0xbd493dc9, 0xbf803f80, 0xbf7d3f7f, 0xbf783f7b, 0xbf713f75, 0xbf673f6d, 0xbf5c3f62,
    0xbf4e3f55, 0xbf3e3f46, 0x3eacbec4, 0x3e79be95, 0x3e16be48, 0x3d49bdc9, 0x3f2cbf35, 0x3f18bf22, 0x3f04bf0e, 0x3edbbef1,
    0x3f67bf6d, 0x3f5cbf62, 0x3f4ebf55, 0x3f3ebf46, 0x3f80bf80, 0x3f7dbf7f, 0x3f78bf7b, 0x3f71bf75, 0x3f71bf6d, 0x3f78bf75,
    0x3f7dbf7b, 0x3f80bf7f, 0x3f3ebf35, 0x3f4ebf46, 0x3f5cbf55, 0x3f67bf62, 0x3edbbec4, 0x3f04bef1, 0x3f18bf0e, 0x3f2cbf22,
    0x3d490000, 0x3e16bdc9, 0x3e79be48, 0x3eacbe95,
};
__device__ const __align__(128) uint32_t c_ga[1536] = {
    0x00003c80, 0x3bc43c6d, 0x00003c80, 0xbbc4bc6d, 0x00003c80, 0x3c6d3bc4, 0x00003c80, 0xbc6dbbc4, 0x00003c80, 0x3c6dbbc4,
    0x00003c80, 0xbc6d3bc4, 0x00003c80, 0x3bc4bc6d, 0x00003c80, 0xbbc43c6d, 0x3a493c80, 0x3bdb3c67, 0x3bdb3c67, 0xbc3ebc2c,
    0x3b163c7d, 0x3c783b79, 0x3c043c5c, 0xbc7d3b16, 0x3b793c78, 0x3c4ebc18, 0x3c183c4e, 0xbc043c5c, 0x3bac3c71, 0x3a49bc80,
    0x3c2c3c3e, 0x3bac3c71, 0x3ac93c7f, 0x3bf13c62, 0x3c463c22, 0xbc75bb95, 0x3b953c75, 0x3c7f3ac9, 0x3c623bf1, 0xbc463c22,
    0x3bf13c62, 0x3c22bc46, 0x3c753b95, 0x3ac93c7f, 0x3c223c46, 0xbb95bc75, 0x3c7f3ac9, 0x3c623bf1, 0x3b163c7d, 0x3c043c5c,
    0x3c783b79, 0xbc7d3b16, 0x3bdb3c67, 0x3c80ba49, 0x3c80ba49, 0xbbac3c71, 0x3c2c3c3e, 0x3bdbbc67, 0x3c71bbac, 0x3c2c3c3e,
    0x3c5c3c04, 0xbc18bc4e, 0x3c4ebc18, 0x3c78bb79, 0x3b483c7b, 0x3c0e3c55, 0x3c7bbb48, 0xbc553c0e, 0x3c0e3c55, 0x3c7bbb48,
    0x3c55bc0e, 0x3b483c7b, 0x3c553c0e, 0x3b48bc7b, 0x3c0ebc55, 0x3c7b3b48, 0x3c7b3b48, 0xbc55bc0e, 0x3b48bc7b, 0x3c0ebc55,
    0x3b793c78, 0x3c183c4e, 0x3c4ebc18, 0xbc043c5c, 0x3c2c3c3e, 0x3c71bbac, 0x3bdbbc67, 0x3c2c3c3e, 0x3c713bac, 0xba49bc80,
    0xba49bc80, 0x3c67bbdb, 0x3c7dbb16, 0xbc78bb79, 0xbc04bc5c, 0xbb16bc7d, 0x3b953c75, 0x3c223c46, 0x3bf1bc62, 0xbac93c7f,
    0x3c463c22, 0x3c62bbf1, 0xbac9bc7f, 0x3c753b95, 0x3c7f3ac9, 0xbb95bc75, 0xbc22bc46, 0x3bf1bc62, 0x3c62bbf1, 0xbc7f3ac9,
    0xbc75bb95, 0xbc46bc22, 0x3bac3c71, 0x3c2c3c3e, 0x3a49bc80, 0x3bac3c71, 0x3c5c3c04, 0x3c4ebc18, 0xbc18bc4e, 0x3c78bb79,
    0x3c7dbb16, 0xbc04bc5c, 0xbc78bb79, 0xbb16bc7d, 0x3c2cbc3e, 0xbc673bdb, 0xbc673bdb, 0xbc803a49, 0x00003c80, 0x3bc43c6d,
    0x00003c80, 0xbbc4bc6d, 0x00003c80, 0x3c6d3bc4, 0x00003c80, 0xbc6dbbc4, 0x00003c80, 0x3c6dbbc4, 0x00003c80, 0xbc6d3bc4,
    0x00003c80, 0x3bc4bc6d, 0x00003c80, 0xbbc43c6d, 0x3c3e3c2c, 0x3c713bac, 0x3c713bac, 0xbc803a49, 0x3c4e3c18, 0x3c5cbc04,
    0x3c783b79, 0xbc183c4e, 0x3c5c3c04, 0x3b16bc7d, 0x3c7d3b16, 0x3b793c78, 0x3c673bdb, 0xbc2cbc3e, 0x3c803a49, 0x3c673bdb,
    0x3c7fbac9, 0x3c62bbf1, 0x3c22bc46, 0xbb953c75, 0x3c75bb95, 0x3ac9bc7f, 0x3bf1bc62, 0x3c223c46, 0x3c62bbf1, 0xbc46bc22,
    0x3b95bc75, 0x3c7fbac9, 0x3c46bc22, 0xbc753b95, 0x3ac9bc7f, 0x3bf1bc62, 0x3c18bc4e, 0x3b79bc78, 0xbc04bc5c, 0x3c4e3c18,
    0x3bacbc71, 0xbc3ebc2c, 0xbc3ebc2c, 0x3c67bbdb, 0x3a49bc80, 0xbc713bac, 0xbc67bbdb, 0x3a49bc80, 0xbb79bc78, 0xbb163c7d,
    0xbc7dbb16, 0xbc5cbc04, 0xbb48bc7b, 0xbc0ebc55, 0xbc7b3b48, 0x3c55bc0e, 0xbc0ebc55, 0xbc7b3b48, 0xbc553c0e, 0xbb48bc7b,
    0xbc55bc0e, 0xbb483c7b, 0xbc0e3c55, 0xbc7bbb48, 0xbc7bbb48, 0x3c553c0e, 0xbb483c7b, 0xbc0e3c55, 0xbc5cbc04, 0xbc7dbb16,
    0xbb163c7d, 0xbb79bc78, 0xbc80ba49, 0xbbdb3c67, 0x3bac3c71, 0xbc80ba49, 0xbc673bdb, 0x3c3e3c2c, 0x3c3e3c2c, 0xbbac3c71,
    0xbc183c4e, 0x3c5cbc04, 0x3c783b79, 0x3c4e3c18, 0xbc753b95, 0xbc463c22, 0x3c623bf1, 0xbc7fbac9, 0xbc223c46, 0x3bf13c62,
    0x3c7fbac9, 0xbb953c75, 0xbac93c7f, 0x3c75bb95, 0x3c46bc22, 0x3c623bf1, 0x3bf13c62, 0xbac9bc7f, 0x3b95bc75, 0x3c22bc46,
    0xbbdb3c67, 0xba493c80, 0x3c3ebc2c, 0xbbdb3c67, 0x3b793c78, 0x3c7d3b16, 0x3b16bc7d, 0x3c5c3c04, 0x3c4e3c18, 0x3b79bc78,
    0xbc04bc5c, 0x3c18bc4e, 0x3c80ba49, 0xbc71bbac, 0xbc71bbac, 0xbc3ebc2c, 0x00003c80, 0x3bc43c6d, 0x00003c80, 0xbbc4bc6d,
    0x00003c80, 0x3c6d3bc4, 0x00003c80, 0xbc6dbbc4, 0x00003c80, 0x3c6dbbc4, 0x00003c80, 0xbc6d3bc4, 0x00003c80, 0x3bc4bc6d,
    0x00003c80, 0xbbc43c6d, 0x3c80ba49, 0x3c67bbdb, 0x3c67bbdb, 0xbc2c3c3e, 0x3c7dbb16, 0x3b79bc78, 0x3c5cbc04, 0x3b163c7d,
    0x3c78bb79, 0xbc18bc4e, 0x3c4ebc18, 0x3c5c3c04, 0x3c71bbac, 0xbc80ba49, 0x3c3ebc2c, 0x3c71bbac, 0xbac9bc7f, 0xbbf1bc62,
    0xbc46bc22, 0x3c753b95, 0xbb95bc75, 0xbc7fbac9, 0xbc62bbf1, 0x3c46bc22, 0xbbf1bc62, 0xbc223c46, 0xbc75bb95, 0xbac9bc7f,
    0xbc22bc46, 0x3b953c75, 0xbc7fbac9, 0xbc62bbf1, 0xbc7d3b16, 0xbc5c3c04, 0xbb793c78, 0xbb16bc7d, 0xbc673bdb, 0x3a493c80,
    0x3a493c80, 0xbc71bbac, 0xbc3e3c2c, 0x3c673bdb, 0x3bac3c71, 0xbc3e3c2c, 0xbc043c5c, 0x3c4ebc18, 0x3c183c4e, 0x3b793c78,
    0x3b483c7b, 0x3c0e3c55, 0x3c7bbb48, 0xbc553c0e, 0x3c0e3c55, 0x3c7bbb48, 0x3c55bc0e, 0x3b483c7b, 0x3c553c0e, 0x3b48bc7b,
    0x3c0ebc55, 0x3c7b3b48, 0x3c7b3b48, 0xbc55bc0e, 0x3b48bc7b, 0x3c0ebc55, 0x3c78bb79, 0x3c4ebc18, 0xbc18bc4e, 0x3c5c3c04,
    0x3c3ebc2c, 0xbbacbc71, 0xbc67bbdb, 0x3c3ebc2c, 0x3bacbc71, 0xbc803a49, 0xbc803a49, 0xbbdbbc67, 0xbb16bc7d, 0xbb793c78,
    0xbc5c3c04, 0xbc7d3b16, 0xbb95bc75, 0xbc22bc46, 0xbbf13c62, 0x3ac9bc7f, 0xbc46bc22, 0xbc623bf1, 0x3ac93c7f, 0xbc75bb95,
    0xbc7fbac9, 0x3b953c75, 0x3c223c46, 0xbbf13c62, 0xbc623bf1, 0x3c7fbac9, 0x3c753b95, 0x3c463c22, 0xbc713bac, 0xbc3e3c2c,
    0x3c803a49, 0xbc713bac, 0xbc043c5c, 0x3c183c4e, 0x3c4ebc18, 0x3b793c78, 0x3b163c7d, 0x3c5cbc04, 0x3b79bc78, 0x3c7dbb16,
    0x3c3e3c2c, 0xbbdbbc67, 0xbbdbbc67, 0xba49bc80, 0x00003c80, 0x3bc43c6d, 0x00003c80, 0xbbc4bc6d, 0x00003c80, 0x3c6d3bc4,
    0x00003c80, 0xbc6dbbc4, 0x00003c80, 0x3c6dbbc4, 0x00003c80, 0xbc6d3bc4, 0x00003c80, 0x3bc4bc6d, 0x00003c80, 0xbbc43c6d,
    0x3c2cbc3e, 0x3bacbc71, 0x3bacbc71, 0x3a493c80, 0x3c18bc4e, 0xbc04bc5c, 0x3b79bc78, 0x3c4e3c18, 0x3c04bc5c, 0xbc7dbb16,
    0x3b16bc7d, 0x3c78bb79, 0x3bdbbc67, 0xbc3e3c2c, 0x3a49bc80, 0x3bdbbc67, 0xbc7f3ac9, 0xbc623bf1, 0xbc223c46, 0x3b95bc75,
    0xbc753b95, 0xbac93c7f, 0xbbf13c62, 0xbc22bc46, 0xbc623bf1, 0x3c463c22, 0xbb953c75, 0xbc7f3ac9, 0xbc463c22, 0x3c75bb95,
    0xbac93c7f, 0xbbf13c62, 0x3c4e3c18, 0x3c783b79, 0x3c5cbc04, 0xbc183c4e, 0x3c713bac, 0x3c2cbc3e, 0x3c2cbc3e, 0x3bdb3c67,
    0x3c803a49, 0xbbacbc71, 0x3bdbbc67, 0x3c803a49, 0x3c78bb79, 0xbc7dbb16, 0x3b16bc7d, 0x3c04bc5c, 0xbb48bc7b, 0xbc0ebc55,
    0xbc7b3b48, 0x3c55bc0e, 0xbc0ebc55, 0xbc7b3b48, 0xbc553c0e, 0xbb48bc7b, 0xbc55bc0e, 0xbb483c7b, 0xbc0e3c55, 0xbc7bbb48,
    0xbc7bbb48, 0x3c553c0e, 0xbb483c7b, 0xbc0e3c55, 0xbc043c5c, 0xbb163c7d, 0x3c7d3b16, 0xbc783b79, 0xba493c80, 0x3c673bdb,
    0x3c71bbac, 0xba493c80, 0x3bdb3c67, 0x3c2cbc3e, 0x3c2cbc3e, 0x3c713bac, 0x3c4e3c18, 0xbc04bc5c, 0x3b79bc78, 0x3c18bc4e,
    0x3c75bb95, 0x3c46bc22, 0xbc62bbf1, 0x3c7f3ac9, 0x3c22bc46, 0xbbf1bc62, 0xbc7f3ac9, 0x3b95bc75, 0x3ac9bc7f, 0xbc753b95,
    0xbc463c22, 0xbc62bbf1, 0xbbf1bc62, 0x3ac93c7f, 0xbb953c75, 0xbc223c46, 0xbc67bbdb, 0xbc80ba49, 0x3c2c3c3e, 0xbc67bbdb,
    0xbc783b79, 0xbb163c7d, 0x3c7d3b16, 0xbc043c5c, 0xbc183c4e, 0x3c783b79, 0x3c5cbc04, 0x3c4e3c18, 0x3a493c80, 0x3bacbc71,
    0x3bacbc71, 0x3c2cbc3e, 0x3c353c35, 0x3c6d3bc4, 0x3c353c35, 0xbc6dbbc4, 0x3c35bc35, 0xbbc4bc6d, 0x3c35bc35, 0x3bc43c6d,
    0xbc35bc35, 0xbbc43c6d, 0xbc35bc35, 0x3bc4bc6d, 0xbc353c35, 0x3c6dbbc4, 0xbc353c35, 0xbc6d3bc4, 0x3c3e3c2c, 0x3c713bac,
    0x3c713bac, 0xbc803a49, 0x3c18bc4e, 0xbc04bc5c, 0x3b79bc78, 0x3c4e3c18, 0xbc5cbc04, 0xbb163c7d, 0xbc7dbb16, 0xbb79bc78,
    0xbbdb3c67, 0x3c3ebc2c, 0xba493c80, 0xbbdb3c67, 0x3c463c22, 0x3c753b95, 0x3c7fbac9, 0xbc623bf1, 0x3bf1bc62, 0xbc22bc46,
    0xbb95bc75, 0x3c7f3ac9, 0xbc75bb95, 0x3ac93c7f, 0xbc623bf1, 0xbc46bc22, 0xbac93c7f, 0x3bf1bc62, 0x3c223c46, 0x3b953c75,
    0x3c4e3c18, 0x3c783b79, 0x3c5cbc04, 0xbc183c4e, 0x3bacbc71, 0xbc3ebc2c, 0xbc3ebc2c, 0x3c67bbdb, 0xbc80ba49, 0x3bac3c71,
    0xbbdb3c67, 0xbc80ba49, 0x3b793c78, 0x3b16bc7d, 0x3c7d3b16, 0x3c5c3c04, 0x3c553c0e, 0x3c7b3b48, 0x3c0ebc55, 0xbb483c7b,
    0x3b48bc7b, 0xbc55bc0e, 0xbc7bbb48, 0x3c0ebc55, 0xbc7b3b48, 0x3c0e3c55, 0x3b483c7b, 0xbc553c0e, 0x3c0e3c55, 0xbb48bc7b,
    0x3c55bc0e, 0x3c7bbb48, 0x3c5c3c04, 0x3c7d3b16, 0x3b16bc7d, 0x3b793c78, 0x3a49bc80, 0xbc67bbdb, 0xbc713bac, 0x3a49bc80,
    0xbc673bdb, 0x3c3e3c2c, 0x3c3e3c2c, 0xbbac3c71, 0x3c4e3c18, 0xbc04bc5c, 0x3b79bc78, 0x3c18bc4e, 0x3c623bf1, 0x3c7f3ac9,
    0xbb95bc75, 0x3c223c46, 0xbac9bc7f, 0xbc75bb95, 0xbc223c46, 0xbbf1bc62, 0xbc463c22, 0x3c623bf1, 0x3c7f3ac9, 0x3b953c75,
    0x3c753b95, 0xbc46bc22, 0xbbf1bc62, 0xbac9bc7f, 0x3c673bdb, 0x3c803a49, 0xbc2cbc3e, 0x3c673bdb, 0xbb79bc78, 0xbc7dbb16,
    0xbb163c7d, 0xbc5cbc04, 0xbc183c4e, 0x3c783b79, 0x3c5cbc04, 0x3c4e3c18, 0x3c80ba49, 0xbc71bbac, 0xbc71bbac, 0xbc3ebc2c,
    0x3c353c35, 0x3c6d3bc4, 0x3c353c35, 0xbc6dbbc4, 0x3c35bc35, 0xbbc4bc6d, 0x3c35bc35, 0x3bc43c6d, 0xbc35bc35, 0xbbc43c6d,
    0xbc35bc35, 0x3bc4bc6d, 0xbc353c35, 0x3c6dbbc4, 0xbc353c35, 0xbc6d3bc4, 0x3c80ba49, 0x3c67bbdb, 0x3c67bbdb, 0xbc2c3c3e,
    0xbb16bc7d, 0xbc78bb79, 0xbc04bc5c, 0x3c7dbb16, 0xbc783b79, 0x3c183c4e, 0xbc4e3c18, 0xbc5cbc04, 0x3bac3c71, 0x3a49bc80,
    0x3c2c3c3e, 0x3bac3c71, 0x3c22bc46, 0x3b95bc75, 0xbac9bc7f, 0x3bf13c62, 0xbc62bbf1, 0xbc463c22, 0xbc753b95, 0x3ac9bc7f,
    0xbb953c75, 0x3c7fbac9, 0x3bf13c62, 0xbc223c46, 0x3c7f3ac9, 0xbc62bbf1, 0x3c46bc22, 0x3c75bb95, 0xbb16bc7d, 0xbc04bc5c,
    0xbc78bb79, 0x3c7dbb16, 0xbc673bdb, 0x3a493c80, 0x3a493c80, 0xbc71bbac, 0x3c2c3c3e, 0x3bdbbc67, 0x3c71bbac, 0x3c2c3c3e,
    0x3c04bc5c, 0xbc4e3c18, 0xbc18bc4e, 0xbb79bc78, 0xbc55bc0e, 0xbc7bbb48, 0xbc0e3c55, 0x3b48bc7b, 0xbb483c7b, 0x3c553c0e,
    0x3c7b3b48, 0xbc0e3c55, 0x3c7bbb48, 0xbc0ebc55, 0xbb48bc7b, 0x3c55bc0e, 0xbc0ebc55, 0x3b483c7b, 0xbc553c0e, 0xbc7b3b48,
    0xbc783b79, 0xbc4e3c18, 0x3c183c4e, 0xbc5cbc04, 0x3c2c3c3e, 0x3c71bbac, 0x3bdbbc67, 0x3c2c3c3e, 0x3bacbc71, 0xbc803a49,
    0xbc803a49, 0xbbdbbc67, 0xbc7d3b16, 0x3c783b79, 0x3c043c5c, 0x3b163c7d, 0xbbf13c62, 0xbac93c7f, 0x3c75bb95, 0xbc463c22,
    0x3c7fbac9, 0x3b95bc75, 0xbc46bc22, 0x3c62bbf1, 0xbc22bc46, 0xbbf13c62, 0xbac93c7f, 0xbc753b95, 0xbb953c75, 0x3c22bc46,
    0x3c62bbf1, 0x3c7fbac9, 0x3bac3c71, 0x3c2c3c3e, 0x3a49bc80, 0x3bac3c71, 0x3c04bc5c, 0xbc18bc4e, 0xbc4e3c18, 0xbb79bc78,
    0xbc7d3b16, 0x3c043c5c, 0x3c783b79, 0x3b163c7d, 0x3c3e3c2c, 0xbbdbbc67, 0xbbdbbc67, 0xba49bc80, 0x3c353c35, 0x3c6d3bc4,
    0x3c353c35, 0xbc6dbbc4, 0x3c35bc35, 0xbbc4bc6d, 0x3c35bc35, 0x3bc43c6d, 0xbc35bc35, 0xbbc43c6d, 0xbc35bc35, 0x3bc4bc6d,
    0xbc353c35, 0x3c6dbbc4, 0xbc353c35, 0xbc6d3bc4, 0x3c2cbc3e, 0x3bacbc71, 0x3bacbc71, 0x3a493c80, 0xbc4ebc18, 0xbc5c3c04,
    0xbc78bb79, 0x3c18bc4e, 0xbc043c5c, 0x3c7d3b16, 0xbb163c7d, 0xbc783b79, 0x3c673bdb, 0xbc2cbc3e, 0x3c803a49, 0x3c673bdb,
    0xbc46bc22, 0xbc75bb95, 0xbc7f3ac9, 0x3c62bbf1, 0xbbf13c62, 0x3c223c46, 0x3b953c75, 0xbc7fbac9, 0x3c753b95, 0xbac9bc7f,
    0x3c62bbf1, 0x3c463c22, 0x3ac9bc7f, 0xbbf13c62, 0xbc22bc46, 0xbb95bc75, 0xbc183c4e, 0xbb793c78, 0x3c043c5c, 0xbc4ebc18,
    0x3c713bac, 0x3c2cbc3e, 0x3c2cbc3e, 0x3bdb3c67, 0x3a49bc80, 0xbc713bac, 0xbc67bbdb, 0x3a49bc80, 0xbc783b79, 0x3c7d3b16,
    0xbb163c7d, 0xbc043c5c, 0x3c553c0e, 0x3c7b3b48, 0x3c0ebc55, 0xbb483c7b, 0x3b48bc7b, 0xbc55bc0e, 0xbc7bbb48, 0x3c0ebc55,
    0xbc7b3b48, 0x3c0e3c55, 0x3b483c7b, 0xbc553c0e, 0x3c0e3c55, 0xbb48bc7b, 0x3c55bc0e, 0x3c7bbb48, 0x3c04bc5c, 0x3b16bc7d,
    0xbc7dbb16, 0x3c78bb79, 0xbc80ba49, 0xbbdb3c67, 0x3bac3c71, 0xbc80ba49, 0x3bdb3c67, 0x3c2cbc3e, 0x3c2cbc3e, 0x3c713bac,
    0x3c18bc4e, 0xbc5c3c04, 0xbc78bb79, 0xbc4ebc18, 0xbc62bbf1, 0xbc7fbac9, 0x3b953c75, 0xbc22bc46, 0x3ac93c7f, 0x3c753b95,
    0x3c22bc46, 0x3bf13c62, 0x3c46bc22, 0xbc62bbf1, 0xbc7fbac9, 0xbb95bc75, 0xbc75bb95, 0x3c463c22, 0x3bf13c62, 0x3ac93c7f,
    0xbbdb3c67, 0xba493c80, 0x3c3ebc2c, 0xbbdb3c67, 0x3c78bb79, 0x3b16bc7d, 0xbc7dbb16, 0x3c04bc5c, 0xbc4ebc18, 0xbb793c78,
    0x3c043c5c, 0xbc183c4e, 0x3a493c80, 0x3bacbc71, 0x3bacbc71, 0x3c2cbc3e, 0x3c353c35, 0x3c6d3bc4, 0x3c353c35, 0xbc6dbbc4,
    0x3c35bc35, 0xbbc4bc6d, 0x3c35bc35, 0x3bc43c6d, 0xbc35bc35, 0xbbc43c6d, 0xbc35bc35, 0x3bc4bc6d, 0xbc353c35, 0x3c6dbbc4,
    0xbc353c35, 0xbc6d3bc4, 0xba49bc80, 0xbbdbbc67, 0xbbdbbc67, 0x3c3e3c2c, 0xbc7d3b16, 0xbb793c78, 0xbc5c3c04, 0xbb16bc7d,
    0x3b793c78, 0x3c4ebc18, 0x3c183c4e, 0xbc043c5c, 0x3c71bbac, 0xbc80ba49, 0x3c3ebc2c, 0x3c71bbac, 0xbc223c46, 0xbb953c75,
    0x3ac93c7f, 0xbbf1bc62, 0x3c623bf1, 0x3c46bc22, 0x3c75bb95, 0xbac93c7f, 0x3b95bc75, 0xbc7f3ac9, 0xbbf1bc62, 0x3c22bc46,
    0xbc7fbac9, 0x3c623bf1, 0xbc463c22, 0xbc753b95, 0x3c7dbb16, 0x3c5cbc04, 0x3b79bc78, 0x3b163c7d, 0xbbdbbc67, 0xbc803a49,
    0xbc803a49, 0x3bacbc71, 0xbc3e3c2c, 0x3c673bdb, 0x3bac3c71, 0xbc3e3c2c, 0x3c5c3c04, 0xbc18bc4e, 0x3c4ebc18, 0x3c78bb79,
    0xbc55bc0e, 0xbc7bbb48, 0xbc0e3c55, 0x3b48bc7b, 0xbb483c7b, 0x3c553c0e, 0x3c7b3b48, 0xbc0e3c55, 0x3c7bbb48, 0xbc0ebc55,
    0xbb48bc7b, 0x3c55bc0e, 0xbc0ebc55, 0x3b483c7b, 0xbc553c0e, 0xbc7b3b48, 0x3b793c78, 0x3c183c4e, 0x3c4ebc18, 0xbc043c5c,
    0x3c3ebc2c, 0xbbacbc71, 0xbc67bbdb, 0x3c3ebc2c, 0xbc71bbac, 0x3a493c80, 0x3a493c80, 0xbc673bdb, 0x3b163c7d, 0x3b79bc78,
    0x3c5cbc04, 0x3c7dbb16, 0x3bf1bc62, 0x3ac9bc7f, 0xbc753b95, 0x3c46bc22, 0xbc7f3ac9, 0xbb953c75, 0x3c463c22, 0xbc623bf1,
    0x3c223c46, 0x3bf1bc62, 0x3ac9bc7f, 0x3c75bb95, 0x3b95bc75, 0xbc223c46, 0xbc623bf1, 0xbc7f3ac9, 0xbc713bac, 0xbc3e3c2c,
    0x3c803a49, 0xbc713bac, 0x3c5c3c04, 0x3c4ebc18, 0xbc18bc4e, 0x3c78bb79, 0xbb16bc7d, 0xbc5c3c04, 0xbb793c78, 0xbc7d3b16,
    0xbc2c3c3e, 0x3c67bbdb, 0x3c67bbdb, 0x3c80ba49, 0x3c800000, 0x3c6dbbc4, 0x3c800000, 0xbc6d3bc4, 0xbc800000, 0xbbc43c6d,
    0xbc800000, 0x3bc4bc6d, 0x3c800000, 0xbbc4bc6d, 0x3c800000, 0x3bc43c6d, 0xbc800000, 0x3c6d3bc4, 0xbc800000, 0xbc6dbbc4,
    0x3c80ba49, 0x3c67bbdb, 0x3c67bbdb, 0xbc2c3c3e, 0xbc7d3b16, 0xbb793c78, 0xbc5c3c04, 0xbb16bc7d, 0x3c78bb79, 0xbc18bc4e,
    0x3c4ebc18, 0x3c5c3c04, 0xbc713bac, 0x3c803a49, 0xbc3e3c2c, 0xbc713bac, 0x3c7fbac9, 0x3c62bbf1, 0x3c22bc46, 0xbb953c75,
    0xbc753b95, 0xbac93c7f, 0xbbf13c62, 0xbc22bc46, 0x3c62bbf1, 0xbc46bc22, 0x3b95bc75, 0x3c7fbac9, 0xbc463c22, 0x3c75bb95,
    0xbac93c7f, 0xbbf13c62, 0x3c7dbb16, 0x3c5cbc04, 0x3b79bc78, 0x3b163c7d, 0xbc673bdb, 0x3a493c80, 0x3a493c80, 0xbc71bbac,
    0x3c3ebc2c, 0xbc67bbdb, 0xbbacbc71, 0x3c3ebc2c, 0xbc043c5c, 0x3c4ebc18, 0x3c183c4e, 0x3b793c78, 0x3c7bbb48, 0x3c55bc0e,
    0xbb48bc7b, 0x3c0e3c55, 0xbc553c0e, 0x3b483c7b, 0x3c0e3c55, 0xbc7b3b48, 0x3c0ebc55, 0xbc7bbb48, 0xbc55bc0e, 0x3b48bc7b,
    0xbb483c7b, 0x3c0ebc55, 0x3c7b3b48, 0x3c553c0e, 0x3c78bb79, 0x3c4ebc18, 0xbc18bc4e, 0x3c5c3c04, 0xbc3e3c2c, 0x3bac3c71,
    0x3c673bdb, 0xbc3e3c2c, 0x3bacbc71, 0xbc803a49, 0xbc803a49, 0xbbdbbc67, 0x3b163c7d, 0x3b79bc78, 0x3c5cbc04, 0x3c7dbb16,
    0x3c75bb95, 0x3c46bc22, 0xbc62bbf1, 0x3c7f3ac9, 0xbc223c46, 0x3bf13c62, 0x3c7fbac9, 0xbb953c75, 0x3ac9bc7f, 0xbc753b95,
    0xbc463c22, 0xbc62bbf1, 0x3bf13c62, 0xbac9bc7f, 0x3b95bc75, 0x3c22bc46, 0x3c71bbac, 0x3c3ebc2c, 0xbc80ba49, 0x3c71bbac,
    0xbc043c5c, 0x3c183c4e, 0x3c4ebc18, 0x3b793c78, 0xbb16bc7d, 0xbc5c3c04, 0xbb793c78, 0xbc7d3b16, 0x3c3e3c2c, 0xbbdbbc67,
    0xbbdbbc67, 0xba49bc80, 0x3c800000, 0x3c6dbbc4, 0x3c800000, 0xbc6d3bc4, 0xbc800000, 0xbbc43c6d, 0xbc800000, 0x3bc4bc6d,
    0x3c800000, 0xbbc4bc6d, 0x3c800000, 0x3bc43c6d, 0xbc800000, 0x3c6d3bc4, 0xbc800000, 0xbc6dbbc4, 0x3c2cbc3e, 0x3bacbc71,
    0x3bacbc71, 0x3a493c80, 0xbc183c4e, 0x3c043c5c, 0xbb793c78, 0xbc4ebc18, 0x3c04bc5c, 0xbc7dbb16, 0x3b16bc7d, 0x3c78bb79,
    0xbbdb3c67, 0x3c3ebc2c, 0xba493c80, 0xbbdb3c67, 0xbac9bc7f, 0xbbf1bc62, 0xbc46bc22, 0x3c753b95, 0x3b953c75, 0x3c7f3ac9,
    0x3c623bf1, 0xbc463c22, 0xbbf1bc62, 0xbc223c46, 0xbc75bb95, 0xbac9bc7f, 0x3c223c46, 0xbb95bc75, 0x3c7f3ac9, 0x3c623bf1,
    0xbc4ebc18, 0xbc78bb79, 0xbc5c3c04, 0x3c18bc4e, 0x3c713bac, 0x3c2cbc3e, 0x3c2cbc3e, 0x3bdb3c67, 0xbc80ba49, 0x3bac3c71,
    0xbbdb3c67, 0xbc80ba49, 0x3c78bb79, 0xbc7dbb16, 0x3b16bc7d, 0x3c04bc5c, 0xbc7b3b48, 0xbc553c0e, 0x3b483c7b, 0xbc0ebc55,
    0x3c55bc0e, 0xbb48bc7b, 0xbc0ebc55, 0x3c7bbb48, 0xbc0e3c55, 0x3c7b3b48, 0x3c553c0e, 0xbb483c7b, 0x3b48bc7b, 0xbc0e3c55,
    0xbc7bbb48, 0xbc55bc0e, 0xbc043c5c, 0xbb163c7d, 0x3c7d3b16, 0xbc783b79, 0x3a49bc80, 0xbc67bbdb, 0xbc713bac, 0x3a49bc80,
    0x3bdb3c67, 0x3c2cbc3e, 0x3c2cbc3e, 0x3c713bac, 0xbc4ebc18, 0x3c043c5c, 0xbb793c78, 0xbc183c4e, 0x3b953c75, 0x3c223c46,
    0x3bf1bc62, 0xbac93c7f, 0xbc46bc22, 0xbc623bf1, 0x3ac93c7f, 0xbc75bb95, 0x3c7f3ac9, 0xbb95bc75, 0xbc22bc46, 0x3bf1bc62,
    0xbc623bf1, 0x3c7fbac9, 0x3c753b95, 0x3c463c22, 0x3c673bdb, 0x3c803a49, 0xbc2cbc3e, 0x3c673bdb, 0xbc783b79, 0xbb163c7d,
    0x3c7d3b16, 0xbc043c5c, 0x3c18bc4e, 0xbc78bb79, 0xbc5c3c04, 0xbc4ebc18, 0x3a493c80, 0x3bacbc71, 0x3bacbc71, 0x3c2cbc3e,
    0x3c800000, 0x3c6dbbc4, 0x3c800000, 0xbc6d3bc4, 0xbc800000, 0xbbc43c6d, 0xbc800000, 0x3bc4bc6d, 0x3c800000, 0xbbc4bc6d,
    0x3c800000, 0x3bc43c6d, 0xbc800000, 0x3c6d3bc4, 0xbc800000, 0xbc6dbbc4, 0xba49bc80, 0xbbdbbc67, 0xbbdbbc67, 0x3c3e3c2c,
    0x3b163c7d, 0x3c783b79, 0x3c043c5c, 0xbc7d3b16, 0xbb79bc78, 0xbc4e3c18, 0xbc18bc4e, 0x3c04bc5c, 0x3bac3c71, 0x3a49bc80,
    0x3c2c3c3e, 0x3bac3c71, 0xbc7f3ac9, 0xbc623bf1, 0xbc223c46, 0x3b95bc75, 0x3c75bb95, 0x3ac9bc7f, 0x3bf1bc62, 0x3c223c46,
    0xbc623bf1, 0x3c463c22, 0xbb953c75, 0xbc7f3ac9, 0x3c46bc22, 0xbc753b95, 0x3ac9bc7f, 0x3bf1bc62, 0x3b163c7d, 0x3c043c5c,
    0x3c783b79, 0xbc7d3b16, 0xbbdbbc67, 0xbc803a49, 0xbc803a49, 0x3bacbc71, 0x3c2c3c3e, 0x3bdbbc67, 0x3c71bbac, 0x3c2c3c3e,
    0xbc5cbc04, 0x3c183c4e, 0xbc4e3c18, 0xbc783b79, 0x3c7bbb48, 0x3c55bc0e, 0xbb48bc7b, 0x3c0e3c55, 0xbc553c0e, 0x3b483c7b,
    0x3c0e3c55, 0xbc7b3b48, 0x3c0ebc55, 0xbc7bbb48, 0xbc55bc0e, 0x3b48bc7b, 0xbb483c7b, 0x3c0ebc55, 0x3c7b3b48, 0x3c553c0e,
    0xbb79bc78, 0xbc18bc4e, 0xbc4e3c18, 0x3c04bc5c, 0x3c2c3c3e, 0x3c71bbac, 0x3bdbbc67, 0x3c2c3c3e, 0xbc71bbac, 0x3a493c80,
    0x3a493c80, 0xbc673bdb, 0x3c7dbb16, 0xbc78bb79, 0xbc04bc5c, 0xbb16bc7d, 0xbc753b95, 0xbc463c22, 0x3c623bf1, 0xbc7fbac9,
    0x3c22bc46, 0xbbf1bc62, 0xbc7f3ac9, 0x3b95bc75, 0xbac93c7f, 0x3c75bb95, 0x3c46bc22, 0x3c623bf1, 0xbbf1bc62, 0x3ac93c7f,
    0xbb953c75, 0xbc223c46, 0x3bac3c71, 0x3c2c3c3e, 0x3a49bc80, 0x3bac3c71, 0xbc5cbc04, 0xbc4e3c18, 0x3c183c4e, 0xbc783b79,
    0x3c7dbb16, 0xbc04bc5c, 0xbc78bb79, 0xbb16bc7d, 0xbc2c3c3e, 0x3c67bbdb, 0x3c67bbdb, 0x3c80ba49, 0x3c800000, 0x3c6dbbc4,
    0x3c800000, 0xbc6d3bc4, 0xbc800000, 0xbbc43c6d, 0xbc800000, 0x3bc4bc6d, 0x3c800000, 0xbbc4bc6d, 0x3c800000, 0x3bc43c6d,
    0xbc800000, 0x3c6d3bc4, 0xbc800000, 0xbc6dbbc4, 0xbc3ebc2c, 0xbc71bbac, 0xbc71bbac, 0x3c80ba49, 0x3c4e3c18, 0x3c5cbc04,
    0x3c783b79, 0xbc183c4e, 0xbc5cbc04, 0xbb163c7d, 0xbc7dbb16, 0xbb79bc78, 0x3c673bdb, 0xbc2cbc3e, 0x3c803a49, 0x3c673bdb,
    0x3ac93c7f, 0x3bf13c62, 0x3c463c22, 0xbc75bb95, 0xbb95bc75, 0xbc7fbac9, 0xbc62bbf1, 0x3c46bc22, 0x3bf13c62, 0x3c22bc46,
    0x3c753b95, 0x3ac93c7f, 0xbc22bc46, 0x3b953c75, 0xbc7fbac9, 0xbc62bbf1, 0x3c18bc4e, 0x3b79bc78, 0xbc04bc5c, 0x3c4e3c18,
    0xbbac3c71, 0x3c3e3c2c, 0x3c3e3c2c, 0xbc673bdb, 0x3a49bc80, 0xbc713bac, 0xbc67bbdb, 0x3a49bc80, 0x3b793c78, 0x3b16bc7d,
    0x3c7d3b16, 0x3c5c3c04, 0xbc7b3b48, 0xbc553c0e, 0x3b483c7b, 0xbc0ebc55, 0x3c55bc0e, 0xbb48bc7b, 0xbc0ebc55, 0x3c7bbb48,
    0xbc0e3c55, 0x3c7b3b48, 0x3c553c0e, 0xbb483c7b, 0x3b48bc7b, 0xbc0e3c55, 0xbc7bbb48, 0xbc55bc0e, 0x3c5c3c04, 0x3c7d3b16,
    0x3b16bc7d, 0x3b793c78, 0xbc80ba49, 0xbbdb3c67, 0x3bac3c71, 0xbc80ba49, 0x3c67bbdb, 0xbc3ebc2c, 0xbc3ebc2c, 0x3bacbc71,
    0xbc183c4e, 0x3c5cbc04, 0x3c783b79, 0x3c4e3c18, 0xbb95bc75, 0xbc22bc46, 0xbbf13c62, 0x3ac9bc7f, 0x3c463c22, 0x3c62bbf1,
    0xbac9bc7f, 0x3c753b95, 0xbc7fbac9, 0x3b953c75, 0x3c223c46, 0xbbf13c62, 0x3c62bbf1, 0xbc7f3ac9, 0xbc75bb95, 0xbc46bc22,
    0xbbdb3c67, 0xba493c80, 0x3c3ebc2c, 0xbbdb3c67, 0xbb79bc78, 0xbc7dbb16, 0xbb163c7d, 0xbc5cbc04, 0x3c4e3c18, 0x3b79bc78,
    0xbc04bc5c, 0x3c18bc4e, 0xbc803a49, 0x3c713bac, 0x3c713bac, 0x3c3e3c2c,
};

template <int G = 1024> __device__ __forceinline__ void store_tile_64(const float (&d)[32], uint32_t base, int warp, int lane) {
  const uint32_t rb = base + (warp * 2 + ((lane >> 3) & 1)) * G + (lane & 7) * 128;
#pragma unroll
  for (int j = 0; j < 8; j += 2) {
    const int jj = j + (lane >> 4);
    stsm4(rb + ((jj ^ (lane & 7)) << 4), pack2(d[4 * j], d[4 * j + 1]), pack2(d[4 * j + 2], d[4 * j + 3]),
          pack2(d[4 * j + 4], d[4 * j + 5]), pack2(d[4 * j + 6], d[4 * j + 7]));
  }
}

#define A_XM0 0xEB5C
#define A_XM1 0xDCBC
#define A_REL 0x22910
#define G_WPOLK 12
#define A_LDW 0x242
#define A_W2PF 2
#define A_DEPS 4
#define A_FREE 0x3F000
#define A_RELS 0x8A80
#define A_ACQ 0x1511
#define A_DEP 3
#define A_PACE0 1000
#define A_PACE1 A_PACE0
#define A_PACE_N 8
#define G_TMASK 0x0FB0
constexpr int A_IN = 112 * 128, A_OUT = 16384, A_NIN = 5, A_NOUT = 6;
constexpr int A_NREL = __builtin_popcount(A_REL);
constexpr int G_XP = NB1 * 64;
constexpr int G_STAGE = 16384 + 2 * G_XP, G_NST = 5;
constexpr int G_TIN = G_NST * G_STAGE, G_TOUT = G_TIN + 8192, G_SMEM = G_TOUT + 32768;
#define G_SLOTS 0x1032410324103210ull
__host__ __device__ constexpr int g_slot(int k) { return (G_SLOTS >> (4 * k)) & 7; }
constexpr uint32_t g_parities() {
  uint32_t m = 0;
  for (int k = 0; k < 16; k++)
    for (int j = 0; j < k; j++)
      if (g_slot(j) == g_slot(k)) m ^= 1u << k;
  return m;
}
constexpr uint32_t G_PAR = g_parities();
constexpr int G_KS = 12;
#define G_KI 14
#define G_KC 2
#define G_HOLDB 1
template <int N> using IC = std::integral_constant<int, N>;
__device__ __align__(128) int g_cnt[4 * 32];

__device__ __forceinline__ int x_decode(int r, int cta) {
  const int v = r * 64 + ((cta >> 2) << 1) + (cta & 1);
  int j = v / 80;
  j -= v < 80 * j + ((0x4840 >> (4 * j)) & 15);
  if (cta < 128) return ((7 - j) << 7) | (v - 80 * j - ((0x4840 >> (4 * j)) & 15));
  return r < 8 ? ((5 - (r >> 2)) << 7) | (76 + 4 * (cta & 1) + (r & 3)) : ((7 - (r >> 1)) << 7) | (80 + 2 * (cta & 1) + (r & 1));
}
__device__ __forceinline__ uint32_t a_out(int n) {
  const int p = n % A_NOUT;
  return (p < 4 ? (3 + (p >> 1)) * G_STAGE : G_TOUT) + (p & 1) * A_OUT;
}
__device__ __forceinline__ uint32_t x1_addr(int L, int b, uint32_t flips) {
  const int p = L >> 4, sel = (b ^ __popc(L & 15) ^ (flips >> p)) & 1;
  return (p << 21) | (sel << 12) | ((L & 1) << 13) | ((L & 6) << 15) | ((L & 8) << 16);
}
__device__ __forceinline__ uint32_t spread16(int i) { return ((i & 3) << 14) | ((i & 4) << 16) | ((i & 8) << 17); }
constexpr int NPG = 19 + W_SHIFT, NVOTE = 6;
__device__ __forceinline__ uint32_t w_addr(int P, int f, int c, int dhalf, uint32_t flips) {
  return x1_addr(16 * P + (c >> 5) + 2 * (f >> 3), dhalf, flips >> 12) + spread16(2 * f) + (c & 31) * 128;
}
__device__ __forceinline__ void w_store(const CUtensorMap* m, uint32_t src, uint32_t a) {
#pragma unroll
  for (int j = 0; j < 8; j++)
    tma_st5<0>(m, src + j * 2048, ((a & 16383) >> 1) ^ ((__popc(j) & 1) << 11), (j & 3) << 1, (j >> 2) << 1, a >> 20, 0);
}
__device__ __forceinline__ uint32_t read_votes(const int* cnt, int lane, int v) {
#pragma unroll 1
  for (int it = 0; it < (1 << 20) && (__ballot_sync(0xffffffffu, v < NVOTE * 256) & ((2 << NPG) - 2)); it++)
    asm volatile("ld.relaxed.gpu.global.s32 %0, [%1];" : "=r"(v) : "l"(cnt + 32 + lane) : "memory");
  return __ballot_sync(0xffffffffu, (v & 255) > NVOTE / 2);
}
__device__ __forceinline__ int take_ticket(int* p) {
  int v;
  asm volatile("atom.relaxed.gpu.global.inc.u32 %0, [%1], 0x7fffffff;" : "=r"(v) : "l"(p) : "memory");
  return v;
}
__device__ __forceinline__ void send_role(uint32_t dst, uint32_t bar, int v) {
  for (int c = 0; c < 2; c++)
    asm volatile("{\n.reg .b32 a, b;\nmapa.shared::cluster.u32 a, %0, %2;\nmapa.shared::cluster.u32 b, %1, %2;\n"
                 "st.async.shared::cluster.mbarrier::complete_tx::bytes.u32 [a], %3, [b];\n}" ::"r"(dst), "r"(bar), "r"(c), "r"(v) : "memory");
}
struct GMaps {
  CUtensorMap in[5];
  CUtensorMap ws, xs, w, y;
  CUtensorMap y1[2], x2s, x2, w2, y2;
};

#define H_EPI 3
#define H_KS 11
#define C_PACE 300
#define C_ORD 1
#define H_HOLD 5
#define C_POL 1
constexpr int H_XP = 168 * 64, H_STAGE = 8192 + 2 * H_XP, H_NST = 7;
constexpr int C_OUT = 7 * 8192, C_GI = 13 * 8192, C_F = C_GI + 6144, C_PIECE = C_F + 8192;
static_assert(C_GI >= 3 * H_STAGE && C_PIECE + C_OUT == 6 * H_STAGE, "slots 0..2 | 3..5 | 6 fall free together");
constexpr int G_IM1 = C_GI - NB1 * 128;

template <int WG>
__device__ __forceinline__ void h_loop(float (&acc)[84], uint32_t sb, uint32_t full0, uint32_t empty0, int lane) {
#pragma unroll 1
  for (int k = 0; k < 16; k++) {
    const int st = k % H_NST;
    if (WG == 1 && k == H_KS) bar_sync(4, 256);
    mbar_wait(full0 + 8 * st, (k / H_NST) & 1);
    const uint32_t base = sb + st * H_STAGE;
    wg_fence();
#pragma unroll
    for (int s = 0; s < 2; s++) {
      const uint64_t dP = mk_desc(base, s * 2048, 0, 1024, 1), dQ = mk_desc(base, 4096 + s * 2048, 0, 1024, 1);
      const uint64_t dA = mk_desc(base, 8192 + s * 32, 0, 512, 2), dB = mk_desc(base, 8192 + H_XP + s * 32, 0, 512, 2);
      wgmma_ss_168<1, 1, 1, 0>(acc, dP, WG == 0 ? dA : dB, k | s);
      wgmma_ss_168<WG == 0 ? 1 : -1, 1, 1, 0>(acc, dQ, WG == 0 ? dB : dA, 1);
    }
    wg_commit();
    if (WG == 0 && k == 15) bar_arrive(4, 256);
    if (k <= 10) {
      wg_wait<1>();
      if (k > 0 && k - 1 + H_NST < 16 && lane < 2) mbar_arrive_cta(empty0 + 8 * ((k - 1) % H_NST), lane);
    }
  }
  wg_wait<0>();
  reg_fence(acc);
}

template <int N> __device__ __forceinline__ void gelu_pack(uint32_t* hp, float (&h)[N], bool zero_first, bool zero_all) {
  reg_fence(h);
#pragma unroll
  for (int c = 0; c < N / 2; c++) {
    const uint32_t v = pack2(gelu(h[2 * c]), gelu(h[2 * c + 1]));
    hp[c] = zero_all || (zero_first && c < 2) ? 0u : v;
  }
#pragma unroll
  for (int c = 0; c < N / 2; c++) asm volatile("" : "+r"(hp[c])::"memory");
}
__device__ __forceinline__ void poll_ge(const int* p, int target) {
  int v = 0;
#pragma unroll 1
  for (int it = 0; it < (1 << 20) && v < target; it++)
    asm volatile("ld.relaxed.gpu.global.s32 %0, [%1];" : "=r"(v) : "l"(p) : "memory");
  asm volatile("fence.acquire.gpu;\nfence.proxy.async.global;" ::: "memory");
}

__global__ void __cluster_dims__(2, 1, 1) __launch_bounds__(384, 1)
kG(int* __restrict__ cnt, char* __restrict__ x1, char* __restrict__ wt, const __nv_bfloat16* __restrict__ g,
   const __nv_bfloat16* __restrict__ wgt, float* __restrict__ ge, const uint32_t* __restrict__ img, const __nv_bfloat16* __restrict__ wf,
   const __nv_bfloat16* __restrict__ wo, const uint32_t* __restrict__ gat, const __grid_constant__ GMaps m) {
  extern __shared__ __align__(1024) uint8_t smem_raw[];
  __shared__ __align__(8) uint64_t bars[20 + A_NIN + 2 * A_NOUT + 2 * G_NST + 16 + 2 * A_NREL + 2 * H_NST + 43];
  __shared__ uint16_t tab[128];
  __shared__ uint32_t lat[8], s_role, s_flips;
  const uint32_t sb = pin(s2u(smem_raw));
  const int tid = threadIdx.x, wg = __shfl_sync(0xffffffffu, tid >> 7, 0), t = tid & 127;
  const int warp = __shfl_sync(0xffffffffu, t >> 5, 0), lane = t & 31;
  const int blk = blockIdx.x, hf = blk & 1, page = 1 + blk % NPG;
  const bool spare = blk >= 128, voter = blk >= 128 - NPG * NVOTE && !spare;
  const int nu = spare ? 16 : 18;
  const uint32_t xm = spare ? 0xFFFF : hf ? A_XM1 : A_XM0;
  const uint32_t wf0 = pin(s2u(&bars[0])), xf0 = wf0 + 32, xe0 = xf0 + 128, aof0 = xe0 + 8 * A_NIN, aoe0 = aof0 + 8 * A_NOUT;
  const uint32_t full0 = aoe0 + 8 * A_NOUT, empty0 = full0 + 8 * G_NST;
  const uint32_t sf0 = empty0 + 8 * G_NST, se0 = sf0 + 16, inf0 = se0 + 16, roleb = inf0 + 16, flipb = roleb + 8;
  const uint32_t rel0 = flipb + 8, got0 = rel0 + 8 * A_NREL, acq0 = got0 + 64;
  const uint32_t hf0 = acq0 + 8 * A_NREL, he0 = hf0 + 8 * H_NST, yo0 = he0 + 8 * H_NST, of0 = yo0 + 96, yf0 = of0 + 96;
  const uint32_t gdone = yf0 + 64, imgb = gdone + 8, rly0 = imgb + 8, depb = rly0 + 32, puby = depb + 8, pubb = puby + 16;
  auto role = [&]() {
    mbar_wait(roleb, 0);
    return 2 * (int)*(volatile uint32_t*)&s_role + hf;
  };
  auto flips = [&]() {
    mbar_wait(flipb, 0);
    return *(volatile uint32_t*)&s_flips;
  };
  auto w_unit = [&](int cta) { return (cta & ~3) | (hf << 1) | ((cta >> 1) & 1); };
  auto w_code = [](int w2, int s, int i) { return (-(s < 4) << 16) | ((2 * w2 + (s >> 2)) << 11) | ((s & 3) << 9) | ((i >> 1) << 3) | ((i & 1) << 1); };
  auto in_load = [&](int c, uint32_t dst, uint32_t bar) {
    tma_ld5<1>(dst, &m.in[(c >> 11) & 7], bar, 0, c >> 16, c & 7, (c >> 3) & 63, (c >> 9) & 3);
  };
  auto y_store = [&](int w, int cta, uint32_t fl) {
    const int bin = cta >> 2, L = 4 * hf + 2 * w + (bin >> 4);
    const uint32_t sel = __ballot_sync(0xffffffffu, x1_addr(96 + 8 * lane + L, (cta >> 1) & 1, fl) & 4096);
#pragma unroll 1
    for (int q = 0; q < 2; q++) {
      const uint32_t stg = sb + (w == 0 ? 4 * G_STAGE + q * NB1 * 128 : q == 0 ? G_TOUT : G_IM1);
      const int c0 = ((L & 1) << 12) + (bin & 15) * 128 + q * 64;
#pragma unroll
      for (int c = 0; c < 3; c++) {
        mbar_wait(yo0 + 8 * (6 * w + 3 * q + c), 0);
        if (lane == 0) {
#pragma unroll
          for (int j = 4 * c; j < 4 * c + 4 && j < 11; j++)
            tma_st4<0>(j == 10 ? &m.y : &m.xs, stg + j * 2048, c0 + (((sel >> j) & 1) << 11), (L & 6) << 1, 2 * (j & 1), 12 + (j & ~1));
        }
        __syncwarp();
      }
    }
    bulk_commit();
    bulk_wait<0>();
    if (lane == 0) mbar_arrive(rly0 + 8 * w);
  };
  if (wg < 2) {
    if (lane == 0) {
      const uint32_t h = blk & 0x59, par = h ^ (h >> 3) ^ (h >> 4) ^ (h >> 6);
      char* p = x1 + (blk << 13) + (((warp ^ par) & 1) << 12) + 3584 + (warp >> 1) * 128;
      if (wg) {
        if (!voter) p += 256;
        else if (page < 12) p += page << 21;
        else p = wt + w_addr(page - 12, warp >> 1, blk >> 1, warp & 1, 0);
      }
      uint32_t c0, c1;
      asm volatile("{\n.reg .u32 v;\n.reg .pred q;\n"
                   "st.global.v4.u32 [%2], {0, 0, 0, 0};\nst.global.v4.u32 [%2 + 16], {0, 0, 0, 0};\n"
                   "mov.u32 %0, %%clock;\nmov.u32 %1, %0;\natom.relaxed.gpu.global.exch.b32 v, [%2], 1;\n"
                   "setp.eq.u32 q, v, 0;\n@q mov.u32 %1, %%clock;\n}\n" : "=r"(c0), "=r"(c1) : "l"(p) : "memory");
      lat[wg * 4 + warp] = c1 - c0;
    }
    __syncwarp();
    if (wg == 0 && hf == 0) bar_arrive(10, 160);
    bar_arrive(9, 288);
  }
  if (wg == 2) {
    if (t == 32) {
      mbar_init(wf0 + 24, 1);
      mbar_expect(wf0 + 24, 8192);
      fence_async();
      if (!spare) tma_ld5<1>(sb + 2 * G_STAGE + 3 * 8192, &m.in[1], wf0 + 24, 0, 0, 2 * hf, blk >> 1, 2);
    }
    __syncwarp();
    int votes = 0;
    if (warp == 3 && !voter) asm volatile("ld.relaxed.gpu.global.s32 %0, [%1];" : "=r"(votes) : "l"(cnt + 32 + lane) : "memory");
    asm volatile("setmaxnreg.dec.sync.aligned.u32 40;");
    if (lane == 0 && warp > 0) {
      if (warp == 1) {
        for (int i = 0; i < 3; i++) {
          mbar_init(wf0 + 8 * i, 1);
          mbar_expect(wf0 + 8 * i, 8192);
        }
      } else if (warp == 2) {
        prefetch_map(&m.in[4]);
        for (int i = 0; i < A_NIN + A_NOUT; i++) mbar_init(xe0 + 8 * i, 4);
        for (int i = 0; i < A_NOUT; i++) mbar_init(aoe0 + 8 * i, 1);
      } else {
        for (int i = 0; i < 2; i++) mbar_init(sf0 + 8 * i, 8);
        for (int i = 0; i < 6 + A_NREL; i++) mbar_init(se0 + 8 * i, 1);
        for (int i = 0; i < 3; i++) mbar_expect(inf0 + 8 * i, i < 2 ? 4096 : 4);
      }
      fence_bar_init();
    }
    __syncwarp();
    asm volatile("barrier.cluster.arrive.relaxed.aligned;" ::: "memory");
    int role_w = warp;
    if (role_w == 0) {
      int cta = blk, side = 0;
      if (hf == 0) {
        bar_sync(10, 160);
        side = min(lat[0], lat[2]) > min(lat[1], lat[3]);
        if (lane == 0) cta = take_ticket(cnt + (spare ? 62 : 54) + side);
      }
      const uint32_t wm = spare ? 0 : A_LDW | 0x6000;
      const int nw = __popc(wm & ((1 << lane) - 1)), r = lane - nw, np = r + A_NIN - (spare ? A_DEPS : A_DEP);
      const bool isw = (wm >> lane) & 1;
      uint32_t dst = sb + (!isw ? (r % A_NIN) * A_IN : nw < 3 ? 2 * G_STAGE + (2 - nw) * 8192 : G_TIN + (nw - 3) * 4096);
      uint32_t bf = !isw ? xf0 + 8 * r : nw < 3 ? wf0 + 8 * (2 - nw) : inf0 + 8 * (nw - 3);
      uint32_t be = isw ? roleb : xe0 + 8 * (np % A_NIN) + ((np / A_NIN - 1) & 1);
      asm volatile("barrier.cluster.wait.aligned;" : "+r"(dst), "+r"(bf), "+r"(be)::"memory");
      if (hf == 0) {
        cta = 2 * __shfl_sync(0xffffffffu, cta, 0) + side;
        if (cta >= 64) cta = 127 - cta;
        if (spare) cta = 64 + (cta >= 2 ? 3 - cta : cta);
        if (lane == 0) send_role(s2u(&s_role), roleb, cta);
        cta *= 2;
      } else {
        cta = role();
      }
      const int b = (cta >> 1) & 1;
      if (lane == 0 && !spare) tma_ld5<1>(sb, &m.in[4], xf0, 0, 96 * (((cta >> 2) << 1) + hf) - 24, 7, 0, b);
      __syncwarp();
      const int xc = x_decode(r, cta);
      const int code = isw ? w_code(nw >= 3, nw < 3 ? 4 - 2 * nw : 10 - nw, w_unit(cta)) : ((96 * (xc & 127) - 24) << 16) | (4 << 11) | (b << 9) | (xc >> 7);
#pragma unroll 1
      for (int p = !spare; p < (spare ? 16 : 15); p++) {
        const int c = __shfl_sync(0xffffffffu, code, p);
        const uint32_t d = __shfl_sync(0xffffffffu, dst, p), f = __shfl_sync(0xffffffffu, bf, p), e = __shfl_sync(0xffffffffu, be, p);
        mbar_wait(e & ~1u, e & 1);
        if (lane == 0) in_load(c, d, f);
        __syncwarp();
      }
      if (!spare) {
        const int bin = cta >> 2, f = 2 * bin + hf;
        if (lane == 0) {
          for (int s = 5; s >= A_W2PF; s--) {
            const int c = w_code(1, s, w_unit(cta));
            asm volatile("cp.async.bulk.prefetch.tensor.5d.L2.global [%0, {0, %1, %2, %3, %4}];" ::"l"(&m.in[(c >> 11) & 7]), "r"(c >> 16), "r"(c & 7), "r"((c >> 3) & 63), "r"((c >> 9) & 3) : "memory");
          }
          prefetch_map(&m.w);
          prefetch_map(&m.y);
          prefetch_map(&m.in[2]);
        }
        const uint32_t xa = x1_addr((21 - lane + 2 * (lane % 3)) * 8 + (f >> 4), b, flips()) + spread16(f);
        const uint32_t wa = w_addr(7 - (lane >> 1), 2 * bin, (lane & 1) * 32, hf, s_flips & ~0xC0000u);
#pragma unroll 1
        for (int k = 0; k < 16; k++) {
          const int st = g_slot(k);
          uint32_t a[3];
#pragma unroll
          for (int th = 0; th < 3; th++) a[th] = __shfl_sync(0xffffffffu, xa, 3 * (k >> 1) + th) ^ ((k & 1) * 0x21000);
          const uint32_t w = __shfl_sync(0xffffffffu, wa, k);
          if ((A_ACQ >> k) & 1) {
            mbar_wait(acq0 + 8 * __popc(A_ACQ & ((1 << k) - 1)), 0);
            asm volatile("fence.proxy.async.global;" ::: "memory");
          }
          mbar_wait(empty0 + 8 * st, (G_PAR >> k) & 1);
          if (lane == 0) {
            const uint32_t base = sb + st * G_STAGE, bar = full0 + 8 * st;
            mbar_expect(bar, G_STAGE);
#pragma unroll
            for (int th = 0; th < 3; th++)
              asm volatile("cp.async.bulk.shared::cluster.global.mbarrier::complete_tx::bytes.multicast::cluster.L2::cache_hint [%0], [%1], %2, [%3], %4, %5;"
                           ::"r"(base + 16384 + hf * G_XP + th * 3584), "l"(x1 + a[th]), "n"(3584), "r"(bar), "h"((uint16_t)3), "l"(policy<1>()) : "memory");
            if (k >= G_WPOLK) tma_ld3<1>(base, &m.w, bar, 0, (w >> 7) & 127, w >> 14);
            else tma_ld3<0>(base, &m.w, bar, 0, (w >> 7) & 127, w >> 14);
          }
          __syncwarp();
        }
        if (lane == 0) {
          if (blk == 0) asm volatile("cp.async.bulk.prefetch.L2.global [%0], 14336;" ::"l"(img) : "memory");
          prefetch_map(&m.y1[0]);
          prefetch_map(&m.y1[1]);
          prefetch_map(&m.x2s);
          prefetch_map(&m.x2);
          prefetch_map(&m.w2);
          prefetch_map(&m.y2);
        }
        mbar_wait(got0 + 24, 0);
        y_store(0, cta, s_flips);
        const int pl = lane >= 7, yb = min(6 * (bin - 4 * pl) + lane - 7 * pl, NB1 - 1);
        const uint32_t ya = x1_addr(96 + 8 * (yb >> 4) + 4 * hf + 2 * pl, b, s_flips) + spread16(yb);
        mbar_wait(gdone, 0);
        if (lane == 0)
          asm volatile("cp.async.bulk.shared::cluster.global.mbarrier::complete_tx::bytes [%0], [%1], 14336, [%2];"
                       ::"r"(sb + C_GI), "l"(img), "r"(imgb) : "memory");
#pragma unroll 1
        for (int p = bin >= 28; p < 2; p++) {
          uint32_t a[7];
#pragma unroll
          for (int i = 0; i < 7; i++) a[i] = __shfl_sync(0xffffffffu, ya, 7 * p + i);
          poll_ge(cnt + 64 + 2 * b + p, 64);
          if (lane == 0 && (p == 0 || bin >= 4)) {
#pragma unroll
            for (int i = 0; i < 7; i++) tma_ld3<C_POL>(sb + p * C_PIECE + i * 8192, &m.y1[(a[i] >> 12) & 1], yf0 + 32 * p + 8 * ((i + 1) >> 1), 0, a[i] >> 7, 0);
          }
          __syncwarp();
        }
        if (lane == 0) mbar_arrive(depb);
        mbar_wait(pubb, 0);
        int st = 0;
#pragma unroll 1
        for (int k = 0; k < 16; k++) {
          if ((k & 7) == 0) {
            poll_ge(cnt + 96 + (k >> 3), 112);
          }
          if (k == H_HOLD) mbar_wait(pubb + 8, 0);
          mbar_wait(he0 + 8 * st, (k >= H_NST) ^ (k >= 2 * H_NST));
          if (lane == 0) tma_ld3mc<0>(sb + st * H_STAGE + 8192 + hf * H_XP, &m.x2, hf0 + 8 * st, (k & 1) * 32, 0, ((k & 6) + (k >> 3)) * 64 + f);
          __syncwarp();
          if (++st == H_NST) st = 0;
        }
      }
    } else if (pin(warp) == 1) {
      if (lane == 0) {
        prefetch_map(&m.ws);
        prefetch_map(&m.xs);
        prefetch_map(&m.in[0]);
        prefetch_map(&m.in[3]);
        for (int i = 0; i < 24; i++) mbar_init(yo0 + 8 * i, 4);
        for (int i = 0; i < 8; i++) {
          mbar_init(yf0 + 8 * i, 1);
          mbar_expect(yf0 + 8 * i, i & 3 ? 16384 : 8192);
        }
        mbar_init(gdone, 8);
        for (int i = 0; i < 10; i++) mbar_init(imgb + 8 * i, 1);
        mbar_expect(imgb, 14336);
        fence_async();
      }
      __syncwarp();
      asm volatile("barrier.cluster.wait.aligned;" ::: "memory");
      if (lane == 0) {
#pragma unroll 1
        for (int r = spare; r < A_NREL; r++) {
          mbar_wait(rel0 + 8 * r, 0);
          asm volatile("fence.acq_rel.gpu;\nred.relaxed.gpu.global.inc.u32 [%0], 0x7fffffff;" ::"l"(cnt + 8 + r) : "memory");
        }
        if (!spare) {
          const int cta = role(), bin = cta >> 2;
#pragma unroll 1
          for (int r = 0; r < 4; r++) {
            if (r < 2 || (r == 2 ? bin < 28 : bin >= 4)) {
              mbar_wait(rly0 + 8 * r, 0);
              asm volatile("fence.acq_rel.gpu;\nred.relaxed.gpu.global.inc.u32 [%0], 0x7fffffff;" ::"l"(cnt + (r < 2 ? 64 + (cta & 2) : 94) + r) : "memory");
            }
            mbar_arrive(puby + 8 * r);
          }
        }
      }
    } else if (warp == 2) {
      asm volatile("barrier.cluster.wait.aligned;" ::: "memory");
      const uint32_t relm = spare ? A_RELS : A_REL;
      const int xr = __popc(xm & ((1 << lane) - 1));
      const uint32_t srcs = sb + a_out(lane), bars = aof0 + 8 * (lane % A_NOUT);
      const uint32_t done = lane < 16 ? bars + 8 * A_NOUT : se0 + 8 * (lane & 1), relb = rel0 + 8 * (spare + __popc(relm & ((1 << lane) - 1)));
      const int cta = role(), xc = x_decode(xr, cta), q = xc & 127, th = q / 28, wi = lane < 2 ? blk : w_unit(cta);
      int code = (xm >> lane) & 1 ? 0x80000000u + x1_addr(((xc >> 7) * 3 + th) * 8, (cta >> 1) & 1, 0) + (q - 28 * th) * 128
                                  : w_addr(7 - lane + xr, 0, wi >> 1, wi & 1, 0);
      uint32_t fl = 0;
      auto tables = [&]() {
        fl = flips();
        code ^= ((fl >> (((code >> 21) & 15) + (code < 0 ? 0 : 12))) & 1) << 12;
      };
      if (spare) tables();
      uint32_t tnext = clock(), src = __shfl_sync(0xffffffffu, srcs, 0), bar = aof0;
      int c = __shfl_sync(0xffffffffu, code, 0);
      mbar_wait(bar, 0);
#pragma unroll 1
      for (int n = 0; n < nu; n++) {
        while ((int)(clock() - tnext) < 0);
        tnext = clock() + (spare ? 0 : n < A_PACE_N ? A_PACE0 : A_PACE1);
        if (lane == n) {
          if (c >= 0) {
            w_store(&m.ws, src, c);
          } else {
#pragma unroll
            for (int j = 0; j < 8; j++)
              tma_st4<0>(&m.xs, src + j * 2048, ((c & 16383) >> 1) ^ ((__popc(j) & 1) << 11) ^ ((j & 1) << 12), (j >> 1) << 2, (c >> 18) & 3, (c >> 20) & 31);
          }
          bulk_commit();
        }
        __syncwarp();
        if (n == 1 && !spare) tables();
        c = __shfl_sync(0xffffffffu, code, n + 1);
        src = __shfl_sync(0xffffffffu, srcs, n + 1);
        bar = __shfl_sync(0xffffffffu, bars, n + 1);
        if (n + 1 < nu) mbar_wait(bar, (n + 1 >= A_NOUT) ^ (n + 1 >= 2 * A_NOUT));
        bulk_wait<0>();
        if (lane == n) {
          mbar_arrive(done);
          if ((relm >> lane) & 1) mbar_arrive(relb);
        }
        __syncwarp();
        if (!spare && (n == 13 || n == 15) && lane < 16) mbar_arrive_cta(empty0 + 8 * ((n - 7) >> 1), lane & 1);
      }
      if (!spare) {
        const int i = w_unit(cta), wc = w_code(1, 5 - lane, i);
        const uint32_t wa = w_addr(7 + W_SHIFT - lane, 0, i >> 1, i & 1, fl);
#pragma unroll 1
        for (int it = 0; it < 8; it++) {
          const uint32_t a = __shfl_sync(0xffffffffu, wa, it), j = it & 1;
          const int c2 = __shfl_sync(0xffffffffu, wc, it);
          mbar_wait(sf0 + 8 * j, (it >> 1) & 1);
          if (lane == 0 && it < 6) {
            mbar_expect(inf0 + 8 * j, 4096);
            in_load(c2, sb + G_TIN + j * 4096, inf0 + 8 * j);
          }
          if (it >= W_SHIFT) mbar_wait(got0 + 8 * (it - W_SHIFT), 0);
          if (lane == 0) {
            w_store(&m.ws, sb + G_TOUT + j * A_OUT, a);
            bulk_commit();
            bulk_wait<0>();
            mbar_arrive(se0 + 8 * j);
          }
          __syncwarp();
        }
        const int bin = cta >> 2;
        mbar_wait(got0 + 56, 0);
        mbar_wait(rly0 + 8, 0);
#pragma unroll 1
        for (int pc = 0; pc < 2; pc++) {
          if (pc ? bin >= 4 : bin < 28) {
#pragma unroll 1
            for (int n = 0; n < 6; n++) {
              mbar_wait(of0 + 8 * (6 * pc + n), 0);
              if (C_PACE) {
                while ((int)(clock() - tnext) < 0);
                tnext = clock() + C_PACE;
              }
              if (lane == 0) tma_st3<0>(&m.x2s, sb + pc * C_PIECE + C_OUT + n * 8192, 0, (4 * (n & 1) + 2 * hf + pc) * 64, (cta & 2) * (NB2 / 2) + 3 * (bin - 4 * pc) + (n >> 1));
              __syncwarp();
            }
            bulk_commit();
            bulk_wait<0>();
            if (lane == 0) mbar_arrive(rly0 + 16 + 8 * pc);
            __syncwarp();
          }
          if (lane < 16)
            for (int i = 6 * pc; i < 3 + 4 * pc; i++) mbar_arrive_cta(he0 + 8 * i, lane & 1);
        }
      }
    } else {
      bar_sync(9, 288);
      const int near = min(lat[0], lat[2]) > min(lat[1], lat[3]);
      if (lane == 0 && voter)
        asm volatile("red.relaxed.gpu.global.add.s32 [%0], %1;" ::"l"(cnt + 32 + page), "r"(256 + (near ^ (min(lat[4], lat[6]) > min(lat[5], lat[7])))) : "memory");
      __syncwarp();
      asm volatile("barrier.cluster.wait.aligned;" ::: "memory");
      const uint32_t fl = read_votes(cnt, lane, votes);
      if (lane == 0) {
        s_flips = fl;
        mbar_arrive(flipb);
      }
      __syncwarp();
      if (!spare) {
        bool open = lane < 8 + A_NREL;
        int k = 0;
        mbar_wait(rel0, 0);
#pragma unroll 1
        for (int p = 0; p < (1 << 16) && __any_sync(0xffffffffu, open); p++) {
          int v;
          asm volatile("ld.relaxed.gpu.global.s32 %0, [%1];" : "=r"(v) : "l"(cnt + (lane & 15)) : "memory");
          while (k < 16 && mbar_test(full0 + 8 * g_slot(k), (G_PAR >> k) & 1)) {
            if (lane == 0) mbar_arrive(empty0 + 8 * g_slot(k));
            if ((k & 1) && lane == 0) asm volatile("red.relaxed.gpu.global.inc.u32 [%0], 0x7fffffff;" ::"l"(cnt + (k >> 1)) : "memory");
            k++;
          }
          if (open && v >= (lane <= 8 ? 128 : 132)) {
            asm volatile("fence.acquire.gpu;" ::: "memory");
            mbar_arrive(got0 + 8 * lane);
            open = false;
          }
        }
        const int cta = role(), b = (cta >> 1) & 1, bin = cta >> 2;
        if (G_HOLDB) mbar_wait(puby, 0);
        y_store(1, cta, fl);
        const uint32_t wa = w_addr((lane & 6) + ((lane >> 3) & 1) + W_SHIFT, 2 * bin, (lane & 1) * 32, b, fl) + (hf << 14);
        mbar_wait(depb, 0);
        mbar_wait(pubb, 0);
        asm volatile("fence.proxy.async.global;" ::: "memory");
        int st = 0;
#pragma unroll 1
        for (int k2 = 0; k2 < 16; k2++) {
          const uint32_t w = __shfl_sync(0xffffffffu, wa, k2);
          if (k2 == H_HOLD) mbar_wait(pubb + 8, 0);
          mbar_wait(he0 + 8 * st, (k2 >= H_NST) ^ (k2 >= 2 * H_NST));
          if (lane == 0) {
            mbar_expect(hf0 + 8 * st, H_STAGE);
            tma_ld3<1>(sb + st * H_STAGE, &m.w2, hf0 + 8 * st, 0, (w >> 7) & 255, w >> 15);
            if (k2 == H_NST) {
              if (cta == 0) asm volatile("cp.async.bulk.prefetch.L2.global [%0], 6144;" ::"l"(gat) : "memory");
              if (cta == 1) asm volatile("cp.async.bulk.prefetch.L2.global [%0], 16384;" ::"l"(ge) : "memory");
              asm volatile("cp.async.bulk.prefetch.L2.global [%0], 1024;" ::"l"(wf + cta * 512) : "memory");
              asm volatile("cp.async.bulk.prefetch.L2.global [%0], 1024;" ::"l"(wo + cta * 512) : "memory");
            }
          }
          __syncwarp();
          if (++st == H_NST) st = 0;
        }
      }
    }
  } else {
    if (lane == 0) {
      const int w8 = 4 * wg + warp;
      for (int i = 0; i < 2; i++) {
        mbar_init(xf0 + 16 * w8 + 8 * i, 1);
        mbar_expect(xf0 + 16 * w8 + 8 * i, A_IN);
      }
      mbar_init(got0 + 8 * w8, 1);
      if (w8 >= 8 - A_NREL) mbar_init(acq0 + 8 * (7 - w8), 1);
      if (w8 < G_NST) {
        mbar_init(full0 + 8 * w8, 1);
        mbar_init(empty0 + 8 * w8, 17);
        mbar_arrive(empty0 + 8 * w8);
      }
      if (w8 > 0) {
        mbar_init(hf0 + 8 * (w8 - 1), 1);
        mbar_init(he0 + 8 * (w8 - 1), 16);
      }
      fence_bar_init();
    }
    __syncwarp();
    asm volatile("barrier.cluster.arrive.relaxed.aligned;" ::: "memory");
    if (wg == 1) tab[t] = __bfloat16_as_ushort(__float2bfloat16_rn(-__cosf((float)(t - 64) * 0.04908738521234052f)));
    bar_sync(1, 256);
    asm volatile("setmaxnreg.inc.sync.aligned.u32 232;");
    uint32_t fa[16];
    auto frag = [&](int i, int l) {
      const int f = warp * 16 + (l >> 2) + 8 * (i & 1), r = 8 * (i >> 1) + (l & 3) * 2;
      const int k0 = (f | 1) * r - ((f & 1) << 5);
      return tab[k0 & 127] | ((uint32_t)tab[(k0 + (f | 1)) & 127] << 16);
    };
#pragma unroll
    for (int i = 0; i < 16; i++) fa[i] = i < 4 ? frag(i, lane) : 0;
    reg_fence(fa);
    asm volatile("barrier.cluster.wait.aligned;" ::: "memory");
    int cta = blk, qs = 0;
#pragma unroll 1
    for (int n = wg; n < nu; n += 2) {
      float e[64];
      if ((n >> 1) == !spare) {
        pdl_launch();
        int l = lane;
        asm volatile("" : "+r"(l));
#pragma unroll
        for (int i = 4; i < 16; i++) fa[i] = frag(i, l);
        reg_fence(fa);
        cta = role();
        qs = ((cta >> 1) & 2) + hf;
      }
      if (spare) qs = n < 8 ? n & 3 : 2 * hf + wg;
      const bool isx = (xm >> n) & 1;
      const int r = __popc(xm & ((1 << n) - 1)), s = 7 - n + r;
      const uint32_t in = isx ? sb + (r % A_NIN) * A_IN : sb + 2 * G_STAGE + s * 4096;
      mbar_wait(isx ? xf0 + 8 * r : wf0 + 8 * (s >> 1), 0);
      if (!isx) {
        wg_fence();
        wgmma_rs_128<1, 1, 1>(e, fa[0], fa[1], fa[2], fa[3], mk_desc(in, 0, 2048, 1024, 1), 0);
        wg_commit();
      } else {
        wg_fence();
#pragma unroll
        for (int k = 0; k < 4; k++)
          wgmma_rs_128<1, 1, 1>(e, fa[4 * k], fa[4 * k + 1], fa[4 * k + 2], fa[4 * k + 3], mk_desc(in, k * 2048, 6144, 1024, 1), k);
        wg_commit();
      }
      wg_wait<0>();
      reg_fence(e);
      if (isx && lane == 0) mbar_arrive(xe0 + 8 * (r % A_NIN));
      if (((A_FREE >> n) & 1) && !spare && lane < 2) mbar_arrive_cta(empty0 + 8 * (__popc(A_FREE & ((1 << n) - 1)) >> 1), lane);
      if (n >= A_NOUT) mbar_wait(aoe0 + 8 * (n % A_NOUT), (n / A_NOUT - 1) & 1);
      const int row = warp * 16 + (lane & 7) + ((lane >> 3) & 1) * 8, hi = lane >> 4;
      const uint32_t rb = sb + a_out(n) + (isx ? row : row + (row & ~7)) * 128, ts = isx ? 8192 : 1024, xr = (lane & 7) ^ (isx ? qs : 0);
#pragma unroll
      for (int j = 0; j < 16; j += 2) {
        const uint32_t tile = isx ? (j >> 2) & 1 : j >> 3, pos = (isx ? (j >> 3) * 4 + (j & 3) : (j & 7)) + hi;
        stsm4(rb + tile * ts + ((pos ^ xr) << 4), pack2(e[4 * j], e[4 * j + 1]), pack2(e[4 * j + 2], e[4 * j + 3]),
              pack2(e[4 * j + 4], e[4 * j + 5]), pack2(e[4 * j + 6], e[4 * j + 7]));
      }
      fence_async();
      __syncwarp();
      if (lane == 0) mbar_arrive(aof0 + 8 * (n % A_NOUT));
    }
    if (spare) {
      float* sg = reinterpret_cast<float*>(smem_raw + (sb - s2u(smem_raw)));
      __nv_bfloat16* sw = reinterpret_cast<__nv_bfloat16*>(sg + 16 * 256);
      const int c0 = (cta - 128) * 64;
      uint4 vw[8], vg[2];
#pragma unroll
      for (int i = 0; i < 8; i++) vw[i] = __ldg(reinterpret_cast<const uint4*>(wgt + ((i * 256 + tid) >> 3) * 256 + c0 + (tid & 7) * 8));
#pragma unroll
      for (int i = 0; i < 2; i++) vg[i] = __ldg(reinterpret_cast<const uint4*>(g) + i * 256 + tid);
      bar_sync(3, 256);
#pragma unroll
      for (int i = 0; i < 8; i++) reinterpret_cast<uint4*>(sw)[i * 256 + tid] = vw[i];
#pragma unroll
      for (int i = 0; i < 2; i++) {
        const uint32_t w4[4] = {vg[i].x, vg[i].y, vg[i].z, vg[i].w};
#pragma unroll
        for (int e = 0; e < 4; e++) {
          sg[(i * 256 + tid) * 8 + 2 * e] = __uint_as_float(w4[e] << 16);
          sg[(i * 256 + tid) * 8 + 2 * e + 1] = __uint_as_float(w4[e] & 0xffff0000u);
        }
      }
      bar_sync(3, 256);
      const int col = tid & 63, r0 = (tid >> 6) * 4;
      float a0 = 0.f, a1 = 0.f, a2 = 0.f, a3 = 0.f;
#pragma unroll 8
      for (int k = 0; k < 256; k++) {
        const float w = __bfloat162float(sw[k * 64 + col]);
        a0 = fmaf(sg[(r0 + 0) * 256 + k], w, a0);
        a1 = fmaf(sg[(r0 + 1) * 256 + k], w, a1);
        a2 = fmaf(sg[(r0 + 2) * 256 + k], w, a2);
        a3 = fmaf(sg[(r0 + 3) * 256 + k], w, a3);
      }
      const int cc = c0 + col;
      const int pos = (cc & ~15) + ((cc >> 1) & 3) * 4 + ((cc >> 3) & 1) * 2 + (cc & 1);
      ge[(r0 + 0) * 256 + pos] = __bfloat162float(__float2bfloat16_rn(a0));
      ge[(r0 + 1) * 256 + pos] = __bfloat162float(__float2bfloat16_rn(a1));
      ge[(r0 + 2) * 256 + pos] = __bfloat162float(__float2bfloat16_rn(a2));
      ge[(r0 + 3) * 256 + pos] = __bfloat162float(__float2bfloat16_rn(a3));
      return;
    }
    const int bin = cta >> 2;
    const uint32_t la = (lane >> 4) * 1024 + (lane & 7) * 128 + (((2 * warp + ((lane >> 3) & 1)) ^ (lane & 7)) << 4);
    {
    float d[32];
    auto t_begin = [&](int it, int hh) {
      mbar_wait(inf0 + 8 * (it & 1), (it >> 1) & 1);
      wg_fence();
      wgmma_rs_64<1, 1, 1>(d, fa[0], fa[1], fa[2], fa[3], mk_desc(sb + G_TIN + (it & 1) * 4096 + hh * 2048, 0, 0, 1024, 1), 0);
      wg_commit();
    };
    auto t_end = [&](int it, int hh) {
      reg_fence(d);
      const int j = it & 1;
      mbar_wait(se0 + 8 * j, (it >> 1) & 1);
      store_tile_64<2048>(d, sb + G_TOUT + j * A_OUT + hh * 1024, warp, lane);
      fence_async();
      __syncwarp();
      if (lane == 0) mbar_arrive(sf0 + 8 * j);
    };
    float re[NB1 / 2], im[NB1 / 2];
#pragma unroll 1
    for (int k = 0; k < G_KS; k++) {
      const int st = g_slot(k);
      const int it = __popc(G_TMASK & ((1 << k) - 1));
      const bool T = (G_TMASK >> k) & 1;
      mbar_wait(full0 + 8 * st, (G_PAR >> k) & 1);
      const uint32_t base = sb + st * G_STAGE;
      const uint32_t wb = base + wg * 4096;
      if (T) t_begin(it, wg);
      wg_fence();
#pragma unroll
      for (int s = 0; s < 2; s++) {
        const int acc = (k | s) != 0;
        const uint64_t dP = mk_desc(wb, s * 2048, 0, 1024, 1), dQ = mk_desc(wb, 8192 + s * 2048, 0, 1024, 1);
        const uint64_t dA = mk_desc(base, 16384 + s * 32, 0, 512, 2), dB = mk_desc(base, 16384 + G_XP + s * 32, 0, 512, 2);
        wgmma_ss_168<1, 1, 1, 0>(re, dP, dA, acc);
        wgmma_ss_168<1, 1, 1, 0>(im, dP, dB, acc);
        wgmma_ss_168<1, 1, 1, 0>(re, dQ, dB, 1);
        wgmma_ss_168<-1, 1, 1, 0>(im, dQ, dA, 1);
      }
      wg_commit();
      wg_wait<1>();
      if (k > 0 && lane < 2) mbar_arrive_cta(empty0 + 8 * g_slot(k - 1), lane);
      if (T) t_end(it, wg);
    }
    auto tail = [&](auto part, auto k0, auto k1) {
      constexpr int PART = decltype(part)::value;
#pragma unroll
      for (int k = k0.value; k < k1.value; k++) {
        if (PART == 0) mbar_wait(full0 + 8 * g_slot(k), (G_PAR >> k) & 1);
        const uint32_t base = sb + g_slot(k) * G_STAGE, wb = base + wg * 4096;
        wg_fence();
#pragma unroll
        for (int s = 0; s < 2; s++) {
          const uint64_t dP = mk_desc(wb, s * 2048, 0, 1024, 1), dQ = mk_desc(wb, 8192 + s * 2048, 0, 1024, 1);
          const uint64_t dA = mk_desc(base, 16384 + s * 32, 0, 512, 2), dB = mk_desc(base, 16384 + G_XP + s * 32, 0, 512, 2);
          if (PART == 0) {
            wgmma_ss_168<1, 1, 1, 0>(re, dP, dA, 1);
            wgmma_ss_168<1, 1, 1, 0>(re, dQ, dB, 1);
          } else {
            wgmma_ss_168<1, 1, 1, 0>(im, dP, dB, 1);
            wgmma_ss_168<-1, 1, 1, 0>(im, dQ, dA, 1);
          }
        }
      }
      wg_commit();
    };
    auto put = [&](float (&v)[NB1 / 2], uint32_t stg, uint32_t bar, auto c0, auto c1) {
      reg_fence(v);
#pragma unroll
      for (int c = c0.value; c < c1.value; c++) {
#pragma unroll
        for (int j = 8 * c; j < 8 * c + 8 && j < 20; j += 2)
          stsm4t(stg + la + j * 1024, pack2(v[4 * j], v[4 * j + 1]), pack2(v[4 * j + 2], v[4 * j + 3]),
                 pack2(v[4 * j + 4], v[4 * j + 5]), pack2(v[4 * j + 6], v[4 * j + 7]));
        if (c == 2)
          asm volatile("stmatrix.sync.aligned.m8n8.x2.trans.shared.b16 [%0], {%1, %2};" ::"r"(stg + la + 20 * 1024),
                       "r"(pack2(v[80], v[81])), "r"(pack2(v[82], v[83])) : "memory");
        fence_async();
        __syncwarp();
        if (lane == 0) mbar_arrive(bar + 8 * c);
      }
    };
    if (wg == 1) {
      wg_wait<0>();
      bar_arrive(5, 256);
#pragma unroll 1
      for (int h2 = 2 * __popc(G_TMASK); h2 < 16; h2++) {
        t_begin(h2 >> 1, h2 & 1);
        wg_wait<0>();
        t_end(h2 >> 1, h2 & 1);
      }
      bar_arrive(6, 256);
      bar_sync(4, 256);
    }
    tail(IC<0>(), IC<G_KS>(), IC<16>());
    tail(IC<1>(), IC<G_KS>(), IC<G_KI>());
    if (G_KI == 16 && wg == 0) bar_arrive(4, 256);
    wg_wait<1>();
    if (wg == 0) {
      bar_sync(5, 256);
    } else {
      mbar_wait(se0, 0);
      mbar_wait(se0 + 8, 0);
    }
    const uint32_t stg = sb + (wg ? G_TOUT : 4 * G_STAGE);
    put(re, stg, yo0 + 48 * wg, IC<0>(), IC<G_KC>());
    if (G_KI < 16) {
      tail(IC<1>(), IC<G_KI>(), IC<16>());
      if (wg == 0) bar_arrive(4, 256);
    }
    put(re, stg, yo0 + 48 * wg, IC<G_KC>(), IC<3>());
    wg_wait<0>();
    if (lane == 0) mbar_arrive(gdone);
    if (wg == 0) bar_sync(6, 256);
    else mbar_wait(gdone, 0);
    put(im, sb + (wg ? G_IM1 : 4 * G_STAGE + NB1 * 128), yo0 + 48 * wg + 24, IC<0>(), IC<3>());
    }
    mbar_wait(imgb, 0);
    const int p0 = bin >= 28, p1 = bin < 4 ? 1 : 2;
#pragma unroll 1
    for (int pc = p0; pc < p1; pc++) {
      const uint32_t in = sb + pc * C_PIECE, yb = yf0 + 32 * pc;
      const bool first = bin == 4 * pc, last = bin == 27 + 4 * pc;
      float h0[12], h1[12], h2[12], h3[12], h4[12], h5[12], h6[8], e[32];
      uint32_t hp[40];
      auto idft = [&](auto& h, int i) {
#pragma unroll
        for (int k = 0; k < 4; k++) {
          const uint64_t da = mk_desc(in, i * 8192 + k * 2048, 0, 1024, 1), db = mk_desc(sb + C_GI + wg * 1024, k * 32, 0, 2048, 1);
          if constexpr (sizeof(h) == 48) wgmma_ss_24<1, 1, 1, 0>(h, da, db, k);
          else wgmma_ss_16<1, 1, 1, 0>(h, da, db, k);
        }
      };
      auto idft2 = [&](auto& ha, auto& hb, int i) {
        mbar_wait(yb + 4 * (i + 1), 0);
        wg_fence();
        idft(ha, i);
        idft(hb, i + 1);
        wg_commit();
      };
      auto dft = [&](int j) {
        wg_fence();
#pragma unroll
        for (int k = 0; k < 4; k++)
          wgmma_rs_64<1, 1, 0>(e, hp[12 * j + 4 * k], hp[12 * j + 4 * k + 1], hp[12 * j + 4 * k + 2], hp[12 * j + 4 * k + 3], mk_desc(sb + C_F, k * 32, 0, 1024, 1), k);
        wg_commit();
      };
      auto out = [&](int j) {
        reg_fence(e);
        if (j == 1) mbar_wait(rly0 + 8, 0);
        const uint32_t a0 = in + la + C_OUT + (2 * j + wg) * 8192;
#pragma unroll
        for (int q = 0; q < 8; q += 2)
          stsm4t(a0 + q * 1024, pack2(e[4 * q], e[4 * q + 1]), pack2(e[4 * q + 2], e[4 * q + 3]),
                 pack2(e[4 * q + 4], e[4 * q + 5]), pack2(e[4 * q + 6], e[4 * q + 7]));
        fence_async();
        __syncwarp();
        if (lane == 0) mbar_arrive(of0 + 8 * (6 * pc + 2 * j + wg));
      };
      mbar_wait(yb, 0);
      wg_fence();
      idft(h0, 0);
      wg_commit();
      idft2(h1, h2, 1);
      wg_wait<1>();
      gelu_pack(hp, h0, first, false);
      wg_wait<0>();
      gelu_pack(hp + 6, h1, false, false);
      gelu_pack(hp + 12, h2, false, false);
      dft(0);
      idft2(h3, h4, 3);
      wg_wait<1>();
      out(0);
      wg_wait<0>();
      gelu_pack(hp + 18, h3, false, false);
      gelu_pack(hp + 24, h4, false, false);
      dft(1);
      idft2(h5, h6, 5);
      wg_wait<1>();
      out(1);
      wg_wait<0>();
      gelu_pack(hp + 30, h5, false, last);
      gelu_pack(hp + 36, h6, false, last);
      dft(2);
      wg_wait<0>();
      if (pc == p1 - 1 && lane < 6) mbar_arrive_cta(he0 + 8 * (3 + (lane >> 1)), lane & 1);
      out(2);
    }
    float acc[84];
    if (wg == 0) {
      h_loop<0>(acc, sb, hf0, he0, lane);
    } else {
      h_loop<1>(acc, sb, hf0, he0, lane);
      bar_sync(3, 128);
    }
    const uint32_t stg = sb + (wg == 0 ? H_NST : 9 % H_NST) * H_STAGE;
    const uint32_t a0 = stg + la;
    constexpr int J = 21 / H_EPI;
#pragma unroll
    for (int c = 0; c < H_EPI; c++) {
#pragma unroll
      for (int j = c * J; j + 1 < (c + 1) * J; j += 2)
        stsm4t(a0 + j * 1024, pack2(acc[4 * j], acc[4 * j + 1]), pack2(acc[4 * j + 2], acc[4 * j + 3]),
               pack2(acc[4 * j + 4], acc[4 * j + 5]), pack2(acc[4 * j + 6], acc[4 * j + 7]));
      const int j = (c + 1) * J - 1;
      asm volatile("stmatrix.sync.aligned.m8n8.x2.trans.shared.b16 [%0], {%1, %2};" ::"r"(a0 + j * 1024),
                   "r"(pack2(acc[4 * j], acc[4 * j + 1])), "r"(pack2(acc[4 * j + 2], acc[4 * j + 3])) : "memory");
      fence_async();
      bar_sync(2 + wg, 128);
      if (t == 0) {
        tma_st4<0>(&m.y2, stg + c * J * 1024, 0, c * J * 8, 2 * bin + wg, cta & 3);
        bulk_commit();
      }
    }
    if (t == 0) {
      bulk_wait_read<0>();
    }
  }
}

#define E_LD 0
#define E_WPRE 2
#define E_EARLY0 2
#define E_CHUNK 1
#define E_EARLY 2
constexpr int E_SMEM = 65536 + 131072 + 32768 + 1024;

__device__ __forceinline__ uint32_t joint2(uint32_t fe, uint32_t g0, uint32_t g1) {
  uint32_t s0, s1;
  asm("{\n.reg .b16 l, h;\n.reg .b32 ll;\nmov.b32 {l, h}, %2;\nmov.b32 ll, {l, l};\n"
      "fma.rn.bf16x2 %0, ll, %5, %3;\nfma.rn.bf16x2 %1, %2, %5, %4;\n}"
      : "=r"(s0), "=r"(s1) : "r"(fe), "r"(g0), "r"(g1), "r"(0x3F800000u));
  return pack2(tanh_f32(__uint_as_float(s0)), tanh_f32(__uint_as_float(s1)));
}
__device__ __forceinline__ uint4 lds128(uint32_t a) {
  uint4 v;
  asm volatile("ld.shared.v4.u32 {%0, %1, %2, %3}, [%4];" : "=r"(v.x), "=r"(v.y), "=r"(v.z), "=r"(v.w) : "r"(a));
  return v;
}
__device__ __forceinline__ void joint_group(uint32_t (&ja)[8], const uint32_t* fe, uint4& g0, uint4& g1, uint32_t gnext) {
  const uint4 c0 = g0, c1 = g1;
  g0 = lds128(gnext);
  g1 = lds128(gnext + 64);
  ja[0] = joint2(fe[0], c0.x, c0.y);
  ja[1] = joint2(fe[1], c0.x, c0.y);
  ja[2] = joint2(fe[2], c0.z, c0.w);
  ja[3] = joint2(fe[3], c0.z, c0.w);
  ja[4] = joint2(fe[4], c1.x, c1.y);
  ja[5] = joint2(fe[5], c1.x, c1.y);
  ja[6] = joint2(fe[6], c1.z, c1.w);
  ja[7] = joint2(fe[7], c1.z, c1.w);
  reg_fence(ja);
}

__global__ void __launch_bounds__(256, 1)
kE(int* __restrict__ cnt, const uint32_t* __restrict__ gat, const float* ge, const __grid_constant__ CUtensorMap my, const __grid_constant__ CUtensorMap mwf, const __grid_constant__ CUtensorMap mwo,
   const __grid_constant__ CUtensorMap mout) {
  extern __shared__ __align__(1024) uint8_t smem_raw[];
  __shared__ __align__(8) uint64_t bars[13];
  const uint32_t sb = (s2u(smem_raw) + 1023) & ~1023u;
  const int tid = threadIdx.x, wg = __shfl_sync(0xffffffffu, tid >> 7, 0), t = tid & 127, warp = t >> 5, lane = t & 31;
  const uint32_t R0 = sb, R1 = sb + 65536, R2 = sb + 65536 + 131072;
  const uint32_t barY = s2u(&bars[0]), barF = barY + 32, barO = barY + 64, barA = barY + 96;
  const int b = blockIdx.x / 63, t0 = (blockIdx.x % 63) * 64;
  const int a = t0 / 48, o = t0 % 48;
  const int qw = o + 16 * warp, sel = qw >= 48;
  uint32_t ga[16];
#pragma unroll
  for (int s = 0; s < 4; s++)
    ldg128(reinterpret_cast<const uint4*>(gat) + ((qw >> 4) - 3 * sel) * 128 + s * 32 + lane, ga[4 * s], ga[4 * s + 1], ga[4 * s + 2], ga[4 * s + 3]);
  if (tid == 0) {
    prefetch_map(&my);
    for (int i = 0; i < 12; i++) mbar_init(barY + 8 * i, 1);
    mbar_init(barA, 8);
    fence_bar_init();
    fence_async();
    for (int i = 0; i < E_WPRE; i++) {
      const int kc = (i >> 1) | ((i & 1) << 1);
      mbar_expect(barF + 8 * kc, 32768);
      tma_ld3<0>(R1 + kc * 32768, &mwf, barF + 8 * kc, 0, kc * 64, 0);
    }
  }
  uint32_t gs[32];
#pragma unroll
  for (int i = 0; i < 16; i++) {
    gs[i] = sel ? 0u : ga[i];
    gs[16 + i] = sel ? ga[i] : 0u;
  }
  __syncthreads();
  pdl_wait();
  uint4 gev0, gev1;
  asm volatile("ld.global.cg.v4.u32 {%0, %1, %2, %3}, [%4];" : "=r"(gev0.x), "=r"(gev0.y), "=r"(gev0.z), "=r"(gev0.w)
               : "l"(reinterpret_cast<const uint4*>(ge) + (b * 8 + wg * 4) * 64 + t));
  asm volatile("ld.global.cg.v4.u32 {%0, %1, %2, %3}, [%4];" : "=r"(gev1.x), "=r"(gev1.y), "=r"(gev1.z), "=r"(gev1.w)
               : "l"(reinterpret_cast<const uint4*>(ge) + (b * 8 + wg * 4) * 64 + 128 + t));
  if (tid == E_LD) {
    for (int i = 0; i < 4; i++) {
      mbar_expect(barY + 8 * i, 16384);
      tma_ld5<0>(R0 + i * 16384, &my, barY + 8 * i, 0, 0, 2 * (i & 1) + (i >> 1), a, b);
    }
    for (int i = E_WPRE; i < 4; i++) {
      const int kc = (i >> 1) | ((i & 1) << 1);
      mbar_expect(barF + 8 * kc, 32768);
      tma_ld3<0>(R1 + kc * 32768, &mwf, barF + 8 * kc, 0, kc * 64, 0);
    }
    prefetch_map(&mwo);
    prefetch_map(&mout);
  }
  if (blockIdx.x == 125 && tid < 128) cnt[tid] = 0;
  reg_fence(gs);
  uint32_t gp = R2 + wg * 4096 + (lane & 3) * 16;
  uint4 g0, g1;
  uint32_t fe[64];
  {
    float d0[32], d1[32], e[64];
    mbar_wait(barY + 8 * wg, 0);
    wg_fence();
#pragma unroll
    for (int k = 0; k < 8; k++)
      wgmma_rs_64<1, 1, 1>(d0, gs[4 * k], gs[4 * k + 1], gs[4 * k + 2], gs[4 * k + 3], mk_desc(R0 + wg * 16384, k * 2048, 0, 1024, 1), k);
    wg_commit();
    wg_wait<0>();
    reg_fence(d0);
#pragma unroll
    for (int i = 0; i < 32; i++) d0[i] = gelu(d0[i]);
    store_tile_64(d0, R2 + wg * 16384, warp, lane);
    mbar_wait(barY + 8 * (2 + wg), 0);
    wg_fence();
#pragma unroll
    for (int k = 0; k < 8; k++)
      wgmma_rs_64<1, 1, 1>(d1, gs[4 * k], gs[4 * k + 1], gs[4 * k + 2], gs[4 * k + 3], mk_desc(R0 + wg * 16384, 32768 + k * 2048, 0, 1024, 1), k);
    wg_commit();
    fence_async();
    mbar_wait(barF, 0);
    mbar_wait(barF + 16, 0);
    __syncthreads();
    wg_fence();
#pragma unroll
    for (int i = 0; i < 8; i++) {
      const int kc = (i >> 2) * 2, s = i & 3;
      wgmma_ss_128<1, 1, 0, 1>(e, mk_desc(R2, kc * 8192 + s * 32, 0, 1024, 1),
                               mk_desc(R1 + wg * 16384, kc * 32768 + s * 2048, 8192, 1024, 1), i);
    }
    wg_commit();
    if (tid == 128) {
      mbar_expect(barO, 32768);
      tma_ld3<0>(R0, &mwo, barO, 0, 0, 0);
    }
    wg_wait<1>();
    reg_fence(d1);
#pragma unroll
    for (int i = 0; i < 32; i++) d1[i] = gelu(d1[i]);
    store_tile_64(d1, R2 + wg * 16384 + 8192, warp, lane);
    fence_async();
    mbar_wait(barF + 8, 0);
    mbar_wait(barF + 24, 0);
    __syncthreads();
    if (tid == 128) {
      mbar_expect(barO + 8, 32768);
      tma_ld3<0>(R0 + 32768, &mwo, barO + 8, 0, 64, 0);
    }
    if (wg == 1) bar_sync(4, 256);
    wg_fence();
#pragma unroll
    for (int i = 0; i < 8; i++) {
      const int kc = (i >> 2) * 2 + 1, s = i & 3;
      wgmma_ss_128<1, 1, 0, 1>(e, mk_desc(R2, kc * 8192 + s * 32, 0, 1024, 1),
                               mk_desc(R1 + wg * 16384, kc * 32768 + s * 2048, 8192, 1024, 1), 1);
    }
    wg_commit();
    if (wg == 0) bar_arrive(4, 256);
    wg_wait<1>();
    if (lane == 0) mbar_arrive(barA);
    if (tid == 128) {
      mbar_wait(barA, 0);
      for (int kc = 2; kc < 4; kc++) {
        mbar_expect(barO + 8 * kc, 32768);
        tma_ld3<0>(R1 + (kc - 2) * 65536, &mwo, barO + 8 * kc, 0, kc * 64, 0);
      }
    }
    mbar_wait(barA, 0);
    asm volatile("st.shared.v4.u32 [%0], {%1, %2, %3, %4};" ::"r"(R2 + wg * 4096 + ((t * 16) ^ (wg * 512))), "r"(gev0.x), "r"(gev0.y), "r"(gev0.z), "r"(gev0.w) : "memory");
    asm volatile("st.shared.v4.u32 [%0], {%1, %2, %3, %4};" ::"r"(R2 + wg * 4096 + 2048 + ((t * 16) ^ (wg * 512))), "r"(gev1.x), "r"(gev1.y), "r"(gev1.z), "r"(gev1.w) : "memory");
    bar_sync(1 + wg, 128);
    g0 = lds128(gp);
    g1 = lds128(gp + 64);
    wg_wait<0>();
    reg_fence(e);
#pragma unroll
    for (int i = 0; i < 32; i++) fe[i] = pack2(e[2 * i], e[2 * i + 1]);
  }
  auto publish = [&]() {
    bar_sync(1 + wg, 128);
    const int row = warp * 16 + (lane & 7) + ((lane >> 3) & 1) * 8;
    const uint32_t xb = R1 + (wg == 0 ? 3 * 32768 : 32768 + 16384) + row * 128;
#pragma unroll
    for (int s = 0; s < 8; s++) {
      const int jj = 2 * s + (lane >> 4);
      stsm4(xb + (s >> 2) * 8192 + (((jj & 7) ^ (lane & 7)) << 4), fe[4 * s], fe[4 * s + 1], fe[4 * s + 2], fe[4 * s + 3]);
    }
    bar_arrive(5 + wg, 256);
  };
  if (wg == 1) publish();
  const uint32_t stg = R1 + 32768 + wg * 65536;
  const uint32_t w0 = sb + wg * 65536, w1 = sb + 32768 + wg * 98304, w2 = sb + 65536 - wg * 65536, w3 = sb + 131072 - wg * 98304;
  float acc[128];
  uint32_t j0[8], j1[8], j2[8], j3[8];
  joint_group(j0, fe, g0, g1, gp + 128);
  mbar_wait(barO + 16 * wg, 0);
  joint_group(j1, fe + 8, g0, g1, gp + 256);
#define E_MMA4(J, K, W, FIRSTK, G, NEXTBAR)                                                     \
  wg_fence();                                                                                   \
  wgmma_rs_256<1, 1, 1>(acc, J[0], J[1], J[2], J[3], mk_desc(W, 0, 8192, 1024, 1), FIRSTK);     \
  wgmma_rs_256<1, 1, 1>(acc, J[4], J[5], J[6], J[7], mk_desc(W, 2048, 8192, 1024, 1), 1);       \
  wgmma_rs_256<1, 1, 1>(acc, K[0], K[1], K[2], K[3], mk_desc(W, 4096, 8192, 1024, 1), 1);       \
  wgmma_rs_256<1, 1, 1>(acc, K[4], K[5], K[6], K[7], mk_desc(W, 6144, 8192, 1024, 1), 1);       \
  wg_commit();                                                                                  \
  if ((ui + wg == 0 ? E_EARLY0 : E_EARLY) == (G) && (ui < 3 || wg == 0)) bar_arrive(4 - wg, 256); \
  wg_wait<1>();                                                                                 \
  if (ui == 0) mbar_wait(NEXTBAR, 0);
  const uint32_t bo0 = barO + 16 * wg, bo2 = barO + 16 * (1 - wg);
#pragma unroll 1
  for (int ui = 0; ui < 4; ui++) {
    if (ui > 0 || wg == 1) bar_sync(3 + wg, 256);
    E_MMA4(j0, j1, w0, 0, 0, bo0)
    joint_group(j2, fe + 16, g0, g1, gp + 384);
    if (ui == 0) mbar_wait(bo0 + 8, 0);
    joint_group(j3, fe + 24, g0, g1, gp + 512);
    E_MMA4(j2, j3, w1, 1, 1, bo0 + 8)
    if (ui == 0) {
      if (wg == 0) publish();
      bar_sync(6 - wg, 256);
      const int row = warp * 16 + (lane & 7) + ((lane >> 3) & 1) * 8;
      const uint32_t xb = R1 + (wg == 1 ? 3 * 32768 : 32768 + 16384) + row * 128;
#pragma unroll
      for (int s = 0; s < 8; s++) {
        const int jj = 2 * s + (lane >> 4);
        ldsm4(xb + (s >> 2) * 8192 + (((jj & 7) ^ (lane & 7)) << 4), fe[32 + 4 * s], fe[33 + 4 * s], fe[34 + 4 * s], fe[35 + 4 * s]);
      }
    }
    joint_group(j0, fe + 32, g0, g1, gp + 640);
    if (ui == 0) mbar_wait(bo2, 0);
    joint_group(j1, fe + 40, g0, g1, gp + 768);
    E_MMA4(j0, j1, w2, 1, 2, bo2)
    joint_group(j2, fe + 48, g0, g1, gp + 896);
    if (ui == 0) mbar_wait(bo2 + 8, 0);
    joint_group(j3, fe + 56, g0, g1, gp + 1024);
    E_MMA4(j2, j3, w3, 1, 3, bo2 + 8)
    gp += 1024;
    if (ui < 3) {
      joint_group(j0, fe, g0, g1, gp + 128);
      if (ui == 0) mbar_wait(bo2 + 8, 0);
      joint_group(j1, fe + 8, g0, g1, gp + 256);
    }
    if (t == 0) bulk_wait_read<0>();
    wg_wait<0>();
    reg_fence(acc);
    bar_sync(1 + wg, 128);
    const uint32_t rb = stg + (warp * 16 + (lane & 7) + ((lane >> 3) & 1) * 8) * 128;
#pragma unroll
    for (int h = 0; h < 2; h++) {
#pragma unroll
      for (int j = 16 * h; j < 16 * h + 16; j += 2) {
        const int jj = j + (lane >> 4);
        stsm4(rb + (j >> 3) * 8192 + (((jj & 7) ^ (lane & 7)) << 4), pack2(acc[4 * j], acc[4 * j + 1]), pack2(acc[4 * j + 2], acc[4 * j + 3]),
              pack2(acc[4 * j + 4], acc[4 * j + 5]), pack2(acc[4 * j + 6], acc[4 * j + 7]));
      }
      const bool split = E_CHUNK == 2 || (E_CHUNK == 1 && ui == 3);
      if (h == 1 || split) {
        fence_async();
        bar_sync(1 + wg, 128);
        if (t == 0) {
          if (h == 1 && !split) tma_st5<1>(&mout, stg, 0, t0, 0, wg * 4 + ui, b);
          tma_st5<1>(&mout, stg + h * 16384, 0, t0, 2 * h, wg * 4 + ui, b);
          bulk_commit();
        }
      }
    }
  }
  if (t == 0) bulk_wait_read<0>();
}

typedef CUresult (*EncodeFn)(CUtensorMap*, CUtensorMapDataType, cuuint32_t, void*, const cuuint64_t*, const cuuint64_t*,
                             const cuuint32_t*, const cuuint32_t*, CUtensorMapInterleave, CUtensorMapSwizzle,
                             CUtensorMapL2promotion, CUtensorMapFloatOOBfill);

CUtensorMap make_map(EncodeFn fn, const void* base, int rank, const uint64_t* dims, const uint64_t* strides, const uint32_t* box,
                     CUtensorMapSwizzle swz) {
  CUtensorMap m;
  cuuint64_t gd[5], gs[4];
  cuuint32_t bx[5], es[5];
  for (int i = 0; i < rank; i++) { gd[i] = dims[i]; bx[i] = box[i]; es[i] = 1; }
  for (int i = 0; i + 1 < rank; i++) gs[i] = strides[i];
  fn(&m, CU_TENSOR_MAP_DATA_TYPE_BFLOAT16, rank, const_cast<void*>(base), gd, gs, bx, es, CU_TENSOR_MAP_INTERLEAVE_NONE, swz,
     CU_TENSOR_MAP_L2_PROMOTION_NONE, CU_TENSOR_MAP_FLOAT_OOB_FILL_NONE);
  return m;
}

template <typename... KArgs, typename... Args>
void launch(void (*k)(KArgs...), int grid, int block, int smem, bool pdl, Args... args) {
  cudaLaunchConfig_t c = {};
  c.gridDim = dim3(grid);
  c.blockDim = dim3(block);
  c.dynamicSmemBytes = smem;
  c.stream = cudaStreamPerThread;
  cudaLaunchAttribute at[1];
  at[0].id = cudaLaunchAttributeProgrammaticStreamSerialization;
  at[0].val.programmaticStreamSerializationAllowed = 1;
  c.attrs = at;
  c.numAttrs = pdl ? 1 : 0;
  cudaLaunchKernelEx(&c, k, args...);
}

}

extern "C" void kernel_launch(void* const* d_in, const int* in_sizes, int n_in, void* d_out, int out_size) {
  const __nv_bfloat16* x = (const __nv_bfloat16*)d_in[0];
  const __nv_bfloat16* w1 = (const __nv_bfloat16*)d_in[1];
  const __nv_bfloat16* w2 = (const __nv_bfloat16*)d_in[2];
  const __nv_bfloat16* g = (const __nv_bfloat16*)d_in[3];
  const __nv_bfloat16* wf = (const __nv_bfloat16*)d_in[4];
  const __nv_bfloat16* wgt = (const __nv_bfloat16*)d_in[5];
  const __nv_bfloat16* wo = (const __nv_bfloat16*)d_in[6];

  void* fp = nullptr;
  cudaDriverEntryPointQueryResult qr;
  cudaGetDriverEntryPoint("cuTensorMapEncodeTiled", &fp, cudaEnableDefault, &qr);
  EncodeFn fn = (EncodeFn)fp;
  void *W, *Y2, *cnt, *ge, *img, *gat;
  cudaGetSymbolAddress(&cnt, g_cnt);
  cudaGetSymbolAddress(&ge, g_ge);
  cudaGetSymbolAddress(&img, c_img);
  cudaGetSymbolAddress(&gat, c_ga);
  cudaGetSymbolAddress(&W, g_W);
  cudaGetSymbolAddress(&Y2, g_Y2);
  cudaFuncSetAttribute(kG, cudaFuncAttributeMaxDynamicSharedMemorySize, G_SMEM);
  cudaFuncSetAttribute(kE, cudaFuncAttributeMaxDynamicSharedMemorySize, E_SMEM);
  auto page_up = [](void* p) { return (void*)(((uintptr_t)p + (1 << 21) - 1) & ~(uintptr_t)((1 << 21) - 1)); };
  void *X1 = page_up(d_out), *X2 = X1;
  W = page_up(W);
  const CUtensorMapSwizzle S128 = CU_TENSOR_MAP_SWIZZLE_128B, S64 = CU_TENSOR_MAP_SWIZZLE_64B;

  auto map_x = [&]() {
    uint64_t d[] = {64, 8000, 8, 1, 2}, s[] = {1024, 128, 8000ull * 1024, 8000ull * 1024};
    uint32_t bx[] = {64, 112, 1, 1, 1};
    return make_map(fn, x, 5, d, s, bx, S128);
  };
  auto map_w_in = [&](const __nv_bfloat16* w, int odd, uint32_t n) {
    uint64_t d[] = {64, (uint64_t)(odd ? 15 : 16), 4, 64, 4}, s[] = {2ull * 65536 * 2, 128, 512, 32768};
    uint32_t bx[] = {64, 16, 2, 1, n};
    return make_map(fn, w + (odd ? 65536 : 0), 5, d, s, bx, S128);
  };
  auto map_X_st = [&](void* p, int nb, int boxb) {
    uint64_t d[] = {64, 512, (uint64_t)(2 * nb)}, s[] = {2ull * nb * 128, 128};
    uint32_t bx[] = {64, 64, (uint32_t)boxb};
    return make_map(fn, p, 3, d, s, bx, S128);
  };
  auto map_X1_st = [&](uint32_t rows) {
    uint64_t d[] = {8192, 16, 4, 24}, s[] = {16384, 262144, 1048576};
    uint32_t bx[] = {64, 4, 2, rows / 8};
    return make_map(fn, X1, 4, d, s, bx, S128);
  };
  auto map_Y1_ld = [&](uint64_t step) {
    uint64_t d[] = {64, 12 << 14, 2}, s[] = {128, step};
    uint32_t bx[] = {64, 32, 2};
    return make_map(fn, X1, 3, d, s, bx, S128);
  };
  auto map_W_st = [&]() {
    uint64_t d[] = {8192, 8, 4, 2 * (8 + W_SHIFT), 2}, s[] = {32768, 262144, 1048576, 16384};
    uint32_t bx[] = {64, 2, 2, 2, 2};
    return make_map(fn, W, 5, d, s, bx, S128);
  };
  auto map_X_ld = [&](void* p, int nb, int boxb) {
    uint64_t d[] = {64, (uint64_t)(2 * nb), 512}, s[] = {128, 2ull * nb * 128};
    uint32_t bx[] = {32, (uint32_t)boxb, 1};
    return make_map(fn, p, 3, d, s, bx, S64);
  };
  auto map_W_ld = [&](uint32_t n) {
    uint64_t d[] = {64, 512 / n, (8ull + W_SHIFT) * 32 * n}, s[] = {128, 65536 / n};
    uint32_t bx[] = {64, 32, n};
    return make_map(fn, W, 3, d, s, bx, S128);
  };
  auto map_Y_st = [&](void* p, int nb, int rows) {
    uint64_t d[] = {64, (uint64_t)(2 * nb), 64, 4}, s[] = {32768, 128, 8192};
    uint32_t bx[] = {64, (uint32_t)rows, 1, 1};
    return make_map(fn, p, 4, d, s, bx, S128);
  };
  auto map_Y_ld = [&](void* p, int nb, int boxc, int boxb) {
    uint64_t d[] = {64, 64, 4, (uint64_t)nb, 2}, s[] = {128, 8192, 32768, (uint64_t)nb * 32768};
    uint32_t bx[] = {64, 64, (uint32_t)boxc, (uint32_t)boxb, 1};
    return make_map(fn, p, 5, d, s, bx, S128);
  };
  auto map_wsq = [&](const __nv_bfloat16* w) {
    uint64_t d[] = {64, 256, 4}, s[] = {512, 128};
    uint32_t bx[] = {64, 64, 4};
    return make_map(fn, w, 3, d, s, bx, S128);
  };
  auto map_out = [&]() {
    uint64_t d[] = {64, 4000, 4, 8, 2}, s[] = {4096, 128, 512, 4000ull * 4096};
    uint32_t bx[] = {64, 64, 2, 1, 1};
    return make_map(fn, d_out, 5, d, s, bx, S128);
  };

  GMaps g1;
  g1.w = map_W_ld(4);
  g1.y = map_X1_st(8);
  g1.in[0] = map_w_in(w1, 1, 2);
  g1.in[1] = map_w_in(w1, 0, 2);
  g1.in[2] = map_w_in(w2, 1, 1);
  g1.in[3] = map_w_in(w2, 0, 1);
  g1.in[4] = map_x();
  g1.xs = map_X1_st(16);
  g1.ws = map_W_st();
  g1.y1[0] = map_Y1_ld(0x3000);
  g1.y1[1] = map_Y1_ld(0x1000);
  g1.x2s = map_X_st(X2, NB2, 1);
  g1.x2 = map_X_ld(X2, NB2, 168);
  g1.w2 = map_W_ld(2);
  g1.y2 = map_Y_st(Y2, NB2, 168 / H_EPI);
  launch(kG, 132, 384, G_SMEM, false, (int*)cnt, (char*)X1, (char*)W, g, wgt, (float*)ge, (const uint32_t*)img, wf, wo, (const uint32_t*)gat, g1);
  launch(kE, 126, 256, E_SMEM, true, (int*)cnt, (const uint32_t*)gat, (const float*)ge, map_Y_ld(Y2, NB2, 1, 2), map_wsq(wf), map_wsq(wo), map_out());
}
```

```cpp
#include <cuda_runtime.h>
#include <cuda_bf16.h>
#include <cuda.h>
#include <stdint.h>
#include <type_traits>

#define W_SHIFT 1
namespace {

constexpr int NB1 = 168;
constexpr int NB2 = 84;

__device__ __align__(1024) __nv_bfloat16 g_W[(9 + W_SHIFT) * 64 * 4 * 64 * 64];
__device__ __align__(1024) __nv_bfloat16 g_Y2[2 * NB2 * 4 * 64 * 64];
__device__ __align__(1024) float g_ge[16 * 256];

__device__ __forceinline__ uint32_t s2u(const void* p) { return (uint32_t)__cvta_generic_to_shared(p); }
__device__ __forceinline__ uint32_t pin(uint32_t v) {
  return __shfl_sync(0xffffffffu, v, 0);
}
__device__ __forceinline__ void mbar_init(uint32_t b, int c) {
  asm volatile("mbarrier.init.shared::cta.b64 [%0], %1;" ::"r"(b), "r"(c) : "memory");
}
__device__ __forceinline__ void mbar_expect(uint32_t b, int bytes) {
  asm volatile("mbarrier.arrive.expect_tx.shared::cta.b64 _, [%0], %1;" ::"r"(b), "r"(bytes) : "memory");
}
__device__ __forceinline__ void mbar_arrive(uint32_t b) {
  asm volatile("mbarrier.arrive.shared::cta.b64 _, [%0];" ::"r"(b) : "memory");
}
__device__ __forceinline__ void mbar_arrive_cta(uint32_t b, uint32_t cta) {
  asm volatile("{\n.reg .b32 r;\nmapa.shared::cluster.u32 r, %0, %1;\nmbarrier.arrive.shared::cluster.b64 _, [r];\n}" ::"r"(b), "r"(cta) : "memory");
}
__device__ __forceinline__ void mbar_wait(uint32_t b, int ph) {
  asm volatile(
      "{\n.reg .pred p;\n.reg .u32 n;\n"
      "mov.u32 n, 0;\n"
      "MBW_LOOP:\n"
      "mbarrier.try_wait.parity.shared::cta.b64 p, [%0], %1;\n"
      "@p bra MBW_DONE;\n"
      "add.u32 n, n, 1;\n"
      "setp.lt.u32 p, n, 1048576;\n"
      "@p bra MBW_LOOP;\n"
      "MBW_DONE:\n}" ::"r"(b), "r"(ph) : "memory");
}
__device__ __forceinline__ bool mbar_test(uint32_t b, int ph) {
  uint32_t ok;
  asm volatile("{\n.reg .pred p;\nmbarrier.test_wait.parity.shared::cta.b64 p, [%1], %2;\nselp.u32 %0, 1, 0, p;\n}" : "=r"(ok) : "r"(b), "r"(ph) : "memory");
  return __all_sync(0xffffffffu, ok);
}
__device__ __forceinline__ void fence_bar_init() { asm volatile("fence.mbarrier_init.release.cluster;" ::: "memory"); }
__device__ __forceinline__ void fence_async() { asm volatile("fence.proxy.async.shared::cta;" ::: "memory"); }
__device__ __forceinline__ void bar_sync(int id, int n) { asm volatile("bar.sync %0, %1;" ::"r"(id), "r"(n) : "memory"); }
__device__ __forceinline__ void bar_arrive(int id, int n) { asm volatile("bar.arrive %0, %1;" ::"r"(id), "r"(n) : "memory"); }
__device__ __forceinline__ void pdl_wait() { asm volatile("griddepcontrol.wait;" ::: "memory"); }
__device__ __forceinline__ void pdl_launch() { asm volatile("griddepcontrol.launch_dependents;" ::: "memory"); }
__device__ __forceinline__ void prefetch_map(const CUtensorMap* m) {
  asm volatile("prefetch.tensormap [%0];" ::"l"(m) : "memory");
}
template <int P> __device__ __forceinline__ uint64_t policy() {
  uint64_t p;
  asm("createpolicy.fractional.L2::evict_first.b64 %0, 1.0;" : "=l"(p));
  return p;
}
template <int P> __device__ __forceinline__ void tma_ld3(uint32_t dst, const CUtensorMap* m, uint32_t bar, int c0, int c1, int c2) {
  if constexpr (P == 0)
    asm volatile("cp.async.bulk.tensor.3d.shared::cluster.global.mbarrier::complete_tx::bytes [%0], [%1, {%3, %4, %5}], [%2];"
                 ::"r"(dst), "l"(m), "r"(bar), "r"(c0), "r"(c1), "r"(c2) : "memory");
  else
    asm volatile("cp.async.bulk.tensor.3d.shared::cluster.global.mbarrier::complete_tx::bytes.L2::cache_hint [%0], [%1, {%3, %4, %5}], [%2], %6;"
                 ::"r"(dst), "l"(m), "r"(bar), "r"(c0), "r"(c1), "r"(c2), "l"(policy<P>()) : "memory");
}
template <int P> __device__ __forceinline__ void tma_ld3mc(uint32_t dst, const CUtensorMap* m, uint32_t bar, int c0, int c1, int c2) {
  if constexpr (P == 0)
    asm volatile("cp.async.bulk.tensor.3d.shared::cluster.global.mbarrier::complete_tx::bytes.multicast::cluster [%0], [%1, {%3, %4, %5}], [%2], %6;"
                 ::"r"(dst), "l"(m), "r"(bar), "r"(c0), "r"(c1), "r"(c2), "h"((uint16_t)3) : "memory");
  else
    asm volatile("cp.async.bulk.tensor.3d.shared::cluster.global.mbarrier::complete_tx::bytes.multicast::cluster.L2::cache_hint [%0], [%1, {%3, %4, %5}], [%2], %6, %7;"
                 ::"r"(dst), "l"(m), "r"(bar), "r"(c0), "r"(c1), "r"(c2), "h"((uint16_t)3), "l"(policy<P>()) : "memory");
}
template <int P> __device__ __forceinline__ void tma_ld4(uint32_t dst, const CUtensorMap* m, uint32_t bar, int c0, int c1, int c2, int c3) {
  if constexpr (P == 0)
    asm volatile("cp.async.bulk.tensor.4d.shared::cluster.global.mbarrier::complete_tx::bytes [%0], [%1, {%3, %4, %5, %6}], [%2];"
                 ::"r"(dst), "l"(m), "r"(bar), "r"(c0), "r"(c1), "r"(c2), "r"(c3) : "memory");
  else
    asm volatile("cp.async.bulk.tensor.4d.shared::cluster.global.mbarrier::complete_tx::bytes.L2::cache_hint [%0], [%1, {%3, %4, %5, %6}], [%2], %7;"
                 ::"r"(dst), "l"(m), "r"(bar), "r"(c0), "r"(c1), "r"(c2), "r"(c3), "l"(policy<P>()) : "memory");
}
template <int P> __device__ __forceinline__ void tma_ld4mc(uint32_t dst, const CUtensorMap* m, uint32_t bar, int c0, int c1, int c2, int c3) {
  if constexpr (P == 0)
    asm volatile("cp.async.bulk.tensor.4d.shared::cluster.global.mbarrier::complete_tx::bytes.multicast::cluster [%0], [%1, {%3, %4, %5, %6}], [%2], %7;"
                 ::"r"(dst), "l"(m), "r"(bar), "r"(c0), "r"(c1), "r"(c2), "r"(c3), "h"((uint16_t)3) : "memory");
  else
    asm volatile("cp.async.bulk.tensor.4d.shared::cluster.global.mbarrier::complete_tx::bytes.multicast::cluster.L2::cache_hint [%0], [%1, {%3, %4, %5, %6}], [%2], %7, %8;"
                 ::"r"(dst), "l"(m), "r"(bar), "r"(c0), "r"(c1), "r"(c2), "r"(c3), "h"((uint16_t)3), "l"(policy<P>()) : "memory");
}
template <int P> __device__ __forceinline__ void tma_ld5(uint32_t dst, const CUtensorMap* m, uint32_t bar, int c0, int c1, int c2, int c3, int c4) {
  if constexpr (P == 0)
    asm volatile("cp.async.bulk.tensor.5d.shared::cluster.global.mbarrier::complete_tx::bytes [%0], [%1, {%3, %4, %5, %6, %7}], [%2];"
                 ::"r"(dst), "l"(m), "r"(bar), "r"(c0), "r"(c1), "r"(c2), "r"(c3), "r"(c4) : "memory");
  else
    asm volatile("cp.async.bulk.tensor.5d.shared::cluster.global.mbarrier::complete_tx::bytes.L2::cache_hint [%0], [%1, {%3, %4, %5, %6, %7}], [%2], %8;"
                 ::"r"(dst), "l"(m), "r"(bar), "r"(c0), "r"(c1), "r"(c2), "r"(c3), "r"(c4), "l"(policy<P>()) : "memory");
}
template <int P> __device__ __forceinline__ void tma_st3(const CUtensorMap* m, uint32_t src, int c0, int c1, int c2) {
  if constexpr (P == 0)
    asm volatile("cp.async.bulk.tensor.3d.global.shared::cta.bulk_group [%0, {%2, %3, %4}], [%1];" ::"l"(m), "r"(src), "r"(c0), "r"(c1), "r"(c2) : "memory");
  else
    asm volatile("cp.async.bulk.tensor.3d.global.shared::cta.bulk_group.L2::cache_hint [%0, {%2, %3, %4}], [%1], %5;" ::"l"(m), "r"(src), "r"(c0), "r"(c1), "r"(c2), "l"(policy<P>()) : "memory");
}
template <int P> __device__ __forceinline__ void tma_st4(const CUtensorMap* m, uint32_t src, int c0, int c1, int c2, int c3) {
  if constexpr (P == 0)
    asm volatile("cp.async.bulk.tensor.4d.global.shared::cta.bulk_group [%0, {%2, %3, %4, %5}], [%1];" ::"l"(m), "r"(src), "r"(c0), "r"(c1), "r"(c2), "r"(c3) : "memory");
  else
    asm volatile("cp.async.bulk.tensor.4d.global.shared::cta.bulk_group.L2::cache_hint [%0, {%2, %3, %4, %5}], [%1], %6;" ::"l"(m), "r"(src), "r"(c0), "r"(c1), "r"(c2), "r"(c3), "l"(policy<P>()) : "memory");
}
template <int P> __device__ __forceinline__ void tma_st5(const CUtensorMap* m, uint32_t src, int c0, int c1, int c2, int c3, int c4) {
  if constexpr (P == 0)
    asm volatile("cp.async.bulk.tensor.5d.global.shared::cta.bulk_group [%0, {%2, %3, %4, %5, %6}], [%1];" ::"l"(m), "r"(src), "r"(c0), "r"(c1), "r"(c2), "r"(c3), "r"(c4) : "memory");
  else
    asm volatile("cp.async.bulk.tensor.5d.global.shared::cta.bulk_group.L2::cache_hint [%0, {%2, %3, %4, %5, %6}], [%1], %7;" ::"l"(m), "r"(src), "r"(c0), "r"(c1), "r"(c2), "r"(c3), "r"(c4), "l"(policy<P>()) : "memory");
}
__device__ __forceinline__ void bulk_commit() { asm volatile("cp.async.bulk.commit_group;" ::: "memory"); }
template <int N> __device__ __forceinline__ void bulk_wait() { asm volatile("cp.async.bulk.wait_group %0;" ::"n"(N) : "memory"); }
template <int N> __device__ __forceinline__ void bulk_wait_read() { asm volatile("cp.async.bulk.wait_group.read %0;" ::"n"(N) : "memory"); }
__device__ __forceinline__ void wg_fence() { asm volatile("wgmma.fence.sync.aligned;" ::: "memory"); }
__device__ __forceinline__ void wg_commit() { asm volatile("wgmma.commit_group.sync.aligned;" ::: "memory"); }
template <int N> __device__ __forceinline__ void wg_wait() { asm volatile("wgmma.wait_group.sync.aligned %0;" ::"n"(N) : "memory"); }
template <int R> __device__ __forceinline__ void reg_fence(float (&d)[R]) {
#pragma unroll
  for (int i = 0; i < R; i++) asm volatile("" : "+f"(d[i])::"memory");
}
template <int R> __device__ __forceinline__ void reg_fence(uint32_t (&d)[R]) {
#pragma unroll
  for (int i = 0; i < R; i++) asm volatile("" : "+r"(d[i])::"memory");
}
__device__ __forceinline__ void stsm4(uint32_t a, uint32_t r0, uint32_t r1, uint32_t r2, uint32_t r3) {
  asm volatile("stmatrix.sync.aligned.m8n8.x4.shared.b16 [%0], {%1, %2, %3, %4};" ::"r"(a), "r"(r0), "r"(r1), "r"(r2), "r"(r3) : "memory");
}
__device__ __forceinline__ void stsm4t(uint32_t a, uint32_t r0, uint32_t r1, uint32_t r2, uint32_t r3) {
  asm volatile("stmatrix.sync.aligned.m8n8.x4.trans.shared.b16 [%0], {%1, %2, %3, %4};" ::"r"(a), "r"(r0), "r"(r1), "r"(r2), "r"(r3) : "memory");
}
__device__ __forceinline__ void ldsm4(uint32_t a, uint32_t& r0, uint32_t& r1, uint32_t& r2, uint32_t& r3) {
  asm volatile("ldmatrix.sync.aligned.m8n8.x4.shared.b16 {%0, %1, %2, %3}, [%4];" : "=r"(r0), "=r"(r1), "=r"(r2), "=r"(r3) : "r"(a) : "memory");
}
__device__ __forceinline__ void ldg128(const uint4* p, uint32_t& a, uint32_t& b, uint32_t& c, uint32_t& d) {
  asm volatile("ld.global.nc.v4.u32 {%0, %1, %2, %3}, [%4];" : "=r"(a), "=r"(b), "=r"(c), "=r"(d) : "l"(p));
}
__device__ __forceinline__ uint32_t pack2(float lo, float hi) {
  uint32_t r;
  asm("cvt.rn.bf16x2.f32 %0, %1, %2;" : "=r"(r) : "f"(hi), "f"(lo));
  return r;
}
__device__ __forceinline__ float tanh_f32(float x) {
  float y;
  asm("tanh.approx.f32 %0, %1;" : "=f"(y) : "f"(x));
  return y;
}
__device__ __forceinline__ float gelu(float hx) {
  const float u = hx * fmaf(hx * hx, 8.0f * 0.044715f * 0.7978845608028654f, 2.0f * 0.7978845608028654f);
  return fmaf(hx, tanh_f32(u), hx);
}
__device__ __forceinline__ uint64_t mk_desc4(uint32_t addr4, uint32_t lbo, uint32_t sbo, uint32_t swz) {
  const uint32_t lo = addr4 + ((lbo >> 4) << 16), hi = (sbo >> 4) | (swz << 30);
  uint64_t d;
  asm("mov.b64 %0, {%1, %2};" : "=l"(d) : "r"(lo), "r"(hi));
  return d;
}
#define mk_desc(base, off, lbo, sbo, swz) mk_desc4((((base) & 0x3FFFF) >> 4) + ((off) >> 4), lbo, sbo, swz)

template <int SA, int SB, int TA, int TB>
__device__ __forceinline__ void wgmma_ss_16(float (&d)[8], uint64_t da, uint64_t db, int sd) {
  asm volatile("{\n.reg .pred p;\nsetp.ne.b32 p, %10, 0;\n"
      "wgmma.mma_async.sync.aligned.m64n16k16.f32.bf16.bf16 {"
      "%0, %1, %2, %3, %4, %5, %6, %7"
      "}, %8, %9, p, %11, %12, %13, %14;\n}\n"
      : "+f"(d[0]), "+f"(d[1]), "+f"(d[2]), "+f"(d[3]), "+f"(d[4]), "+f"(d[5]), "+f"(d[6]), "+f"(d[7])
      : "l"(da), "l"(db), "r"(sd), "n"(SA), "n"(SB), "n"(TA), "n"(TB));
}
template <int SA, int SB, int TA, int TB>
__device__ __forceinline__ void wgmma_ss_24(float (&d)[12], uint64_t da, uint64_t db, int sd) {
  asm volatile("{\n.reg .pred p;\nsetp.ne.b32 p, %14, 0;\n"
      "wgmma.mma_async.sync.aligned.m64n24k16.f32.bf16.bf16 {"
      "%0, %1, %2, %3, %4, %5, %6, %7, %8, %9, %10, %11"
      "}, %12, %13, p, %15, %16, %17, %18;\n}\n"
      : "+f"(d[0]), "+f"(d[1]), "+f"(d[2]), "+f"(d[3]), "+f"(d[4]), "+f"(d[5]), "+f"(d[6]), "+f"(d[7]), "+f"(d[8]),
        "+f"(d[9]), "+f"(d[10]), "+f"(d[11])
      : "l"(da), "l"(db), "r"(sd), "n"(SA), "n"(SB), "n"(TA), "n"(TB));
}
template <int SA, int SB, int TA, int TB>
__device__ __forceinline__ void wgmma_ss_128(float (&d)[64], uint64_t da, uint64_t db, int sd) {
  asm volatile("{\n.reg .pred p;\nsetp.ne.b32 p, %66, 0;\n"
      "wgmma.mma_async.sync.aligned.m64n128k16.f32.bf16.bf16 {"
      "%0, %1, %2, %3, %4, %5, %6, %7, %8, %9, %10, %11, %12, %13, %14, %15, %16, %17, %18, %19, %20, %21, %22, %23, "
      "%24, %25, %26, %27, %28, %29, %30, %31, %32, %33, %34, %35, %36, %37, %38, %39, %40, %41, %42, %43, %44, %45, "
      "%46, %47, %48, %49, %50, %51, %52, %53, %54, %55, %56, %57, %58, %59, %60, %61, %62, %63"
      "}, %64, %65, p, %67, %68, %69, %70;\n}\n"
      : "+f"(d[0]), "+f"(d[1]), "+f"(d[2]), "+f"(d[3]), "+f"(d[4]), "+f"(d[5]), "+f"(d[6]), "+f"(d[7]), "+f"(d[8]),
        "+f"(d[9]), "+f"(d[10]), "+f"(d[11]), "+f"(d[12]), "+f"(d[13]), "+f"(d[14]), "+f"(d[15]), "+f"(d[16]),
        "+f"(d[17]), "+f"(d[18]), "+f"(d[19]), "+f"(d[20]), "+f"(d[21]), "+f"(d[22]), "+f"(d[23]), "+f"(d[24]),
        "+f"(d[25]), "+f"(d[26]), "+f"(d[27]), "+f"(d[28]), "+f"(d[29]), "+f"(d[30]), "+f"(d[31]), "+f"(d[32]),
        "+f"(d[33]), "+f"(d[34]), "+f"(d[35]), "+f"(d[36]), "+f"(d[37]), "+f"(d[38]), "+f"(d[39]), "+f"(d[40]),
        "+f"(d[41]), "+f"(d[42]), "+f"(d[43]), "+f"(d[44]), "+f"(d[45]), "+f"(d[46]), "+f"(d[47]), "+f"(d[48]),
        "+f"(d[49]), "+f"(d[50]), "+f"(d[51]), "+f"(d[52]), "+f"(d[53]), "+f"(d[54]), "+f"(d[55]), "+f"(d[56]),
        "+f"(d[57]), "+f"(d[58]), "+f"(d[59]), "+f"(d[60]), "+f"(d[61]), "+f"(d[62]), "+f"(d[63])
      : "l"(da), "l"(db), "r"(sd), "n"(SA), "n"(SB), "n"(TA), "n"(TB));
}
template <int SA, int SB, int TA, int TB>
__device__ __forceinline__ void wgmma_ss_168(float (&d)[84], uint64_t da, uint64_t db, int sd) {
  asm volatile("{\n.reg .pred p;\nsetp.ne.b32 p, %86, 0;\n"
      "wgmma.mma_async.sync.aligned.m64n168k16.f32.bf16.bf16 {"
      "%0, %1, %2, %3, %4, %5, %6, %7, %8, %9, %10, %11, %12, %13, %14, %15, %16, %17, %18, %19, %20, %21, %22, %23, "
      "%24, %25, %26, %27, %28, %29, %30, %31, %32, %33, %34, %35, %36, %37, %38, %39, %40, %41, %42, %43, %44, %45, "
      "%46, %47, %48, %49, %50, %51, %52, %53, %54, %55, %56, %57, %58, %59, %60, %61, %62, %63, %64, %65, %66, %67, "
      "%68, %69, %70, %71, %72, %73, %74, %75, %76, %77, %78, %79, %80, %81, %82, %83"
      "}, %84, %85, p, %87, %88, %89, %90;\n}\n"
      : "+f"(d[0]), "+f"(d[1]), "+f"(d[2]), "+f"(d[3]), "+f"(d[4]), "+f"(d[5]), "+f"(d[6]), "+f"(d[7]), "+f"(d[8]),
        "+f"(d[9]), "+f"(d[10]), "+f"(d[11]), "+f"(d[12]), "+f"(d[13]), "+f"(d[14]), "+f"(d[15]), "+f"(d[16]),
        "+f"(d[17]), "+f"(d[18]), "+f"(d[19]), "+f"(d[20]), "+f"(d[21]), "+f"(d[22]), "+f"(d[23]), "+f"(d[24]),
        "+f"(d[25]), "+f"(d[26]), "+f"(d[27]), "+f"(d[28]), "+f"(d[29]), "+f"(d[30]), "+f"(d[31]), "+f"(d[32]),
        "+f"(d[33]), "+f"(d[34]), "+f"(d[35]), "+f"(d[36]), "+f"(d[37]), "+f"(d[38]), "+f"(d[39]), "+f"(d[40]),
        "+f"(d[41]), "+f"(d[42]), "+f"(d[43]), "+f"(d[44]), "+f"(d[45]), "+f"(d[46]), "+f"(d[47]), "+f"(d[48]),
        "+f"(d[49]), "+f"(d[50]), "+f"(d[51]), "+f"(d[52]), "+f"(d[53]), "+f"(d[54]), "+f"(d[55]), "+f"(d[56]),
        "+f"(d[57]), "+f"(d[58]), "+f"(d[59]), "+f"(d[60]), "+f"(d[61]), "+f"(d[62]), "+f"(d[63]), "+f"(d[64]),
        "+f"(d[65]), "+f"(d[66]), "+f"(d[67]), "+f"(d[68]), "+f"(d[69]), "+f"(d[70]), "+f"(d[71]), "+f"(d[72]),
        "+f"(d[73]), "+f"(d[74]), "+f"(d[75]), "+f"(d[76]), "+f"(d[77]), "+f"(d[78]), "+f"(d[79]), "+f"(d[80]),
        "+f"(d[81]), "+f"(d[82]), "+f"(d[83])
      : "l"(da), "l"(db), "r"(sd), "n"(SA), "n"(SB), "n"(TA), "n"(TB));
}
template <int SA, int SB, int TB>
__device__ __forceinline__ void wgmma_rs_64(float (&d)[32], uint32_t a0, uint32_t a1, uint32_t a2, uint32_t a3, uint64_t db, int sd) {
  asm volatile("{\n.reg .pred p;\nsetp.ne.b32 p, %37, 0;\n"
      "wgmma.mma_async.sync.aligned.m64n64k16.f32.bf16.bf16 {"
      "%0, %1, %2, %3, %4, %5, %6, %7, %8, %9, %10, %11, %12, %13, %14, %15, %16, %17, %18, %19, %20, %21, %22, %23, "
      "%24, %25, %26, %27, %28, %29, %30, %31"
      "}, {%32, %33, %34, %35}, %36, p, %38, %39, %40;\n}\n"
      : "+f"(d[0]), "+f"(d[1]), "+f"(d[2]), "+f"(d[3]), "+f"(d[4]), "+f"(d[5]), "+f"(d[6]), "+f"(d[7]), "+f"(d[8]),
        "+f"(d[9]), "+f"(d[10]), "+f"(d[11]), "+f"(d[12]), "+f"(d[13]), "+f"(d[14]), "+f"(d[15]), "+f"(d[16]),
        "+f"(d[17]), "+f"(d[18]), "+f"(d[19]), "+f"(d[20]), "+f"(d[21]), "+f"(d[22]), "+f"(d[23]), "+f"(d[24]),
        "+f"(d[25]), "+f"(d[26]), "+f"(d[27]), "+f"(d[28]), "+f"(d[29]), "+f"(d[30]), "+f"(d[31])
      : "r"(a0), "r"(a1), "r"(a2), "r"(a3), "l"(db), "r"(sd), "n"(SA), "n"(SB), "n"(TB));
}
template <int SA, int SB, int TB>
__device__ __forceinline__ void wgmma_rs_128(float (&d)[64], uint32_t a0, uint32_t a1, uint32_t a2, uint32_t a3, uint64_t db, int sd) {
  asm volatile("{\n.reg .pred p;\nsetp.ne.b32 p, %69, 0;\n"
      "wgmma.mma_async.sync.aligned.m64n128k16.f32.bf16.bf16 {"
      "%0, %1, %2, %3, %4, %5, %6, %7, %8, %9, %10, %11, %12, %13, %14, %15, %16, %17, %18, %19, %20, %21, %22, %23, "
      "%24, %25, %26, %27, %28, %29, %30, %31, %32, %33, %34, %35, %36, %37, %38, %39, %40, %41, %42, %43, %44, %45, "
      "%46, %47, %48, %49, %50, %51, %52, %53, %54, %55, %56, %57, %58, %59, %60, %61, %62, %63"
      "}, {%64, %65, %66, %67}, %68, p, %70, %71, %72;\n}\n"
      : "+f"(d[0]), "+f"(d[1]), "+f"(d[2]), "+f"(d[3]), "+f"(d[4]), "+f"(d[5]), "+f"(d[6]), "+f"(d[7]), "+f"(d[8]),
        "+f"(d[9]), "+f"(d[10]), "+f"(d[11]), "+f"(d[12]), "+f"(d[13]), "+f"(d[14]), "+f"(d[15]), "+f"(d[16]),
        "+f"(d[17]), "+f"(d[18]), "+f"(d[19]), "+f"(d[20]), "+f"(d[21]), "+f"(d[22]), "+f"(d[23]), "+f"(d[24]),
        "+f"(d[25]), "+f"(d[26]), "+f"(d[27]), "+f"(d[28]), "+f"(d[29]), "+f"(d[30]), "+f"(d[31]), "+f"(d[32]),
        "+f"(d[33]), "+f"(d[34]), "+f"(d[35]), "+f"(d[36]), "+f"(d[37]), "+f"(d[38]), "+f"(d[39]), "+f"(d[40]),
        "+f"(d[41]), "+f"(d[42]), "+f"(d[43]), "+f"(d[44]), "+f"(d[45]), "+f"(d[46]), "+f"(d[47]), "+f"(d[48]),
        "+f"(d[49]), "+f"(d[50]), "+f"(d[51]), "+f"(d[52]), "+f"(d[53]), "+f"(d[54]), "+f"(d[55]), "+f"(d[56]),
        "+f"(d[57]), "+f"(d[58]), "+f"(d[59]), "+f"(d[60]), "+f"(d[61]), "+f"(d[62]), "+f"(d[63])
      : "r"(a0), "r"(a1), "r"(a2), "r"(a3), "l"(db), "r"(sd), "n"(SA), "n"(SB), "n"(TB));
}
template <int SA, int SB, int TB>
__device__ __forceinline__ void wgmma_rs_256(float (&d)[128], uint32_t a0, uint32_t a1, uint32_t a2, uint32_t a3, uint64_t db, int sd) {
  asm volatile("{\n.reg .pred p;\nsetp.ne.b32 p, %133, 0;\n"
      "wgmma.mma_async.sync.aligned.m64n256k16.f32.bf16.bf16 {"
      "%0, %1, %2, %3, %4, %5, %6, %7, %8, %9, %10, %11, %12, %13, %14, %15, %16, %17, %18, %19, %20, %21, %22, %23, "
      "%24, %25, %26, %27, %28, %29, %30, %31, %32, %33, %34, %35, %36, %37, %38, %39, %40, %41, %42, %43, %44, %45, "
      "%46, %47, %48, %49, %50, %51, %52, %53, %54, %55, %56, %57, %58, %59, %60, %61, %62, %63, %64, %65, %66, %67, "
      "%68, %69, %70, %71, %72, %73, %74, %75, %76, %77, %78, %79, %80, %81, %82, %83, %84, %85, %86, %87, %88, %89, "
      "%90, %91, %92, %93, %94, %95, %96, %97, %98, %99, %100, %101, %102, %103, %104, %105, %106, %107, %108, %109, "
      "%110, %111, %112, %113, %114, %115, %116, %117, %118, %119, %120, %121, %122, %123, %124, %125, %126, %127"
      "}, {%128, %129, %130, %131}, %132, p, %134, %135, %136;\n}\n"
      : "+f"(d[0]), "+f"(d[1]), "+f"(d[2]), "+f"(d[3]), "+f"(d[4]), "+f"(d[5]), "+f"(d[6]), "+f"(d[7]), "+f"(d[8]),
        "+f"(d[9]), "+f"(d[10]), "+f"(d[11]), "+f"(d[12]), "+f"(d[13]), "+f"(d[14]), "+f"(d[15]), "+f"(d[16]),
        "+f"(d[17]), "+f"(d[18]), "+f"(d[19]), "+f"(d[20]), "+f"(d[21]), "+f"(d[22]), "+f"(d[23]), "+f"(d[24]),
        "+f"(d[25]), "+f"(d[26]), "+f"(d[27]), "+f"(d[28]), "+f"(d[29]), "+f"(d[30]), "+f"(d[31]), "+f"(d[32]),
        "+f"(d[33]), "+f"(d[34]), "+f"(d[35]), "+f"(d[36]), "+f"(d[37]), "+f"(d[38]), "+f"(d[39]), "+f"(d[40]),
        "+f"(d[41]), "+f"(d[42]), "+f"(d[43]), "+f"(d[44]), "+f"(d[45]), "+f"(d[46]), "+f"(d[47]), "+f"(d[48]),
        "+f"(d[49]), "+f"(d[50]), "+f"(d[51]), "+f"(d[52]), "+f"(d[53]), "+f"(d[54]), "+f"(d[55]), "+f"(d[56]),
        "+f"(d[57]), "+f"(d[58]), "+f"(d[59]), "+f"(d[60]), "+f"(d[61]), "+f"(d[62]), "+f"(d[63]), "+f"(d[64]),
        "+f"(d[65]), "+f"(d[66]), "+f"(d[67]), "+f"(d[68]), "+f"(d[69]), "+f"(d[70]), "+f"(d[71]), "+f"(d[72]),
        "+f"(d[73]), "+f"(d[74]), "+f"(d[75]), "+f"(d[76]), "+f"(d[77]), "+f"(d[78]), "+f"(d[79]), "+f"(d[80]),
        "+f"(d[81]), "+f"(d[82]), "+f"(d[83]), "+f"(d[84]), "+f"(d[85]), "+f"(d[86]), "+f"(d[87]), "+f"(d[88]),
        "+f"(d[89]), "+f"(d[90]), "+f"(d[91]), "+f"(d[92]), "+f"(d[93]), "+f"(d[94]), "+f"(d[95]), "+f"(d[96]),
        "+f"(d[97]), "+f"(d[98]), "+f"(d[99]), "+f"(d[100]), "+f"(d[101]), "+f"(d[102]), "+f"(d[103]), "+f"(d[104]),
        "+f"(d[105]), "+f"(d[106]), "+f"(d[107]), "+f"(d[108]), "+f"(d[109]), "+f"(d[110]), "+f"(d[111]),
        "+f"(d[112]), "+f"(d[113]), "+f"(d[114]), "+f"(d[115]), "+f"(d[116]), "+f"(d[117]), "+f"(d[118]),
        "+f"(d[119]), "+f"(d[120]), "+f"(d[121]), "+f"(d[122]), "+f"(d[123]), "+f"(d[124]), "+f"(d[125]),
        "+f"(d[126]), "+f"(d[127])
      : "r"(a0), "r"(a1), "r"(a2), "r"(a3), "l"(db), "r"(sd), "n"(SA), "n"(SB), "n"(TB));
}

__device__ const __align__(128) uint32_t c_img[3584] = {
    0x00003c80, 0x00003c80, 0x00003c80, 0x00003c80, 0x00003c80, 0x00003c80, 0x00003c80, 0x00003c80, 0x00003c80, 0x00003c80,
    0x00003c80, 0x00003c80, 0x00003c80, 0x00003c80, 0x00003c80, 0x00003c80, 0x00003c80, 0x00003c80, 0x00003c80, 0x00003c80,
    0x00003c80, 0x00003c80, 0x00003c80, 0x00003c80, 0x00003c80, 0x00003c80, 0x00003c80, 0x00003c80, 0x00003c80, 0x00003c80,
    0x00003c80, 0x00003c80, 0x3c463c22, 0x3c623bf1, 0x3c753b95, 0x3c7f3ac9, 0x3ac93c7f, 0x3b953c75, 0x3bf13c62, 0x3c223c46,
    0x3c22bc46, 0x3bf1bc62, 0x3b95bc75, 0x3ac9bc7f, 0x3c7fbac9, 0x3c75bb95, 0x3c62bbf1, 0x3c46bc22, 0xbc46bc22, 0xbc62bbf1,
    0xbc75bb95, 0xbc7fbac9, 0xbac9bc7f, 0xbb95bc75, 0xbbf1bc62, 0xbc22bc46, 0xbc223c46, 0xbbf13c62, 0xbb953c75, 0xbac93c7f,
    0xbc7f3ac9, 0xbc753b95, 0xbc623bf1, 0xbc463c22, 0xbb48bc7b, 0xbc0ebc55, 0xbc55bc0e, 0xbc7bbb48, 0xbc7b3b48, 0xbc553c0e,
    0xbc0e3c55, 0xbb483c7b, 0x3b483c7b, 0x3c0e3c55, 0x3c553c0e, 0x3c7b3b48, 0x3c7bbb48, 0x3c55bc0e, 0x3c0ebc55, 0x3b48bc7b,
    0xbb48bc7b, 0xbc0ebc55, 0xbc55bc0e, 0xbc7bbb48, 0xbc7b3b48, 0xbc553c0e, 0xbc0e3c55, 0xbb483c7b, 0x3b483c7b, 0x3c0e3c55,
    0x3c553c0e, 0x3c7b3b48, 0x3c7bbb48, 0x3c55bc0e, 0x3c0ebc55, 0x3b48bc7b, 0x3c623bf1, 0x3c7fbac9, 0x3c46bc22, 0x3b95bc75,
    0xbc753b95, 0xbc223c46, 0xbac93c7f, 0x3bf13c62, 0x3bf1bc62, 0xbac9bc7f, 0xbc22bc46, 0xbc75bb95, 0x3b953c75, 0x3c463c22,
    0x3c7f3ac9, 0x3c62bbf1, 0xbc62bbf1, 0xbc7f3ac9, 0xbc463c22, 0xbb953c75, 0x3c75bb95, 0x3c22bc46, 0x3ac9bc7f, 0xbbf1bc62,
    0xbbf13c62, 0x3ac93c7f, 0x3c223c46, 0x3c753b95, 0xbb95bc75, 0xbc46bc22, 0xbc7fbac9, 0xbc623bf1, 0x3bc43c6d, 0x3c6d3bc4,
    0x3c6dbbc4, 0x3bc4bc6d, 0xbbc4bc6d, 0xbc6dbbc4, 0xbc6d3bc4, 0xbbc43c6d, 0x3bc43c6d, 0x3c6d3bc4, 0x3c6dbbc4, 0x3bc4bc6d,
    0xbbc4bc6d, 0xbc6dbbc4, 0xbc6d3bc4, 0xbbc43c6d, 0x3bc43c6d, 0x3c6d3bc4, 0x3c6dbbc4, 0x3bc4bc6d, 0xbbc4bc6d, 0xbc6dbbc4,
    0xbc6d3bc4, 0xbbc43c6d, 0x3bc43c6d, 0x3c6d3bc4, 0x3c6dbbc4, 0x3bc4bc6d, 0xbbc4bc6d, 0xbc6dbbc4, 0xbc6d3bc4, 0xbbc43c6d,
    0x3c753b95, 0x3c46bc22, 0xbac9bc7f, 0xbc62bbf1, 0xbbf1bc62, 0xbc7fbac9, 0xbc223c46, 0x3b953c75, 0x3b95bc75, 0xbc22bc46,
    0xbc7f3ac9, 0xbbf13c62, 0xbc623bf1, 0xbac93c7f, 0x3c463c22, 0x3c75bb95, 0xbc75bb95, 0xbc463c22, 0x3ac93c7f, 0x3c623bf1,
    0x3bf13c62, 0x3c7f3ac9, 0x3c22bc46, 0xbb95bc75, 0xbb953c75, 0x3c223c46, 0x3c7fbac9, 0x3bf1bc62, 0x3c62bbf1, 0x3ac9bc7f,
    0xbc46bc22, 0xbc753b95, 0xbc0ebc55, 0xbc7b3b48, 0xbb483c7b, 0x3c553c0e, 0x3c55bc0e, 0xbb48bc7b, 0xbc7bbb48, 0xbc0e3c55,
    0x3c0e3c55, 0x3c7bbb48, 0x3b48bc7b, 0xbc55bc0e, 0xbc553c0e, 0x3b483c7b, 0x3c7b3b48, 0x3c0ebc55, 0xbc0ebc55, 0xbc7b3b48,
    0xbb483c7b, 0x3c553c0e, 0x3c55bc0e, 0xbb48bc7b, 0xbc7bbb48, 0xbc0e3c55, 0x3c0e3c55, 0x3c7bbb48, 0x3b48bc7b, 0xbc55bc0e,
    0xbc553c0e, 0x3b483c7b, 0x3c7b3b48, 0x3c0ebc55, 0x3c7f3ac9, 0x3b95bc75, 0xbc62bbf1, 0xbc223c46, 0x3c46bc22, 0xbbf1bc62,
    0xbc753b95, 0x3ac93c7f, 0x3ac9bc7f, 0xbc75bb95, 0xbbf13c62, 0x3c463c22, 0xbc22bc46, 0xbc623bf1, 0x3b953c75, 0x3c7fbac9,
    0xbc7fbac9, 0xbb953c75, 0x3c623bf1, 0x3c22bc46, 0xbc463c22, 0x3bf13c62, 0x3c75bb95, 0xbac9bc7f, 0xbac93c7f, 0x3c753b95,
    0x3bf1bc62, 0xbc46bc22, 0x3c223c46, 0x3c62bbf1, 0xbb95bc75, 0xbc7f3ac9, 0x3a493c80, 0x3b163c7d, 0x3b793c78, 0x3bac3c71,
    0x3bdb3c67, 0x3c043c5c, 0x3c183c4e, 0x3c2c3c3e, 0x3c3e3c2c, 0x3c4e3c18, 0x3c5c3c04, 0x3c673bdb, 0x3c713bac, 0x3c783b79,
    0x3c7d3b16, 0x3c803a49, 0x3c80ba49, 0x3c7dbb16, 0x3c78bb79, 0x3c71bbac, 0x3c67bbdb, 0x3c5cbc04, 0x3c4ebc18, 0x3c3ebc2c,
    0x3c2cbc3e, 0x3c18bc4e, 0x3c04bc5c, 0x3bdbbc67, 0x3bacbc71, 0x3b79bc78, 0x3b16bc7d, 0x3a49bc80, 0x3c783b79, 0x3c80ba49,
    0x3c71bbac, 0x3c4ebc18, 0x3b163c7d, 0x3bdb3c67, 0x3c2c3c3e, 0x3c5c3c04, 0xbc04bc5c, 0xbc3ebc2c, 0xbc67bbdb, 0xbc7dbb16,
    0x3c18bc4e, 0x3bacbc71, 0x3a49bc80, 0xbb79bc78, 0xbb793c78, 0x3a493c80, 0x3bac3c71, 0x3c183c4e, 0xbc7d3b16, 0xbc673bdb,
    0xbc3e3c2c, 0xbc043c5c, 0x3c5cbc04, 0x3c2cbc3e, 0x3bdbbc67, 0x3b16bc7d, 0x3c4e3c18, 0x3c713bac, 0x3c803a49, 0x3c78bb79,
    0xbc5cbc04, 0xbc80ba49, 0xbc673bdb, 0xbc183c4e, 0xbb163c7d, 0x3bac3c71, 0x3c3e3c2c, 0x3c783b79, 0x3b793c78, 0x3c2c3c3e,
    0x3c713bac, 0x3c7dbb16, 0x3c4ebc18, 0x3bdbbc67, 0xba49bc80, 0xbc04bc5c, 0xbc043c5c, 0xba493c80, 0x3bdb3c67, 0x3c4e3c18,
    0x3c7d3b16, 0x3c71bbac, 0x3c2cbc3e, 0x3b79bc78, 0x3c78bb79, 0x3c3ebc2c, 0x3bacbc71, 0xbb16bc7d, 0xbc18bc4e, 0xbc67bbdb,
    0xbc803a49, 0xbc5c3c04, 0x3c3ebc2c, 0x3b16bc7d, 0xbc04bc5c, 0xbc71bbac, 0xbbdb3c67, 0x3b793c78, 0x3c4e3c18, 0x3c80ba49,
    0x3a49bc80, 0xbc18bc4e, 0xbc78bb79, 0xbc673bdb, 0x3bac3c71, 0x3c5c3c04, 0x3c7dbb16, 0x3c2cbc3e, 0x3c2c3c3e, 0x3c7d3b16,
    0x3c5cbc04, 0x3bacbc71, 0xbc67bbdb, 0xbc783b79, 0xbc183c4e, 0x3a493c80, 0x3c803a49, 0x3c4ebc18, 0x3b79bc78, 0xbbdbbc67,
    0xbc713bac, 0xbc043c5c, 0x3b163c7d, 0x3c3e3c2c, 0x3c67bbdb, 0x3b79bc78, 0xbc18bc4e, 0xbc80ba49, 0xbc2c3c3e, 0x3b163c7d,
    0x3c5c3c04, 0x3c71bbac, 0x3bacbc71, 0xbc04bc5c, 0xbc7dbb16, 0xbc3e3c2c, 0x3a493c80, 0x3c4e3c18, 0x3c78bb79, 0x3bdbbc67,
    0x3bdb3c67, 0x3c783b79, 0x3c4ebc18, 0x3a49bc80, 0xbc3ebc2c, 0xbc7d3b16, 0xbc043c5c, 0x3bac3c71, 0x3c713bac, 0x3c5cbc04,
    0x3b16bc7d, 0xbc2cbc3e, 0xbc803a49, 0xbc183c4e, 0x3b793c78, 0x3c673bdb, 0xbb16bc7d, 0xbc71bbac, 0xbc3e3c2c, 0x3b793c78,
    0xbc5c3c04, 0x3a493c80, 0x3c673bdb, 0x3c4ebc18, 0xbc183c4e, 0x3bdb3c67, 0x3c803a49, 0x3c04bc5c, 0x3c783b79, 0x3c2cbc3e,
    0xbbacbc71, 0xbc7dbb16, 0xbc7d3b16, 0xbbac3c71, 0x3c2c3c3e, 0x3c78bb79, 0x3c043c5c, 0x3c80ba49, 0x3bdbbc67, 0xbc18bc4e,
    0x3c4e3c18, 0x3c67bbdb, 0x3a49bc80, 0xbc5cbc04, 0x3b79bc78, 0xbc3ebc2c, 0xbc713bac, 0xbb163c7d, 0xbb163c7d, 0x3c673bdb,
    0x3c2cbc3e, 0xbc04bc5c, 0xbc783b79, 0xba493c80, 0x3c713bac, 0x3c18bc4e, 0x3c4ebc18, 0xbbacbc71, 0xbc803a49, 0xbb793c78,
    0x3c5c3c04, 0x3c3ebc2c, 0xbbdbbc67, 0xbc7d3b16, 0xbc7dbb16, 0xbbdb3c67, 0x3c3e3c2c, 0x3c5cbc04, 0xbb79bc78, 0xbc80ba49,
    0xbbac3c71, 0x3c4e3c18, 0x3c183c4e, 0x3c71bbac, 0xba49bc80, 0xbc78bb79, 0xbc043c5c, 0x3c2c3c3e, 0x3c67bbdb, 0xbb16bc7d,
    0xbc67bbdb, 0xbc043c5c, 0x3c4e3c18, 0x3c2cbc3e, 0xbc80ba49, 0xbb163c7d, 0x3c783b79, 0x3bacbc71, 0xbc713bac, 0x3b793c78,
    0x3c7dbb16, 0xba49bc80, 0xbc3e3c2c, 0x3c183c4e, 0x3c5cbc04, 0xbbdbbc67, 0xbbdb3c67, 0x3c5c3c04, 0x3c18bc4e, 0xbc3ebc2c,
    0xba493c80, 0x3c7d3b16, 0x3b79bc78, 0xbc71bbac, 0x3bac3c71, 0x3c78bb79, 0xbb16bc7d, 0xbc803a49, 0x3c2c3c3e, 0x3c4ebc18,
    0xbc04bc5c, 0xbc673bdb, 0x3c353c35, 0x3c35bc35, 0xbc35bc35, 0xbc353c35, 0x3c353c35, 0x3c35bc35, 0xbc35bc35, 0xbc353c35,
    0x3c353c35, 0x3c35bc35, 0xbc35bc35, 0xbc353c35, 0x3c353c35, 0x3c35bc35, 0xbc35bc35, 0xbc353c35, 0x3c353c35, 0x3c35bc35,
    0xbc35bc35, 0xbc353c35, 0x3c353c35, 0x3c35bc35, 0xbc35bc35, 0xbc353c35, 0x3c353c35, 0x3c35bc35, 0xbc35bc35, 0xbc353c35,
    0x3c353c35, 0x3c35bc35, 0xbc35bc35, 0xbc353c35, 0x3c7fbac9, 0xbb95bc75, 0xbc623bf1, 0x3c223c46, 0x3c463c22, 0x3bf1bc62,
    0xbc75bb95, 0xbac93c7f, 0xbac9bc7f, 0xbc753b95, 0x3bf13c62, 0x3c46bc22, 0x3c22bc46, 0xbc62bbf1, 0xbb953c75, 0x3c7f3ac9,
    0xbc7f3ac9, 0x3b953c75, 0x3c62bbf1, 0xbc22bc46, 0xbc46bc22, 0xbbf13c62, 0x3c753b95, 0x3ac9bc7f, 0x3ac93c7f, 0x3c75bb95,
    0xbbf1bc62, 0xbc463c22, 0xbc223c46, 0x3c623bf1, 0x3b95bc75, 0xbc7fbac9, 0xbc55bc0e, 0xbb483c7b, 0x3c7bbb48, 0xbc0ebc55,
    0xbc0e3c55, 0x3c7b3b48, 0xbb48bc7b, 0xbc553c0e, 0x3c553c0e, 0x3b48bc7b, 0xbc7b3b48, 0x3c0e3c55, 0x3c0ebc55, 0xbc7bbb48,
    0x3b483c7b, 0x3c55bc0e, 0xbc55bc0e, 0xbb483c7b, 0x3c7bbb48, 0xbc0ebc55, 0xbc0e3c55, 0x3c7b3b48, 0xbb48bc7b, 0xbc553c0e,
    0x3c553c0e, 0x3b48bc7b, 0xbc7b3b48, 0x3c0e3c55, 0x3c0ebc55, 0xbc7bbb48, 0x3b483c7b, 0x3c55bc0e, 0x3c75bb95, 0xbc46bc22,
    0xbac93c7f, 0x3c62bbf1, 0xbbf13c62, 0x3c7fbac9, 0xbc22bc46, 0xbb953c75, 0xbb95bc75, 0xbc223c46, 0x3c7f3ac9, 0xbbf1bc62,
    0x3c623bf1, 0xbac9bc7f, 0xbc463c22, 0x3c753b95, 0xbc753b95, 0x3c463c22, 0x3ac9bc7f, 0xbc623bf1, 0x3bf1bc62, 0xbc7f3ac9,
    0x3c223c46, 0x3b95bc75, 0x3b953c75, 0x3c22bc46, 0xbc7fbac9, 0x3bf13c62, 0xbc62bbf1, 0x3ac93c7f, 0x3c46bc22, 0xbc75bb95,
    0x3c6d3bc4, 0xbbc4bc6d, 0xbbc43c6d, 0x3c6dbbc4, 0xbc6dbbc4, 0x3bc43c6d, 0x3bc4bc6d, 0xbc6d3bc4, 0x3c6d3bc4, 0xbbc4bc6d,
    0xbbc43c6d, 0x3c6dbbc4, 0xbc6dbbc4, 0x3bc43c6d, 0x3bc4bc6d, 0xbc6d3bc4, 0x3c6d3bc4, 0xbbc4bc6d, 0xbbc43c6d, 0x3c6dbbc4,
    0xbc6dbbc4, 0x3bc43c6d, 0x3bc4bc6d, 0xbc6d3bc4, 0x3c6d3bc4, 0xbbc4bc6d, 0xbbc43c6d, 0x3c6dbbc4, 0xbc6dbbc4, 0x3bc43c6d,
    0x3bc4bc6d, 0xbc6d3bc4, 0x3c62bbf1, 0xbc7fbac9, 0x3c463c22, 0xbb95bc75, 0xbc75bb95, 0x3c223c46, 0xbac9bc7f, 0xbbf13c62,
    0xbbf1bc62, 0xbac93c7f, 0x3c22bc46, 0xbc753b95, 0xbb953c75, 0x3c46bc22, 0xbc7f3ac9, 0x3c623bf1, 0xbc623bf1, 0x3c7f3ac9,
    0xbc46bc22, 0x3b953c75, 0x3c753b95, 0xbc22bc46, 0x3ac93c7f, 0x3bf1bc62, 0x3bf13c62, 0x3ac9bc7f, 0xbc223c46, 0x3c75bb95,
    0x3b95bc75, 0xbc463c22, 0x3c7fbac9, 0xbc62bbf1, 0xbc7bbb48, 0x3c553c0e, 0xbc0ebc55, 0x3b483c7b, 0x3b48bc7b, 0xbc0e3c55,
    0x3c55bc0e, 0xbc7b3b48, 0x3c7b3b48, 0xbc55bc0e, 0x3c0e3c55, 0xbb48bc7b, 0xbb483c7b, 0x3c0ebc55, 0xbc553c0e, 0x3c7bbb48,
    0xbc7bbb48, 0x3c553c0e, 0xbc0ebc55, 0x3b483c7b, 0x3b48bc7b, 0xbc0e3c55, 0x3c55bc0e, 0xbc7b3b48, 0x3c7b3b48, 0xbc55bc0e,
    0x3c0e3c55, 0xbb48bc7b, 0xbb483c7b, 0x3c0ebc55, 0xbc553c0e, 0x3c7bbb48, 0x3c46bc22, 0xbc623bf1, 0x3c75bb95, 0xbc7f3ac9,
    0x3ac9bc7f, 0xbb953c75, 0x3bf1bc62, 0xbc223c46, 0xbc22bc46, 0x3bf13c62, 0xbb95bc75, 0x3ac93c7f, 0xbc7fbac9, 0x3c753b95,
    0xbc62bbf1, 0x3c463c22, 0xbc463c22, 0x3c62bbf1, 0xbc753b95, 0x3c7fbac9, 0xbac93c7f, 0x3b95bc75, 0xbbf13c62, 0x3c22bc46,
    0x3c223c46, 0xbbf1bc62, 0x3b953c75, 0xbac9bc7f, 0x3c7f3ac9, 0xbc75bb95, 0x3c623bf1, 0xbc46bc22, 0x3c3e3c2c, 0x3c18bc4e,
    0xbc5cbc04, 0xbbdb3c67, 0x3c713bac, 0x3b79bc78, 0xbc7dbb16, 0xba493c80, 0x3c80ba49, 0xbb16bc7d, 0xbc783b79, 0x3bac3c71,
    0x3c67bbdb, 0xbc04bc5c, 0xbc4e3c18, 0x3c2c3c3e, 0x3c2cbc3e, 0xbc4ebc18, 0xbc043c5c, 0x3c673bdb, 0x3bacbc71, 0xbc78bb79,
    0xbb163c7d, 0x3c803a49, 0xba49bc80, 0xbc7d3b16, 0x3b793c78, 0x3c71bbac, 0xbbdbbc67, 0xbc5c3c04, 0x3c183c4e, 0x3c3ebc2c,
    0x3c5cbc04, 0xbc3ebc2c, 0xbbdb3c67, 0x3c7d3b16, 0x3c4e3c18, 0x3bacbc71, 0xbc80ba49, 0x3b793c78, 0xbc78bb79, 0x3a493c80,
    0x3c71bbac, 0xbc18bc4e, 0xbb16bc7d, 0xbc673bdb, 0x3c2c3c3e, 0x3c04bc5c, 0x3c043c5c, 0x3c2cbc3e, 0xbc67bbdb, 0xbb163c7d,
    0xbc183c4e, 0x3c713bac, 0x3a49bc80, 0xbc783b79, 0x3b79bc78, 0xbc803a49, 0x3bac3c71, 0x3c4ebc18, 0x3c7dbb16, 0xbbdbbc67,
    0xbc3e3c2c, 0x3c5c3c04, 0xbc783b79, 0x3c2c3c3e, 0x3bacbc71, 0xbc7d3b16, 0x3c183c4e, 0x3bdbbc67, 0xbc803a49, 0x3c043c5c,
    0x3c5c3c04, 0x3a49bc80, 0xbc673bdb, 0x3c4e3c18, 0x3b16bc7d, 0xbc713bac, 0x3c3e3c2c, 0x3b79bc78, 0x3b793c78, 0x3c3ebc2c,
    0xbc71bbac, 0x3b163c7d, 0x3c4ebc18, 0xbc67bbdb, 0x3a493c80, 0x3c5cbc04, 0x3c04bc5c, 0xbc80ba49, 0x3bdb3c67, 0x3c18bc4e,
    0xbc7dbb16, 0x3bac3c71, 0x3c2cbc3e, 0xbc78bb79, 0x3a49bc80, 0xbc4e3c18, 0x3c783b79, 0xbbdbbc67, 0x3bac3c71, 0x3c04bc5c,
    0xbc7d3b16, 0x3c3e3c2c, 0xbc2cbc3e, 0xbb163c7d, 0x3c5cbc04, 0xbc71bbac, 0x3c673bdb, 0xbb79bc78, 0xbc183c4e, 0x3c80ba49,
    0x3c803a49, 0xbc18bc4e, 0xbb793c78, 0x3c67bbdb, 0xbc713bac, 0x3c5c3c04, 0xbb16bc7d, 0xbc2c3c3e, 0x3c3ebc2c, 0xbc7dbb16,
    0x3c043c5c, 0x3bacbc71, 0xbbdb3c67, 0x3c78bb79, 0xbc4ebc18, 0x3a493c80, 0x3bacbc71, 0xbc5c3c04, 0x3c7d3b16, 0xbc2cbc3e,
    0x3a493c80, 0x3c18bc4e, 0xbc783b79, 0x3c673bdb, 0xbbdbbc67, 0xbb793c78, 0x3c4ebc18, 0xbc80ba49, 0x3c3e3c2c, 0xbb16bc7d,
    0xbc043c5c, 0x3c71bbac, 0x3c713bac, 0xbc04bc5c, 0xbb163c7d, 0x3c3ebc2c, 0xbc803a49, 0x3c4e3c18, 0xbb79bc78, 0xbbdb3c67,
    0x3c67bbdb, 0xbc78bb79, 0x3c183c4e, 0x3a49bc80, 0xbc2c3c3e, 0x3c7dbb16, 0xbc5cbc04, 0x3bac3c71, 0xbc4ebc18, 0x3bdb3c67,
    0x3a49bc80, 0xbc043c5c, 0xbb793c78, 0x3c2cbc3e, 0xbc713bac, 0x3c7d3b16, 0x3b163c7d, 0x3bacbc71, 0xbc3e3c2c, 0x3c78bb79,
    0x3c5cbc04, 0xbc803a49, 0x3c673bdb, 0xbc18bc4e, 0xbc183c4e, 0x3c67bbdb, 0xbc80ba49, 0x3c5c3c04, 0x3c783b79, 0xbc3ebc2c,
    0x3bac3c71, 0x3b16bc7d, 0x3c7dbb16, 0xbc71bbac, 0x3c2c3c3e, 0xbb79bc78, 0xbc04bc5c, 0x3a493c80, 0x3bdbbc67, 0xbc4e3c18,
    0x3c183c4e, 0xbbacbc71, 0x3a493c80, 0x3b79bc78, 0xbc043c5c, 0x3c3ebc2c, 0xbc673bdb, 0x3c7dbb16, 0x3b16bc7d, 0xbbdb3c67,
    0x3c2cbc3e, 0xbc5c3c04, 0x3c78bb79, 0xbc80ba49, 0x3c713bac, 0xbc4ebc18, 0xbc4e3c18, 0x3c71bbac, 0xbc803a49, 0x3c783b79,
    0xbc5cbc04, 0x3c2c3c3e, 0xbbdbbc67, 0x3b163c7d, 0x3c7d3b16, 0xbc67bbdb, 0x3c3e3c2c, 0xbc04bc5c, 0x3b793c78, 0x3a49bc80,
    0xbbac3c71, 0x3c18bc4e, 0xbc713bac, 0x3c78bb79, 0xbc7d3b16, 0x3c80ba49, 0xbc3e3c2c, 0x3c4ebc18, 0xbc5c3c04, 0x3c67bbdb,
    0xbbdb3c67, 0x3c04bc5c, 0xbc183c4e, 0x3c2cbc3e, 0xba493c80, 0x3b16bc7d, 0xbb793c78, 0x3bacbc71, 0x3bac3c71, 0xbb79bc78,
    0x3b163c7d, 0xba49bc80, 0x3c2c3c3e, 0xbc18bc4e, 0x3c043c5c, 0xbbdbbc67, 0x3c673bdb, 0xbc5cbc04, 0x3c4e3c18, 0xbc3ebc2c,
    0x3c803a49, 0xbc7dbb16, 0x3c783b79, 0xbc71bbac, 0x3c800000, 0xbc800000, 0x3c800000, 0xbc800000, 0x3c800000, 0xbc800000,
    0x3c800000, 0xbc800000, 0x3c800000, 0xbc800000, 0x3c800000, 0xbc800000, 0x3c800000, 0xbc800000, 0x3c800000, 0xbc800000,
    0x3c800000, 0xbc800000, 0x3c800000, 0xbc800000, 0x3c800000, 0xbc800000, 0x3c800000, 0xbc800000, 0x3c800000, 0xbc800000,
    0x3c800000, 0xbc800000, 0x3c800000, 0xbc800000, 0x3c800000, 0xbc800000, 0x3c22bc46, 0xbbf13c62, 0x3b95bc75, 0xbac93c7f,
    0x3c7fbac9, 0xbc753b95, 0x3c62bbf1, 0xbc463c22, 0xbc46bc22, 0x3c623bf1, 0xbc75bb95, 0x3c7f3ac9, 0xbac9bc7f, 0x3b953c75,
    0xbbf1bc62, 0x3c223c46, 0xbc223c46, 0x3bf1bc62, 0xbb953c75, 0x3ac9bc7f, 0xbc7f3ac9, 0x3c75bb95, 0xbc623bf1, 0x3c46bc22,
    0x3c463c22, 0xbc62bbf1, 0x3c753b95, 0xbc7fbac9, 0x3ac93c7f, 0xbb95bc75, 0x3bf13c62, 0xbc22bc46, 0xbc7b3b48, 0x3c55bc0e,
    0xbc0e3c55, 0x3b48bc7b, 0x3b483c7b, 0xbc0ebc55, 0x3c553c0e, 0xbc7bbb48, 0x3c7bbb48, 0xbc553c0e, 0x3c0ebc55, 0xbb483c7b,
    0xbb48bc7b, 0x3c0e3c55, 0xbc55bc0e, 0x3c7b3b48, 0xbc7b3b48, 0x3c55bc0e, 0xbc0e3c55, 0x3b48bc7b, 0x3b483c7b, 0xbc0ebc55,
    0x3c553c0e, 0xbc7bbb48, 0x3c7bbb48, 0xbc553c0e, 0x3c0ebc55, 0xbb483c7b, 0xbb48bc7b, 0x3c0e3c55, 0xbc55bc0e, 0x3c7b3b48,
    0x3bf1bc62, 0x3ac93c7f, 0xbc22bc46, 0x3c753b95, 0x3b953c75, 0xbc46bc22, 0x3c7f3ac9, 0xbc623bf1, 0xbc62bbf1, 0x3c7fbac9,
    0xbc463c22, 0x3b95bc75, 0x3c75bb95, 0xbc223c46, 0x3ac9bc7f, 0x3bf13c62, 0xbbf13c62, 0xbac9bc7f, 0x3c223c46, 0xbc75bb95,
    0xbb95bc75, 0x3c463c22, 0xbc7fbac9, 0x3c62bbf1, 0x3c623bf1, 0xbc7f3ac9, 0x3c46bc22, 0xbb953c75, 0xbc753b95, 0x3c22bc46,
    0xbac93c7f, 0xbbf1bc62, 0x3c6dbbc4, 0xbbc43c6d, 0xbbc4bc6d, 0x3c6d3bc4, 0xbc6d3bc4, 0x3bc4bc6d, 0x3bc43c6d, 0xbc6dbbc4,
    0x3c6dbbc4, 0xbbc43c6d, 0xbbc4bc6d, 0x3c6d3bc4, 0xbc6d3bc4, 0x3bc4bc6d, 0x3bc43c6d, 0xbc6dbbc4, 0x3c6dbbc4, 0xbbc43c6d,
    0xbbc4bc6d, 0x3c6d3bc4, 0xbc6d3bc4, 0x3bc4bc6d, 0x3bc43c6d, 0xbc6dbbc4, 0x3c6dbbc4, 0xbbc43c6d, 0xbbc4bc6d, 0x3c6d3bc4,
    0xbc6d3bc4, 0x3bc4bc6d, 0x3bc43c6d, 0xbc6dbbc4, 0x3b95bc75, 0x3c223c46, 0xbc7f3ac9, 0x3bf1bc62, 0xbc623bf1, 0x3ac9bc7f,
    0x3c463c22, 0xbc753b95, 0xbc75bb95, 0x3c46bc22, 0x3ac93c7f, 0xbc62bbf1, 0x3bf13c62, 0xbc7fbac9, 0x3c22bc46, 0x3b953c75,
    0xbb953c75, 0xbc22bc46, 0x3c7fbac9, 0xbbf13c62, 0x3c62bbf1, 0xbac93c7f, 0xbc46bc22, 0x3c75bb95, 0x3c753b95, 0xbc463c22,
    0xbac9bc7f, 0x3c623bf1, 0xbbf1bc62, 0x3c7f3ac9, 0xbc223c46, 0xbb95bc75, 0xbc553c0e, 0xbb48bc7b, 0x3c7b3b48, 0xbc0e3c55,
    0xbc0ebc55, 0x3c7bbb48, 0xbb483c7b, 0xbc55bc0e, 0x3c55bc0e, 0x3b483c7b, 0xbc7bbb48, 0x3c0ebc55, 0x3c0e3c55, 0xbc7b3b48,
    0x3b48bc7b, 0x3c553c0e, 0xbc553c0e, 0xbb48bc7b, 0x3c7b3b48, 0xbc0e3c55, 0xbc0ebc55, 0x3c7bbb48, 0xbb483c7b, 0xbc55bc0e,
    0x3c55bc0e, 0x3b483c7b, 0xbc7bbb48, 0x3c0ebc55, 0x3c0e3c55, 0xbc7b3b48, 0x3b48bc7b, 0x3c553c0e, 0x3ac9bc7f, 0x3c753b95,
    0xbbf13c62, 0xbc46bc22, 0xbc22bc46, 0x3c62bbf1, 0x3b953c75, 0xbc7f3ac9, 0xbc7fbac9, 0x3b95bc75, 0x3c623bf1, 0xbc223c46,
    0xbc463c22, 0xbbf1bc62, 0x3c75bb95, 0x3ac93c7f, 0xbac93c7f, 0xbc75bb95, 0x3bf1bc62, 0x3c463c22, 0x3c223c46, 0xbc623bf1,
    0xbb95bc75, 0x3c7fbac9, 0x3c7f3ac9, 0xbb953c75, 0xbc62bbf1, 0x3c22bc46, 0x3c46bc22, 0x3bf13c62, 0xbc753b95, 0xbac9bc7f,
    0x3c80ba49, 0xbc7d3b16, 0x3c78bb79, 0xbc713bac, 0x3c67bbdb, 0xbc5c3c04, 0x3c4ebc18, 0xbc3e3c2c, 0x3c2cbc3e, 0xbc183c4e,
    0x3c04bc5c, 0xbbdb3c67, 0x3bacbc71, 0xbb793c78, 0x3b16bc7d, 0xba493c80, 0xba49bc80, 0x3b163c7d, 0xbb79bc78, 0x3bac3c71,
    0xbbdbbc67, 0x3c043c5c, 0xbc18bc4e, 0x3c2c3c3e, 0xbc3ebc2c, 0x3c4e3c18, 0xbc5cbc04, 0x3c673bdb, 0xbc71bbac, 0x3c783b79,
    0xbc7dbb16, 0x3c803a49, 0x3b79bc78, 0x3a493c80, 0xbbacbc71, 0x3c183c4e, 0x3c7dbb16, 0xbc673bdb, 0x3c3ebc2c, 0xbc043c5c,
    0xbc5c3c04, 0x3c2cbc3e, 0xbbdb3c67, 0x3b16bc7d, 0xbc4ebc18, 0x3c713bac, 0xbc80ba49, 0x3c78bb79, 0x3c783b79, 0xbc803a49,
    0x3c71bbac, 0xbc4e3c18, 0x3b163c7d, 0xbbdbbc67, 0x3c2c3c3e, 0xbc5cbc04, 0xbc04bc5c, 0x3c3e3c2c, 0xbc67bbdb, 0x3c7d3b16,
    0x3c18bc4e, 0xbbac3c71, 0x3a49bc80, 0x3b793c78, 0xbc043c5c, 0x3a49bc80, 0x3bdb3c67, 0xbc4ebc18, 0x3c7d3b16, 0xbc713bac,
    0x3c2cbc3e, 0xbb793c78, 0x3c78bb79, 0xbc3e3c2c, 0x3bacbc71, 0x3b163c7d, 0xbc18bc4e, 0x3c673bdb, 0xbc803a49, 0x3c5cbc04,
    0x3c5c3c04, 0xbc80ba49, 0x3c67bbdb, 0xbc183c4e, 0x3b16bc7d, 0x3bac3c71, 0xbc3ebc2c, 0x3c783b79, 0xbb79bc78, 0x3c2c3c3e,
    0xbc71bbac, 0x3c7dbb16, 0xbc4e3c18, 0x3bdbbc67, 0x3a493c80, 0xbc04bc5c, 0xbc2cbc3e, 0x3c7d3b16, 0xbc5c3c04, 0x3bacbc71,
    0x3c673bdb, 0xbc783b79, 0x3c18bc4e, 0x3a493c80, 0xbc80ba49, 0x3c4ebc18, 0xbb793c78, 0xbbdbbc67, 0x3c71bbac, 0xbc043c5c,
    0xbb16bc7d, 0x3c3e3c2c, 0x3c3ebc2c, 0xbb163c7d, 0xbc04bc5c, 0x3c713bac, 0xbbdb3c67, 0xbb79bc78, 0x3c4e3c18, 0xbc803a49,
    0x3a49bc80, 0x3c183c4e, 0xbc78bb79, 0x3c67bbdb, 0x3bac3c71, 0xbc5cbc04, 0x3c7dbb16, 0xbc2c3c3e, 0xbbdbbc67, 0x3c783b79,
    0xbc4e3c18, 0x3a49bc80, 0x3c3e3c2c, 0xbc7d3b16, 0x3c04bc5c, 0x3bac3c71, 0xbc71bbac, 0x3c5cbc04, 0xbb163c7d, 0xbc2cbc3e,
    0x3c80ba49, 0xbc183c4e, 0xbb79bc78, 0x3c673bdb, 0x3c67bbdb, 0xbb793c78, 0xbc18bc4e, 0x3c803a49, 0xbc2c3c3e, 0xbb16bc7d,
    0x3c5c3c04, 0xbc713bac, 0x3bacbc71, 0x3c043c5c, 0xbc7dbb16, 0x3c3ebc2c, 0x3a493c80, 0xbc4ebc18, 0x3c78bb79, 0xbbdb3c67,
    0xbc7d3b16, 0x3bacbc71, 0x3c2c3c3e, 0xbc783b79, 0x3c043c5c, 0xbc803a49, 0x3bdbbc67, 0x3c183c4e, 0x3c4e3c18, 0xbc673bdb,
    0x3a49bc80, 0x3c5c3c04, 0x3b79bc78, 0x3c3e3c2c, 0xbc713bac, 0x3b16bc7d, 0x3b163c7d, 0xbc71bbac, 0x3c3ebc2c, 0x3b793c78,
    0x3c5cbc04, 0x3a493c80, 0xbc67bbdb, 0x3c4ebc18, 0x3c18bc4e, 0x3bdb3c67, 0xbc80ba49, 0x3c04bc5c, 0xbc78bb79, 0x3c2cbc3e,
    0x3bac3c71, 0xbc7dbb16, 0x3c7d3b16, 0xbbdb3c67, 0xbc3ebc2c, 0x3c5cbc04, 0x3b793c78, 0xbc80ba49, 0x3bacbc71, 0x3c4e3c18,
    0xbc18bc4e, 0x3c71bbac, 0x3a493c80, 0xbc78bb79, 0x3c04bc5c, 0x3c2c3c3e, 0xbc673bdb, 0xbb16bc7d, 0xbb163c7d, 0xbc67bbdb,
    0x3c2cbc3e, 0x3c043c5c, 0xbc783b79, 0x3a49bc80, 0x3c713bac, 0xbc183c4e, 0x3c4ebc18, 0x3bac3c71, 0xbc803a49, 0x3b79bc78,
    0x3c5c3c04, 0xbc3e3c2c, 0xbbdbbc67, 0x3c7dbb16, 0xbbdb3c67, 0xbc5cbc04, 0x3c18bc4e, 0x3c3e3c2c, 0xba493c80, 0xbc7dbb16,
    0x3b79bc78, 0x3c713bac, 0x3bac3c71, 0xbc783b79, 0xbb16bc7d, 0x3c80ba49, 0x3c2c3c3e, 0xbc4e3c18, 0xbc04bc5c, 0x3c67bbdb,
    0x3c673bdb, 0xbc043c5c, 0xbc4ebc18, 0x3c2cbc3e, 0x3c803a49, 0xbb163c7d, 0xbc78bb79, 0x3bacbc71, 0x3c71bbac, 0x3b793c78,
    0xbc7d3b16, 0xba49bc80, 0x3c3ebc2c, 0x3c183c4e, 0xbc5c3c04, 0xbbdbbc67, 0x3f803f80, 0x3f7d3f7f, 0x3f783f7b, 0x3f713f75,
    0x3f673f6d, 0x3f5c3f62, 0x3f4e3f55, 0x3f3e3f46, 0x3f2c3f35, 0x3f183f22, 0x3f043f0e, 0x3edb3ef1, 0x3eac3ec4, 0x3e793e95,
    0x3e163e48, 0x3d493dc9, 0xbd490000, 0xbe16bdc9, 0xbe79be48, 0xbeacbe95, 0xbedbbec4, 0xbf04bef1, 0xbf18bf0e, 0xbf2cbf22,
    0xbf3ebf35, 0xbf4ebf46, 0xbf5cbf55, 0xbf67bf62, 0xbf71bf6d, 0xbf78bf75, 0xbf7dbf7b, 0xbf80bf7f, 0x3edb3ec4, 0x3f043ef1,
    0x3f183f0e, 0x3f2c3f22, 0x3d490000, 0x3e163dc9, 0x3e793e48, 0x3eac3e95, 0x3f713f6d, 0x3f783f75, 0x3f7d3f7b, 0x3f803f7f,
    0x3f3e3f35, 0x3f4e3f46, 0x3f5c3f55, 0x3f673f62, 0x3f673f6d, 0x3f5c3f62, 0x3f4e3f55, 0x3f3e3f46, 0x3f803f80, 0x3f7d3f7f,
    0x3f783f7b, 0x3f713f75, 0x3eac3ec4, 0x3e793e95, 0x3e163e48, 0x3d493dc9, 0x3f2c3f35, 0x3f183f22, 0x3f043f0e, 0x3edb3ef1,
    0xbf4ebf35, 0xbf71bf62, 0xbf80bf7b, 0xbf78bf7f, 0xbf5cbf6d, 0xbf2cbf46, 0xbedbbf0e, 0xbe16be95, 0x3f7d3f80, 0x3f673f75,
    0x3f3e3f55, 0x3f043f22, 0x3e793ec4, 0xbd493dc9, 0xbeacbe48, 0xbf18bef1, 0x3f183f35, 0x3eac3ef1, 0x3d493e48, 0xbe79bdc9,
    0xbf04bec4, 0xbf3ebf22, 0xbf67bf55, 0xbf7dbf75, 0x3e160000, 0x3edb3e95, 0x3f2c3f0e, 0x3f5c3f46, 0x3f783f6d, 0x3f803f7f,
    0x3f713f7b, 0x3f4e3f62, 0xbf04bec4, 0xbf3ebf22, 0xbf67bf55, 0xbf7dbf75, 0x3f183f35, 0x3eac3ef1, 0x3d493e48, 0xbe79bdc9,
    0x3f783f6d, 0x3f803f7f, 0x3f713f7b, 0x3f4e3f62, 0x3e160000, 0x3edb3e95, 0x3f2c3f0e, 0x3f5c3f46, 0x3f5c3f6d, 0x3f2c3f46,
    0x3edb3f0e, 0x3e163e95, 0x3f4e3f35, 0x3f713f62, 0x3f803f7b, 0x3f783f7f, 0xbe79bec4, 0x3d49bdc9, 0x3eac3e48, 0x3f183ef1,
    0xbf7dbf80, 0xbf67bf75, 0xbf3ebf55, 0xbf04bf22, 0xbe790000, 0xbf2cbef1, 0xbf71bf55, 0xbf7dbf7f, 0xbf4ebf6d, 0xbedbbf22,
    0x3d49be48, 0x3f043e95, 0x3f5c3f35, 0x3f803f75, 0x3f673f7b, 0x3f183f46, 0x3e163ec4, 0xbeacbdc9, 0xbf3ebf0e, 0xbf78bf62,
    0x3f783f80, 0x3f3e3f62, 0x3eac3f0e, 0xbe163dc9, 0xbf18bec4, 0xbf67bf46, 0xbf80bf7b, 0xbf5cbf75, 0xbf04bf35, 0xbd49be95,
    0x3edb3e48, 0x3f4e3f22, 0x3f7d3f6d, 0x3f713f7f, 0x3f2c3f55, 0x3e793ef1, 0xbf18bec4, 0xbf67bf46, 0xbf80bf7b, 0xbf5cbf75,
    0x3f783f80, 0x3f3e3f62, 0x3eac3f0e, 0xbe163dc9, 0x3f7d3f6d, 0x3f713f7f, 0x3f2c3f55, 0x3e793ef1, 0xbf04bf35, 0xbd49be95,
    0x3edb3e48, 0x3f4e3f22, 0x3f4e3f6d, 0x3edb3f22, 0xbd493e48, 0xbf04be95, 0x3e790000, 0x3f2c3ef1, 0x3f713f55, 0x3f7d3f7f,
    0xbe16bec4, 0x3eac3dc9, 0x3f3e3f0e, 0x3f783f62, 0xbf5cbf35, 0xbf80bf75, 0xbf67bf7b, 0xbf18bf46, 0xbedbbf35, 0x3e79bdc9,
    0x3f4e3f0e, 0x3f803f75, 0x3f3e3f6d, 0x3e163ef1, 0xbf04be48, 0xbf71bf46, 0x3eac0000, 0x3f5c3f22, 0x3f7d3f7b, 0x3f2c3f62,
    0x3d493ec4, 0xbf18be95, 0xbf78bf55, 0xbf67bf7f, 0x3f673f35, 0x3f783f7f, 0x3f183f55, 0xbd493e95, 0xbf2cbec4, 0xbf7dbf62,
    0xbf5cbf7b, 0xbeacbf22, 0x3f713f80, 0x3f043f46, 0xbe163e48, 0xbf3ebef1, 0xbf80bf6d, 0xbf4ebf75, 0xbe79bf0e, 0x3edb3dc9,
    0x3f2c3ec4, 0x3f7d3f62, 0x3f5c3f7b, 0x3eac3f22, 0xbf67bf35, 0xbf78bf7f, 0xbf18bf55, 0x3d49be95, 0x3f803f6d, 0x3f4e3f75,
    0x3e793f0e, 0xbedbbdc9, 0xbf71bf80, 0xbf04bf46, 0x3e16be48, 0x3f3e3ef1, 0x3f3e3f6d, 0x3e163ef1, 0xbf04be48, 0xbf71bf46,
    0xbedbbf35, 0x3e79bdc9, 0x3f4e3f0e, 0x3f803f75, 0x3d493ec4, 0xbf18be95, 0xbf78bf55, 0xbf67bf7f, 0x3eac0000, 0x3f5c3f22,
    0x3f7d3f7b, 0x3f2c3f62, 0x3f673f80, 0x3e793f22, 0xbf18be48, 0xbf80bf62, 0xbf2cbf6d, 0x3e16be95, 0x3f5c3f0e, 0x3f713f7f,
    0x3eac3f35, 0xbf04bdc9, 0xbf7dbf55, 0xbf3ebf75, 0x3d49bec4, 0x3f4e3ef1, 0x3f783f7b, 0x3edb3f46, 0xbedb0000, 0xbf78bf46,
    0xbf4ebf7b, 0xbd49bef1, 0x3f3e3ec4, 0x3f7d3f75, 0x3f043f55, 0xbeac3dc9, 0xbf71bf35, 0xbf5cbf7f, 0xbe16bf0e, 0x3f2c3e95,
    0x3f803f6d, 0x3f183f62, 0xbe793e48, 0xbf67bf22, 0xbf3ebec4, 0xbf7dbf75, 0xbf04bf55, 0x3eacbdc9, 0x3edb0000, 0x3f783f46,
    0x3f4e3f7b, 0x3d493ef1, 0xbf80bf6d, 0xbf18bf62, 0x3e79be48, 0x3f673f22, 0x3f713f35, 0x3f5c3f7f, 0x3e163f0e, 0xbf2cbe95,
    0xbf2cbf6d, 0x3e16be95, 0x3f5c3f0e, 0x3f713f7f, 0x3f673f80, 0x3e793f22, 0xbf18be48, 0xbf80bf62, 0x3d49bec4, 0x3f4e3ef1,
    0x3f783f7b, 0x3edb3f46, 0x3eac3f35, 0xbf04bdc9, 0xbf7dbf55, 0xbf3ebf75, 0xbf78bf35, 0xbf2cbf75, 0x3eacbe48, 0x3f7d3f46,
    0x3f183f6d, 0xbedb3dc9, 0xbf80bf55, 0xbf04bf62, 0x3f5c3f80, 0xbd493ef1, 0xbf67bf0e, 0xbf4ebf7f, 0x3e16bec4, 0x3f713f22,
    0x3f3e3f7b, 0xbe793e95, 0x3e793f35, 0xbf3ebe95, 0xbf71bf7b, 0xbe16bf22, 0x3f4e3ec4, 0x3f673f7f, 0x3d493f0e, 0xbf5cbef1,
    0x3f040000, 0x3f803f62, 0x3edb3f55, 0xbf18bdc9, 0xbf7dbf6d, 0xbeacbf46, 0x3f2c3e48, 0x3f783f75, 0x3f4e3ec4, 0x3f673f7f,
    0x3d493f0e, 0xbf5cbef1, 0x3e793f35, 0xbf3ebe95, 0xbf71bf7b, 0xbe16bf22, 0xbf7dbf6d, 0xbeacbf46, 0x3f2c3e48, 0x3f783f75,
    0x3f040000, 0x3f803f62, 0x3edb3f55, 0xbf18bdc9, 0xbf18bf6d, 0x3edbbdc9, 0x3f803f55, 0x3f043f62, 0x3f783f35, 0x3f2c3f75,
    0xbeac3e48, 0xbf7dbf46, 0xbe163ec4, 0xbf71bf22, 0xbf3ebf7b, 0x3e79be95, 0xbf5cbf80, 0x3d49bef1, 0x3f673f0e, 0x3f4e3f7f,
    0xbf180000, 0xbf71bf75, 0x3d49bf0e, 0x3f783f22, 0x3f043f6d, 0xbf2cbdc9, 0xbf67bf7b, 0x3e16bef1, 0x3f7d3f35, 0x3edb3f62,
    0xbf3ebe48, 0xbf5cbf7f, 0x3e79bec4, 0x3f803f46, 0x3eac3f55, 0xbf4ebe95, 0x3f4e3f80, 0xbeac3e95, 0xbf80bf55, 0xbe79bf46,
    0x3f5c3ec4, 0x3f3e3f7f, 0xbedb3e48, 0xbf7dbf62, 0xbe16bf35, 0x3f673ef1, 0x3f2c3f7b, 0xbf043dc9, 0xbf78bf6d, 0xbd49bf22,
    0x3f713f0e, 0x3f183f75, 0x3f5c3ec4, 0x3f3e3f7f, 0xbedb3e48, 0xbf7dbf62, 0x3f4e3f80, 0xbeac3e95, 0xbf80bf55, 0xbe79bf46,
    0xbf78bf6d, 0xbd49bf22, 0x3f713f0e, 0x3f183f75, 0xbe16bf35, 0x3f673ef1, 0x3f2c3f7b, 0xbf043dc9, 0xbf04bf6d, 0x3f2c3dc9,
    0x3f673f7b, 0xbe163ef1, 0x3f180000, 0x3f713f75, 0xbd493f0e, 0xbf78bf22, 0xbe793ec4, 0xbf80bf46, 0xbeacbf55, 0x3f4e3e95,
    0xbf7dbf35, 0xbedbbf62, 0x3f3e3e48, 0x3f5c3f7f, 0xbd49bf35, 0x3f7d3f22, 0x3e793f55, 0xbf71bef1, 0xbedbbf6d, 0x3f5c3e95,
    0x3f183f7b, 0xbf3ebdc9, 0x3f2c0000, 0x3f4e3f7f, 0xbf043e48, 0xbf67bf75, 0x3eacbec4, 0x3f783f62, 0xbe163f0e, 0xbf80bf46,
    0x3f803f35, 0x3e163f46, 0xbf78bf0e, 0xbeacbf62, 0x3f673ec4, 0x3f043f75, 0xbf4ebe48, 0xbf2cbf7f, 0x3f3e3f80, 0xbf183dc9,
    0xbf5cbf7b, 0x3edbbe95, 0x3f713f6d, 0xbe793ef1, 0xbf7dbf55, 0x3d49bf22, 0xbf67bec4, 0xbf04bf75, 0x3f4e3e48, 0x3f2c3f7f,
    0xbf80bf35, 0xbe16bf46, 0x3f783f0e, 0x3eac3f62, 0xbf71bf6d, 0x3e79bef1, 0x3f7d3f55, 0xbd493f22, 0xbf3ebf80, 0x3f18bdc9,
    0x3f5c3f7b, 0xbedb3e95, 0xbedbbf6d, 0x3f5c3e95, 0x3f183f7b, 0xbf3ebdc9, 0xbd49bf35, 0x3f7d3f22, 0x3e793f55, 0xbf71bef1,
    0x3eacbec4, 0x3f783f62, 0xbe163f0e, 0xbf80bf46, 0x3f2c0000, 0x3f4e3f7f, 0xbf043e48, 0xbf67bf75, 0x3f2c3f80, 0xbf4ebdc9,
    0xbf04bf7b, 0x3f673e95, 0x3eac3f6d, 0xbf78bef1, 0xbe16bf55, 0x3f803f22, 0xbd493f35, 0xbf7dbf46, 0x3e79bf0e, 0x3f713f62,
    0xbedb3ec4, 0xbf5cbf75, 0x3f18be48, 0x3f3e3f7f, 0xbf3e0000, 0xbf18bf7f, 0x3f5c3e48, 0x3edb3f75, 0xbf71bec4, 0xbe79bf62,
    0x3f7d3f0e, 0x3d493f46, 0xbf80bf35, 0x3e16bf22, 0x3f783f55, 0xbeac3ef1, 0xbf67bf6d, 0x3f04be95, 0x3f4e3f7b, 0xbf2c3dc9,
    0x3f713ec4, 0x3e793f62, 0xbf7dbf0e, 0xbd49bf46, 0x3f3e0000, 0x3f183f7f, 0xbf5cbe48, 0xbedbbf75, 0x3f673f6d, 0xbf043e95,
    0xbf4ebf7b, 0x3f2cbdc9, 0x3f803f35, 0xbe163f22, 0xbf78bf55, 0x3eacbef1, 0x3eac3f6d, 0xbf78bef1, 0xbe16bf55, 0x3f803f22,
    0x3f2c3f80, 0xbf4ebdc9, 0xbf04bf7b, 0x3f673e95, 0xbedb3ec4, 0xbf5cbf75, 0x3f18be48, 0x3f3e3f7f, 0xbd493f35, 0xbf7dbf46,
    0x3e79bf0e, 0x3f713f62, 0xbf7dbf35, 0x3edbbef1, 0x3f3e3f7b, 0xbf5cbdc9, 0xbe79bf6d, 0x3f803f22, 0xbeac3f0e, 0xbf4ebf75,
    0x3f183f80, 0xbf71be95, 0xbd49bf55, 0x3f783f46, 0xbf043ec4, 0xbf2cbf7f, 0x3f673e48, 0x3e163f62, 0xbe163f35, 0xbf67bf62,
    0x3f2cbe48, 0x3f043f7f, 0xbf78bec4, 0x3d49bf46, 0x3f713f55, 0xbf183e95, 0x3f4e0000, 0x3eac3f75, 0xbf80bf0e, 0x3e79bf22,
    0x3f5c3f6d, 0xbf3e3dc9, 0xbedbbf7b, 0x3f7d3ef1, 0xbf78bec4, 0x3d49bf46, 0x3f713f55, 0xbf183e95, 0xbe163f35, 0xbf67bf62,
    0x3f2cbe48, 0x3f043f7f, 0x3f5c3f6d, 0xbf3e3dc9, 0xbedbbf7b, 0x3f7d3ef1, 0x3f4e0000, 0x3eac3f75, 0xbf80bf0e, 0x3e79bf22,
    0x3e793f6d, 0xbf80bf22, 0x3eacbf0e, 0x3f4e3f75, 0x3f7d3f35, 0xbedb3ef1, 0xbf3ebf7b, 0x3f5c3dc9, 0x3f04bec4, 0x3f2c3f7f,
    0xbf67be48, 0xbe16bf62, 0xbf18bf80, 0x3f713e95, 0x3d493f55, 0xbf78bf46, 0xbf5c0000, 0xbd49bf62, 0x3f673f55, 0xbf4e3dc9,
    0xbe16bf6d, 0x3f713f46, 0xbf3e3e48, 0xbe79bf75, 0x3f783f35, 0xbf2c3e95, 0xbeacbf7b, 0x3f7d3f22, 0xbf183ec4, 0xbedbbf7f,
    0x3f803f0e, 0xbf043ef1, 0x3f043f80, 0xbf80bef1, 0x3edbbf0e, 0x3f183f7f, 0xbf7dbec4, 0x3eacbf22, 0x3f2c3f7b, 0xbf78be95,
    0x3e79bf35, 0x3f3e3f75, 0xbf71be48, 0x3e16bf46, 0x3f4e3f6d, 0xbf67bdc9, 0x3d49bf55, 0x3f5c3f62, 0xbf7dbec4, 0x3eacbf22,
    0x3f2c3f7b, 0xbf78be95, 0x3f043f80, 0xbf80bef1, 0x3edbbf0e, 0x3f183f7f, 0x3f4e3f6d, 0xbf67bdc9, 0x3d49bf55, 0x3f5c3f62,
    0x3e79bf35, 0x3f3e3f75, 0xbf71be48, 0x3e16bf46, 0x3e163f6d, 0xbf71bf46, 0x3f3ebe48, 0x3e793f75, 0x3f5c0000, 0x3d493f62,
    0xbf67bf55, 0x3f4ebdc9, 0x3f18bec4, 0x3edb3f7f, 0xbf80bf0e, 0x3f04bef1, 0xbf78bf35, 0x3f2cbe95, 0x3eac3f7b, 0xbf7dbf22,
    0x3eacbf35, 0x3f043f7f, 0xbf7dbf0e, 0x3f3ebe95, 0x3d493f6d, 0xbf4ebf62, 0x3f783e48, 0xbedb3f22, 0x3f670000, 0xbe793f46,
    0xbf18bf7b, 0x3f803ef1, 0xbf2c3ec4, 0xbe16bf75, 0x3f5c3f55, 0xbf71bdc9, 0x3f713f35, 0xbf5c3dc9, 0x3e16bf55, 0x3f2c3f75,
    0xbf80bec4, 0x3f18bef1, 0x3e793f7b, 0xbf67bf46, 0x3edb3f80, 0xbf78bf22, 0x3f4ebe48, 0xbd493f62, 0xbf3ebf6d, 0x3f7d3e95,
    0xbf043f0e, 0xbeacbf7f, 0x3f803ec4, 0xbf183ef1, 0xbe79bf7b, 0x3f673f46, 0xbf71bf35, 0x3f5cbdc9, 0xbe163f55, 0xbf2cbf75,
    0x3f3e3f6d, 0xbf7dbe95, 0x3f04bf0e, 0x3eac3f7f, 0xbedbbf80, 0x3f783f22, 0xbf4e3e48, 0x3d49bf62, 0x3d493f6d, 0xbf4ebf62,
    0x3f783e48, 0xbedb3f22, 0x3eacbf35, 0x3f043f7f, 0xbf7dbf0e, 0x3f3ebe95, 0xbf2c3ec4, 0xbe16bf75, 0x3f5c3f55, 0xbf71bdc9,
    0x3f670000, 0xbe793f46, 0xbf18bf7b, 0x3f803ef1, 0x3eac3f80, 0xbf5cbf46, 0x3f7d3e48, 0xbf2c3ef1, 0x3d49bf6d, 0x3f183f75,
    0xbf78bf0e, 0x3f67bdc9, 0xbedb3f35, 0xbe79bf7f, 0x3f4e3f55, 0xbf80be95, 0x3f3ebec4, 0xbe163f62, 0xbf04bf7b, 0x3f713f22,
    0xbf710000, 0x3f04bf22, 0x3e163f7b, 0xbf3ebf62, 0x3f803ec4, 0xbf4e3e95, 0x3e79bf55, 0x3edb3f7f, 0xbf67bf35, 0x3f783dc9,
    0xbf183f0e, 0xbd49bf75, 0x3f2c3f6d, 0xbf7dbef1, 0x3f5cbe48, 0xbeac3f46, 0xbf80bec4, 0x3f4ebe95, 0xbe793f55, 0xbedbbf7f,
    0x3f710000, 0xbf043f22, 0xbe16bf7b, 0x3f3e3f62, 0xbf2cbf6d, 0x3f7d3ef1, 0xbf5c3e48, 0x3eacbf46, 0x3f673f35, 0xbf78bdc9,
    0x3f18bf0e, 0x3d493f75, 0x3d49bf6d, 0x3f183f75, 0xbf78bf0e, 0x3f67bdc9, 0x3eac3f80, 0xbf5cbf46, 0x3f7d3e48, 0xbf2c3ef1,
    0x3f3ebec4, 0xbe163f62, 0xbf04bf7b, 0x3f713f22, 0xbedb3f35, 0xbe79bf7f, 0x3f4e3f55, 0xbf80be95, 0xbf5cbf35, 0x3f803e95,
    0xbf673e48, 0x3f18bf22, 0xbe163f6d, 0xbeacbf7f, 0x3f3e3f55, 0xbf78bef1, 0x3e793f80, 0xbf2cbf62, 0x3f713f0e, 0xbf7dbdc9,
    0x3f4ebec4, 0xbedb3f46, 0xbd49bf7b, 0x3f043f75, 0xbf043f35, 0x3d49bf75, 0x3edb3f7b, 0xbf4ebf46, 0x3f7d3ec4, 0xbf713dc9,
    0x3f2cbf0e, 0xbe793f62, 0x3f780000, 0xbf3e3ef1, 0x3eacbf55, 0x3e163f7f, 0xbf18bf6d, 0x3f673f22, 0xbf80be48, 0x3f5cbe95,
    0x3f7d3ec4, 0xbf713dc9, 0x3f2cbf0e, 0xbe793f62, 0xbf043f35, 0x3d49bf75, 0x3edb3f7b, 0xbf4ebf46, 0xbf18bf6d, 0x3f673f22,
    0xbf80be48, 0x3f5cbe95, 0x3f780000, 0xbf3e3ef1, 0x3eacbf55, 0x3e163f7f, 0x3e16bf6d, 0x3eac3f7f, 0xbf3ebf55, 0x3f783ef1,
    0x3f5c3f35, 0xbf80be95, 0x3f67be48, 0xbf183f22, 0xbf4e3ec4, 0x3edbbf46, 0x3d493f7b, 0xbf04bf75, 0xbe79bf80, 0x3f2c3f62,
    0xbf71bf0e, 0x3f7d3dc9, 0xbf7d0000, 0x3f67be95, 0xbf3e3f0e, 0x3f04bf46, 0xbe793f6d, 0xbd49bf7f, 0x3eac3f7b, 0xbf18bf62,
    0x3f4e3f35, 0xbf71bef1, 0x3f803e48, 0xbf783dc9, 0x3f5cbec4, 0xbf2c3f22, 0x3edbbf55, 0xbe163f75, 0x3e163f80, 0xbedbbf75,
    0x3f2c3f55, 0xbf5cbf22, 0x3f783ec4, 0xbf80bdc9, 0x3f71be48, 0xbf4e3ef1, 0x3f18bf35, 0xbeac3f62, 0x3d49bf7b, 0x3e793f7f,
    0xbf04bf6d, 0x3f3e3f46, 0xbf67bf0e, 0x3f7d3e95, 0x3f783ec4, 0xbf80bdc9, 0x3f71be48, 0xbf4e3ef1, 0x3e163f80, 0xbedbbf75,
    0x3f2c3f55, 0xbf5cbf22, 0xbf04bf6d, 0x3f3e3f46, 0xbf67bf0e, 0x3f7d3e95, 0x3f18bf35, 0xbeac3f62, 0x3d49bf7b, 0x3e793f7f,
    0x3e79bf6d, 0x3d493f7f, 0xbeacbf7b, 0x3f183f62, 0x3f7d0000, 0xbf673e95, 0x3f3ebf0e, 0xbf043f46, 0xbf5c3ec4, 0x3f2cbf22,
    0xbedb3f55, 0x3e16bf75, 0xbf4ebf35, 0x3f713ef1, 0xbf80be48, 0x3f78bdc9, 0x3f2cbf35, 0xbf183f46, 0x3f04bf55, 0xbedb3f62,
    0x3eacbf6d, 0xbe793f75, 0x3e16bf7b, 0xbd493f7f, 0x3f800000, 0xbf7d3dc9, 0x3f78be48, 0xbf713e95, 0x3f67bec4, 0xbf5c3ef1,
    0x3f4ebf0e, 0xbf3e3f22, 0x3f3e3f35, 0xbf4ebf22, 0x3f5c3f0e, 0xbf67bef1, 0x3f713ec4, 0xbf78be95, 0x3f7d3e48, 0xbf80bdc9,
    0x3d493f80, 0xbe16bf7f, 0x3e793f7b, 0xbeacbf75, 0x3edb3f6d, 0xbf04bf62, 0x3f183f55, 0xbf2cbf46, 0xbf71bec4, 0x3f783e95,
    0xbf7dbe48, 0x3f803dc9, 0xbf3ebf35, 0x3f4e3f22, 0xbf5cbf0e, 0x3f673ef1, 0xbedbbf6d, 0x3f043f62, 0xbf18bf55, 0x3f2c3f46,
    0xbd49bf80, 0x3e163f7f, 0xbe79bf7b, 0x3eac3f75, 0x3eacbf6d, 0xbe793f75, 0x3e16bf7b, 0xbd493f7f, 0x3f2cbf35, 0xbf183f46,
    0x3f04bf55, 0xbedb3f62, 0x3f67bec4, 0xbf5c3ef1, 0x3f4ebf0e, 0xbf3e3f22, 0x3f800000, 0xbf7d3dc9, 0x3f78be48, 0xbf713e95,
    0xbd493f80, 0x3e16bf7f, 0xbe793f7b, 0x3eacbf75, 0xbedb3f6d, 0x3f04bf62, 0xbf183f55, 0x3f2cbf46, 0xbf3e3f35, 0x3f4ebf22,
    0xbf5c3f0e, 0x3f67bef1, 0xbf713ec4, 0x3f78be95, 0xbf7d3e48, 0x3f80bdc9, 0xbf800000, 0x3f7d3dc9, 0xbf78be48, 0x3f713e95,
    0xbf67bec4, 0x3f5c3ef1, 0xbf4ebf0e, 0x3f3e3f22, 0xbf2cbf35, 0x3f183f46, 0xbf04bf55, 0x3edb3f62, 0xbeacbf6d, 0x3e793f75,
    0xbe16bf7b, 0x3d493f7f, 0x3f673ec4, 0xbf5cbef1, 0x3f4e3f0e, 0xbf3ebf22, 0x3f800000, 0xbf7dbdc9, 0x3f783e48, 0xbf71be95,
    0x3eac3f6d, 0xbe79bf75, 0x3e163f7b, 0xbd49bf7f, 0x3f2c3f35, 0xbf18bf46, 0x3f043f55, 0xbedbbf62, 0xbedb3f6d, 0x3f04bf62,
    0xbf183f55, 0x3f2cbf46, 0xbd493f80, 0x3e16bf7f, 0xbe793f7b, 0x3eacbf75, 0xbf713ec4, 0x3f78be95, 0xbf7d3e48, 0x3f80bdc9,
    0xbf3e3f35, 0x3f4ebf22, 0xbf5c3f0e, 0x3f67bef1, 0xbf18bf35, 0x3eac3f62, 0xbd49bf7b, 0xbe793f7f, 0x3f04bf6d, 0xbf3e3f46,
    0x3f67bf0e, 0xbf7d3e95, 0xbe163f80, 0x3edbbf75, 0xbf2c3f55, 0x3f5cbf22, 0xbf783ec4, 0x3f80bdc9, 0xbf71be48, 0x3f4e3ef1,
    0xbf4e3f35, 0x3f71bef1, 0xbf803e48, 0x3f783dc9, 0xbf5cbec4, 0x3f2c3f22, 0xbedbbf55, 0x3e163f75, 0x3f7d0000, 0xbf67be95,
    0x3f3e3f0e, 0xbf04bf46, 0x3e793f6d, 0x3d49bf7f, 0xbeac3f7b, 0x3f18bf62, 0xbf5cbec4, 0x3f2c3f22, 0xbedbbf55, 0x3e163f75,
    0xbf4e3f35, 0x3f71bef1, 0xbf803e48, 0x3f783dc9, 0x3e793f6d, 0x3d49bf7f, 0xbeac3f7b, 0x3f18bf62, 0x3f7d0000, 0xbf67be95,
    0x3f3e3f0e, 0xbf04bf46, 0xbf043f6d, 0x3f3ebf46, 0xbf673f0e, 0x3f7dbe95, 0x3f183f35, 0xbeacbf62, 0x3d493f7b, 0x3e79bf7f,
    0x3f78bec4, 0xbf803dc9, 0x3f713e48, 0xbf4ebef1, 0x3e16bf80, 0xbedb3f75, 0x3f2cbf55, 0xbf5c3f22, 0xbf780000, 0x3f3e3ef1,
    0xbeacbf55, 0xbe163f7f, 0x3f18bf6d, 0xbf673f22, 0x3f80be48, 0xbf5cbe95, 0x3f043f35, 0xbd49bf75, 0xbedb3f7b, 0x3f4ebf46,
    0xbf7d3ec4, 0x3f713dc9, 0xbf2cbf0e, 0x3e793f62, 0xbe793f80, 0x3f2cbf62, 0xbf713f0e, 0x3f7dbdc9, 0xbf4ebec4, 0x3edb3f46,
    0x3d49bf7b, 0xbf043f75, 0x3f5cbf35, 0xbf803e95, 0x3f673e48, 0xbf18bf22, 0x3e163f6d, 0x3eacbf7f, 0xbf3e3f55, 0x3f78bef1,
    0xbf4ebec4, 0x3edb3f46, 0x3d49bf7b, 0xbf043f75, 0xbe793f80, 0x3f2cbf62, 0xbf713f0e, 0x3f7dbdc9, 0x3e163f6d, 0x3eacbf7f,
    0xbf3e3f55, 0x3f78bef1, 0x3f5cbf35, 0xbf803e95, 0x3f673e48, 0xbf18bf22, 0xbf183f6d, 0x3f67bf22, 0xbf803e48, 0x3f5c3e95,
    0x3f780000, 0xbf3ebef1, 0x3eac3f55, 0x3e16bf7f, 0x3f7dbec4, 0xbf71bdc9, 0x3f2c3f0e, 0xbe79bf62, 0xbf04bf35, 0x3d493f75,
    0x3edbbf7b, 0xbf4e3f46, 0x3f67bf35, 0xbf783dc9, 0x3f183f0e, 0x3d49bf75, 0xbf2c3f6d, 0x3f7dbef1, 0xbf5cbe48, 0x3eac3f46,
    0x3f710000, 0xbf04bf22, 0xbe163f7b, 0x3f3ebf62, 0xbf803ec4, 0x3f4e3e95, 0xbe79bf55, 0xbedb3f7f, 0x3edb3f35, 0x3e79bf7f,
    0xbf4e3f55, 0x3f80be95, 0xbf3ebec4, 0x3e163f62, 0x3f04bf7b, 0xbf713f22, 0xbeac3f80, 0x3f5cbf46, 0xbf7d3e48, 0x3f2c3ef1,
    0xbd49bf6d, 0xbf183f75, 0x3f78bf0e, 0xbf67bdc9, 0x3f3e3ec4, 0xbe16bf62, 0xbf043f7b, 0x3f71bf22, 0xbedbbf35, 0xbe793f7f,
    0x3f4ebf55, 0xbf803e95, 0x3d493f6d, 0x3f18bf75, 0xbf783f0e, 0x3f673dc9, 0x3eacbf80, 0xbf5c3f46, 0x3f7dbe48, 0xbf2cbef1,
    0xbf2c3f6d, 0x3f7dbef1, 0xbf5cbe48, 0x3eac3f46, 0x3f67bf35, 0xbf783dc9, 0x3f183f0e, 0x3d49bf75, 0xbf803ec4, 0x3f4e3e95,
    0xbe79bf55, 0xbedb3f7f, 0x3f710000, 0xbf04bf22, 0xbe163f7b, 0x3f3ebf62, 0xbedb3f80, 0x3f78bf22, 0xbf4ebe48, 0x3d493f62,
    0x3f3ebf6d, 0xbf7d3e95, 0x3f043f0e, 0x3eacbf7f, 0xbf713f35, 0x3f5c3dc9, 0xbe16bf55, 0xbf2c3f75, 0x3f80bec4, 0xbf18bef1,
    0xbe793f7b, 0x3f67bf46, 0xbf670000, 0x3e793f46, 0x3f18bf7b, 0xbf803ef1, 0x3f2c3ec4, 0x3e16bf75, 0xbf5c3f55, 0x3f71bdc9,
    0xbeacbf35, 0xbf043f7f, 0x3f7dbf0e, 0xbf3ebe95, 0xbd493f6d, 0x3f4ebf62, 0xbf783e48, 0x3edb3f22, 0xbf2cbec4, 0xbe163f75,
    0x3f5cbf55, 0xbf713dc9, 0x3f670000, 0xbe79bf46, 0xbf183f7b, 0x3f80bef1, 0x3d49bf6d, 0xbf4e3f62, 0x3f78be48, 0xbedbbf22,
    0x3eac3f35, 0x3f04bf7f, 0xbf7d3f0e, 0x3f3e3e95, 0x3f3ebf6d, 0xbf7d3e95, 0x3f043f0e, 0x3eacbf7f, 0xbedb3f80, 0x3f78bf22,
    0xbf4ebe48, 0x3d493f62, 0x3f80bec4, 0xbf18bef1, 0xbe793f7b, 0x3f67bf46, 0xbf713f35, 0x3f5c3dc9, 0xbe16bf55, 0xbf2c3f75,
    0xbe79bf35, 0xbf3e3f75, 0x3f71be48, 0xbe16bf46, 0xbf4e3f6d, 0x3f67bdc9, 0xbd49bf55, 0xbf5c3f62, 0xbf043f80, 0x3f80bef1,
    0xbedbbf0e, 0xbf183f7f, 0x3f7dbec4, 0xbeacbf22, 0xbf2c3f7b, 0x3f78be95, 0xbf783f35, 0x3f2c3e95, 0x3eacbf7b, 0xbf7d3f22,
    0x3f183ec4, 0x3edbbf7f, 0xbf803f0e, 0x3f043ef1, 0x3f5c0000, 0x3d49bf62, 0xbf673f55, 0x3f4e3dc9, 0x3e16bf6d, 0xbf713f46,
    0x3f3e3e48, 0x3e79bf75, 0x3f183ec4, 0x3edbbf7f, 0xbf803f0e, 0x3f043ef1, 0xbf783f35, 0x3f2c3e95, 0x3eacbf7b, 0xbf7d3f22,
    0x3e16bf6d, 0xbf713f46, 0x3f3e3e48, 0x3e79bf75, 0x3f5c0000, 0x3d49bf62, 0xbf673f55, 0x3f4e3dc9, 0x3f4ebf6d, 0xbf673dc9,
    0x3d493f55, 0x3f5cbf62, 0x3e793f35, 0x3f3ebf75, 0xbf713e48, 0x3e163f46, 0xbf7d3ec4, 0x3eac3f22, 0x3f2cbf7b, 0xbf783e95,
    0x3f04bf80, 0xbf803ef1, 0x3edb3f0e, 0x3f18bf7f, 0xbf4e0000, 0xbeac3f75, 0x3f80bf0e, 0xbe79bf22, 0xbf5c3f6d, 0x3f3e3dc9,
    0x3edbbf7b, 0xbf7d3ef1, 0x3e163f35, 0x3f67bf62, 0xbf2cbe48, 0xbf043f7f, 0x3f78bec4, 0xbd49bf46, 0xbf713f55, 0x3f183e95,
    0xbf183f80, 0x3f71be95, 0x3d49bf55, 0xbf783f46, 0x3f043ec4, 0x3f2cbf7f, 0xbf673e48, 0xbe163f62, 0x3f7dbf35, 0xbedbbef1,
    0xbf3e3f7b, 0x3f5cbdc9, 0x3e79bf6d, 0xbf803f22, 0x3eac3f0e, 0x3f4ebf75, 0x3f043ec4, 0x3f2cbf7f, 0xbf673e48, 0xbe163f62,
    0xbf183f80, 0x3f71be95, 0x3d49bf55, 0xbf783f46, 0x3e79bf6d, 0xbf803f22, 0x3eac3f0e, 0x3f4ebf75, 0x3f7dbf35, 0xbedbbef1,
    0xbf3e3f7b, 0x3f5cbdc9, 0x3f5cbf6d, 0xbf3ebdc9, 0xbedb3f7b, 0x3f7dbef1, 0x3f4e0000, 0x3eacbf75, 0xbf803f0e, 0x3e793f22,
    0xbf783ec4, 0x3d493f46, 0x3f71bf55, 0xbf18be95, 0xbe16bf35, 0xbf673f62, 0x3f2c3e48, 0x3f04bf7f, 0x3f80bf35, 0xbe16bf22,
    0xbf783f55, 0x3eac3ef1, 0x3f67bf6d, 0xbf04be95, 0xbf4e3f7b, 0x3f2c3dc9, 0x3f3e0000, 0x3f18bf7f, 0xbf5c3e48, 0xbedb3f75,
    0x3f71bec4, 0x3e79bf62, 0xbf7d3f0e, 0xbd493f46, 0x3d493f35, 0x3f7dbf46, 0xbe79bf0e, 0xbf713f62, 0x3edb3ec4, 0x3f5cbf75,
    0xbf18be48, 0xbf3e3f7f, 0xbf2c3f80, 0x3f4ebdc9, 0x3f04bf7b, 0xbf673e95, 0xbeac3f6d, 0x3f78bef1, 0x3e16bf55, 0xbf803f22,
    0xbedbbec4, 0xbf5c3f75, 0x3f183e48, 0x3f3ebf7f, 0xbd49bf35, 0xbf7d3f46, 0x3e793f0e, 0x3f71bf62, 0x3eacbf6d, 0xbf783ef1,
    0xbe163f55, 0x3f80bf22, 0x3f2cbf80, 0xbf4e3dc9, 0xbf043f7b, 0x3f67be95, 0x3f67bf6d, 0xbf04be95, 0xbf4e3f7b, 0x3f2c3dc9,
    0x3f80bf35, 0xbe16bf22, 0xbf783f55, 0x3eac3ef1, 0x3f71bec4, 0x3e79bf62, 0xbf7d3f0e, 0xbd493f46, 0x3f3e0000, 0x3f18bf7f,
    0xbf5c3e48, 0xbedb3f75, 0xbf3e3f80, 0x3f183dc9, 0x3f5cbf7b, 0xbedbbe95, 0xbf713f6d, 0x3e793ef1, 0x3f7dbf55, 0xbd49bf22,
    0xbf803f35, 0xbe163f46, 0x3f78bf0e, 0x3eacbf62, 0xbf673ec4, 0xbf043f75, 0x3f4ebe48, 0x3f2cbf7f, 0xbf2c0000, 0xbf4e3f7f,
    0x3f043e48, 0x3f67bf75, 0xbeacbec4, 0xbf783f62, 0x3e163f0e, 0x3f80bf46, 0x3d49bf35, 0xbf7d3f22, 0xbe793f55, 0x3f71bef1,
    0x3edbbf6d, 0xbf5c3e95, 0xbf183f7b, 0x3f3ebdc9, 0x3eac3ec4, 0x3f78bf62, 0xbe16bf0e, 0xbf803f46, 0x3f2c0000, 0x3f4ebf7f,
    0xbf04be48, 0xbf673f75, 0xbedb3f6d, 0x3f5cbe95, 0x3f18bf7b, 0xbf3e3dc9, 0xbd493f35, 0x3f7dbf22, 0x3e79bf55, 0xbf713ef1,
    0xbf713f6d, 0x3e793ef1, 0x3f7dbf55, 0xbd49bf22, 0xbf3e3f80, 0x3f183dc9, 0x3f5cbf7b, 0xbedbbe95, 0xbf673ec4, 0xbf043f75,
    0x3f4ebe48, 0x3f2cbf7f, 0xbf803f35, 0xbe163f46, 0x3f78bf0e, 0x3eacbf62, 0x3e16bf35, 0xbf673ef1, 0xbf2c3f7b, 0x3f043dc9,
    0x3f78bf6d, 0x3d49bf22, 0xbf713f0e, 0xbf183f75, 0xbf4e3f80, 0x3eac3e95, 0x3f80bf55, 0x3e79bf46, 0xbf5c3ec4, 0xbf3e3f7f,
    0x3edb3e48, 0x3f7dbf62, 0xbf7d3f35, 0xbedb3f62, 0x3f3ebe48, 0x3f5cbf7f, 0xbe79bec4, 0xbf803f46, 0xbeac3f55, 0x3f4ebe95,
    0x3f180000, 0x3f71bf75, 0xbd49bf0e, 0xbf783f22, 0xbf043f6d, 0x3f2cbdc9, 0x3f67bf7b, 0xbe16bef1, 0xbe79bec4, 0xbf803f46,
    0xbeac3f55, 0x3f4ebe95, 0xbf7d3f35, 0xbedb3f62, 0x3f3ebe48, 0x3f5cbf7f, 0xbf043f6d, 0x3f2cbdc9, 0x3f67bf7b, 0xbe16bef1,
    0x3f180000, 0x3f71bf75, 0xbd49bf0e, 0xbf783f22, 0xbf783f6d, 0xbd493f22, 0x3f71bf0e, 0x3f18bf75, 0xbe163f35, 0x3f67bef1,
    0x3f2cbf7b, 0xbf04bdc9, 0x3f5cbec4, 0x3f3ebf7f, 0xbedbbe48, 0xbf7d3f62, 0x3f4ebf80, 0xbeacbe95, 0xbf803f55, 0xbe793f46,
    0xbf040000, 0xbf803f62, 0xbedb3f55, 0x3f18bdc9, 0x3f7dbf6d, 0x3eacbf46, 0xbf2c3e48, 0xbf783f75, 0xbe793f35, 0x3f3ebe95,
    0x3f71bf7b, 0x3e16bf22, 0xbf4e3ec4, 0xbf673f7f, 0xbd493f0e, 0x3f5cbef1, 0xbf5c3f80, 0x3d493ef1, 0x3f67bf0e, 0x3f4ebf7f,
    0xbe16bec4, 0xbf713f22, 0xbf3e3f7b, 0x3e793e95, 0x3f78bf35, 0x3f2cbf75, 0xbeacbe48, 0xbf7d3f46, 0xbf183f6d, 0x3edb3dc9,
    0x3f80bf55, 0x3f04bf62, 0xbe16bec4, 0xbf713f22, 0xbf3e3f7b, 0x3e793e95, 0xbf5c3f80, 0x3d493ef1, 0x3f67bf0e, 0x3f4ebf7f,
    0xbf183f6d, 0x3edb3dc9, 0x3f80bf55, 0x3f04bf62, 0x3f78bf35, 0x3f2cbf75, 0xbeacbe48, 0xbf7d3f46, 0xbf7d3f6d, 0xbeac3f46,
    0x3f2cbe48, 0x3f78bf75, 0x3f040000, 0x3f80bf62, 0x3edbbf55, 0xbf183dc9, 0x3f4ebec4, 0x3f67bf7f, 0x3d49bf0e, 0xbf5c3ef1,
    0x3e79bf35, 0xbf3e3e95, 0xbf713f7b, 0xbe163f22, 0x3f71bf35, 0x3f5cbf7f, 0x3e16bf0e, 0xbf2c3e95, 0xbf803f6d, 0xbf183f62,
    0x3e793e48, 0x3f67bf22, 0x3edb0000, 0x3f78bf46, 0x3f4ebf7b, 0x3d49bef1, 0xbf3e3ec4, 0xbf7d3f75, 0xbf043f55, 0x3eac3dc9,
    0xbeac3f35, 0x3f04bdc9, 0x3f7dbf55, 0x3f3ebf75, 0xbd49bec4, 0xbf4e3ef1, 0xbf783f7b, 0xbedb3f46, 0xbf673f80, 0xbe793f22,
    0x3f18be48, 0x3f80bf62, 0x3f2cbf6d, 0xbe16be95, 0xbf5c3f0e, 0xbf713f7f, 0x3d493ec4, 0x3f4ebef1, 0x3f78bf7b, 0x3edbbf46,
    0x3eacbf35, 0xbf043dc9, 0xbf7d3f55, 0xbf3e3f75, 0xbf2c3f6d, 0x3e163e95, 0x3f5cbf0e, 0x3f71bf7f, 0x3f67bf80, 0x3e79bf22,
    0xbf183e48, 0xbf803f62, 0xbf803f6d, 0xbf183f62, 0x3e793e48, 0x3f67bf22, 0x3f71bf35, 0x3f5cbf7f, 0x3e16bf0e, 0xbf2c3e95,
    0xbf3e3ec4, 0xbf7d3f75, 0xbf043f55, 0x3eac3dc9, 0x3edb0000, 0x3f78bf46, 0x3f4ebf7b, 0x3d49bef1, 0xbf713f80, 0xbf043f46,
    0x3e163e48, 0x3f3ebef1, 0x3f80bf6d, 0x3f4ebf75, 0x3e79bf0e, 0xbedb3dc9, 0xbf673f35, 0xbf783f7f, 0xbf183f55, 0x3d493e95,
    0x3f2cbec4, 0x3f7dbf62, 0x3f5cbf7b, 0x3eacbf22, 0xbeac0000, 0xbf5c3f22, 0xbf7d3f7b, 0xbf2c3f62, 0xbd493ec4, 0x3f18be95,
    0x3f78bf55, 0x3f67bf7f, 0x3edbbf35, 0xbe79bdc9, 0xbf4e3f0e, 0xbf803f75, 0xbf3e3f6d, 0xbe163ef1, 0x3f04be48, 0x3f71bf46,
    0x3d49bec4, 0xbf183e95, 0xbf783f55, 0xbf673f7f, 0x3eac0000, 0x3f5cbf22, 0x3f7dbf7b, 0x3f2cbf62, 0x3f3ebf6d, 0x3e16bef1,
    0xbf043e48, 0xbf713f46, 0xbedb3f35, 0x3e793dc9, 0x3f4ebf0e, 0x3f80bf75, 0x3f80bf6d, 0x3f4ebf75, 0x3e79bf0e, 0xbedb3dc9,
    0xbf713f80, 0xbf043f46, 0x3e163e48, 0x3f3ebef1, 0x3f2cbec4, 0x3f7dbf62, 0x3f5cbf7b, 0x3eacbf22, 0xbf673f35, 0xbf783f7f,
    0xbf183f55, 0x3d493e95, 0x3f04bf35, 0x3d49be95, 0xbedb3e48, 0xbf4e3f22, 0xbf7d3f6d, 0xbf713f7f, 0xbf2c3f55, 0xbe793ef1,
    0xbf783f80, 0xbf3e3f62, 0xbeac3f0e, 0x3e163dc9, 0x3f18bec4, 0x3f67bf46, 0x3f80bf7b, 0x3f5cbf75, 0xbf5c3f35, 0xbf803f75,
    0xbf673f7b, 0xbf183f46, 0xbe163ec4, 0x3eacbdc9, 0x3f3ebf0e, 0x3f78bf62, 0x3e790000, 0x3f2cbef1, 0x3f71bf55, 0x3f7dbf7f,
    0x3f4ebf6d, 0x3edbbf22, 0xbd49be48, 0xbf043e95, 0xbe163ec4, 0x3eacbdc9, 0x3f3ebf0e, 0x3f78bf62, 0xbf5c3f35, 0xbf803f75,
    0xbf673f7b, 0xbf183f46, 0x3f4ebf6d, 0x3edbbf22, 0xbd49be48, 0xbf043e95, 0x3e790000, 0x3f2cbef1, 0x3f71bf55, 0x3f7dbf7f,
    0x3f7dbf6d, 0x3f71bf7f, 0x3f2cbf55, 0x3e79bef1, 0xbf043f35, 0xbd493e95, 0x3edbbe48, 0x3f4ebf22, 0xbf183ec4, 0xbf673f46,
    0xbf803f7b, 0xbf5c3f75, 0x3f78bf80, 0x3f3ebf62, 0x3eacbf0e, 0xbe16bdc9, 0xbe160000, 0xbedb3e95, 0xbf2c3f0e, 0xbf5c3f46,
    0xbf783f6d, 0xbf803f7f, 0xbf713f7b, 0xbf4e3f62, 0xbf183f35, 0xbeac3ef1, 0xbd493e48, 0x3e79bdc9, 0x3f04bec4, 0x3f3ebf22,
    0x3f67bf55, 0x3f7dbf75, 0xbf7d3f80, 0xbf673f75, 0xbf3e3f55, 0xbf043f22, 0xbe793ec4, 0x3d493dc9, 0x3eacbe48, 0x3f18bef1,
    0x3f4ebf35, 0x3f71bf62, 0x3f80bf7b, 0x3f78bf7f, 0x3f5cbf6d, 0x3f2cbf46, 0x3edbbf0e, 0x3e16be95, 0xbe793ec4, 0x3d493dc9,
    0x3eacbe48, 0x3f18bef1, 0xbf7d3f80, 0xbf673f75, 0xbf3e3f55, 0xbf043f22, 0x3f5cbf6d, 0x3f2cbf46, 0x3edbbf0e, 0x3e16be95,
    0x3f4ebf35, 0x3f71bf62, 0x3f80bf7b, 0x3f78bf7f, 0x3f78bf6d, 0x3f80bf7f, 0x3f71bf7b, 0x3f4ebf62, 0x3e160000, 0x3edbbe95,
    0x3f2cbf0e, 0x3f5cbf46, 0xbf043ec4, 0xbf3e3f22, 0xbf673f55, 0xbf7d3f75, 0x3f18bf35, 0x3eacbef1, 0x3d49be48, 0xbe793dc9,
    0x3f3ebf35, 0x3f4ebf46, 0x3f5cbf55, 0x3f67bf62, 0x3f71bf6d, 0x3f78bf75, 0x3f7dbf7b, 0x3f80bf7f, 0x3d490000, 0x3e16bdc9,
    0x3e79be48, 0x3eacbe95, 0x3edbbec4, 0x3f04bef1, 0x3f18bf0e, 0x3f2cbf22, 0xbf2c3f35, 0xbf183f22, 0xbf043f0e, 0xbedb3ef1,
    0xbeac3ec4, 0xbe793e95, 0xbe163e48, 0xbd493dc9, 0xbf803f80, 0xbf7d3f7f, 0xbf783f7b, 0xbf713f75, 0xbf673f6d, 0xbf5c3f62,
    0xbf4e3f55, 0xbf3e3f46, 0x3eacbec4, 0x3e79be95, 0x3e16be48, 0x3d49bdc9, 0x3f2cbf35, 0x3f18bf22, 0x3f04bf0e, 0x3edbbef1,
    0x3f67bf6d, 0x3f5cbf62, 0x3f4ebf55, 0x3f3ebf46, 0x3f80bf80, 0x3f7dbf7f, 0x3f78bf7b, 0x3f71bf75, 0x3f71bf6d, 0x3f78bf75,
    0x3f7dbf7b, 0x3f80bf7f, 0x3f3ebf35, 0x3f4ebf46, 0x3f5cbf55, 0x3f67bf62, 0x3edbbec4, 0x3f04bef1, 0x3f18bf0e, 0x3f2cbf22,
    0x3d490000, 0x3e16bdc9, 0x3e79be48, 0x3eacbe95,
};
__device__ const __align__(128) uint32_t c_ga[1536] = {
    0x00003c80, 0x3bc43c6d, 0x00003c80, 0xbbc4bc6d, 0x00003c80, 0x3c6d3bc4, 0x00003c80, 0xbc6dbbc4, 0x00003c80, 0x3c6dbbc4,
    0x00003c80, 0xbc6d3bc4, 0x00003c80, 0x3bc4bc6d, 0x00003c80, 0xbbc43c6d, 0x3a493c80, 0x3bdb3c67, 0x3bdb3c67, 0xbc3ebc2c,
    0x3b163c7d, 0x3c783b79, 0x3c043c5c, 0xbc7d3b16, 0x3b793c78, 0x3c4ebc18, 0x3c183c4e, 0xbc043c5c, 0x3bac3c71, 0x3a49bc80,
    0x3c2c3c3e, 0x3bac3c71, 0x3ac93c7f, 0x3bf13c62, 0x3c463c22, 0xbc75bb95, 0x3b953c75, 0x3c7f3ac9, 0x3c623bf1, 0xbc463c22,
    0x3bf13c62, 0x3c22bc46, 0x3c753b95, 0x3ac93c7f, 0x3c223c46, 0xbb95bc75, 0x3c7f3ac9, 0x3c623bf1, 0x3b163c7d, 0x3c043c5c,
    0x3c783b79, 0xbc7d3b16, 0x3bdb3c67, 0x3c80ba49, 0x3c80ba49, 0xbbac3c71, 0x3c2c3c3e, 0x3bdbbc67, 0x3c71bbac, 0x3c2c3c3e,
    0x3c5c3c04, 0xbc18bc4e, 0x3c4ebc18, 0x3c78bb79, 0x3b483c7b, 0x3c0e3c55, 0x3c7bbb48, 0xbc553c0e, 0x3c0e3c55, 0x3c7bbb48,
    0x3c55bc0e, 0x3b483c7b, 0x3c553c0e, 0x3b48bc7b, 0x3c0ebc55, 0x3c7b3b48, 0x3c7b3b48, 0xbc55bc0e, 0x3b48bc7b, 0x3c0ebc55,
    0x3b793c78, 0x3c183c4e, 0x3c4ebc18, 0xbc043c5c, 0x3c2c3c3e, 0x3c71bbac, 0x3bdbbc67, 0x3c2c3c3e, 0x3c713bac, 0xba49bc80,
    0xba49bc80, 0x3c67bbdb, 0x3c7dbb16, 0xbc78bb79, 0xbc04bc5c, 0xbb16bc7d, 0x3b953c75, 0x3c223c46, 0x3bf1bc62, 0xbac93c7f,
    0x3c463c22, 0x3c62bbf1, 0xbac9bc7f, 0x3c753b95, 0x3c7f3ac9, 0xbb95bc75, 0xbc22bc46, 0x3bf1bc62, 0x3c62bbf1, 0xbc7f3ac9,
    0xbc75bb95, 0xbc46bc22, 0x3bac3c71, 0x3c2c3c3e, 0x3a49bc80, 0x3bac3c71, 0x3c5c3c04, 0x3c4ebc18, 0xbc18bc4e, 0x3c78bb79,
    0x3c7dbb16, 0xbc04bc5c, 0xbc78bb79, 0xbb16bc7d, 0x3c2cbc3e, 0xbc673bdb, 0xbc673bdb, 0xbc803a49, 0x00003c80, 0x3bc43c6d,
    0x00003c80, 0xbbc4bc6d, 0x00003c80, 0x3c6d3bc4, 0x00003c80, 0xbc6dbbc4, 0x00003c80, 0x3c6dbbc4, 0x00003c80, 0xbc6d3bc4,
    0x00003c80, 0x3bc4bc6d, 0x00003c80, 0xbbc43c6d, 0x3c3e3c2c, 0x3c713bac, 0x3c713bac, 0xbc803a49, 0x3c4e3c18, 0x3c5cbc04,
    0x3c783b79, 0xbc183c4e, 0x3c5c3c04, 0x3b16bc7d, 0x3c7d3b16, 0x3b793c78, 0x3c673bdb, 0xbc2cbc3e, 0x3c803a49, 0x3c673bdb,
    0x3c7fbac9, 0x3c62bbf1, 0x3c22bc46, 0xbb953c75, 0x3c75bb95, 0x3ac9bc7f, 0x3bf1bc62, 0x3c223c46, 0x3c62bbf1, 0xbc46bc22,
    0x3b95bc75, 0x3c7fbac9, 0x3c46bc22, 0xbc753b95, 0x3ac9bc7f, 0x3bf1bc62, 0x3c18bc4e, 0x3b79bc78, 0xbc04bc5c, 0x3c4e3c18,
    0x3bacbc71, 0xbc3ebc2c, 0xbc3ebc2c, 0x3c67bbdb, 0x3a49bc80, 0xbc713bac, 0xbc67bbdb, 0x3a49bc80, 0xbb79bc78, 0xbb163c7d,
    0xbc7dbb16, 0xbc5cbc04, 0xbb48bc7b, 0xbc0ebc55, 0xbc7b3b48, 0x3c55bc0e, 0xbc0ebc55, 0xbc7b3b48, 0xbc553c0e, 0xbb48bc7b,
    0xbc55bc0e, 0xbb483c7b, 0xbc0e3c55, 0xbc7bbb48, 0xbc7bbb48, 0x3c553c0e, 0xbb483c7b, 0xbc0e3c55, 0xbc5cbc04, 0xbc7dbb16,
    0xbb163c7d, 0xbb79bc78, 0xbc80ba49, 0xbbdb3c67, 0x3bac3c71, 0xbc80ba49, 0xbc673bdb, 0x3c3e3c2c, 0x3c3e3c2c, 0xbbac3c71,
    0xbc183c4e, 0x3c5cbc04, 0x3c783b79, 0x3c4e3c18, 0xbc753b95, 0xbc463c22, 0x3c623bf1, 0xbc7fbac9, 0xbc223c46, 0x3bf13c62,
    0x3c7fbac9, 0xbb953c75, 0xbac93c7f, 0x3c75bb95, 0x3c46bc22, 0x3c623bf1, 0x3bf13c62, 0xbac9bc7f, 0x3b95bc75, 0x3c22bc46,
    0xbbdb3c67, 0xba493c80, 0x3c3ebc2c, 0xbbdb3c67, 0x3b793c78, 0x3c7d3b16, 0x3b16bc7d, 0x3c5c3c04, 0x3c4e3c18, 0x3b79bc78,
    0xbc04bc5c, 0x3c18bc4e, 0x3c80ba49, 0xbc71bbac, 0xbc71bbac, 0xbc3ebc2c, 0x00003c80, 0x3bc43c6d, 0x00003c80, 0xbbc4bc6d,
    0x00003c80, 0x3c6d3bc4, 0x00003c80, 0xbc6dbbc4, 0x00003c80, 0x3c6dbbc4, 0x00003c80, 0xbc6d3bc4, 0x00003c80, 0x3bc4bc6d,
    0x00003c80, 0xbbc43c6d, 0x3c80ba49, 0x3c67bbdb, 0x3c67bbdb, 0xbc2c3c3e, 0x3c7dbb16, 0x3b79bc78, 0x3c5cbc04, 0x3b163c7d,
    0x3c78bb79, 0xbc18bc4e, 0x3c4ebc18, 0x3c5c3c04, 0x3c71bbac, 0xbc80ba49, 0x3c3ebc2c, 0x3c71bbac, 0xbac9bc7f, 0xbbf1bc62,
    0xbc46bc22, 0x3c753b95, 0xbb95bc75, 0xbc7fbac9, 0xbc62bbf1, 0x3c46bc22, 0xbbf1bc62, 0xbc223c46, 0xbc75bb95, 0xbac9bc7f,
    0xbc22bc46, 0x3b953c75, 0xbc7fbac9, 0xbc62bbf1, 0xbc7d3b16, 0xbc5c3c04, 0xbb793c78, 0xbb16bc7d, 0xbc673bdb, 0x3a493c80,
    0x3a493c80, 0xbc71bbac, 0xbc3e3c2c, 0x3c673bdb, 0x3bac3c71, 0xbc3e3c2c, 0xbc043c5c, 0x3c4ebc18, 0x3c183c4e, 0x3b793c78,
    0x3b483c7b, 0x3c0e3c55, 0x3c7bbb48, 0xbc553c0e, 0x3c0e3c55, 0x3c7bbb48, 0x3c55bc0e, 0x3b483c7b, 0x3c553c0e, 0x3b48bc7b,
    0x3c0ebc55, 0x3c7b3b48, 0x3c7b3b48, 0xbc55bc0e, 0x3b48bc7b, 0x3c0ebc55, 0x3c78bb79, 0x3c4ebc18, 0xbc18bc4e, 0x3c5c3c04,
    0x3c3ebc2c, 0xbbacbc71, 0xbc67bbdb, 0x3c3ebc2c, 0x3bacbc71, 0xbc803a49, 0xbc803a49, 0xbbdbbc67, 0xbb16bc7d, 0xbb793c78,
    0xbc5c3c04, 0xbc7d3b16, 0xbb95bc75, 0xbc22bc46, 0xbbf13c62, 0x3ac9bc7f, 0xbc46bc22, 0xbc623bf1, 0x3ac93c7f, 0xbc75bb95,
    0xbc7fbac9, 0x3b953c75, 0x3c223c46, 0xbbf13c62, 0xbc623bf1, 0x3c7fbac9, 0x3c753b95, 0x3c463c22, 0xbc713bac, 0xbc3e3c2c,
    0x3c803a49, 0xbc713bac, 0xbc043c5c, 0x3c183c4e, 0x3c4ebc18, 0x3b793c78, 0x3b163c7d, 0x3c5cbc04, 0x3b79bc78, 0x3c7dbb16,
    0x3c3e3c2c, 0xbbdbbc67, 0xbbdbbc67, 0xba49bc80, 0x00003c80, 0x3bc43c6d, 0x00003c80, 0xbbc4bc6d, 0x00003c80, 0x3c6d3bc4,
    0x00003c80, 0xbc6dbbc4, 0x00003c80, 0x3c6dbbc4, 0x00003c80, 0xbc6d3bc4, 0x00003c80, 0x3bc4bc6d, 0x00003c80, 0xbbc43c6d,
    0x3c2cbc3e, 0x3bacbc71, 0x3bacbc71, 0x3a493c80, 0x3c18bc4e, 0xbc04bc5c, 0x3b79bc78, 0x3c4e3c18, 0x3c04bc5c, 0xbc7dbb16,
    0x3b16bc7d, 0x3c78bb79, 0x3bdbbc67, 0xbc3e3c2c, 0x3a49bc80, 0x3bdbbc67, 0xbc7f3ac9, 0xbc623bf1, 0xbc223c46, 0x3b95bc75,
    0xbc753b95, 0xbac93c7f, 0xbbf13c62, 0xbc22bc46, 0xbc623bf1, 0x3c463c22, 0xbb953c75, 0xbc7f3ac9, 0xbc463c22, 0x3c75bb95,
    0xbac93c7f, 0xbbf13c62, 0x3c4e3c18, 0x3c783b79, 0x3c5cbc04, 0xbc183c4e, 0x3c713bac, 0x3c2cbc3e, 0x3c2cbc3e, 0x3bdb3c67,
    0x3c803a49, 0xbbacbc71, 0x3bdbbc67, 0x3c803a49, 0x3c78bb79, 0xbc7dbb16, 0x3b16bc7d, 0x3c04bc5c, 0xbb48bc7b, 0xbc0ebc55,
    0xbc7b3b48, 0x3c55bc0e, 0xbc0ebc55, 0xbc7b3b48, 0xbc553c0e, 0xbb48bc7b, 0xbc55bc0e, 0xbb483c7b, 0xbc0e3c55, 0xbc7bbb48,
    0xbc7bbb48, 0x3c553c0e, 0xbb483c7b, 0xbc0e3c55, 0xbc043c5c, 0xbb163c7d, 0x3c7d3b16, 0xbc783b79, 0xba493c80, 0x3c673bdb,
    0x3c71bbac, 0xba493c80, 0x3bdb3c67, 0x3c2cbc3e, 0x3c2cbc3e, 0x3c713bac, 0x3c4e3c18, 0xbc04bc5c, 0x3b79bc78, 0x3c18bc4e,
    0x3c75bb95, 0x3c46bc22, 0xbc62bbf1, 0x3c7f3ac9, 0x3c22bc46, 0xbbf1bc62, 0xbc7f3ac9, 0x3b95bc75, 0x3ac9bc7f, 0xbc753b95,
    0xbc463c22, 0xbc62bbf1, 0xbbf1bc62, 0x3ac93c7f, 0xbb953c75, 0xbc223c46, 0xbc67bbdb, 0xbc80ba49, 0x3c2c3c3e, 0xbc67bbdb,
    0xbc783b79, 0xbb163c7d, 0x3c7d3b16, 0xbc043c5c, 0xbc183c4e, 0x3c783b79, 0x3c5cbc04, 0x3c4e3c18, 0x3a493c80, 0x3bacbc71,
    0x3bacbc71, 0x3c2cbc3e, 0x3c353c35, 0x3c6d3bc4, 0x3c353c35, 0xbc6dbbc4, 0x3c35bc35, 0xbbc4bc6d, 0x3c35bc35, 0x3bc43c6d,
    0xbc35bc35, 0xbbc43c6d, 0xbc35bc35, 0x3bc4bc6d, 0xbc353c35, 0x3c6dbbc4, 0xbc353c35, 0xbc6d3bc4, 0x3c3e3c2c, 0x3c713bac,
    0x3c713bac, 0xbc803a49, 0x3c18bc4e, 0xbc04bc5c, 0x3b79bc78, 0x3c4e3c18, 0xbc5cbc04, 0xbb163c7d, 0xbc7dbb16, 0xbb79bc78,
    0xbbdb3c67, 0x3c3ebc2c, 0xba493c80, 0xbbdb3c67, 0x3c463c22, 0x3c753b95, 0x3c7fbac9, 0xbc623bf1, 0x3bf1bc62, 0xbc22bc46,
    0xbb95bc75, 0x3c7f3ac9, 0xbc75bb95, 0x3ac93c7f, 0xbc623bf1, 0xbc46bc22, 0xbac93c7f, 0x3bf1bc62, 0x3c223c46, 0x3b953c75,
    0x3c4e3c18, 0x3c783b79, 0x3c5cbc04, 0xbc183c4e, 0x3bacbc71, 0xbc3ebc2c, 0xbc3ebc2c, 0x3c67bbdb, 0xbc80ba49, 0x3bac3c71,
    0xbbdb3c67, 0xbc80ba49, 0x3b793c78, 0x3b16bc7d, 0x3c7d3b16, 0x3c5c3c04, 0x3c553c0e, 0x3c7b3b48, 0x3c0ebc55, 0xbb483c7b,
    0x3b48bc7b, 0xbc55bc0e, 0xbc7bbb48, 0x3c0ebc55, 0xbc7b3b48, 0x3c0e3c55, 0x3b483c7b, 0xbc553c0e, 0x3c0e3c55, 0xbb48bc7b,
    0x3c55bc0e, 0x3c7bbb48, 0x3c5c3c04, 0x3c7d3b16, 0x3b16bc7d, 0x3b793c78, 0x3a49bc80, 0xbc67bbdb, 0xbc713bac, 0x3a49bc80,
    0xbc673bdb, 0x3c3e3c2c, 0x3c3e3c2c, 0xbbac3c71, 0x3c4e3c18, 0xbc04bc5c, 0x3b79bc78, 0x3c18bc4e, 0x3c623bf1, 0x3c7f3ac9,
    0xbb95bc75, 0x3c223c46, 0xbac9bc7f, 0xbc75bb95, 0xbc223c46, 0xbbf1bc62, 0xbc463c22, 0x3c623bf1, 0x3c7f3ac9, 0x3b953c75,
    0x3c753b95, 0xbc46bc22, 0xbbf1bc62, 0xbac9bc7f, 0x3c673bdb, 0x3c803a49, 0xbc2cbc3e, 0x3c673bdb, 0xbb79bc78, 0xbc7dbb16,
    0xbb163c7d, 0xbc5cbc04, 0xbc183c4e, 0x3c783b79, 0x3c5cbc04, 0x3c4e3c18, 0x3c80ba49, 0xbc71bbac, 0xbc71bbac, 0xbc3ebc2c,
    0x3c353c35, 0x3c6d3bc4, 0x3c353c35, 0xbc6dbbc4, 0x3c35bc35, 0xbbc4bc6d, 0x3c35bc35, 0x3bc43c6d, 0xbc35bc35, 0xbbc43c6d,
    0xbc35bc35, 0x3bc4bc6d, 0xbc353c35, 0x3c6dbbc4, 0xbc353c35, 0xbc6d3bc4, 0x3c80ba49, 0x3c67bbdb, 0x3c67bbdb, 0xbc2c3c3e,
    0xbb16bc7d, 0xbc78bb79, 0xbc04bc5c, 0x3c7dbb16, 0xbc783b79, 0x3c183c4e, 0xbc4e3c18, 0xbc5cbc04, 0x3bac3c71, 0x3a49bc80,
    0x3c2c3c3e, 0x3bac3c71, 0x3c22bc46, 0x3b95bc75, 0xbac9bc7f, 0x3bf13c62, 0xbc62bbf1, 0xbc463c22, 0xbc753b95, 0x3ac9bc7f,
    0xbb953c75, 0x3c7fbac9, 0x3bf13c62, 0xbc223c46, 0x3c7f3ac9, 0xbc62bbf1, 0x3c46bc22, 0x3c75bb95, 0xbb16bc7d, 0xbc04bc5c,
    0xbc78bb79, 0x3c7dbb16, 0xbc673bdb, 0x3a493c80, 0x3a493c80, 0xbc71bbac, 0x3c2c3c3e, 0x3bdbbc67, 0x3c71bbac, 0x3c2c3c3e,
    0x3c04bc5c, 0xbc4e3c18, 0xbc18bc4e, 0xbb79bc78, 0xbc55bc0e, 0xbc7bbb48, 0xbc0e3c55, 0x3b48bc7b, 0xbb483c7b, 0x3c553c0e,
    0x3c7b3b48, 0xbc0e3c55, 0x3c7bbb48, 0xbc0ebc55, 0xbb48bc7b, 0x3c55bc0e, 0xbc0ebc55, 0x3b483c7b, 0xbc553c0e, 0xbc7b3b48,
    0xbc783b79, 0xbc4e3c18, 0x3c183c4e, 0xbc5cbc04, 0x3c2c3c3e, 0x3c71bbac, 0x3bdbbc67, 0x3c2c3c3e, 0x3bacbc71, 0xbc803a49,
    0xbc803a49, 0xbbdbbc67, 0xbc7d3b16, 0x3c783b79, 0x3c043c5c, 0x3b163c7d, 0xbbf13c62, 0xbac93c7f, 0x3c75bb95, 0xbc463c22,
    0x3c7fbac9, 0x3b95bc75, 0xbc46bc22, 0x3c62bbf1, 0xbc22bc46, 0xbbf13c62, 0xbac93c7f, 0xbc753b95, 0xbb953c75, 0x3c22bc46,
    0x3c62bbf1, 0x3c7fbac9, 0x3bac3c71, 0x3c2c3c3e, 0x3a49bc80, 0x3bac3c71, 0x3c04bc5c, 0xbc18bc4e, 0xbc4e3c18, 0xbb79bc78,
    0xbc7d3b16, 0x3c043c5c, 0x3c783b79, 0x3b163c7d, 0x3c3e3c2c, 0xbbdbbc67, 0xbbdbbc67, 0xba49bc80, 0x3c353c35, 0x3c6d3bc4,
    0x3c353c35, 0xbc6dbbc4, 0x3c35bc35, 0xbbc4bc6d, 0x3c35bc35, 0x3bc43c6d, 0xbc35bc35, 0xbbc43c6d, 0xbc35bc35, 0x3bc4bc6d,
    0xbc353c35, 0x3c6dbbc4, 0xbc353c35, 0xbc6d3bc4, 0x3c2cbc3e, 0x3bacbc71, 0x3bacbc71, 0x3a493c80, 0xbc4ebc18, 0xbc5c3c04,
    0xbc78bb79, 0x3c18bc4e, 0xbc043c5c, 0x3c7d3b16, 0xbb163c7d, 0xbc783b79, 0x3c673bdb, 0xbc2cbc3e, 0x3c803a49, 0x3c673bdb,
    0xbc46bc22, 0xbc75bb95, 0xbc7f3ac9, 0x3c62bbf1, 0xbbf13c62, 0x3c223c46, 0x3b953c75, 0xbc7fbac9, 0x3c753b95, 0xbac9bc7f,
    0x3c62bbf1, 0x3c463c22, 0x3ac9bc7f, 0xbbf13c62, 0xbc22bc46, 0xbb95bc75, 0xbc183c4e, 0xbb793c78, 0x3c043c5c, 0xbc4ebc18,
    0x3c713bac, 0x3c2cbc3e, 0x3c2cbc3e, 0x3bdb3c67, 0x3a49bc80, 0xbc713bac, 0xbc67bbdb, 0x3a49bc80, 0xbc783b79, 0x3c7d3b16,
    0xbb163c7d, 0xbc043c5c, 0x3c553c0e, 0x3c7b3b48, 0x3c0ebc55, 0xbb483c7b, 0x3b48bc7b, 0xbc55bc0e, 0xbc7bbb48, 0x3c0ebc55,
    0xbc7b3b48, 0x3c0e3c55, 0x3b483c7b, 0xbc553c0e, 0x3c0e3c55, 0xbb48bc7b, 0x3c55bc0e, 0x3c7bbb48, 0x3c04bc5c, 0x3b16bc7d,
    0xbc7dbb16, 0x3c78bb79, 0xbc80ba49, 0xbbdb3c67, 0x3bac3c71, 0xbc80ba49, 0x3bdb3c67, 0x3c2cbc3e, 0x3c2cbc3e, 0x3c713bac,
    0x3c18bc4e, 0xbc5c3c04, 0xbc78bb79, 0xbc4ebc18, 0xbc62bbf1, 0xbc7fbac9, 0x3b953c75, 0xbc22bc46, 0x3ac93c7f, 0x3c753b95,
    0x3c22bc46, 0x3bf13c62, 0x3c46bc22, 0xbc62bbf1, 0xbc7fbac9, 0xbb95bc75, 0xbc75bb95, 0x3c463c22, 0x3bf13c62, 0x3ac93c7f,
    0xbbdb3c67, 0xba493c80, 0x3c3ebc2c, 0xbbdb3c67, 0x3c78bb79, 0x3b16bc7d, 0xbc7dbb16, 0x3c04bc5c, 0xbc4ebc18, 0xbb793c78,
    0x3c043c5c, 0xbc183c4e, 0x3a493c80, 0x3bacbc71, 0x3bacbc71, 0x3c2cbc3e, 0x3c353c35, 0x3c6d3bc4, 0x3c353c35, 0xbc6dbbc4,
    0x3c35bc35, 0xbbc4bc6d, 0x3c35bc35, 0x3bc43c6d, 0xbc35bc35, 0xbbc43c6d, 0xbc35bc35, 0x3bc4bc6d, 0xbc353c35, 0x3c6dbbc4,
    0xbc353c35, 0xbc6d3bc4, 0xba49bc80, 0xbbdbbc67, 0xbbdbbc67, 0x3c3e3c2c, 0xbc7d3b16, 0xbb793c78, 0xbc5c3c04, 0xbb16bc7d,
    0x3b793c78, 0x3c4ebc18, 0x3c183c4e, 0xbc043c5c, 0x3c71bbac, 0xbc80ba49, 0x3c3ebc2c, 0x3c71bbac, 0xbc223c46, 0xbb953c75,
    0x3ac93c7f, 0xbbf1bc62, 0x3c623bf1, 0x3c46bc22, 0x3c75bb95, 0xbac93c7f, 0x3b95bc75, 0xbc7f3ac9, 0xbbf1bc62, 0x3c22bc46,
    0xbc7fbac9, 0x3c623bf1, 0xbc463c22, 0xbc753b95, 0x3c7dbb16, 0x3c5cbc04, 0x3b79bc78, 0x3b163c7d, 0xbbdbbc67, 0xbc803a49,
    0xbc803a49, 0x3bacbc71, 0xbc3e3c2c, 0x3c673bdb, 0x3bac3c71, 0xbc3e3c2c, 0x3c5c3c04, 0xbc18bc4e, 0x3c4ebc18, 0x3c78bb79,
    0xbc55bc0e, 0xbc7bbb48, 0xbc0e3c55, 0x3b48bc7b, 0xbb483c7b, 0x3c553c0e, 0x3c7b3b48, 0xbc0e3c55, 0x3c7bbb48, 0xbc0ebc55,
    0xbb48bc7b, 0x3c55bc0e, 0xbc0ebc55, 0x3b483c7b, 0xbc553c0e, 0xbc7b3b48, 0x3b793c78, 0x3c183c4e, 0x3c4ebc18, 0xbc043c5c,
    0x3c3ebc2c, 0xbbacbc71, 0xbc67bbdb, 0x3c3ebc2c, 0xbc71bbac, 0x3a493c80, 0x3a493c80, 0xbc673bdb, 0x3b163c7d, 0x3b79bc78,
    0x3c5cbc04, 0x3c7dbb16, 0x3bf1bc62, 0x3ac9bc7f, 0xbc753b95, 0x3c46bc22, 0xbc7f3ac9, 0xbb953c75, 0x3c463c22, 0xbc623bf1,
    0x3c223c46, 0x3bf1bc62, 0x3ac9bc7f, 0x3c75bb95, 0x3b95bc75, 0xbc223c46, 0xbc623bf1, 0xbc7f3ac9, 0xbc713bac, 0xbc3e3c2c,
    0x3c803a49, 0xbc713bac, 0x3c5c3c04, 0x3c4ebc18, 0xbc18bc4e, 0x3c78bb79, 0xbb16bc7d, 0xbc5c3c04, 0xbb793c78, 0xbc7d3b16,
    0xbc2c3c3e, 0x3c67bbdb, 0x3c67bbdb, 0x3c80ba49, 0x3c800000, 0x3c6dbbc4, 0x3c800000, 0xbc6d3bc4, 0xbc800000, 0xbbc43c6d,
    0xbc800000, 0x3bc4bc6d, 0x3c800000, 0xbbc4bc6d, 0x3c800000, 0x3bc43c6d, 0xbc800000, 0x3c6d3bc4, 0xbc800000, 0xbc6dbbc4,
    0x3c80ba49, 0x3c67bbdb, 0x3c67bbdb, 0xbc2c3c3e, 0xbc7d3b16, 0xbb793c78, 0xbc5c3c04, 0xbb16bc7d, 0x3c78bb79, 0xbc18bc4e,
    0x3c4ebc18, 0x3c5c3c04, 0xbc713bac, 0x3c803a49, 0xbc3e3c2c, 0xbc713bac, 0x3c7fbac9, 0x3c62bbf1, 0x3c22bc46, 0xbb953c75,
    0xbc753b95, 0xbac93c7f, 0xbbf13c62, 0xbc22bc46, 0x3c62bbf1, 0xbc46bc22, 0x3b95bc75, 0x3c7fbac9, 0xbc463c22, 0x3c75bb95,
    0xbac93c7f, 0xbbf13c62, 0x3c7dbb16, 0x3c5cbc04, 0x3b79bc78, 0x3b163c7d, 0xbc673bdb, 0x3a493c80, 0x3a493c80, 0xbc71bbac,
    0x3c3ebc2c, 0xbc67bbdb, 0xbbacbc71, 0x3c3ebc2c, 0xbc043c5c, 0x3c4ebc18, 0x3c183c4e, 0x3b793c78, 0x3c7bbb48, 0x3c55bc0e,
    0xbb48bc7b, 0x3c0e3c55, 0xbc553c0e, 0x3b483c7b, 0x3c0e3c55, 0xbc7b3b48, 0x3c0ebc55, 0xbc7bbb48, 0xbc55bc0e, 0x3b48bc7b,
    0xbb483c7b, 0x3c0ebc55, 0x3c7b3b48, 0x3c553c0e, 0x3c78bb79, 0x3c4ebc18, 0xbc18bc4e, 0x3c5c3c04, 0xbc3e3c2c, 0x3bac3c71,
    0x3c673bdb, 0xbc3e3c2c, 0x3bacbc71, 0xbc803a49, 0xbc803a49, 0xbbdbbc67, 0x3b163c7d, 0x3b79bc78, 0x3c5cbc04, 0x3c7dbb16,
    0x3c75bb95, 0x3c46bc22, 0xbc62bbf1, 0x3c7f3ac9, 0xbc223c46, 0x3bf13c62, 0x3c7fbac9, 0xbb953c75, 0x3ac9bc7f, 0xbc753b95,
    0xbc463c22, 0xbc62bbf1, 0x3bf13c62, 0xbac9bc7f, 0x3b95bc75, 0x3c22bc46, 0x3c71bbac, 0x3c3ebc2c, 0xbc80ba49, 0x3c71bbac,
    0xbc043c5c, 0x3c183c4e, 0x3c4ebc18, 0x3b793c78, 0xbb16bc7d, 0xbc5c3c04, 0xbb793c78, 0xbc7d3b16, 0x3c3e3c2c, 0xbbdbbc67,
    0xbbdbbc67, 0xba49bc80, 0x3c800000, 0x3c6dbbc4, 0x3c800000, 0xbc6d3bc4, 0xbc800000, 0xbbc43c6d, 0xbc800000, 0x3bc4bc6d,
    0x3c800000, 0xbbc4bc6d, 0x3c800000, 0x3bc43c6d, 0xbc800000, 0x3c6d3bc4, 0xbc800000, 0xbc6dbbc4, 0x3c2cbc3e, 0x3bacbc71,
    0x3bacbc71, 0x3a493c80, 0xbc183c4e, 0x3c043c5c, 0xbb793c78, 0xbc4ebc18, 0x3c04bc5c, 0xbc7dbb16, 0x3b16bc7d, 0x3c78bb79,
    0xbbdb3c67, 0x3c3ebc2c, 0xba493c80, 0xbbdb3c67, 0xbac9bc7f, 0xbbf1bc62, 0xbc46bc22, 0x3c753b95, 0x3b953c75, 0x3c7f3ac9,
    0x3c623bf1, 0xbc463c22, 0xbbf1bc62, 0xbc223c46, 0xbc75bb95, 0xbac9bc7f, 0x3c223c46, 0xbb95bc75, 0x3c7f3ac9, 0x3c623bf1,
    0xbc4ebc18, 0xbc78bb79, 0xbc5c3c04, 0x3c18bc4e, 0x3c713bac, 0x3c2cbc3e, 0x3c2cbc3e, 0x3bdb3c67, 0xbc80ba49, 0x3bac3c71,
    0xbbdb3c67, 0xbc80ba49, 0x3c78bb79, 0xbc7dbb16, 0x3b16bc7d, 0x3c04bc5c, 0xbc7b3b48, 0xbc553c0e, 0x3b483c7b, 0xbc0ebc55,
    0x3c55bc0e, 0xbb48bc7b, 0xbc0ebc55, 0x3c7bbb48, 0xbc0e3c55, 0x3c7b3b48, 0x3c553c0e, 0xbb483c7b, 0x3b48bc7b, 0xbc0e3c55,
    0xbc7bbb48, 0xbc55bc0e, 0xbc043c5c, 0xbb163c7d, 0x3c7d3b16, 0xbc783b79, 0x3a49bc80, 0xbc67bbdb, 0xbc713bac, 0x3a49bc80,
    0x3bdb3c67, 0x3c2cbc3e, 0x3c2cbc3e, 0x3c713bac, 0xbc4ebc18, 0x3c043c5c, 0xbb793c78, 0xbc183c4e, 0x3b953c75, 0x3c223c46,
    0x3bf1bc62, 0xbac93c7f, 0xbc46bc22, 0xbc623bf1, 0x3ac93c7f, 0xbc75bb95, 0x3c7f3ac9, 0xbb95bc75, 0xbc22bc46, 0x3bf1bc62,
    0xbc623bf1, 0x3c7fbac9, 0x3c753b95, 0x3c463c22, 0x3c673bdb, 0x3c803a49, 0xbc2cbc3e, 0x3c673bdb, 0xbc783b79, 0xbb163c7d,
    0x3c7d3b16, 0xbc043c5c, 0x3c18bc4e, 0xbc78bb79, 0xbc5c3c04, 0xbc4ebc18, 0x3a493c80, 0x3bacbc71, 0x3bacbc71, 0x3c2cbc3e,
    0x3c800000, 0x3c6dbbc4, 0x3c800000, 0xbc6d3bc4, 0xbc800000, 0xbbc43c6d, 0xbc800000, 0x3bc4bc6d, 0x3c800000, 0xbbc4bc6d,
    0x3c800000, 0x3bc43c6d, 0xbc800000, 0x3c6d3bc4, 0xbc800000, 0xbc6dbbc4, 0xba49bc80, 0xbbdbbc67, 0xbbdbbc67, 0x3c3e3c2c,
    0x3b163c7d, 0x3c783b79, 0x3c043c5c, 0xbc7d3b16, 0xbb79bc78, 0xbc4e3c18, 0xbc18bc4e, 0x3c04bc5c, 0x3bac3c71, 0x3a49bc80,
    0x3c2c3c3e, 0x3bac3c71, 0xbc7f3ac9, 0xbc623bf1, 0xbc223c46, 0x3b95bc75, 0x3c75bb95, 0x3ac9bc7f, 0x3bf1bc62, 0x3c223c46,
    0xbc623bf1, 0x3c463c22, 0xbb953c75, 0xbc7f3ac9, 0x3c46bc22, 0xbc753b95, 0x3ac9bc7f, 0x3bf1bc62, 0x3b163c7d, 0x3c043c5c,
    0x3c783b79, 0xbc7d3b16, 0xbbdbbc67, 0xbc803a49, 0xbc803a49, 0x3bacbc71, 0x3c2c3c3e, 0x3bdbbc67, 0x3c71bbac, 0x3c2c3c3e,
    0xbc5cbc04, 0x3c183c4e, 0xbc4e3c18, 0xbc783b79, 0x3c7bbb48, 0x3c55bc0e, 0xbb48bc7b, 0x3c0e3c55, 0xbc553c0e, 0x3b483c7b,
    0x3c0e3c55, 0xbc7b3b48, 0x3c0ebc55, 0xbc7bbb48, 0xbc55bc0e, 0x3b48bc7b, 0xbb483c7b, 0x3c0ebc55, 0x3c7b3b48, 0x3c553c0e,
    0xbb79bc78, 0xbc18bc4e, 0xbc4e3c18, 0x3c04bc5c, 0x3c2c3c3e, 0x3c71bbac, 0x3bdbbc67, 0x3c2c3c3e, 0xbc71bbac, 0x3a493c80,
    0x3a493c80, 0xbc673bdb, 0x3c7dbb16, 0xbc78bb79, 0xbc04bc5c, 0xbb16bc7d, 0xbc753b95, 0xbc463c22, 0x3c623bf1, 0xbc7fbac9,
    0x3c22bc46, 0xbbf1bc62, 0xbc7f3ac9, 0x3b95bc75, 0xbac93c7f, 0x3c75bb95, 0x3c46bc22, 0x3c623bf1, 0xbbf1bc62, 0x3ac93c7f,
    0xbb953c75, 0xbc223c46, 0x3bac3c71, 0x3c2c3c3e, 0x3a49bc80, 0x3bac3c71, 0xbc5cbc04, 0xbc4e3c18, 0x3c183c4e, 0xbc783b79,
    0x3c7dbb16, 0xbc04bc5c, 0xbc78bb79, 0xbb16bc7d, 0xbc2c3c3e, 0x3c67bbdb, 0x3c67bbdb, 0x3c80ba49, 0x3c800000, 0x3c6dbbc4,
    0x3c800000, 0xbc6d3bc4, 0xbc800000, 0xbbc43c6d, 0xbc800000, 0x3bc4bc6d, 0x3c800000, 0xbbc4bc6d, 0x3c800000, 0x3bc43c6d,
    0xbc800000, 0x3c6d3bc4, 0xbc800000, 0xbc6dbbc4, 0xbc3ebc2c, 0xbc71bbac, 0xbc71bbac, 0x3c80ba49, 0x3c4e3c18, 0x3c5cbc04,
    0x3c783b79, 0xbc183c4e, 0xbc5cbc04, 0xbb163c7d, 0xbc7dbb16, 0xbb79bc78, 0x3c673bdb, 0xbc2cbc3e, 0x3c803a49, 0x3c673bdb,
    0x3ac93c7f, 0x3bf13c62, 0x3c463c22, 0xbc75bb95, 0xbb95bc75, 0xbc7fbac9, 0xbc62bbf1, 0x3c46bc22, 0x3bf13c62, 0x3c22bc46,
    0x3c753b95, 0x3ac93c7f, 0xbc22bc46, 0x3b953c75, 0xbc7fbac9, 0xbc62bbf1, 0x3c18bc4e, 0x3b79bc78, 0xbc04bc5c, 0x3c4e3c18,
    0xbbac3c71, 0x3c3e3c2c, 0x3c3e3c2c, 0xbc673bdb, 0x3a49bc80, 0xbc713bac, 0xbc67bbdb, 0x3a49bc80, 0x3b793c78, 0x3b16bc7d,
    0x3c7d3b16, 0x3c5c3c04, 0xbc7b3b48, 0xbc553c0e, 0x3b483c7b, 0xbc0ebc55, 0x3c55bc0e, 0xbb48bc7b, 0xbc0ebc55, 0x3c7bbb48,
    0xbc0e3c55, 0x3c7b3b48, 0x3c553c0e, 0xbb483c7b, 0x3b48bc7b, 0xbc0e3c55, 0xbc7bbb48, 0xbc55bc0e, 0x3c5c3c04, 0x3c7d3b16,
    0x3b16bc7d, 0x3b793c78, 0xbc80ba49, 0xbbdb3c67, 0x3bac3c71, 0xbc80ba49, 0x3c67bbdb, 0xbc3ebc2c, 0xbc3ebc2c, 0x3bacbc71,
    0xbc183c4e, 0x3c5cbc04, 0x3c783b79, 0x3c4e3c18, 0xbb95bc75, 0xbc22bc46, 0xbbf13c62, 0x3ac9bc7f, 0x3c463c22, 0x3c62bbf1,
    0xbac9bc7f, 0x3c753b95, 0xbc7fbac9, 0x3b953c75, 0x3c223c46, 0xbbf13c62, 0x3c62bbf1, 0xbc7f3ac9, 0xbc75bb95, 0xbc46bc22,
    0xbbdb3c67, 0xba493c80, 0x3c3ebc2c, 0xbbdb3c67, 0xbb79bc78, 0xbc7dbb16, 0xbb163c7d, 0xbc5cbc04, 0x3c4e3c18, 0x3b79bc78,
    0xbc04bc5c, 0x3c18bc4e, 0xbc803a49, 0x3c713bac, 0x3c713bac, 0x3c3e3c2c,
};

template <int G = 1024> __device__ __forceinline__ void store_tile_64(const float (&d)[32], uint32_t base, int warp, int lane) {
  const uint32_t rb = base + (warp * 2 + ((lane >> 3) & 1)) * G + (lane & 7) * 128;
#pragma unroll
  for (int j = 0; j < 8; j += 2) {
    const int jj = j + (lane >> 4);
    stsm4(rb + ((jj ^ (lane & 7)) << 4), pack2(d[4 * j], d[4 * j + 1]), pack2(d[4 * j + 2], d[4 * j + 3]),
          pack2(d[4 * j + 4], d[4 * j + 5]), pack2(d[4 * j + 6], d[4 * j + 7]));
  }
}

#define A_XM0 0xEB5C
#define A_XM1 0xDCBC
#define A_REL 0x22910
#define G_WPOLK 12
#define A_LDW 0x242
#define A_W2PF 2
#define A_DEPS 4
#define A_FREE 0x3F000
#define A_RELS 0x8A80
#define A_ACQ 0x1511
#define A_DEP 3
#define A_PACE0 1000
#define A_PACE1 A_PACE0
#define A_PACE_N 8
#define G_TMASK 0x0FB0
constexpr int A_IN = 112 * 128, A_OUT = 16384, A_NIN = 5, A_NOUT = 6;
constexpr int A_NREL = __builtin_popcount(A_REL);
constexpr int G_XP = NB1 * 64;
constexpr int G_STAGE = 16384 + 2 * G_XP, G_NST = 5;
constexpr int G_TIN = G_NST * G_STAGE, G_TOUT = G_TIN + 8192, G_SMEM = G_TOUT + 32768;
#define G_SLOTS 0x1032410324103210ull
__host__ __device__ constexpr int g_slot(int k) { return (G_SLOTS >> (4 * k)) & 7; }
constexpr uint32_t g_parities() {
  uint32_t m = 0;
  for (int k = 0; k < 16; k++)
    for (int j = 0; j < k; j++)
      if (g_slot(j) == g_slot(k)) m ^= 1u << k;
  return m;
}
constexpr uint32_t G_PAR = g_parities();
constexpr int G_KS = 12;
#define G_KI 14
#define G_KC 2
#define G_HOLDQ 1
#define G_HOLDI 2
#define C_HOLD 1
#define G_HOLDB 1
template <int N> using IC = std::integral_constant<int, N>;
__device__ __align__(128) int g_cnt[4 * 32];

__device__ __forceinline__ int x_decode(int r, int cta) {
  const int v = r * 64 + ((cta >> 2) << 1) + (cta & 1);
  int j = v / 80;
  j -= v < 80 * j + ((0x4840 >> (4 * j)) & 15);
  if (cta < 128) return ((7 - j) << 7) | (v - 80 * j - ((0x4840 >> (4 * j)) & 15));
  return r < 8 ? ((5 - (r >> 2)) << 7) | (76 + 4 * (cta & 1) + (r & 3)) : ((7 - (r >> 1)) << 7) | (80 + 2 * (cta & 1) + (r & 1));
}
__device__ __forceinline__ uint32_t a_out(int n) {
  const int p = n % A_NOUT;
  return (p < 4 ? (3 + (p >> 1)) * G_STAGE : G_TOUT) + (p & 1) * A_OUT;
}
__device__ __forceinline__ uint32_t x1_addr(int L, int b, uint32_t flips) {
  const int p = L >> 4, sel = (b ^ __popc(L & 15) ^ (flips >> p)) & 1;
  return (p << 21) | (sel << 12) | ((L & 1) << 13) | ((L & 6) << 15) | ((L & 8) << 16);
}
__device__ __forceinline__ uint32_t spread16(int i) { return ((i & 3) << 14) | ((i & 4) << 16) | ((i & 8) << 17); }
constexpr int NPG = 19 + W_SHIFT, NVOTE = 6;
__device__ __forceinline__ uint32_t w_addr(int P, int f, int c, int dhalf, uint32_t flips) {
  return x1_addr(16 * P + (c >> 5) + 2 * (f >> 3), dhalf, flips >> 12) + spread16(2 * f) + (c & 31) * 128;
}
__device__ __forceinline__ void w_store(const CUtensorMap* m, uint32_t src, uint32_t a) {
#pragma unroll
  for (int j = 0; j < 8; j++)
    tma_st5<0>(m, src + j * 2048, ((a & 16383) >> 1) ^ ((__popc(j) & 1) << 11), (j & 3) << 1, (j >> 2) << 1, a >> 20, 0);
}
__device__ __forceinline__ uint32_t read_votes(const int* cnt, int lane, int v) {
#pragma unroll 1
  for (int it = 0; it < (1 << 20) && (__ballot_sync(0xffffffffu, v < NVOTE * 256) & ((2 << NPG) - 2)); it++)
    asm volatile("ld.relaxed.gpu.global.s32 %0, [%1];" : "=r"(v) : "l"(cnt + 32 + lane) : "memory");
  return __ballot_sync(0xffffffffu, (v & 255) > NVOTE / 2);
}
__device__ __forceinline__ int take_ticket(int* p) {
  int v;
  asm volatile("atom.relaxed.gpu.global.inc.u32 %0, [%1], 0x7fffffff;" : "=r"(v) : "l"(p) : "memory");
  return v;
}
__device__ __forceinline__ void send_role(uint32_t dst, uint32_t bar, int v) {
  for (int c = 0; c < 2; c++)
    asm volatile("{\n.reg .b32 a, b;\nmapa.shared::cluster.u32 a, %0, %2;\nmapa.shared::cluster.u32 b, %1, %2;\n"
                 "st.async.shared::cluster.mbarrier::complete_tx::bytes.u32 [a], %3, [b];\n}" ::"r"(dst), "r"(bar), "r"(c), "r"(v) : "memory");
}
struct GMaps {
  CUtensorMap in[5];
  CUtensorMap ws, xs, w, y;
  CUtensorMap y1[2], x2s, x2, w2, y2;
};

#define H_EPI 3
#define H_KS 11
#define C_PACE 300
#define C_ORD 1
#define H_HOLD 5
#define C_POL 1
constexpr int H_XP = 168 * 64, H_STAGE = 8192 + 2 * H_XP, H_NST = 7;
constexpr int C_OUT = 7 * 8192, C_GI = 13 * 8192, C_F = C_GI + 6144, C_PIECE = C_F + 8192;
static_assert(C_GI >= 3 * H_STAGE && C_PIECE + C_OUT == 6 * H_STAGE, "slots 0..2 | 3..5 | 6 fall free together");
constexpr int G_IM1 = C_GI - NB1 * 128;

template <int WG>
__device__ __forceinline__ void h_loop(float (&acc)[84], uint32_t sb, uint32_t full0, uint32_t empty0, int lane) {
#pragma unroll 1
  for (int k = 0; k < 16; k++) {
    const int st = k % H_NST;
    if (WG == 1 && k == H_KS) bar_sync(4, 256);
    mbar_wait(full0 + 8 * st, (k / H_NST) & 1);
    const uint32_t base = sb + st * H_STAGE;
    wg_fence();
#pragma unroll
    for (int s = 0; s < 2; s++) {
      const uint64_t dP = mk_desc(base, s * 2048, 0, 1024, 1), dQ = mk_desc(base, 4096 + s * 2048, 0, 1024, 1);
      const uint64_t dA = mk_desc(base, 8192 + s * 32, 0, 512, 2), dB = mk_desc(base, 8192 + H_XP + s * 32, 0, 512, 2);
      wgmma_ss_168<1, 1, 1, 0>(acc, dP, WG == 0 ? dA : dB, k | s);
      wgmma_ss_168<WG == 0 ? 1 : -1, 1, 1, 0>(acc, dQ, WG == 0 ? dB : dA, 1);
    }
    wg_commit();
    if (WG == 0 && k == 15) bar_arrive(4, 256);
    if (k <= 10) {
      wg_wait<1>();
      if (k > 0 && k - 1 + H_NST < 16 && lane < 2) mbar_arrive_cta(empty0 + 8 * ((k - 1) % H_NST), lane);
    }
  }
  wg_wait<0>();
  reg_fence(acc);
}

template <int N> __device__ __forceinline__ void gelu_pack(uint32_t* hp, float (&h)[N], bool zero_first, bool zero_all) {
  reg_fence(h);
#pragma unroll
  for (int c = 0; c < N / 2; c++) {
    const uint32_t v = pack2(gelu(h[2 * c]), gelu(h[2 * c + 1]));
    hp[c] = zero_all || (zero_first && c < 2) ? 0u : v;
  }
#pragma unroll
  for (int c = 0; c < N / 2; c++) asm volatile("" : "+r"(hp[c])::"memory");
}
__device__ __forceinline__ void poll_ge(const int* p, int target) {
  int v = 0;
#pragma unroll 1
  for (int it = 0; it < (1 << 20) && v < target; it++)
    asm volatile("ld.relaxed.gpu.global.s32 %0, [%1];" : "=r"(v) : "l"(p) : "memory");
  asm volatile("fence.acquire.gpu;\nfence.proxy.async.global;" ::: "memory");
}

__global__ void __cluster_dims__(2, 1, 1) __launch_bounds__(384, 1)
kG(int* __restrict__ cnt, char* __restrict__ x1, char* __restrict__ wt, const __nv_bfloat16* __restrict__ g,
   const __nv_bfloat16* __restrict__ wgt, float* __restrict__ ge, const uint32_t* __restrict__ img, const __nv_bfloat16* __restrict__ wf,
   const __nv_bfloat16* __restrict__ wo, const uint32_t* __restrict__ gat, const __grid_constant__ GMaps m) {
  extern __shared__ __align__(1024) uint8_t smem_raw[];
  __shared__ __align__(8) uint64_t bars[20 + A_NIN + 2 * A_NOUT + 2 * G_NST + 16 + 2 * A_NREL + 2 * H_NST + 44];
  __shared__ uint16_t tab[128];
  __shared__ uint32_t lat[8], s_role, s_flips;
  const uint32_t sb = pin(s2u(smem_raw));
  const int tid = threadIdx.x, wg = __shfl_sync(0xffffffffu, tid >> 7, 0), t = tid & 127;
  const int warp = __shfl_sync(0xffffffffu, t >> 5, 0), lane = t & 31;
  const int blk = blockIdx.x, hf = blk & 1, page = 1 + blk % NPG;
  const bool spare = blk >= 128, voter = blk >= 128 - NPG * NVOTE && !spare;
  const int nu = spare ? 16 : 18;
  const uint32_t xm = spare ? 0xFFFF : hf ? A_XM1 : A_XM0;
  const uint32_t wf0 = pin(s2u(&bars[0])), xf0 = wf0 + 32, xe0 = xf0 + 128, aof0 = xe0 + 8 * A_NIN, aoe0 = aof0 + 8 * A_NOUT;
  const uint32_t full0 = aoe0 + 8 * A_NOUT, empty0 = full0 + 8 * G_NST;
  const uint32_t sf0 = empty0 + 8 * G_NST, se0 = sf0 + 16, inf0 = se0 + 16, roleb = inf0 + 16, flipb = roleb + 8;
  const uint32_t rel0 = flipb + 8, got0 = rel0 + 8 * A_NREL, acq0 = got0 + 64;
  const uint32_t hf0 = acq0 + 8 * A_NREL, he0 = hf0 + 8 * H_NST, yo0 = he0 + 8 * H_NST, of0 = yo0 + 96, yf0 = of0 + 96;
  const uint32_t gdone = yf0 + 64, imgb = gdone + 8, rly0 = imgb + 8, depb = rly0 + 32, puby = depb + 16, pubb = puby + 16;
  auto role = [&]() {
    mbar_wait(roleb, 0);
    return 2 * (int)*(volatile uint32_t*)&s_role + hf;
  };
  auto flips = [&]() {
    mbar_wait(flipb, 0);
    return *(volatile uint32_t*)&s_flips;
  };
  auto w_unit = [&](int cta) { return (cta & ~3) | (hf << 1) | ((cta >> 1) & 1); };
  auto w_code = [](int w2, int s, int i) { return (-(s < 4) << 16) | ((2 * w2 + (s >> 2)) << 11) | ((s & 3) << 9) | ((i >> 1) << 3) | ((i & 1) << 1); };
  auto in_load = [&](int c, uint32_t dst, uint32_t bar) {
    tma_ld5<1>(dst, &m.in[(c >> 11) & 7], bar, 0, c >> 16, c & 7, (c >> 3) & 63, (c >> 9) & 3);
  };
  auto y_store = [&](int w, int cta, uint32_t fl) {
    const int bin = cta >> 2, L = 4 * hf + 2 * w + (bin >> 4);
    const uint32_t sel = __ballot_sync(0xffffffffu, x1_addr(96 + 8 * lane + L, (cta >> 1) & 1, fl) & 4096);
#pragma unroll 1
    for (int q = 0; q < 2; q++) {
      const uint32_t stg = sb + (w == 0 ? 4 * G_STAGE + q * NB1 * 128 : q == 0 ? G_TOUT : G_IM1);
      const int c0 = ((L & 1) << 12) + (bin & 15) * 128 + q * 64;
      if (w == 1 && q == G_HOLDQ) mbar_wait(depb, 0);
#pragma unroll
      for (int c = 0; c < 3; c++) {
        mbar_wait(yo0 + 8 * (6 * w + 3 * q + c), 0);
        if (lane == 0) {
#pragma unroll
          for (int j = 4 * c; j < 4 * c + 4 && j < 11; j++)
            tma_st4<0>(j == 10 ? &m.y : &m.xs, stg + j * 2048, c0 + (((sel >> j) & 1) << 11), (L & 6) << 1, 2 * (j & 1), 12 + (j & ~1));
        }
        __syncwarp();
      }
    }
    bulk_commit();
    bulk_wait<0>();
    if (lane == 0) mbar_arrive(rly0 + 8 * w);
  };
  if (wg < 2) {
    if (lane == 0) {
      const uint32_t h = blk & 0x59, par = h ^ (h >> 3) ^ (h >> 4) ^ (h >> 6);
      char* p = x1 + (blk << 13) + (((warp ^ par) & 1) << 12) + 3584 + (warp >> 1) * 128;
      if (wg) {
        if (!voter) p += 256;
        else if (page < 12) p += page << 21;
        else p = wt + w_addr(page - 12, warp >> 1, blk >> 1, warp & 1, 0);
      }
      uint32_t c0, c1;
      asm volatile("{\n.reg .u32 v;\n.reg .pred q;\n"
                   "st.global.v4.u32 [%2], {0, 0, 0, 0};\nst.global.v4.u32 [%2 + 16], {0, 0, 0, 0};\n"
                   "mov.u32 %0, %%clock;\nmov.u32 %1, %0;\natom.relaxed.gpu.global.exch.b32 v, [%2], 1;\n"
                   "setp.eq.u32 q, v, 0;\n@q mov.u32 %1, %%clock;\n}\n" : "=r"(c0), "=r"(c1) : "l"(p) : "memory");
      lat[wg * 4 + warp] = c1 - c0;
    }
    __syncwarp();
    if (wg == 0 && hf == 0) bar_arrive(10, 160);
    bar_arrive(9, 288);
  }
  if (wg == 2) {
    if (t == 32) {
      mbar_init(wf0 + 24, 1);
      mbar_expect(wf0 + 24, 8192);
      fence_async();
      if (!spare) tma_ld5<1>(sb + 2 * G_STAGE + 3 * 8192, &m.in[1], wf0 + 24, 0, 0, 2 * hf, blk >> 1, 2);
    }
    __syncwarp();
    int votes = 0;
    if (warp == 3 && !voter) asm volatile("ld.relaxed.gpu.global.s32 %0, [%1];" : "=r"(votes) : "l"(cnt + 32 + lane) : "memory");
    asm volatile("setmaxnreg.dec.sync.aligned.u32 40;");
    if (lane == 0 && warp > 0) {
      if (warp == 1) {
        for (int i = 0; i < 3; i++) {
          mbar_init(wf0 + 8 * i, 1);
          mbar_expect(wf0 + 8 * i, 8192);
        }
      } else if (warp == 2) {
        prefetch_map(&m.in[4]);
        for (int i = 0; i < A_NIN + A_NOUT; i++) mbar_init(xe0 + 8 * i, 4);
        for (int i = 0; i < A_NOUT; i++) mbar_init(aoe0 + 8 * i, 1);
      } else {
        for (int i = 0; i < 2; i++) mbar_init(sf0 + 8 * i, 8);
        for (int i = 0; i < 6 + A_NREL; i++) mbar_init(se0 + 8 * i, 1);
        for (int i = 0; i < 3; i++) mbar_expect(inf0 + 8 * i, i < 2 ? 4096 : 4);
      }
      fence_bar_init();
    }
    __syncwarp();
    asm volatile("barrier.cluster.arrive.relaxed.aligned;" ::: "memory");
    int role_w = warp;
    if (role_w == 0) {
      int cta = blk, side = 0;
      if (hf == 0) {
        bar_sync(10, 160);
        side = min(lat[0], lat[2]) > min(lat[1], lat[3]);
        if (lane == 0) cta = take_ticket(cnt + (spare ? 62 : 54) + side);
      }
      const uint32_t wm = spare ? 0 : A_LDW | 0x6000;
      const int nw = __popc(wm & ((1 << lane) - 1)), r = lane - nw, np = r + A_NIN - (spare ? A_DEPS : A_DEP);
      const bool isw = (wm >> lane) & 1;
      uint32_t dst = sb + (!isw ? (r % A_NIN) * A_IN : nw < 3 ? 2 * G_STAGE + (2 - nw) * 8192 : G_TIN + (nw - 3) * 4096);
      uint32_t bf = !isw ? xf0 + 8 * r : nw < 3 ? wf0 + 8 * (2 - nw) : inf0 + 8 * (nw - 3);
      uint32_t be = isw ? roleb : xe0 + 8 * (np % A_NIN) + ((np / A_NIN - 1) & 1);
      asm volatile("barrier.cluster.wait.aligned;" : "+r"(dst), "+r"(bf), "+r"(be)::"memory");
      if (hf == 0) {
        cta = 2 * __shfl_sync(0xffffffffu, cta, 0) + side;
        if (cta >= 64) cta = 127 - cta;
        if (spare) cta = 64 + (cta >= 2 ? 3 - cta : cta);
        if (lane == 0) send_role(s2u(&s_role), roleb, cta);
        cta *= 2;
      } else {
        cta = role();
      }
      const int b = (cta >> 1) & 1;
      if (lane == 0 && !spare) tma_ld5<1>(sb, &m.in[4], xf0, 0, 96 * (((cta >> 2) << 1) + hf) - 24, 7, 0, b);
      __syncwarp();
      const int xc = x_decode(r, cta);
      const int code = isw ? w_code(nw >= 3, nw < 3 ? 4 - 2 * nw : 10 - nw, w_unit(cta)) : ((96 * (xc & 127) - 24) << 16) | (4 << 11) | (b << 9) | (xc >> 7);
#pragma unroll 1
      for (int p = !spare; p < (spare ? 16 : 15); p++) {
        const int c = __shfl_sync(0xffffffffu, code, p);
        const uint32_t d = __shfl_sync(0xffffffffu, dst, p), f = __shfl_sync(0xffffffffu, bf, p), e = __shfl_sync(0xffffffffu, be, p);
        mbar_wait(e & ~1u, e & 1);
        if (lane == 0) in_load(c, d, f);
        __syncwarp();
      }
      if (!spare) {
        const int bin = cta >> 2, f = 2 * bin + hf;
        if (lane == 0) {
          for (int s = 5; s >= A_W2PF; s--) {
            const int c = w_code(1, s, w_unit(cta));
            asm volatile("cp.async.bulk.prefetch.tensor.5d.L2.global [%0, {0, %1, %2, %3, %4}];" ::"l"(&m.in[(c >> 11) & 7]), "r"(c >> 16), "r"(c & 7), "r"((c >> 3) & 63), "r"((c >> 9) & 3) : "memory");
          }
          prefetch_map(&m.w);
          prefetch_map(&m.y);
          prefetch_map(&m.in[2]);
        }
        const uint32_t xa = x1_addr((21 - lane + 2 * (lane % 3)) * 8 + (f >> 4), b, flips()) + spread16(f);
        const uint32_t wa = w_addr(7 - (lane >> 1), 2 * bin, (lane & 1) * 32, hf, s_flips & ~0xC0000u);
#pragma unroll 1
        for (int k = 0; k < 16; k++) {
          const int st = g_slot(k);
          uint32_t a[3];
#pragma unroll
          for (int th = 0; th < 3; th++) a[th] = __shfl_sync(0xffffffffu, xa, 3 * (k >> 1) + th) ^ ((k & 1) * 0x21000);
          const uint32_t w = __shfl_sync(0xffffffffu, wa, k);
          if ((A_ACQ >> k) & 1) {
            mbar_wait(acq0 + 8 * __popc(A_ACQ & ((1 << k) - 1)), 0);
            asm volatile("fence.proxy.async.global;" ::: "memory");
          }
          mbar_wait(empty0 + 8 * st, (G_PAR >> k) & 1);
          if (lane == 0) {
            const uint32_t base = sb + st * G_STAGE, bar = full0 + 8 * st;
            mbar_expect(bar, G_STAGE);
#pragma unroll
            for (int th = 0; th < 3; th++)
              asm volatile("cp.async.bulk.shared::cluster.global.mbarrier::complete_tx::bytes.multicast::cluster.L2::cache_hint [%0], [%1], %2, [%3], %4, %5;"
                           ::"r"(base + 16384 + hf * G_XP + th * 3584), "l"(x1 + a[th]), "n"(3584), "r"(bar), "h"((uint16_t)3), "l"(policy<1>()) : "memory");
            if (k >= G_WPOLK) tma_ld3<1>(base, &m.w, bar, 0, (w >> 7) & 127, w >> 14);
            else tma_ld3<0>(base, &m.w, bar, 0, (w >> 7) & 127, w >> 14);
          }
          __syncwarp();
        }
        if (lane == 0) {
          if (blk == 0) asm volatile("cp.async.bulk.prefetch.L2.global [%0], 14336;" ::"l"(img) : "memory");
          prefetch_map(&m.y1[0]);
          prefetch_map(&m.y1[1]);
          prefetch_map(&m.x2s);
          prefetch_map(&m.x2);
          prefetch_map(&m.w2);
          prefetch_map(&m.y2);
        }
        mbar_wait(got0 + 24, 0);
        y_store(0, cta, s_flips);
        const int pl = lane >= 7, yb = min(6 * (bin - 4 * pl) + lane - 7 * pl, NB1 - 1);
        const uint32_t ya = x1_addr(96 + 8 * (yb >> 4) + 4 * hf + 2 * pl, b, s_flips) + spread16(yb);
        mbar_wait(puby, 0);
        bool over = false;
        auto img_load = [&]() {
          asm volatile("cp.async.bulk.shared::cluster.global.mbarrier::complete_tx::bytes [%0], [%1], 14336, [%2];"
                       ::"r"(sb + C_GI), "l"(img), "r"(imgb) : "memory");
        };
#pragma unroll 1
        for (int p = 0; p < 2; p++) {
          uint32_t a[7];
#pragma unroll
          for (int i = 0; i < 7; i++) a[i] = __shfl_sync(0xffffffffu, ya, 7 * p + i);
#pragma unroll 1
          for (int it = 0; it < (1 << 20); it++) {
            int v;
            asm volatile("ld.relaxed.gpu.global.s32 %0, [%1];" : "=r"(v) : "l"(cnt + 64 + 2 * b + p) : "memory");
            if (__all_sync(0xffffffffu, v >= 64)) break;
            if (!over && mbar_test(gdone, 0)) {
              over = true;
              if (lane == 0) {
                mbar_arrive(depb);
                img_load();
              }
              __syncwarp();
            }
          }
          asm volatile("fence.acquire.gpu;\nfence.proxy.async.global;" ::: "memory");
          mbar_wait(gdone, 0);
          if (lane == 0) {
            const bool any = p ? bin >= 4 : bin < 28;
#pragma unroll
            for (int i = 0; i < 7; i++) {
              if (any) tma_ld3<C_POL>(sb + p * C_PIECE + i * 8192, &m.y1[(a[i] >> 12) & 1], yf0 + 32 * p + 8 * ((i + 1) >> 1), 0, a[i] >> 7, 0);
              if (i == 0 && !over) img_load();
              if (i == G_HOLDI && !over) mbar_arrive(depb);
            }
          }
          __syncwarp();
          over = true;
        }
        if (lane == 0) mbar_arrive(depb + 8);
        mbar_wait(pubb, 0);
        int st = 0;
#pragma unroll 1
        for (int k = 0; k < 16; k++) {
          if ((k & 7) == 0) {
            poll_ge(cnt + 96 + (k >> 3), 112);
          }
          if (k == H_HOLD) mbar_wait(pubb + 8, 0);
          mbar_wait(he0 + 8 * st, (k >= H_NST) ^ (k >= 2 * H_NST));
          if (lane == 0) tma_ld3mc<0>(sb + st * H_STAGE + 8192 + hf * H_XP, &m.x2, hf0 + 8 * st, (k & 1) * 32, 0, ((k & 6) + (k >> 3)) * 64 + f);
          __syncwarp();
          if (++st == H_NST) st = 0;
        }
      }
    } else if (pin(warp) == 1) {
      if (lane == 0) {
        prefetch_map(&m.ws);
        prefetch_map(&m.xs);
        prefetch_map(&m.in[0]);
        prefetch_map(&m.in[3]);
        for (int i = 0; i < 24; i++) mbar_init(yo0 + 8 * i, 4);
        for (int i = 0; i < 8; i++) {
          mbar_init(yf0 + 8 * i, 1);
          mbar_expect(yf0 + 8 * i, i & 3 ? 16384 : 8192);
        }
        mbar_init(gdone, 8);
        for (int i = 0; i < 11; i++) mbar_init(imgb + 8 * i, 1);
        mbar_expect(imgb, 14336);
        fence_async();
      }
      __syncwarp();
      asm volatile("barrier.cluster.wait.aligned;" ::: "memory");
      if (lane == 0) {
#pragma unroll 1
        for (int r = spare; r < A_NREL; r++) {
          mbar_wait(rel0 + 8 * r, 0);
          asm volatile("fence.acq_rel.gpu;\nred.relaxed.gpu.global.inc.u32 [%0], 0x7fffffff;" ::"l"(cnt + 8 + r) : "memory");
        }
        if (!spare) {
          const int cta = role(), bin = cta >> 2;
#pragma unroll 1
          for (int r = 0; r < 4; r++) {
            if (r < 2 || (r == 2 ? bin < 28 : bin >= 4)) {
              mbar_wait(rly0 + 8 * r, 0);
              asm volatile("fence.acq_rel.gpu;\nred.relaxed.gpu.global.inc.u32 [%0], 0x7fffffff;" ::"l"(cnt + (r < 2 ? 64 + (cta & 2) : 94) + r) : "memory");
            }
            mbar_arrive(puby + 8 * r);
          }
        }
      }
    } else if (warp == 2) {
      asm volatile("barrier.cluster.wait.aligned;" ::: "memory");
      const uint32_t relm = spare ? A_RELS : A_REL;
      const int xr = __popc(xm & ((1 << lane) - 1));
      const uint32_t srcs = sb + a_out(lane), bars = aof0 + 8 * (lane % A_NOUT);
      const uint32_t done = lane < 16 ? bars + 8 * A_NOUT : se0 + 8 * (lane & 1), relb = rel0 + 8 * (spare + __popc(relm & ((1 << lane) - 1)));
      const int cta = role(), xc = x_decode(xr, cta), q = xc & 127, th = q / 28, wi = lane < 2 ? blk : w_unit(cta);
      int code = (xm >> lane) & 1 ? 0x80000000u + x1_addr(((xc >> 7) * 3 + th) * 8, (cta >> 1) & 1, 0) + (q - 28 * th) * 128
                                  : w_addr(7 - lane + xr, 0, wi >> 1, wi & 1, 0);
      uint32_t fl = 0;
      auto tables = [&]() {
        fl = flips();
        code ^= ((fl >> (((code >> 21) & 15) + (code < 0 ? 0 : 12))) & 1) << 12;
      };
      if (spare) tables();
      uint32_t tnext = clock(), src = __shfl_sync(0xffffffffu, srcs, 0), bar = aof0;
      int c = __shfl_sync(0xffffffffu, code, 0);
      mbar_wait(bar, 0);
#pragma unroll 1
      for (int n = 0; n < nu; n++) {
        while ((int)(clock() - tnext) < 0);
        tnext = clock() + (spare ? 0 : n < A_PACE_N ? A_PACE0 : A_PACE1);
        if (lane == n) {
          if (c >= 0) {
            w_store(&m.ws, src, c);
          } else {
#pragma unroll
            for (int j = 0; j < 8; j++)
              tma_st4<0>(&m.xs, src + j * 2048, ((c & 16383) >> 1) ^ ((__popc(j) & 1) << 11) ^ ((j & 1) << 12), (j >> 1) << 2, (c >> 18) & 3, (c >> 20) & 31);
          }
          bulk_commit();
        }
        __syncwarp();
        if (n == 1 && !spare) tables();
        c = __shfl_sync(0xffffffffu, code, n + 1);
        src = __shfl_sync(0xffffffffu, srcs, n + 1);
        bar = __shfl_sync(0xffffffffu, bars, n + 1);
        if (n + 1 < nu) mbar_wait(bar, (n + 1 >= A_NOUT) ^ (n + 1 >= 2 * A_NOUT));
        bulk_wait<0>();
        if (lane == n) {
          mbar_arrive(done);
          if ((relm >> lane) & 1) mbar_arrive(relb);
        }
        __syncwarp();
        if (!spare && (n == 13 || n == 15) && lane < 16) mbar_arrive_cta(empty0 + 8 * ((n - 7) >> 1), lane & 1);
      }
      if (!spare) {
        const int i = w_unit(cta), wc = w_code(1, 5 - lane, i);
        const uint32_t wa = w_addr(7 + W_SHIFT - lane, 0, i >> 1, i & 1, fl);
#pragma unroll 1
        for (int it = 0; it < 8; it++) {
          const uint32_t a = __shfl_sync(0xffffffffu, wa, it), j = it & 1;
          const int c2 = __shfl_sync(0xffffffffu, wc, it);
          mbar_wait(sf0 + 8 * j, (it >> 1) & 1);
          if (lane == 0 && it < 6) {
            mbar_expect(inf0 + 8 * j, 4096);
            in_load(c2, sb + G_TIN + j * 4096, inf0 + 8 * j);
          }
          if (it >= W_SHIFT) mbar_wait(got0 + 8 * (it - W_SHIFT), 0);
          if (lane == 0) {
            w_store(&m.ws, sb + G_TOUT + j * A_OUT, a);
            bulk_commit();
            bulk_wait<0>();
            mbar_arrive(se0 + 8 * j);
          }
          __syncwarp();
        }
        const int bin = cta >> 2;
        mbar_wait(got0 + 56, 0);
        mbar_wait(rly0 + 8, 0);
#pragma unroll 1
        for (int pc = 0; pc < 2; pc++) {
          if (pc ? bin >= 4 : bin < 28) {
            if (C_HOLD && pc) mbar_wait(pubb, 0);
#pragma unroll 1
            for (int n = 0; n < 6; n++) {
              mbar_wait(of0 + 8 * (6 * pc + n), 0);
              if (C_PACE) {
                while ((int)(clock() - tnext) < 0);
                tnext = clock() + C_PACE;
              }
              if (lane == 0) tma_st3<0>(&m.x2s, sb + pc * C_PIECE + C_OUT + n * 8192, 0, (4 * (n & 1) + 2 * hf + pc) * 64, (cta & 2) * (NB2 / 2) + 3 * (bin - 4 * pc) + (n >> 1));
              __syncwarp();
            }
            bulk_commit();
            bulk_wait<0>();
            if (lane == 0) mbar_arrive(rly0 + 16 + 8 * pc);
            __syncwarp();
          }
          if (lane < 16)
            for (int i = 6 * pc; i < 3 + 4 * pc; i++) mbar_arrive_cta(he0 + 8 * i, lane & 1);
        }
      }
    } else {
      bar_sync(9, 288);
      const int near = min(lat[0], lat[2]) > min(lat[1], lat[3]);
      if (lane == 0 && voter)
        asm volatile("red.relaxed.gpu.global.add.s32 [%0], %1;" ::"l"(cnt + 32 + page), "r"(256 + (near ^ (min(lat[4], lat[6]) > min(lat[5], lat[7])))) : "memory");
      __syncwarp();
      asm volatile("barrier.cluster.wait.aligned;" ::: "memory");
      const uint32_t fl = read_votes(cnt, lane, votes);
      if (lane == 0) {
        s_flips = fl;
        mbar_arrive(flipb);
      }
      __syncwarp();
      if (!spare) {
        bool open = lane < 8 + A_NREL;
        int k = 0;
        mbar_wait(rel0, 0);
#pragma unroll 1
        for (int p = 0; p < (1 << 16) && __any_sync(0xffffffffu, open); p++) {
          int v;
          asm volatile("ld.relaxed.gpu.global.s32 %0, [%1];" : "=r"(v) : "l"(cnt + (lane & 15)) : "memory");
          while (k < 16 && mbar_test(full0 + 8 * g_slot(k), (G_PAR >> k) & 1)) {
            if (lane == 0) mbar_arrive(empty0 + 8 * g_slot(k));
            if ((k & 1) && lane == 0) asm volatile("red.relaxed.gpu.global.inc.u32 [%0], 0x7fffffff;" ::"l"(cnt + (k >> 1)) : "memory");
            k++;
          }
          if (open && v >= (lane <= 8 ? 128 : 132)) {
            asm volatile("fence.acquire.gpu;" ::: "memory");
            mbar_arrive(got0 + 8 * lane);
            open = false;
          }
        }
        const int cta = role(), b = (cta >> 1) & 1, bin = cta >> 2;
        if (G_HOLDB) mbar_wait(puby, 0);
        y_store(1, cta, fl);
        const uint32_t wa = w_addr((lane & 6) + ((lane >> 3) & 1) + W_SHIFT, 2 * bin, (lane & 1) * 32, b, fl) + (hf << 14);
        mbar_wait(depb + 8, 0);
        mbar_wait(pubb, 0);
        asm volatile("fence.proxy.async.global;" ::: "memory");
        int st = 0;
#pragma unroll 1
        for (int k2 = 0; k2 < 16; k2++) {
          const uint32_t w = __shfl_sync(0xffffffffu, wa, k2);
          if (k2 == H_HOLD) mbar_wait(pubb + 8, 0);
          mbar_wait(he0 + 8 * st, (k2 >= H_NST) ^ (k2 >= 2 * H_NST));
          if (lane == 0) {
            mbar_expect(hf0 + 8 * st, H_STAGE);
            tma_ld3<1>(sb + st * H_STAGE, &m.w2, hf0 + 8 * st, 0, (w >> 7) & 255, w >> 15);
            if (k2 == H_NST) {
              if (cta == 0) asm volatile("cp.async.bulk.prefetch.L2.global [%0], 6144;" ::"l"(gat) : "memory");
              if (cta == 1) asm volatile("cp.async.bulk.prefetch.L2.global [%0], 16384;" ::"l"(ge) : "memory");
              asm volatile("cp.async.bulk.prefetch.L2.global [%0], 1024;" ::"l"(wf + cta * 512) : "memory");
              asm volatile("cp.async.bulk.prefetch.L2.global [%0], 1024;" ::"l"(wo + cta * 512) : "memory");
            }
          }
          __syncwarp();
          if (++st == H_NST) st = 0;
        }
      }
    }
  } else {
    if (lane == 0) {
      const int w8 = 4 * wg + warp;
      for (int i = 0; i < 2; i++) {
        mbar_init(xf0 + 16 * w8 + 8 * i, 1);
        mbar_expect(xf0 + 16 * w8 + 8 * i, A_IN);
      }
      mbar_init(got0 + 8 * w8, 1);
      if (w8 >= 8 - A_NREL) mbar_init(acq0 + 8 * (7 - w8), 1);
      if (w8 < G_NST) {
        mbar_init(full0 + 8 * w8, 1);
        mbar_init(empty0 + 8 * w8, 17);
        mbar_arrive(empty0 + 8 * w8);
      }
      if (w8 > 0) {
        mbar_init(hf0 + 8 * (w8 - 1), 1);
        mbar_init(he0 + 8 * (w8 - 1), 16);
      }
      fence_bar_init();
    }
    __syncwarp();
    asm volatile("barrier.cluster.arrive.relaxed.aligned;" ::: "memory");
    if (wg == 1) tab[t] = __bfloat16_as_ushort(__float2bfloat16_rn(-__cosf((float)(t - 64) * 0.04908738521234052f)));
    bar_sync(1, 256);
    asm volatile("setmaxnreg.inc.sync.aligned.u32 232;");
    uint32_t fa[16];
    auto frag = [&](int i, int l) {
      const int f = warp * 16 + (l >> 2) + 8 * (i & 1), r = 8 * (i >> 1) + (l & 3) * 2;
      const int k0 = (f | 1) * r - ((f & 1) << 5);
      return tab[k0 & 127] | ((uint32_t)tab[(k0 + (f | 1)) & 127] << 16);
    };
#pragma unroll
    for (int i = 0; i < 16; i++) fa[i] = i < 4 ? frag(i, lane) : 0;
    reg_fence(fa);
    asm volatile("barrier.cluster.wait.aligned;" ::: "memory");
    int cta = blk, qs = 0;
#pragma unroll 1
    for (int n = wg; n < nu; n += 2) {
      float e[64];
      if ((n >> 1) == !spare) {
        pdl_launch();
        int l = lane;
        asm volatile("" : "+r"(l));
#pragma unroll
        for (int i = 4; i < 16; i++) fa[i] = frag(i, l);
        reg_fence(fa);
        cta = role();
        qs = ((cta >> 1) & 2) + hf;
      }
      if (spare) qs = n < 8 ? n & 3 : 2 * hf + wg;
      const bool isx = (xm >> n) & 1;
      const int r = __popc(xm & ((1 << n) - 1)), s = 7 - n + r;
      const uint32_t in = isx ? sb + (r % A_NIN) * A_IN : sb + 2 * G_STAGE + s * 4096;
      mbar_wait(isx ? xf0 + 8 * r : wf0 + 8 * (s >> 1), 0);
      if (!isx) {
        wg_fence();
        wgmma_rs_128<1, 1, 1>(e, fa[0], fa[1], fa[2], fa[3], mk_desc(in, 0, 2048, 1024, 1), 0);
        wg_commit();
      } else {
        wg_fence();
#pragma unroll
        for (int k = 0; k < 4; k++)
          wgmma_rs_128<1, 1, 1>(e, fa[4 * k], fa[4 * k + 1], fa[4 * k + 2], fa[4 * k + 3], mk_desc(in, k * 2048, 6144, 1024, 1), k);
        wg_commit();
      }
      wg_wait<0>();
      reg_fence(e);
      if (isx && lane == 0) mbar_arrive(xe0 + 8 * (r % A_NIN));
      if (((A_FREE >> n) & 1) && !spare && lane < 2) mbar_arrive_cta(empty0 + 8 * (__popc(A_FREE & ((1 << n) - 1)) >> 1), lane);
      if (n >= A_NOUT) mbar_wait(aoe0 + 8 * (n % A_NOUT), (n / A_NOUT - 1) & 1);
      const int row = warp * 16 + (lane & 7) + ((lane >> 3) & 1) * 8, hi = lane >> 4;
      const uint32_t rb = sb + a_out(n) + (isx ? row : row + (row & ~7)) * 128, ts = isx ? 8192 : 1024, xr = (lane & 7) ^ (isx ? qs : 0);
#pragma unroll
      for (int j = 0; j < 16; j += 2) {
        const uint32_t tile = isx ? (j >> 2) & 1 : j >> 3, pos = (isx ? (j >> 3) * 4 + (j & 3) : (j & 7)) + hi;
        stsm4(rb + tile * ts + ((pos ^ xr) << 4), pack2(e[4 * j], e[4 * j + 1]), pack2(e[4 * j + 2], e[4 * j + 3]),
              pack2(e[4 * j + 4], e[4 * j + 5]), pack2(e[4 * j + 6], e[4 * j + 7]));
      }
      fence_async();
      __syncwarp();
      if (lane == 0) mbar_arrive(aof0 + 8 * (n % A_NOUT));
    }
    if (spare) {
      float* sg = reinterpret_cast<float*>(smem_raw + (sb - s2u(smem_raw)));
      __nv_bfloat16* sw = reinterpret_cast<__nv_bfloat16*>(sg + 16 * 256);
      const int c0 = (cta - 128) * 64;
      uint4 vw[8], vg[2];
#pragma unroll
      for (int i = 0; i < 8; i++) vw[i] = __ldg(reinterpret_cast<const uint4*>(wgt + ((i * 256 + tid) >> 3) * 256 + c0 + (tid & 7) * 8));
#pragma unroll
      for (int i = 0; i < 2; i++) vg[i] = __ldg(reinterpret_cast<const uint4*>(g) + i * 256 + tid);
      bar_sync(3, 256);
#pragma unroll
      for (int i = 0; i < 8; i++) reinterpret_cast<uint4*>(sw)[i * 256 + tid] = vw[i];
#pragma unroll
      for (int i = 0; i < 2; i++) {
        const uint32_t w4[4] = {vg[i].x, vg[i].y, vg[i].z, vg[i].w};
#pragma unroll
        for (int e = 0; e < 4; e++) {
          sg[(i * 256 + tid) * 8 + 2 * e] = __uint_as_float(w4[e] << 16);
          sg[(i * 256 + tid) * 8 + 2 * e + 1] = __uint_as_float(w4[e] & 0xffff0000u);
        }
      }
      bar_sync(3, 256);
      const int col = tid & 63, r0 = (tid >> 6) * 4;
      float a0 = 0.f, a1 = 0.f, a2 = 0.f, a3 = 0.f;
#pragma unroll 8
      for (int k = 0; k < 256; k++) {
        const float w = __bfloat162float(sw[k * 64 + col]);
        a0 = fmaf(sg[(r0 + 0) * 256 + k], w, a0);
        a1 = fmaf(sg[(r0 + 1) * 256 + k], w, a1);
        a2 = fmaf(sg[(r0 + 2) * 256 + k], w, a2);
        a3 = fmaf(sg[(r0 + 3) * 256 + k], w, a3);
      }
      const int cc = c0 + col;
      const int pos = (cc & ~15) + ((cc >> 1) & 3) * 4 + ((cc >> 3) & 1) * 2 + (cc & 1);
      ge[(r0 + 0) * 256 + pos] = __bfloat162float(__float2bfloat16_rn(a0));
      ge[(r0 + 1) * 256 + pos] = __bfloat162float(__float2bfloat16_rn(a1));
      ge[(r0 + 2) * 256 + pos] = __bfloat162float(__float2bfloat16_rn(a2));
      ge[(r0 + 3) * 256 + pos] = __bfloat162float(__float2bfloat16_rn(a3));
      return;
    }
    const int bin = cta >> 2;
    const uint32_t la = (lane >> 4) * 1024 + (lane & 7) * 128 + (((2 * warp + ((lane >> 3) & 1)) ^ (lane & 7)) << 4);
    {
    float d[32];
    auto t_begin = [&](int it, int hh) {
      mbar_wait(inf0 + 8 * (it & 1), (it >> 1) & 1);
      wg_fence();
      wgmma_rs_64<1, 1, 1>(d, fa[0], fa[1], fa[2], fa[3], mk_desc(sb + G_TIN + (it & 1) * 4096 + hh * 2048, 0, 0, 1024, 1), 0);
      wg_commit();
    };
    auto t_end = [&](int it, int hh) {
      reg_fence(d);
      const int j = it & 1;
      mbar_wait(se0 + 8 * j, (it >> 1) & 1);
      store_tile_64<2048>(d, sb + G_TOUT + j * A_OUT + hh * 1024, warp, lane);
      fence_async();
      __syncwarp();
      if (lane == 0) mbar_arrive(sf0 + 8 * j);
    };
    float re[NB1 / 2], im[NB1 / 2];
#pragma unroll 1
    for (int k = 0; k < G_KS; k++) {
      const int st = g_slot(k);
      const int it = __popc(G_TMASK & ((1 << k) - 1));
      const bool T = (G_TMASK >> k) & 1;
      mbar_wait(full0 + 8 * st, (G_PAR >> k) & 1);
      const uint32_t base = sb + st * G_STAGE;
      const uint32_t wb = base + wg * 4096;
      if (T) t_begin(it, wg);
      wg_fence();
#pragma unroll
      for (int s = 0; s < 2; s++) {
        const int acc = (k | s) != 0;
        const uint64_t dP = mk_desc(wb, s * 2048, 0, 1024, 1), dQ = mk_desc(wb, 8192 + s * 2048, 0, 1024, 1);
        const uint64_t dA = mk_desc(base, 16384 + s * 32, 0, 512, 2), dB = mk_desc(base, 16384 + G_XP + s * 32, 0, 512, 2);
        wgmma_ss_168<1, 1, 1, 0>(re, dP, dA, acc);
        wgmma_ss_168<1, 1, 1, 0>(im, dP, dB, acc);
        wgmma_ss_168<1, 1, 1, 0>(re, dQ, dB, 1);
        wgmma_ss_168<-1, 1, 1, 0>(im, dQ, dA, 1);
      }
      wg_commit();
      wg_wait<1>();
      if (k > 0 && lane < 2) mbar_arrive_cta(empty0 + 8 * g_slot(k - 1), lane);
      if (T) t_end(it, wg);
    }
    auto tail = [&](auto part, auto k0, auto k1) {
      constexpr int PART = decltype(part)::value;
#pragma unroll
      for (int k = k0.value; k < k1.value; k++) {
        if (PART == 0) mbar_wait(full0 + 8 * g_slot(k), (G_PAR >> k) & 1);
        const uint32_t base = sb + g_slot(k) * G_STAGE, wb = base + wg * 4096;
        wg_fence();
#pragma unroll
        for (int s = 0; s < 2; s++) {
          const uint64_t dP = mk_desc(wb, s * 2048, 0, 1024, 1), dQ = mk_desc(wb, 8192 + s * 2048, 0, 1024, 1);
          const uint64_t dA = mk_desc(base, 16384 + s * 32, 0, 512, 2), dB = mk_desc(base, 16384 + G_XP + s * 32, 0, 512, 2);
          if (PART == 0) {
            wgmma_ss_168<1, 1, 1, 0>(re, dP, dA, 1);
            wgmma_ss_168<1, 1, 1, 0>(re, dQ, dB, 1);
          } else {
            wgmma_ss_168<1, 1, 1, 0>(im, dP, dB, 1);
            wgmma_ss_168<-1, 1, 1, 0>(im, dQ, dA, 1);
          }
        }
      }
      wg_commit();
    };
    auto put = [&](float (&v)[NB1 / 2], uint32_t stg, uint32_t bar, auto c0, auto c1) {
      reg_fence(v);
#pragma unroll
      for (int c = c0.value; c < c1.value; c++) {
#pragma unroll
        for (int j = 8 * c; j < 8 * c + 8 && j < 20; j += 2)
          stsm4t(stg + la + j * 1024, pack2(v[4 * j], v[4 * j + 1]), pack2(v[4 * j + 2], v[4 * j + 3]),
                 pack2(v[4 * j + 4], v[4 * j + 5]), pack2(v[4 * j + 6], v[4 * j + 7]));
        if (c == 2)
          asm volatile("stmatrix.sync.aligned.m8n8.x2.trans.shared.b16 [%0], {%1, %2};" ::"r"(stg + la + 20 * 1024),
                       "r"(pack2(v[80], v[81])), "r"(pack2(v[82], v[83])) : "memory");
        fence_async();
        __syncwarp();
        if (lane == 0) mbar_arrive(bar + 8 * c);
      }
    };
    if (wg == 1) {
      wg_wait<0>();
      bar_arrive(5, 256);
#pragma unroll 1
      for (int h2 = 2 * __popc(G_TMASK); h2 < 16; h2++) {
        t_begin(h2 >> 1, h2 & 1);
        wg_wait<0>();
        t_end(h2 >> 1, h2 & 1);
      }
      bar_arrive(6, 256);
      bar_sync(4, 256);
    }
    tail(IC<0>(), IC<G_KS>(), IC<16>());
    tail(IC<1>(), IC<G_KS>(), IC<G_KI>());
    if (G_KI == 16 && wg == 0) bar_arrive(4, 256);
    wg_wait<1>();
    if (wg == 0) {
      bar_sync(5, 256);
    } else {
      mbar_wait(se0, 0);
      mbar_wait(se0 + 8, 0);
    }
    const uint32_t stg = sb + (wg ? G_TOUT : 4 * G_STAGE);
    put(re, stg, yo0 + 48 * wg, IC<0>(), IC<G_KC>());
    if (G_KI < 16) {
      tail(IC<1>(), IC<G_KI>(), IC<16>());
      if (wg == 0) bar_arrive(4, 256);
    }
    put(re, stg, yo0 + 48 * wg, IC<G_KC>(), IC<3>());
    wg_wait<0>();
    if (lane == 0) mbar_arrive(gdone);
    if (wg == 0) bar_sync(6, 256);
    else mbar_wait(gdone, 0);
    put(im, sb + (wg ? G_IM1 : 4 * G_STAGE + NB1 * 128), yo0 + 48 * wg + 24, IC<0>(), IC<3>());
    }
    mbar_wait(imgb, 0);
    const int p0 = bin >= 28, p1 = bin < 4 ? 1 : 2;
#pragma unroll 1
    for (int pc = p0; pc < p1; pc++) {
      const uint32_t in = sb + pc * C_PIECE, yb = yf0 + 32 * pc;
      const bool first = bin == 4 * pc, last = bin == 27 + 4 * pc;
      float h0[12], h1[12], h2[12], h3[12], h4[12], h5[12], h6[8], e[32];
      uint32_t hp[40];
      auto idft = [&](auto& h, int i) {
#pragma unroll
        for (int k = 0; k < 4; k++) {
          const uint64_t da = mk_desc(in, i * 8192 + k * 2048, 0, 1024, 1), db = mk_desc(sb + C_GI + wg * 1024, k * 32, 0, 2048, 1);
          if constexpr (sizeof(h) == 48) wgmma_ss_24<1, 1, 1, 0>(h, da, db, k);
          else wgmma_ss_16<1, 1, 1, 0>(h, da, db, k);
        }
      };
      auto idft2 = [&](auto& ha, auto& hb, int i) {
        mbar_wait(yb + 4 * (i + 1), 0);
        wg_fence();
        idft(ha, i);
        idft(hb, i + 1);
        wg_commit();
      };
      auto dft = [&](int j) {
        wg_fence();
#pragma unroll
        for (int k = 0; k < 4; k++)
          wgmma_rs_64<1, 1, 0>(e, hp[12 * j + 4 * k], hp[12 * j + 4 * k + 1], hp[12 * j + 4 * k + 2], hp[12 * j + 4 * k + 3], mk_desc(sb + C_F, k * 32, 0, 1024, 1), k);
        wg_commit();
      };
      auto out = [&](int j) {
        reg_fence(e);
        if (j == 1) mbar_wait(rly0 + 8, 0);
        const uint32_t a0 = in + la + C_OUT + (2 * j + wg) * 8192;
#pragma unroll
        for (int q = 0; q < 8; q += 2)
          stsm4t(a0 + q * 1024, pack2(e[4 * q], e[4 * q + 1]), pack2(e[4 * q + 2], e[4 * q + 3]),
                 pack2(e[4 * q + 4], e[4 * q + 5]), pack2(e[4 * q + 6], e[4 * q + 7]));
        fence_async();
        __syncwarp();
        if (lane == 0) mbar_arrive(of0 + 8 * (6 * pc + 2 * j + wg));
      };
      mbar_wait(yb, 0);
      wg_fence();
      idft(h0, 0);
      wg_commit();
      idft2(h1, h2, 1);
      wg_wait<1>();
      gelu_pack(hp, h0, first, false);
      wg_wait<0>();
      gelu_pack(hp + 6, h1, false, false);
      gelu_pack(hp + 12, h2, false, false);
      dft(0);
      idft2(h3, h4, 3);
      wg_wait<1>();
      out(0);
      wg_wait<0>();
      gelu_pack(hp + 18, h3, false, false);
      gelu_pack(hp + 24, h4, false, false);
      dft(1);
      idft2(h5, h6, 5);
      wg_wait<1>();
      out(1);
      wg_wait<0>();
      gelu_pack(hp + 30, h5, false, last);
      gelu_pack(hp + 36, h6, false, last);
      dft(2);
      wg_wait<0>();
      if (pc == p1 - 1 && lane < 6) mbar_arrive_cta(he0 + 8 * (3 + (lane >> 1)), lane & 1);
      out(2);
    }
    float acc[84];
    if (wg == 0) {
      h_loop<0>(acc, sb, hf0, he0, lane);
    } else {
      h_loop<1>(acc, sb, hf0, he0, lane);
      bar_sync(3, 128);
    }
    const uint32_t stg = sb + (wg == 0 ? H_NST : 9 % H_NST) * H_STAGE;
    const uint32_t a0 = stg + la;
    constexpr int J = 21 / H_EPI;
#pragma unroll
    for (int c = 0; c < H_EPI; c++) {
#pragma unroll
      for (int j = c * J; j + 1 < (c + 1) * J; j += 2)
        stsm4t(a0 + j * 1024, pack2(acc[4 * j], acc[4 * j + 1]), pack2(acc[4 * j + 2], acc[4 * j + 3]),
               pack2(acc[4 * j + 4], acc[4 * j + 5]), pack2(acc[4 * j + 6], acc[4 * j + 7]));
      const int j = (c + 1) * J - 1;
      asm volatile("stmatrix.sync.aligned.m8n8.x2.trans.shared.b16 [%0], {%1, %2};" ::"r"(a0 + j * 1024),
                   "r"(pack2(acc[4 * j], acc[4 * j + 1])), "r"(pack2(acc[4 * j + 2], acc[4 * j + 3])) : "memory");
      fence_async();
      bar_sync(2 + wg, 128);
      if (t == 0) {
        tma_st4<0>(&m.y2, stg + c * J * 1024, 0, c * J * 8, 2 * bin + wg, cta & 3);
        bulk_commit();
      }
    }
    if (t == 0) {
      bulk_wait_read<0>();
    }
  }
}

#define E_LD 0
#define E_WPRE 2
#define E_EARLY0 2
#define E_CHUNK 1
#define E_EARLY 2
constexpr int E_SMEM = 65536 + 131072 + 32768 + 1024;

__device__ __forceinline__ uint32_t joint2(uint32_t fe, uint32_t g0, uint32_t g1) {
  uint32_t s0, s1;
  asm("{\n.reg .b16 l, h;\n.reg .b32 ll;\nmov.b32 {l, h}, %2;\nmov.b32 ll, {l, l};\n"
      "fma.rn.bf16x2 %0, ll, %5, %3;\nfma.rn.bf16x2 %1, %2, %5, %4;\n}"
      : "=r"(s0), "=r"(s1) : "r"(fe), "r"(g0), "r"(g1), "r"(0x3F800000u));
  return pack2(tanh_f32(__uint_as_float(s0)), tanh_f32(__uint_as_float(s1)));
}
__device__ __forceinline__ uint4 lds128(uint32_t a) {
  uint4 v;
  asm volatile("ld.shared.v4.u32 {%0, %1, %2, %3}, [%4];" : "=r"(v.x), "=r"(v.y), "=r"(v.z), "=r"(v.w) : "r"(a));
  return v;
}
__device__ __forceinline__ void joint_group(uint32_t (&ja)[8], const uint32_t* fe, uint4& g0, uint4& g1, uint32_t gnext) {
  const uint4 c0 = g0, c1 = g1;
  g0 = lds128(gnext);
  g1 = lds128(gnext + 64);
  ja[0] = joint2(fe[0], c0.x, c0.y);
  ja[1] = joint2(fe[1], c0.x, c0.y);
  ja[2] = joint2(fe[2], c0.z, c0.w);
  ja[3] = joint2(fe[3], c0.z, c0.w);
  ja[4] = joint2(fe[4], c1.x, c1.y);
  ja[5] = joint2(fe[5], c1.x, c1.y);
  ja[6] = joint2(fe[6], c1.z, c1.w);
  ja[7] = joint2(fe[7], c1.z, c1.w);
  reg_fence(ja);
}

__global__ void __launch_bounds__(256, 1)
kE(int* __restrict__ cnt, const uint32_t* __restrict__ gat, const float* ge, const __grid_constant__ CUtensorMap my, const __grid_constant__ CUtensorMap mwf, const __grid_constant__ CUtensorMap mwo,
   const __grid_constant__ CUtensorMap mout) {
  extern __shared__ __align__(1024) uint8_t smem_raw[];
  __shared__ __align__(8) uint64_t bars[13];
  const uint32_t sb = (s2u(smem_raw) + 1023) & ~1023u;
  const int tid = threadIdx.x, wg = __shfl_sync(0xffffffffu, tid >> 7, 0), t = tid & 127, warp = t >> 5, lane = t & 31;
  const uint32_t R0 = sb, R1 = sb + 65536, R2 = sb + 65536 + 131072;
  const uint32_t barY = s2u(&bars[0]), barF = barY + 32, barO = barY + 64, barA = barY + 96;
  const int b = blockIdx.x / 63, t0 = (blockIdx.x % 63) * 64;
  const int a = t0 / 48, o = t0 % 48;
  const int qw = o + 16 * warp, sel = qw >= 48;
  uint32_t ga[16];
#pragma unroll
  for (int s = 0; s < 4; s++)
    ldg128(reinterpret_cast<const uint4*>(gat) + ((qw >> 4) - 3 * sel) * 128 + s * 32 + lane, ga[4 * s], ga[4 * s + 1], ga[4 * s + 2], ga[4 * s + 3]);
  if (tid == 0) {
    prefetch_map(&my);
    for (int i = 0; i < 12; i++) mbar_init(barY + 8 * i, 1);
    mbar_init(barA, 8);
    fence_bar_init();
    fence_async();
    for (int i = 0; i < E_WPRE; i++) {
      const int kc = (i >> 1) | ((i & 1) << 1);
      mbar_expect(barF + 8 * kc, 32768);
      tma_ld3<0>(R1 + kc * 32768, &mwf, barF + 8 * kc, 0, kc * 64, 0);
    }
  }
  uint32_t gs[32];
#pragma unroll
  for (int i = 0; i < 16; i++) {
    gs[i] = sel ? 0u : ga[i];
    gs[16 + i] = sel ? ga[i] : 0u;
  }
  __syncthreads();
  pdl_wait();
  uint4 gev0, gev1;
  asm volatile("ld.global.cg.v4.u32 {%0, %1, %2, %3}, [%4];" : "=r"(gev0.x), "=r"(gev0.y), "=r"(gev0.z), "=r"(gev0.w)
               : "l"(reinterpret_cast<const uint4*>(ge) + (b * 8 + wg * 4) * 64 + t));
  asm volatile("ld.global.cg.v4.u32 {%0, %1, %2, %3}, [%4];" : "=r"(gev1.x), "=r"(gev1.y), "=r"(gev1.z), "=r"(gev1.w)
               : "l"(reinterpret_cast<const uint4*>(ge) + (b * 8 + wg * 4) * 64 + 128 + t));
  if (tid == E_LD) {
    for (int i = 0; i < 4; i++) {
      mbar_expect(barY + 8 * i, 16384);
      tma_ld5<0>(R0 + i * 16384, &my, barY + 8 * i, 0, 0, 2 * (i & 1) + (i >> 1), a, b);
    }
    for (int i = E_WPRE; i < 4; i++) {
      const int kc = (i >> 1) | ((i & 1) << 1);
      mbar_expect(barF + 8 * kc, 32768);
      tma_ld3<0>(R1 + kc * 32768, &mwf, barF + 8 * kc, 0, kc * 64, 0);
    }
    prefetch_map(&mwo);
    prefetch_map(&mout);
  }
  if (blockIdx.x == 125 && tid < 128) cnt[tid] = 0;
  reg_fence(gs);
  uint32_t gp = R2 + wg * 4096 + (lane & 3) * 16;
  uint4 g0, g1;
  uint32_t fe[64];
  {
    float d0[32], d1[32], e[64];
    mbar_wait(barY + 8 * wg, 0);
    wg_fence();
#pragma unroll
    for (int k = 0; k < 8; k++)
      wgmma_rs_64<1, 1, 1>(d0, gs[4 * k], gs[4 * k + 1], gs[4 * k + 2], gs[4 * k + 3], mk_desc(R0 + wg * 16384, k * 2048, 0, 1024, 1), k);
    wg_commit();
    wg_wait<0>();
    reg_fence(d0);
#pragma unroll
    for (int i = 0; i < 32; i++) d0[i] = gelu(d0[i]);
    store_tile_64(d0, R2 + wg * 16384, warp, lane);
    mbar_wait(barY + 8 * (2 + wg), 0);
    wg_fence();
#pragma unroll
    for (int k = 0; k < 8; k++)
      wgmma_rs_64<1, 1, 1>(d1, gs[4 * k], gs[4 * k + 1], gs[4 * k + 2], gs[4 * k + 3], mk_desc(R0 + wg * 16384, 32768 + k * 2048, 0, 1024, 1), k);
    wg_commit();
    fence_async();
    mbar_wait(barF, 0);
    mbar_wait(barF + 16, 0);
    __syncthreads();
    wg_fence();
#pragma unroll
    for (int i = 0; i < 8; i++) {
      const int kc = (i >> 2) * 2, s = i & 3;
      wgmma_ss_128<1, 1, 0, 1>(e, mk_desc(R2, kc * 8192 + s * 32, 0, 1024, 1),
                               mk_desc(R1 + wg * 16384, kc * 32768 + s * 2048, 8192, 1024, 1), i);
    }
    wg_commit();
    if (tid == 128) {
      mbar_expect(barO, 32768);
      tma_ld3<0>(R0, &mwo, barO, 0, 0, 0);
    }
    wg_wait<1>();
    reg_fence(d1);
#pragma unroll
    for (int i = 0; i < 32; i++) d1[i] = gelu(d1[i]);
    store_tile_64(d1, R2 + wg * 16384 + 8192, warp, lane);
    fence_async();
    mbar_wait(barF + 8, 0);
    mbar_wait(barF + 24, 0);
    __syncthreads();
    if (tid == 128) {
      mbar_expect(barO + 8, 32768);
      tma_ld3<0>(R0 + 32768, &mwo, barO + 8, 0, 64, 0);
    }
    if (wg == 1) bar_sync(4, 256);
    wg_fence();
#pragma unroll
    for (int i = 0; i < 8; i++) {
      const int kc = (i >> 2) * 2 + 1, s = i & 3;
      wgmma_ss_128<1, 1, 0, 1>(e, mk_desc(R2, kc * 8192 + s * 32, 0, 1024, 1),
                               mk_desc(R1 + wg * 16384, kc * 32768 + s * 2048, 8192, 1024, 1), 1);
    }
    wg_commit();
    if (wg == 0) bar_arrive(4, 256);
    wg_wait<1>();
    if (lane == 0) mbar_arrive(barA);
    if (tid == 128) {
      mbar_wait(barA, 0);
      for (int kc = 2; kc < 4; kc++) {
        mbar_expect(barO + 8 * kc, 32768);
        tma_ld3<0>(R1 + (kc - 2) * 65536, &mwo, barO + 8 * kc, 0, kc * 64, 0);
      }
    }
    mbar_wait(barA, 0);
    asm volatile("st.shared.v4.u32 [%0], {%1, %2, %3, %4};" ::"r"(R2 + wg * 4096 + ((t * 16) ^ (wg * 512))), "r"(gev0.x), "r"(gev0.y), "r"(gev0.z), "r"(gev0.w) : "memory");
    asm volatile("st.shared.v4.u32 [%0], {%1, %2, %3, %4};" ::"r"(R2 + wg * 4096 + 2048 + ((t * 16) ^ (wg * 512))), "r"(gev1.x), "r"(gev1.y), "r"(gev1.z), "r"(gev1.w) : "memory");
    bar_sync(1 + wg, 128);
    g0 = lds128(gp);
    g1 = lds128(gp + 64);
    wg_wait<0>();
    reg_fence(e);
#pragma unroll
    for (int i = 0; i < 32; i++) fe[i] = pack2(e[2 * i], e[2 * i + 1]);
  }
  auto publish = [&]() {
    bar_sync(1 + wg, 128);
    const int row = warp * 16 + (lane & 7) + ((lane >> 3) & 1) * 8;
    const uint32_t xb = R1 + (wg == 0 ? 3 * 32768 : 32768 + 16384) + row * 128;
#pragma unroll
    for (int s = 0; s < 8; s++) {
      const int jj = 2 * s + (lane >> 4);
      stsm4(xb + (s >> 2) * 8192 + (((jj & 7) ^ (lane & 7)) << 4), fe[4 * s], fe[4 * s + 1], fe[4 * s + 2], fe[4 * s + 3]);
    }
    bar_arrive(5 + wg, 256);
  };
  if (wg == 1) publish();
  const uint32_t stg = R1 + 32768 + wg * 65536;
  const uint32_t w0 = sb + wg * 65536, w1 = sb + 32768 + wg * 98304, w2 = sb + 65536 - wg * 65536, w3 = sb + 131072 - wg * 98304;
  float acc[128];
  uint32_t j0[8], j1[8], j2[8], j3[8];
  joint_group(j0, fe, g0, g1, gp + 128);
  mbar_wait(barO + 16 * wg, 0);
  joint_group(j1, fe + 8, g0, g1, gp + 256);
#define E_MMA4(J, K, W, FIRSTK, G, NEXTBAR)                                                     \
  wg_fence();                                                                                   \
  wgmma_rs_256<1, 1, 1>(acc, J[0], J[1], J[2], J[3], mk_desc(W, 0, 8192, 1024, 1), FIRSTK);     \
  wgmma_rs_256<1, 1, 1>(acc, J[4], J[5], J[6], J[7], mk_desc(W, 2048, 8192, 1024, 1), 1);       \
  wgmma_rs_256<1, 1, 1>(acc, K[0], K[1], K[2], K[3], mk_desc(W, 4096, 8192, 1024, 1), 1);       \
  wgmma_rs_256<1, 1, 1>(acc, K[4], K[5], K[6], K[7], mk_desc(W, 6144, 8192, 1024, 1), 1);       \
  wg_commit();                                                                                  \
  if ((ui + wg == 0 ? E_EARLY0 : E_EARLY) == (G) && (ui < 3 || wg == 0)) bar_arrive(4 - wg, 256); \
  wg_wait<1>();                                                                                 \
  if (ui == 0) mbar_wait(NEXTBAR, 0);
  const uint32_t bo0 = barO + 16 * wg, bo2 = barO + 16 * (1 - wg);
#pragma unroll 1
  for (int ui = 0; ui < 4; ui++) {
    if (ui > 0 || wg == 1) bar_sync(3 + wg, 256);
    E_MMA4(j0, j1, w0, 0, 0, bo0)
    joint_group(j2, fe + 16, g0, g1, gp + 384);
    if (ui == 0) mbar_wait(bo0 + 8, 0);
    joint_group(j3, fe + 24, g0, g1, gp + 512);
    E_MMA4(j2, j3, w1, 1, 1, bo0 + 8)
    if (ui == 0) {
      if (wg == 0) publish();
      bar_sync(6 - wg, 256);
      const int row = warp * 16 + (lane & 7) + ((lane >> 3) & 1) * 8;
      const uint32_t xb = R1 + (wg == 1 ? 3 * 32768 : 32768 + 16384) + row * 128;
#pragma unroll
      for (int s = 0; s < 8; s++) {
        const int jj = 2 * s + (lane >> 4);
        ldsm4(xb + (s >> 2) * 8192 + (((jj & 7) ^ (lane & 7)) << 4), fe[32 + 4 * s], fe[33 + 4 * s], fe[34 + 4 * s], fe[35 + 4 * s]);
      }
    }
    joint_group(j0, fe + 32, g0, g1, gp + 640);
    if (ui == 0) mbar_wait(bo2, 0);
    joint_group(j1, fe + 40, g0, g1, gp + 768);
    E_MMA4(j0, j1, w2, 1, 2, bo2)
    joint_group(j2, fe + 48, g0, g1, gp + 896);
    if (ui == 0) mbar_wait(bo2 + 8, 0);
    joint_group(j3, fe + 56, g0, g1, gp + 1024);
    E_MMA4(j2, j3, w3, 1, 3, bo2 + 8)
    gp += 1024;
    if (ui < 3) {
      joint_group(j0, fe, g0, g1, gp + 128);
      if (ui == 0) mbar_wait(bo2 + 8, 0);
      joint_group(j1, fe + 8, g0, g1, gp + 256);
    }
    if (t == 0) bulk_wait_read<0>();
    wg_wait<0>();
    reg_fence(acc);
    bar_sync(1 + wg, 128);
    const uint32_t rb = stg + (warp * 16 + (lane & 7) + ((lane >> 3) & 1) * 8) * 128;
#pragma unroll
    for (int h = 0; h < 2; h++) {
#pragma unroll
      for (int j = 16 * h; j < 16 * h + 16; j += 2) {
        const int jj = j + (lane >> 4);
        stsm4(rb + (j >> 3) * 8192 + (((jj & 7) ^ (lane & 7)) << 4), pack2(acc[4 * j], acc[4 * j + 1]), pack2(acc[4 * j + 2], acc[4 * j + 3]),
              pack2(acc[4 * j + 4], acc[4 * j + 5]), pack2(acc[4 * j + 6], acc[4 * j + 7]));
      }
      const bool split = E_CHUNK == 2 || (E_CHUNK == 1 && ui == 3);
      if (h == 1 || split) {
        fence_async();
        bar_sync(1 + wg, 128);
        if (t == 0) {
          if (h == 1 && !split) tma_st5<1>(&mout, stg, 0, t0, 0, wg * 4 + ui, b);
          tma_st5<1>(&mout, stg + h * 16384, 0, t0, 2 * h, wg * 4 + ui, b);
          bulk_commit();
        }
      }
    }
  }
  if (t == 0) bulk_wait_read<0>();
}

typedef CUresult (*EncodeFn)(CUtensorMap*, CUtensorMapDataType, cuuint32_t, void*, const cuuint64_t*, const cuuint64_t*,
                             const cuuint32_t*, const cuuint32_t*, CUtensorMapInterleave, CUtensorMapSwizzle,
                             CUtensorMapL2promotion, CUtensorMapFloatOOBfill);

CUtensorMap make_map(EncodeFn fn, const void* base, int rank, const uint64_t* dims, const uint64_t* strides, const uint32_t* box,
                     CUtensorMapSwizzle swz) {
  CUtensorMap m;
  cuuint64_t gd[5], gs[4];
  cuuint32_t bx[5], es[5];
  for (int i = 0; i < rank; i++) { gd[i] = dims[i]; bx[i] = box[i]; es[i] = 1; }
  for (int i = 0; i + 1 < rank; i++) gs[i] = strides[i];
  fn(&m, CU_TENSOR_MAP_DATA_TYPE_BFLOAT16, rank, const_cast<void*>(base), gd, gs, bx, es, CU_TENSOR_MAP_INTERLEAVE_NONE, swz,
     CU_TENSOR_MAP_L2_PROMOTION_NONE, CU_TENSOR_MAP_FLOAT_OOB_FILL_NONE);
  return m;
}

template <typename... KArgs, typename... Args>
void launch(void (*k)(KArgs...), int grid, int block, int smem, bool pdl, Args... args) {
  cudaLaunchConfig_t c = {};
  c.gridDim = dim3(grid);
  c.blockDim = dim3(block);
  c.dynamicSmemBytes = smem;
  c.stream = cudaStreamPerThread;
  cudaLaunchAttribute at[1];
  at[0].id = cudaLaunchAttributeProgrammaticStreamSerialization;
  at[0].val.programmaticStreamSerializationAllowed = 1;
  c.attrs = at;
  c.numAttrs = pdl ? 1 : 0;
  cudaLaunchKernelEx(&c, k, args...);
}

}

extern "C" void kernel_launch(void* const* d_in, const int* in_sizes, int n_in, void* d_out, int out_size) {
  const __nv_bfloat16* x = (const __nv_bfloat16*)d_in[0];
  const __nv_bfloat16* w1 = (const __nv_bfloat16*)d_in[1];
  const __nv_bfloat16* w2 = (const __nv_bfloat16*)d_in[2];
  const __nv_bfloat16* g = (const __nv_bfloat16*)d_in[3];
  const __nv_bfloat16* wf = (const __nv_bfloat16*)d_in[4];
  const __nv_bfloat16* wgt = (const __nv_bfloat16*)d_in[5];
  const __nv_bfloat16* wo = (const __nv_bfloat16*)d_in[6];

  void* fp = nullptr;
  cudaDriverEntryPointQueryResult qr;
  cudaGetDriverEntryPoint("cuTensorMapEncodeTiled", &fp, cudaEnableDefault, &qr);
  EncodeFn fn = (EncodeFn)fp;
  void *W, *Y2, *cnt, *ge, *img, *gat;
  cudaGetSymbolAddress(&cnt, g_cnt);
  cudaGetSymbolAddress(&ge, g_ge);
  cudaGetSymbolAddress(&img, c_img);
  cudaGetSymbolAddress(&gat, c_ga);
  cudaGetSymbolAddress(&W, g_W);
  cudaGetSymbolAddress(&Y2, g_Y2);
  cudaFuncSetAttribute(kG, cudaFuncAttributeMaxDynamicSharedMemorySize, G_SMEM);
  cudaFuncSetAttribute(kE, cudaFuncAttributeMaxDynamicSharedMemorySize, E_SMEM);
  auto page_up = [](void* p) { return (void*)(((uintptr_t)p + (1 << 21) - 1) & ~(uintptr_t)((1 << 21) - 1)); };
  void *X1 = page_up(d_out), *X2 = X1;
  W = page_up(W);
  const CUtensorMapSwizzle S128 = CU_TENSOR_MAP_SWIZZLE_128B, S64 = CU_TENSOR_MAP_SWIZZLE_64B;

  auto map_x = [&]() {
    uint64_t d[] = {64, 8000, 8, 1, 2}, s[] = {1024, 128, 8000ull * 1024, 8000ull * 1024};
    uint32_t bx[] = {64, 112, 1, 1, 1};
    return make_map(fn, x, 5, d, s, bx, S128);
  };
  auto map_w_in = [&](const __nv_bfloat16* w, int odd, uint32_t n) {
    uint64_t d[] = {64, (uint64_t)(odd ? 15 : 16), 4, 64, 4}, s[] = {2ull * 65536 * 2, 128, 512, 32768};
    uint32_t bx[] = {64, 16, 2, 1, n};
    return make_map(fn, w + (odd ? 65536 : 0), 5, d, s, bx, S128);
  };
  auto map_X_st = [&](void* p, int nb, int boxb) {
    uint64_t d[] = {64, 512, (uint64_t)(2 * nb)}, s[] = {2ull * nb * 128, 128};
    uint32_t bx[] = {64, 64, (uint32_t)boxb};
    return make_map(fn, p, 3, d, s, bx, S128);
  };
  auto map_X1_st = [&](uint32_t rows) {
    uint64_t d[] = {8192, 16, 4, 24}, s[] = {16384, 262144, 1048576};
    uint32_t bx[] = {64, 4, 2, rows / 8};
    return make_map(fn, X1, 4, d, s, bx, S128);
  };
  auto map_Y1_ld = [&](uint64_t step) {
    uint64_t d[] = {64, 12 << 14, 2}, s[] = {128, step};
    uint32_t bx[] = {64, 32, 2};
    return make_map(fn, X1, 3, d, s, bx, S128);
  };
  auto map_W_st = [&]() {
    uint64_t d[] = {8192, 8, 4, 2 * (8 + W_SHIFT), 2}, s[] = {32768, 262144, 1048576, 16384};
    uint32_t bx[] = {64, 2, 2, 2, 2};
    return make_map(fn, W, 5, d, s, bx, S128);
  };
  auto map_X_ld = [&](void* p, int nb, int boxb) {
    uint64_t d[] = {64, (uint64_t)(2 * nb), 512}, s[] = {128, 2ull * nb * 128};
    uint32_t bx[] = {32, (uint32_t)boxb, 1};
    return make_map(fn, p, 3, d, s, bx, S64);
  };
  auto map_W_ld = [&](uint32_t n) {
    uint64_t d[] = {64, 512 / n, (8ull + W_SHIFT) * 32 * n}, s[] = {128, 65536 / n};
    uint32_t bx[] = {64, 32, n};
    return make_map(fn, W, 3, d, s, bx, S128);
  };
  auto map_Y_st = [&](void* p, int nb, int rows) {
    uint64_t d[] = {64, (uint64_t)(2 * nb), 64, 4}, s[] = {32768, 128, 8192};
    uint32_t bx[] = {64, (uint32_t)rows, 1, 1};
    return make_map(fn, p, 4, d, s, bx, S128);
  };
  auto map_Y_ld = [&](void* p, int nb, int boxc, int boxb) {
    uint64_t d[] = {64, 64, 4, (uint64_t)nb, 2}, s[] = {128, 8192, 32768, (uint64_t)nb * 32768};
    uint32_t bx[] = {64, 64, (uint32_t)boxc, (uint32_t)boxb, 1};
    return make_map(fn, p, 5, d, s, bx, S128);
  };
  auto map_wsq = [&](const __nv_bfloat16* w) {
    uint64_t d[] = {64, 256, 4}, s[] = {512, 128};
    uint32_t bx[] = {64, 64, 4};
    return make_map(fn, w, 3, d, s, bx, S128);
  };
  auto map_out = [&]() {
    uint64_t d[] = {64, 4000, 4, 8, 2}, s[] = {4096, 128, 512, 4000ull * 4096};
    uint32_t bx[] = {64, 64, 2, 1, 1};
    return make_map(fn, d_out, 5, d, s, bx, S128);
  };

  GMaps g1;
  g1.w = map_W_ld(4);
  g1.y = map_X1_st(8);
  g1.in[0] = map_w_in(w1, 1, 2);
  g1.in[1] = map_w_in(w1, 0, 2);
  g1.in[2] = map_w_in(w2, 1, 1);
  g1.in[3] = map_w_in(w2, 0, 1);
  g1.in[4] = map_x();
  g1.xs = map_X1_st(16);
  g1.ws = map_W_st();
  g1.y1[0] = map_Y1_ld(0x3000);
  g1.y1[1] = map_Y1_ld(0x1000);
  g1.x2s = map_X_st(X2, NB2, 1);
  g1.x2 = map_X_ld(X2, NB2, 168);
  g1.w2 = map_W_ld(2);
  g1.y2 = map_Y_st(Y2, NB2, 168 / H_EPI);
  launch(kG, 132, 384, G_SMEM, false, (int*)cnt, (char*)X1, (char*)W, g, wgt, (float*)ge, (const uint32_t*)img, wf, wo, (const uint32_t*)gat, g1);
  launch(kE, 126, 256, E_SMEM, true, (int*)cnt, (const uint32_t*)gat, (const float*)ge, map_Y_ld(Y2, NB2, 1, 2), map_wsq(wf), map_wsq(wo), map_out());
}
```
